```python
import torch

def _softmax(x, axis=-1):
    return torch.softmax(x, dim=axis)

def _gelu(x):
    return torch.nn.functional.gelu(x, approximate='tanh')

def _silu(x):
    return torch.nn.functional.silu(x)

def _sigmoid(x):
    return torch.sigmoid(x)

def _layernorm(x, axis=-1, eps=1e-05):
    m = x.mean(dim=axis, keepdim=True)
    v = x.var(dim=axis, keepdim=True, unbiased=False)
    return (x - m) / torch.sqrt(v + eps)

def _scatter_add(tgt, idx, src, axis=0):
    return tgt.clone().index_add_(axis, idx, src)

def _segment_sum(src, seg, n):
    out = torch.zeros((n,) + src.shape[1:], dtype=src.dtype)
    return out.index_add_(0, seg, src)

def _pad(x, pw):
    flat = tuple((v for pair in reversed(pw) for v in pair))
    return torch.nn.functional.pad(x, flat)
kernel_name = 'standalone__window_attn_davit__vision'

def setup_inputs():

    _w = lambda a: (lambda t: t.to(torch.bfloat16) if t.is_floating_point() else t)(torch.as_tensor(a))
    HW = 512
    C0 = 192
    ws = 7
    nh = 4
    H = W = max(HW // ws * ws, ws)
    C = max(C0 // nh * nh, nh)
    k = 3
    return {'x': _w((lambda *s: torch.randn(*s, dtype=torch.bfloat16) * 1.6)(1, H, W, C)), 'dw_pe': _w((lambda *s: torch.randn(*s, dtype=torch.bfloat16) * 1.6)(k, k, C) * 0.1), 'w_qkv': _w((lambda *s: torch.randn(*s, dtype=torch.bfloat16) * 1.6)(C, 3 * C) * C ** (-0.5)), 'w_o': _w((lambda *s: torch.randn(*s, dtype=torch.bfloat16) * 0.4)(C, C) * C ** (-0.5))}

def reference(x, dw_pe, w_qkv, w_o):
    B, H, W, C = x.shape
    ws = 7
    nh = 4
    dh = C // nh
    kk = dw_pe.shape[0]
    pad = kk // 2
    xp = _pad(x, ((0, 0), (pad, pad), (pad, pad), (0, 0)))
    pe = torch.zeros_like(x)
    for i in range(kk):
        for j in range(kk):
            pe = pe + xp[:, i:i + H, j:j + W, :] * dw_pe[i, j][None, None, None, :]
    x0 = x + pe
    h = _layernorm(x0, axis=-1)
    hw = h.reshape(B, H // ws, ws, W // ws, ws, C)
    hw = (lambda x, *d: x.permute(*d))(hw, 0, 1, 3, 2, 4, 5)
    hw = hw.reshape(-1, ws * ws, C)
    qkv = (hw @ w_qkv).reshape(-1, ws * ws, 3, nh, dh)
    q = qkv[:, :, 0].clone()
    k = qkv[:, :, 1].clone()
    v = qkv[:, :, 2].clone()
    scale = dh ** (-0.5)
    attn = torch.einsum('wnhd,wmhd->whnm', q, k) * scale
    attn = _softmax(attn, axis=-1)
    out = torch.einsum('whnm,wmhd->wnhd', attn, v)
    out = out.reshape(-1, ws * ws, C) @ w_o
    out = out.reshape(B, H // ws, W // ws, ws, ws, C)
    out = (lambda x, *d: x.permute(*d))(out, 0, 1, 3, 2, 4, 5)
    out = out.reshape(B, H, W, C)
    return x0 + out
```

```cpp
#include <cuda_runtime.h>
#include <cuda_bf16.h>
#include <cuda.h>
#include <stdint.h>

namespace {

constexpr int IMG = 511;
constexpr int CH = 192;
constexpr int NWX = 73;
constexpr int NWIN = NWX * NWX;
constexpr int SLICE = 18432;
constexpr int OFF_W = 0;
constexpr int KV_BYTES = 12544, KV_PITCH = 1920;
constexpr int OFF_KV = 8 * SLICE;
constexpr int TILE_BYTES = 25 * 768;
constexpr int OFF_TILE = OFF_KV + 2 * KV_BYTES;
constexpr int XSLOT = 2304;
constexpr int OFF_X = OFF_TILE + 2 * TILE_BYTES;
constexpr int OFF_BAR = OFF_X + 9 * XSLOT;
constexpr int BAR_WFULL = OFF_BAR;
constexpr int BAR_WEMPTY = OFF_BAR + 48;
constexpr int BAR_XFULL = OFF_BAR + 96;
constexpr int BAR_TFULL = OFF_BAR + 168;
constexpr int BAR_TEMPTY = OFF_BAR + 176;
constexpr int SMEM_BYTES = OFF_BAR + 192;

__device__ uint4 g_wpack[16 * SLICE / 16];

typedef __nv_bfloat162 bf2;
__device__ __forceinline__ bf2 u2b(uint32_t u) { return *reinterpret_cast<bf2*>(&u); }
__device__ __forceinline__ uint32_t b2u(bf2 b) { return *reinterpret_cast<uint32_t*>(&b); }
__device__ __forceinline__ uint32_t pack2(float lo, float hi) {
  uint32_t r; asm("cvt.rn.bf16x2.f32 %0, %1, %2;" : "=r"(r) : "f"(hi), "f"(lo)); return r;
}
__device__ __forceinline__ uint32_t hadd(uint32_t a, uint32_t b) { return b2u(__hadd2_rn(u2b(a), u2b(b))); }
__device__ __forceinline__ uint32_t hmul(uint32_t a, uint32_t b) { return b2u(__hmul2_rn(u2b(a), u2b(b))); }
__device__ __forceinline__ uint32_t hfma(uint32_t a, uint32_t b, uint32_t c) { return b2u(__hfma2(u2b(a), u2b(b), u2b(c))); }
__device__ __forceinline__ uint32_t hmax(uint32_t a, uint32_t b) { return b2u(__hmax2(u2b(a), u2b(b))); }
template <int HI> __device__ __forceinline__ bf2 bcast(uint32_t a) { return HI ? __high2bfloat162(u2b(a)) : __low2bfloat162(u2b(a)); }
template <int HI> __device__ __forceinline__ uint32_t hmul_b(uint32_t a, uint32_t s) { return b2u(__hmul2_rn(u2b(a), bcast<HI>(s))); }
template <int HI> __device__ __forceinline__ uint32_t hsub_b(uint32_t a, uint32_t s) { return b2u(__hsub2_rn(u2b(a), bcast<HI>(s))); }
__device__ __forceinline__ uint32_t hex2(uint32_t a) { uint32_t r; asm("ex2.approx.ftz.bf16x2 %0, %1;" : "=r"(r) : "r"(a)); return r; }
__device__ __forceinline__ uint32_t hex1(uint32_t a) {
  uint32_t r; asm("{\n.reg .b16 l, h, e;\nmov.b32 {l, h}, %1;\nex2.approx.ftz.bf16 e, l;\ncvt.u32.u16 %0, e;\n}\n" : "=r"(r) : "r"(a)); return r;
}
__device__ __forceinline__ float lo2f(uint32_t a) { return __uint_as_float(a << 16); }
__device__ __forceinline__ float hi2f(uint32_t a) { return __uint_as_float(a & 0xffff0000u); }

__device__ __forceinline__ void mbar_init(uint32_t bar, uint32_t cnt) { asm volatile("mbarrier.init.shared::cta.b64 [%0], %1;" :: "r"(bar), "r"(cnt) : "memory"); }
__device__ __forceinline__ void mbar_arrive(uint32_t bar) { asm volatile("mbarrier.arrive.shared::cta.b64 _, [%0];" :: "r"(bar) : "memory"); }
__device__ __forceinline__ void mbar_expect(uint32_t bar, uint32_t bytes) { asm volatile("mbarrier.arrive.expect_tx.shared::cta.b64 _, [%0], %1;" :: "r"(bar), "r"(bytes) : "memory"); }
__device__ __forceinline__ bool mbar_try(uint32_t bar, uint32_t parity) {
  uint32_t ok;
  asm volatile("{\n.reg .pred p;\nmbarrier.try_wait.parity.shared::cta.b64 p, [%1], %2;\nselp.u32 %0, 1, 0, p;\n}\n" : "=r"(ok) : "r"(bar), "r"(parity) : "memory");
  return ok != 0;
}
__device__ __forceinline__ void mbar_wait(uint32_t bar, uint32_t parity) {
  uint32_t n = 0;
  while (!mbar_try(bar, parity)) { if (++n > (1u << 22)) __trap(); }
}
__device__ __forceinline__ void wg_fence() { asm volatile("wgmma.fence.sync.aligned;" ::: "memory"); }
__device__ __forceinline__ void wg_commit() { asm volatile("wgmma.commit_group.sync.aligned;" ::: "memory"); }
template <int N> __device__ __forceinline__ void wg_wait() { asm volatile("wgmma.wait_group.sync.aligned %0;" :: "n"(N) : "memory"); }
__device__ __forceinline__ void bar_sync(int id) { asm volatile("bar.sync %0, 128;" :: "r"(id) : "memory"); }
__device__ __forceinline__ void stsm4(uint32_t addr, uint32_t a, uint32_t b, uint32_t c, uint32_t d) {
  asm volatile("stmatrix.sync.aligned.m8n8.x4.shared.b16 [%0], {%1,%2,%3,%4};" :: "r"(addr), "r"(a), "r"(b), "r"(c), "r"(d) : "memory");
}
template <int N> __device__ __forceinline__ void keep(float (&d)[N]) {
#pragma unroll
  for (int i = 0; i < N; i++) asm volatile("" : "+f"(d[i]) :: "memory");
}
__device__ __forceinline__ uint64_t mkdesc(uint32_t addr, uint32_t lbo, uint32_t sbo) {
  return ((uint64_t)(sbo >> 4) << 32) | ((uint64_t)(lbo >> 4) << 16) | (uint64_t)((addr & 0x3FFFF) >> 4);
}

template <int SCALE_D>
__device__ __forceinline__ void wgmma_n144(float (&d)[72], uint32_t a0, uint32_t a1, uint32_t a2, uint32_t a3, uint64_t descB) {
  asm volatile("wgmma.mma_async.sync.aligned.m64n144k16.f32.bf16.bf16 "
    "{%0, %1, %2, %3, %4, %5, %6, %7, %8, %9, %10, %11, %12, %13, %14, %15, "
    "%16, %17, %18, %19, %20, %21, %22, %23, %24, %25, %26, %27, %28, %29, %30, %31, "
    "%32, %33, %34, %35, %36, %37, %38, %39, %40, %41, %42, %43, %44, %45, %46, %47, "
    "%48, %49, %50, %51, %52, %53, %54, %55, %56, %57, %58, %59, %60, %61, %62, %63, "
    "%64, %65, %66, %67, %68, %69, %70, %71}, "
    "{%72, %73, %74, %75}, %76, %77, 1, 1, 0;\n"
    : "+f"(d[0]), "+f"(d[1]), "+f"(d[2]), "+f"(d[3]), "+f"(d[4]), "+f"(d[5]), "+f"(d[6]), "+f"(d[7]),
      "+f"(d[8]), "+f"(d[9]), "+f"(d[10]), "+f"(d[11]), "+f"(d[12]), "+f"(d[13]), "+f"(d[14]), "+f"(d[15]),
      "+f"(d[16]), "+f"(d[17]), "+f"(d[18]), "+f"(d[19]), "+f"(d[20]), "+f"(d[21]), "+f"(d[22]), "+f"(d[23]),
      "+f"(d[24]), "+f"(d[25]), "+f"(d[26]), "+f"(d[27]), "+f"(d[28]), "+f"(d[29]), "+f"(d[30]), "+f"(d[31]),
      "+f"(d[32]), "+f"(d[33]), "+f"(d[34]), "+f"(d[35]), "+f"(d[36]), "+f"(d[37]), "+f"(d[38]), "+f"(d[39]),
      "+f"(d[40]), "+f"(d[41]), "+f"(d[42]), "+f"(d[43]), "+f"(d[44]), "+f"(d[45]), "+f"(d[46]), "+f"(d[47]),
      "+f"(d[48]), "+f"(d[49]), "+f"(d[50]), "+f"(d[51]), "+f"(d[52]), "+f"(d[53]), "+f"(d[54]), "+f"(d[55]),
      "+f"(d[56]), "+f"(d[57]), "+f"(d[58]), "+f"(d[59]), "+f"(d[60]), "+f"(d[61]), "+f"(d[62]), "+f"(d[63]),
      "+f"(d[64]), "+f"(d[65]), "+f"(d[66]), "+f"(d[67]), "+f"(d[68]), "+f"(d[69]), "+f"(d[70]), "+f"(d[71])
    : "r"(a0), "r"(a1), "r"(a2), "r"(a3), "l"(descB), "n"(SCALE_D));
}

template <int SCALE_D>
__device__ __forceinline__ void wgmma_n96(float (&d)[48], uint32_t a0, uint32_t a1, uint32_t a2, uint32_t a3, uint64_t descB) {
  asm volatile("wgmma.mma_async.sync.aligned.m64n96k16.f32.bf16.bf16 "
    "{%0, %1, %2, %3, %4, %5, %6, %7, %8, %9, %10, %11, %12, %13, %14, %15, "
    "%16, %17, %18, %19, %20, %21, %22, %23, %24, %25, %26, %27, %28, %29, %30, %31, "
    "%32, %33, %34, %35, %36, %37, %38, %39, %40, %41, %42, %43, %44, %45, %46, %47}, "
    "{%48, %49, %50, %51}, %52, %53, 1, 1, 0;\n"
    : "+f"(d[0]), "+f"(d[1]), "+f"(d[2]), "+f"(d[3]), "+f"(d[4]), "+f"(d[5]), "+f"(d[6]), "+f"(d[7]),
      "+f"(d[8]), "+f"(d[9]), "+f"(d[10]), "+f"(d[11]), "+f"(d[12]), "+f"(d[13]), "+f"(d[14]), "+f"(d[15]),
      "+f"(d[16]), "+f"(d[17]), "+f"(d[18]), "+f"(d[19]), "+f"(d[20]), "+f"(d[21]), "+f"(d[22]), "+f"(d[23]),
      "+f"(d[24]), "+f"(d[25]), "+f"(d[26]), "+f"(d[27]), "+f"(d[28]), "+f"(d[29]), "+f"(d[30]), "+f"(d[31]),
      "+f"(d[32]), "+f"(d[33]), "+f"(d[34]), "+f"(d[35]), "+f"(d[36]), "+f"(d[37]), "+f"(d[38]), "+f"(d[39]),
      "+f"(d[40]), "+f"(d[41]), "+f"(d[42]), "+f"(d[43]), "+f"(d[44]), "+f"(d[45]), "+f"(d[46]), "+f"(d[47])
    : "r"(a0), "r"(a1), "r"(a2), "r"(a3), "l"(descB), "n"(SCALE_D));
}

template <int SCALE_D>
__device__ __forceinline__ void wgmma_n56(float (&d)[28], uint32_t a0, uint32_t a1, uint32_t a2, uint32_t a3, uint64_t descB) {
  asm volatile("wgmma.mma_async.sync.aligned.m64n56k16.f32.bf16.bf16 "
    "{%0, %1, %2, %3, %4, %5, %6, %7, %8, %9, %10, %11, %12, %13, %14, %15, "
    "%16, %17, %18, %19, %20, %21, %22, %23, %24, %25, %26, %27}, "
    "{%28, %29, %30, %31}, %32, %33, 1, 1, 0;\n"
    : "+f"(d[0]), "+f"(d[1]), "+f"(d[2]), "+f"(d[3]), "+f"(d[4]), "+f"(d[5]), "+f"(d[6]), "+f"(d[7]),
      "+f"(d[8]), "+f"(d[9]), "+f"(d[10]), "+f"(d[11]), "+f"(d[12]), "+f"(d[13]), "+f"(d[14]), "+f"(d[15]),
      "+f"(d[16]), "+f"(d[17]), "+f"(d[18]), "+f"(d[19]), "+f"(d[20]), "+f"(d[21]), "+f"(d[22]), "+f"(d[23]),
      "+f"(d[24]), "+f"(d[25]), "+f"(d[26]), "+f"(d[27])
    : "r"(a0), "r"(a1), "r"(a2), "r"(a3), "l"(descB), "n"(SCALE_D));
}

template <int SCALE_D>
__device__ __forceinline__ void wgmma_n56t(float (&d)[28], uint32_t a0, uint32_t a1, uint32_t a2, uint32_t a3, uint64_t descB) {
  asm volatile("wgmma.mma_async.sync.aligned.m64n56k16.f32.bf16.bf16 "
    "{%0, %1, %2, %3, %4, %5, %6, %7, %8, %9, %10, %11, %12, %13, %14, %15, "
    "%16, %17, %18, %19, %20, %21, %22, %23, %24, %25, %26, %27}, "
    "{%28, %29, %30, %31}, %32, %33, 1, 1, 1;\n"
    : "+f"(d[0]), "+f"(d[1]), "+f"(d[2]), "+f"(d[3]), "+f"(d[4]), "+f"(d[5]), "+f"(d[6]), "+f"(d[7]),
      "+f"(d[8]), "+f"(d[9]), "+f"(d[10]), "+f"(d[11]), "+f"(d[12]), "+f"(d[13]), "+f"(d[14]), "+f"(d[15]),
      "+f"(d[16]), "+f"(d[17]), "+f"(d[18]), "+f"(d[19]), "+f"(d[20]), "+f"(d[21]), "+f"(d[22]), "+f"(d[23]),
      "+f"(d[24]), "+f"(d[25]), "+f"(d[26]), "+f"(d[27])
    : "r"(a0), "r"(a1), "r"(a2), "r"(a3), "l"(descB), "n"(SCALE_D));
}


__global__ void __launch_bounds__(192) prepack_kernel(const __nv_bfloat16* __restrict__ wqkv, const __nv_bfloat16* __restrict__ wo) {
  __nv_bfloat16* dst = reinterpret_cast<__nv_bfloat16*>(g_wpack);
  const int c = threadIdx.x, nb = blockIdx.x;
  if (nb < 72) {
    __shared__ float red[6][8];
    const int h = nb / 18, j = nb % 18, part = j / 6;
    const int col = (part == 0 ? 192 : part == 1 ? 384 : 0) + h * 48 + (j % 6) * 8;
    uint4 raw = *reinterpret_cast<const uint4*>(wqkv + c * 576 + col);
    uint32_t u[4] = {raw.x, raw.y, raw.z, raw.w};
    float v[8];
#pragma unroll
    for (int i = 0; i < 4; i++) { v[2 * i] = lo2f(u[i]); v[2 * i + 1] = hi2f(u[i]); }
#pragma unroll
    for (int i = 0; i < 8; i++) {
      float s = v[i];
#pragma unroll
      for (int o = 16; o; o >>= 1) s += __shfl_xor_sync(~0u, s, o);
      if ((c & 31) == 0) red[c >> 5][i] = s;
    }
    __syncthreads();
    const int cc = c >> 5, q = (c >> 3) & 3, s1 = (c >> 2) & 1, hh = (c >> 1) & 1, e = c & 1;
    const int base = h * 27648 + (2 * cc + s1) * 2304 + j * 128 + hh * 64 + 2 * q + e;
#pragma unroll
    for (int n = 0; n < 8; n++) {
      float m = (red[0][n] + red[1][n] + red[2][n] + red[3][n] + red[4][n] + red[5][n]) * (1.0f / 192.0f);
      dst[base + n * 8] = __float2bfloat16(v[n] - m);
    }
  } else {
    const int jb = nb - 72, half = jb / 12, j = jb % 12;
    const int s = c >> 4, hh = (c >> 3) & 1, kk = c & 7;
    const int base = 110592 + half * 18432 + s * 1536 + j * 128 + hh * 64 + kk;
#pragma unroll
    for (int n = 0; n < 8; n++) {
      const int ch = 32 * (jb >> 2) + 8 * (n >> 1) + 2 * (jb & 3) + (n & 1);
      dst[base + n * 8] = wo[c * 192 + ch];
    }
  }
}

__device__ __forceinline__ int window_of(int round, int nfull, int cta, int ncta, int wg) {
  if (round < nfull) return round * 2 * ncta + 2 * cta + wg;
  const int rem = NWIN - nfull * 2 * ncta;
  const int i = cta + wg * ncta;
  return i < rem ? nfull * 2 * ncta + i : -1;
}

__device__ __forceinline__ constexpr int qkv_off(int h, int s) { return ((3 * h + s / 4) % 8) * SLICE + (s % 4) * 4608; }
__device__ __forceinline__ constexpr int wo_off(int half, int s) { return ((12 + 2 * half + s / 6) % 8) * SLICE + (s % 6) * 3072; }

template <int H>
__device__ __forceinline__ void issue_qkv(float (&acc)[72], const uint32_t (&X)[48], uint64_t dW) {
#pragma unroll
  for (int s = 0; s < 12; s++) {
    if (s == 0) wgmma_n144<0>(acc, X[4 * s], X[4 * s + 1], X[4 * s + 2], X[4 * s + 3], dW + (qkv_off(H, s) >> 4));
    else        wgmma_n144<1>(acc, X[4 * s], X[4 * s + 1], X[4 * s + 2], X[4 * s + 3], dW + (qkv_off(H, s) >> 4));
  }
}

__device__ __forceinline__ void finish_o(const float (&o)[28], uint32_t* Of) {
  const uint32_t inv = pack2(__fdividef(1.0f, o[24]), __fdividef(1.0f, o[26]));
#pragma unroll
  for (int j = 0; j < 6; j++) {
    Of[2 * j]     = hmul_b<0>(pack2(o[4 * j], o[4 * j + 1]), inv);
    Of[2 * j + 1] = hmul_b<1>(pack2(o[4 * j + 2], o[4 * j + 3]), inv);
  }
}

__global__ void __launch_bounds__(384, 1)
fused_kernel(const __grid_constant__ CUtensorMap tmx, const __nv_bfloat16* __restrict__ dw, __nv_bfloat16* __restrict__ out) {
  extern __shared__ __align__(1024) uint8_t smem[];
  const uint32_t sb = (uint32_t)__cvta_generic_to_shared(smem);
  const int tid = threadIdx.x, warp = tid >> 5, lane = tid & 31;
  const int cta = blockIdx.x, ncta = gridDim.x;
  const int nfull = NWIN / (2 * ncta);
  const int nrounds = nfull + ((NWIN - nfull * 2 * ncta) > cta ? 1 : 0);

  if (tid == 0) {
    for (int i = 0; i < 6; i++) { mbar_init(sb + BAR_WFULL + 8 * i, 1); mbar_init(sb + BAR_WEMPTY + 8 * i, 8); }
    for (int i = 0; i < 9; i++) mbar_init(sb + BAR_XFULL + 8 * i, 1);
    mbar_init(sb + BAR_TFULL, 3);
    mbar_init(sb + BAR_TEMPTY, 8);
    asm volatile("fence.mbarrier_init.release.cluster;" ::: "memory");
  }
  if (tid < 128) {
    const uint32_t v = (tid & 63) < 49 ? 0x3f803f80u : 0u;
    *reinterpret_cast<uint4*>(smem + OFF_KV + (tid >> 6) * KV_BYTES + 6 * KV_PITCH + (tid & 63) * 16) = make_uint4(v, v, v, v);
    asm volatile("fence.proxy.async.shared::cta;" ::: "memory");
  }
  __syncthreads();

  if (warp >= 8) {
    asm volatile("setmaxnreg.dec.sync.aligned.u32 88;");
    if (warp == 11) {
      if (lane == 0) {
        const uint8_t* wp = reinterpret_cast<const uint8_t*>(g_wpack);
        for (int r = 0; r < nrounds; r++) {
#pragma unroll
          for (int k = 0; k < 16; k++) {
            const int st = k < 12 ? k / 3 : 4 + (k - 12) / 2;
            const int kp = (k + 8) & 15;
            const int stp = kp < 12 ? kp / 3 : 4 + (kp - 12) / 2;
            const bool first_of_prev = (k == 0) || (stp != (((k + 7) & 15) < 12 ? ((k + 7) & 15) / 3 : 4 + (((k + 7) & 15) - 12) / 2));
            if (first_of_prev || k == 8) {
              if (k >= 8) mbar_wait(sb + BAR_WEMPTY + 8 * stp, r & 1);
              else if (r > 0) mbar_wait(sb + BAR_WEMPTY + 8 * stp, (r - 1) & 1);
            }
            const bool first = k < 12 ? (k % 3 == 0) : (k % 2 == 0);
            if (first) mbar_expect(sb + BAR_WFULL + 8 * st, (k < 12 ? 3 : 2) * SLICE);
            asm volatile("cp.async.bulk.shared::cluster.global.mbarrier::complete_tx::bytes [%0], [%1], %2, [%3];"
                         :: "r"(sb + OFF_W + (k & 7) * SLICE), "l"(wp + k * SLICE), "n"(SLICE), "r"(sb + BAR_WFULL + 8 * st) : "memory");
          }
        }
      }
    } else {
      const int cw = warp - 8;
      const int box = 2 * cw + (lane >> 4);
      const int win = box / 3, cblk = box % 3;
      const int ch0 = cblk * 64 + (lane & 15) * 4;
      uint32_t wt[9][2];
#pragma unroll
      for (int t = 0; t < 9; t++) {
        uint2 v = *reinterpret_cast<const uint2*>(dw + t * CH + ch0);
        wt[t][0] = v.x; wt[t][1] = v.y;
      }
      const uint32_t xs = sb + OFF_X + cw * 3 * XSLOT;
      const uint32_t xld = xs + (lane >> 4) * 1152 + (lane & 15) * 8;
      const uint32_t xbar = sb + BAR_XFULL + cw * 24;
      const uint32_t st0 = sb + OFF_TILE + win * TILE_BYTES + ch0 * 4;
      const uint32_t st1 = sb + OFF_TILE + win * TILE_BYTES + ((ch0 * 4) ^ 16);
      const uint64_t tm = reinterpret_cast<uint64_t>(&tmx);
      auto coords = [&](int r, int& cx, int& cy) {
        int w = window_of(r, nfull, cta, ncta, win);
        if (w < 0) w = window_of(r, nfull, cta, ncta, 0);
        const int wy = w / NWX, wx = w - wy * NWX;
        cx = wx * 7 - 1; cy = wy * 7 - 1;
      };
      auto issue = [&](int slot, int cx, int cy) {
        if (lane == 0) mbar_expect(xbar + slot * 8, XSLOT);
        __syncwarp();
        if ((lane & 15) == 0)
          asm volatile("cp.async.bulk.tensor.3d.shared::cluster.global.mbarrier::complete_tx::bytes [%0], [%1, {%3, %4, %5}], [%2];"
                       :: "r"(xs + slot * XSLOT + (lane >> 4) * 1152), "l"(tm), "r"(xbar + slot * 8), "r"(cblk * 64), "r"(cx), "r"(cy) : "memory");
      };
      int cx, cy, nx = 0, ny = 0;
      coords(0, cx, cy);
      issue(0, cx, cy); issue(1, cx, cy + 1); issue(2, cx, cy + 2);
      for (int r = 0; r < nrounds; r++) {
        const bool more = r + 1 < nrounds;
        if (more) coords(r + 1, nx, ny);
        uint32_t accA[7][2], accB[7][2], ctr[7][2], held[2];
#pragma unroll
        for (int i = 0; i < 9; i++) {
          mbar_wait(xbar + (i % 3) * 8, (r + i / 3) & 1);
          if (i == 2 && r > 0) mbar_wait(sb + BAR_TEMPTY, (r - 1) & 1);
          uint32_t cur[9][2];
#pragma unroll
          for (int p = 0; p < 5; p++)
            asm volatile("ld.shared.v2.u32 {%0,%1}, [%2];" : "=r"(cur[p][0]), "=r"(cur[p][1]) : "r"(xld + (i % 3) * XSLOT + p * 128));
#pragma unroll
          for (int j = 0; j < 7; j++) {
            if (j >= 1 && j + 4 < 9)
              asm volatile("ld.shared.v2.u32 {%0,%1}, [%2];" : "=r"(cur[j + 4][0]), "=r"(cur[j + 4][1]) : "r"(xld + (i % 3) * XSLOT + (j + 4) * 128));
            if (i >= 2) {
              uint32_t o[2];
#pragma unroll
              for (int e = 0; e < 2; e++) {
                uint32_t a = hfma(cur[j][e], wt[6][e], accA[j][e]);
                a = hfma(cur[j + 1][e], wt[7][e], a);
                a = hfma(cur[j + 2][e], wt[8][e], a);
                o[e] = hadd(ctr[j][e], a);
              }
              const int tok = (i - 2) * 7 + j, ps = tok >> 1;
              if (!(tok & 1)) { held[0] = o[0]; held[1] = o[1]; }
              if ((tok & 1) || tok == 48)
                asm volatile("st.shared.v4.u32 [%0], {%1,%2,%3,%4};" :: "r"(((ps & 1) ? st1 : st0) + ps * 768), "r"(held[0]), "r"(o[0]), "r"(held[1]), "r"(o[1]) : "memory");
            }
#pragma unroll
            for (int e = 0; e < 2; e++) {
              if (i >= 1 && i <= 7) {
                uint32_t a = hfma(cur[j][e], wt[3][e], accB[j][e]);
                a = hfma(cur[j + 1][e], wt[4][e], a);
                accA[j][e] = hfma(cur[j + 2][e], wt[5][e], a);
                ctr[j][e] = cur[j + 1][e];
              }
              if (i <= 6) {
                uint32_t a = hmul(cur[j][e], wt[0][e]);
                a = hfma(cur[j + 1][e], wt[1][e], a);
                accB[j][e] = hfma(cur[j + 2][e], wt[2][e], a);
              }
            }
          }
          __syncwarp();
          if (i < 6) issue(i % 3, cx, cy + i + 3);
          else if (more) issue(i % 3, nx, ny + i - 6);
        }
        __syncwarp();
        if (lane == 0) mbar_arrive(sb + BAR_TFULL);
        cx = nx; cy = ny;
      }
    }
  } else {
    asm volatile("setmaxnreg.inc.sync.aligned.u32 208;");
    const int wg = warp >> 2, w4 = warp & 3, g = lane >> 2, q = lane & 3;
    const int row0 = w4 * 16 + g, row1 = row0 + 8;
    const int ps = min(w4 * 8 + g, 24);
    const int tok0 = 2 * ps, tok1 = min(2 * ps + 1, 48);
    const uint32_t kv = sb + OFF_KV + wg * KV_BYTES;
    const int srow = w4 * 16 + (lane & 15);
    const uint32_t vst = kv + (lane >> 4) * KV_PITCH + srow * 16;
    const uint32_t kst = vst + (srow < 56 ? 1024 : 0);
    const uint64_t dW = mkdesc(sb + OFF_W, 128, 256);
    const uint64_t dK = mkdesc(kv + 1024, KV_PITCH, 128);
    const uint64_t dV = mkdesc(kv, 128, KV_PITCH);
    const uint32_t vmask = (row0 < 49 ? 0xffffu : 0u) | (row1 < 49 ? 0xffff0000u : 0u);
    const float qscale = 0.14433756729740643f * 1.4426950408889634f;

    for (int r = 0; r < nrounds; r++) {
      const uint32_t par = r & 1;
      const int w = window_of(r, nfull, cta, ncta, wg);
      if (w < 0) {
        for (int s = 0; s < 6; s++) { mbar_wait(sb + BAR_WFULL + 8 * s, par); if (lane == 0) mbar_arrive(sb + BAR_WEMPTY + 8 * s); }
        break;
      }
      uint32_t X[48];
      mbar_wait(sb + BAR_TFULL, par);
      {
        const uint32_t t0 = sb + OFF_TILE + wg * TILE_BYTES + ps * 768 + q * 32 + (ps & 1) * 16;
#pragma unroll
        for (int s = 0; s < 12; s++)
          asm volatile("ld.shared.v4.u32 {%0,%1,%2,%3}, [%4];" : "=r"(X[4 * s]), "=r"(X[4 * s + 1]), "=r"(X[4 * s + 2]), "=r"(X[4 * s + 3])
                       : "r"(((s & 1) ? (t0 ^ 16) : t0) + (s >> 1) * 128));
      }
      uint32_t rK, rV, rQ;
      {
        uint32_t sm[2];
#pragma unroll
        for (int a = 0; a < 2; a++) {
          uint32_t t[12];
#pragma unroll
          for (int i = 0; i < 12; i++) t[i] = hadd(X[4 * i + a], X[4 * i + 2 + a]);
#pragma unroll
          for (int i = 0; i < 6; i++) t[i] = hadd(t[i], t[i + 6]);
#pragma unroll
          for (int i = 0; i < 3; i++) t[i] = hadd(t[i], t[i + 3]);
          sm[a] = hadd(hadd(t[0], t[1]), t[2]);
        }
        __syncwarp();
        if (lane == 0) mbar_arrive(sb + BAR_TEMPTY);
        uint32_t m = hadd(__byte_perm(sm[0], sm[1], 0x5410), __byte_perm(sm[0], sm[1], 0x7632));
        m = hadd(m, __shfl_xor_sync(~0u, m, 1));
        m = hadd(m, __shfl_xor_sync(~0u, m, 2));
        m = hmul(m, 0x3bab3babu);
        float var[2];
#pragma unroll
        for (int a = 0; a < 2; a++) {
          uint32_t t[4];
#pragma unroll
          for (int i = 0; i < 24; i++) {
            const uint32_t d = a ? hsub_b<1>(X[2 * i + 1], m) : hsub_b<0>(X[2 * i], m);
            t[i & 3] = i < 4 ? hmul(d, d) : hfma(d, d, t[i & 3]);
          }
          const uint32_t s = hadd(hadd(t[0], t[1]), hadd(t[2], t[3]));
          float v = lo2f(s) + hi2f(s);
          v += __shfl_xor_sync(~0u, v, 1);
          v += __shfl_xor_sync(~0u, v, 2);
          var[a] = rsqrtf(fmaf(v, 1.0f / 192.0f, 1e-5f));
        }
        rK = pack2(var[0], var[1]);
        rV = rK & vmask;
        rQ = pack2(var[0] * qscale, var[1] * qscale);
      }

      uint32_t Of[48];
      float acc[72];
      float oacc[28];
#define HEAD(H)                                                                                         \
      {                                                                                                 \
        mbar_wait(sb + BAR_WFULL + 8 * H, par);                                                         \
        if (H == 3) { wg_wait<0>(); keep(oacc); }                                                       \
        wg_fence();                                                                                     \
        issue_qkv<H>(acc, X, dW);                                                                       \
        wg_commit();                                                                                    \
        if (H > 0) {                                                                                    \
          if (H < 3) { wg_wait<1>(); keep(oacc); }                                                      \
          bar_sync(1 + wg);                                                                             \
          finish_o(oacc, Of + 12 * (H > 0 ? H - 1 : 0));                                                \
        }                                                                                               \
        wg_wait<0>(); keep(acc);                                                                        \
        if (lane == 0) mbar_arrive(sb + BAR_WEMPTY + 8 * H);                                            \
        _Pragma("unroll") for (int j = 0; j < 6; j += 2)                                                \
          stsm4(kst + j * KV_PITCH, hmul_b<0>(pack2(acc[4 * j], acc[4 * j + 1]), rK), hmul_b<1>(pack2(acc[4 * j + 2], acc[4 * j + 3]), rK), \
                hmul_b<0>(pack2(acc[4 * j + 4], acc[4 * j + 5]), rK), hmul_b<1>(pack2(acc[4 * j + 6], acc[4 * j + 7]), rK));                 \
        _Pragma("unroll") for (int j = 0; j < 6; j += 2)                                                \
          stsm4(vst + j * KV_PITCH, hmul_b<0>(pack2(acc[24 + 4 * j], acc[25 + 4 * j]), rV), hmul_b<1>(pack2(acc[26 + 4 * j], acc[27 + 4 * j]), rV), \
                hmul_b<0>(pack2(acc[28 + 4 * j], acc[29 + 4 * j]), rV), hmul_b<1>(pack2(acc[30 + 4 * j], acc[31 + 4 * j]), rV));             \
        asm volatile("fence.proxy.async.shared::cta;" ::: "memory");                                    \
        uint32_t Q[12];                                                                                 \
        _Pragma("unroll") for (int j = 0; j < 6; j++) {                                                 \
          Q[2 * j] = hmul_b<0>(pack2(acc[48 + 4 * j], acc[49 + 4 * j]), rQ);                            \
          Q[2 * j + 1] = hmul_b<1>(pack2(acc[50 + 4 * j], acc[51 + 4 * j]), rQ);                        \
        }                                                                                               \
        bar_sync(1 + wg);                                                                               \
        float S[28];                                                                                    \
        wg_fence();                                                                                     \
        wgmma_n56<0>(S, Q[0], Q[1], Q[2], Q[3], dK);                                                    \
        wgmma_n56<1>(S, Q[4], Q[5], Q[6], Q[7], dK + (2 * KV_PITCH >> 4));                              \
        wgmma_n56<1>(S, Q[8], Q[9], Q[10], Q[11], dK + (4 * KV_PITCH >> 4));                            \
        wg_commit();                                                                                    \
        wg_wait<0>(); keep(S);                                                                          \
        uint32_t P[16];                                                                                 \
        _Pragma("unroll") for (int j = 0; j < 14; j++) P[j] = pack2(S[2 * j], S[2 * j + 1]);            \
        uint32_t m0 = hmax(hmax(hmax(P[0], P[2]), P[4]), hmax(hmax(P[6], P[8]), hmax(P[10], P[12])));   \
        uint32_t m1 = hmax(hmax(hmax(P[1], P[3]), P[5]), hmax(hmax(P[7], P[9]), hmax(P[11], P[13])));   \
        uint32_t mx = hmax(__byte_perm(m0, m1, 0x5410), __byte_perm(m0, m1, 0x7632));                   \
        mx = hmax(mx, __shfl_xor_sync(~0u, mx, 1));                                                     \
        mx = hmax(mx, __shfl_xor_sync(~0u, mx, 2));                                                     \
        P[14] = hsub_b<0>(P[12], mx); P[15] = hsub_b<1>(P[13], mx);                                     \
        P[12] = hex1(P[14]); P[13] = hex1(P[15]);                                                       \
        _Pragma("unroll") for (int j = 0; j < 12; j++) P[j] = hex2((j & 1) ? hsub_b<1>(P[j], mx) : hsub_b<0>(P[j], mx)); \
        wg_fence();                                                                                     \
        wgmma_n56t<0>(oacc, P[0], P[1], P[2], P[3], dV);                                                \
        wgmma_n56t<1>(oacc, P[4], P[5], P[6], P[7], dV + (256 >> 4));                                   \
        wgmma_n56t<1>(oacc, P[8], P[9], P[10], P[11], dV + (512 >> 4));                                 \
        wgmma_n56t<1>(oacc, P[12], P[13], P[14], P[15], dV + (768 >> 4));                               \
        wg_commit();                                                                                    \
      }
      HEAD(0) HEAD(1) HEAD(2) HEAD(3)
#undef HEAD
      wg_wait<0>(); keep(oacc);
      finish_o(oacc, Of + 36);

      const int wy = w / NWX, wx = w - wy * NWX;
      uint8_t* ob = reinterpret_cast<uint8_t*>(out) + (size_t)(wy * 7 * IMG + wx * 7) * 384 + q * 16;
      uint8_t* o0 = ob + ((tok0 / 7) * IMG + tok0 % 7) * 384;
      uint8_t* o1 = ob + ((tok1 / 7) * IMG + tok1 % 7) * 384;
#pragma unroll
      for (int half = 0; half < 2; half++) {
        float pacc[48];
        mbar_wait(sb + BAR_WFULL + 8 * (4 + half), par);
        wg_fence();
#pragma unroll
        for (int s = 0; s < 12; s++) {
          if (s == 0) wgmma_n96<0>(pacc, Of[4 * s], Of[4 * s + 1], Of[4 * s + 2], Of[4 * s + 3], dW + (wo_off(half, s) >> 4));
          else        wgmma_n96<1>(pacc, Of[4 * s], Of[4 * s + 1], Of[4 * s + 2], Of[4 * s + 3], dW + (wo_off(half, s) >> 4));
        }
        wg_commit();
        if (half == 0) bar_sync(1 + wg);
        wg_wait<0>(); keep(pacc);
        if (lane == 0) mbar_arrive(sb + BAR_WEMPTY + 8 * (4 + half));
#pragma unroll
        for (int c = 0; c < 3; c++) {
          const int cc = half * 3 + c;
          uint4 a, b;
          a.x = hadd(X[8 * cc],     pack2(pacc[16 * c],      pacc[16 * c + 1]));
          b.x = hadd(X[8 * cc + 1], pack2(pacc[16 * c + 2],  pacc[16 * c + 3]));
          a.y = hadd(X[8 * cc + 2], pack2(pacc[16 * c + 4],  pacc[16 * c + 5]));
          b.y = hadd(X[8 * cc + 3], pack2(pacc[16 * c + 6],  pacc[16 * c + 7]));
          a.z = hadd(X[8 * cc + 4], pack2(pacc[16 * c + 8],  pacc[16 * c + 9]));
          b.z = hadd(X[8 * cc + 5], pack2(pacc[16 * c + 10], pacc[16 * c + 11]));
          a.w = hadd(X[8 * cc + 6], pack2(pacc[16 * c + 12], pacc[16 * c + 13]));
          b.w = hadd(X[8 * cc + 7], pack2(pacc[16 * c + 14], pacc[16 * c + 15]));
          if (row0 < 49) *reinterpret_cast<uint4*>(o0 + cc * 64) = a;
          if (row1 < 49) *reinterpret_cast<uint4*>(o1 + cc * 64) = b;
        }
      }
    }
  }
}

typedef CUresult (*EncodeFn)(CUtensorMap*, CUtensorMapDataType, cuuint32_t, void*, const cuuint64_t*, const cuuint64_t*,
                             const cuuint32_t*, const cuuint32_t*, CUtensorMapInterleave, CUtensorMapSwizzle,
                             CUtensorMapL2promotion, CUtensorMapFloatOOBfill);

}

extern "C" void kernel_launch(void* const* d_in, const int* in_sizes, int n_in, void* d_out, int out_size) {
  const __nv_bfloat16* x = (const __nv_bfloat16*)d_in[0];
  const __nv_bfloat16* dw = (const __nv_bfloat16*)d_in[1];
  const __nv_bfloat16* wqkv = (const __nv_bfloat16*)d_in[2];
  const __nv_bfloat16* wo = (const __nv_bfloat16*)d_in[3];
  static EncodeFn encode = nullptr;
  static int nsm = 0;
  if (!encode) {
    void* fn = nullptr;
    cudaDriverEntryPointQueryResult qr;
    cudaGetDriverEntryPoint("cuTensorMapEncodeTiled", &fn, cudaEnableDefault, &qr);
    encode = (EncodeFn)fn;
    int dev = 0;
    cudaGetDevice(&dev);
    cudaDeviceGetAttribute(&nsm, cudaDevAttrMultiProcessorCount, dev);
    cudaFuncSetAttribute(fused_kernel, cudaFuncAttributeMaxDynamicSharedMemorySize, SMEM_BYTES);
  }
  CUtensorMap tmx;
  cuuint64_t gdim[3] = {CH, IMG, IMG};
  cuuint64_t gstr[2] = {CH * 2, (cuuint64_t)CH * 2 * IMG};
  cuuint32_t box[3] = {64, 9, 1};
  cuuint32_t estr[3] = {1, 1, 1};
  encode(&tmx, CU_TENSOR_MAP_DATA_TYPE_BFLOAT16, 3, (void*)x, gdim, gstr, box, estr, CU_TENSOR_MAP_INTERLEAVE_NONE,
         CU_TENSOR_MAP_SWIZZLE_NONE, CU_TENSOR_MAP_L2_PROMOTION_L2_128B, CU_TENSOR_MAP_FLOAT_OOB_FILL_NONE);
  prepack_kernel<<<96, 192>>>(wqkv, wo);
  fused_kernel<<<nsm, 384, SMEM_BYTES>>>(tmx, dw, (__nv_bfloat16*)d_out);
}
```

```cpp
#include <cuda_runtime.h>
#include <cuda_bf16.h>
#include <cuda.h>
#include <stdint.h>

#define CREGS "208"
#define PREGS "88"
#define XWIN 0
namespace {

constexpr int IMG = 511;
constexpr int CH = 192;
constexpr int NWX = 73;
constexpr int NWIN = NWX * NWX;
constexpr int SLICE = 18432;
constexpr int OFF_W = 0;
constexpr int KV_BYTES = 12544, KV_PITCH = 1920;
constexpr int OFF_KV = 8 * SLICE;
constexpr int TILE_BYTES = 25 * 768;
constexpr int OFF_TILE = OFF_KV + 2 * KV_BYTES;
constexpr int XSLOT = 2304;
constexpr int OFF_X = OFF_TILE + 2 * TILE_BYTES;
constexpr int OFF_BAR = OFF_X + 9 * XSLOT;
constexpr int BAR_WFULL = OFF_BAR;
constexpr int BAR_WEMPTY = OFF_BAR + 48;
constexpr int BAR_XFULL = OFF_BAR + 96;
constexpr int BAR_TFULL = OFF_BAR + 168;
constexpr int BAR_TEMPTY = OFF_BAR + 176;
constexpr int SMEM_BYTES = OFF_BAR + 192;

__device__ uint4 g_wpack[16 * SLICE / 16];
#define TR(id)
template <int ID> __device__ __forceinline__ void sched_fence(uint32_t v) {
  asm volatile("{\n.reg .pred p;\nsetp.ne.u32 p, %0, %1;\n@p bra SF_%=;\ntrap;\nSF_%=:\n}\n" :: "r"(v), "n"(ID) : "memory");
}
__device__ __forceinline__ void anchor(uint32_t v) { sched_fence<0x7fc1ffc1>(v); }

typedef __nv_bfloat162 bf2;
__device__ __forceinline__ bf2 u2b(uint32_t u) { return *reinterpret_cast<bf2*>(&u); }
__device__ __forceinline__ uint32_t b2u(bf2 b) { return *reinterpret_cast<uint32_t*>(&b); }
__device__ __forceinline__ uint32_t pack2(float lo, float hi) {
  uint32_t r; asm("cvt.rn.bf16x2.f32 %0, %1, %2;" : "=r"(r) : "f"(hi), "f"(lo)); return r;
}
__device__ __forceinline__ uint32_t hadd(uint32_t a, uint32_t b) { return b2u(__hadd2_rn(u2b(a), u2b(b))); }
__device__ __forceinline__ uint32_t hmul(uint32_t a, uint32_t b) { return b2u(__hmul2_rn(u2b(a), u2b(b))); }
__device__ __forceinline__ uint32_t hfma(uint32_t a, uint32_t b, uint32_t c) { return b2u(__hfma2(u2b(a), u2b(b), u2b(c))); }
__device__ __forceinline__ uint32_t hmax(uint32_t a, uint32_t b) { return b2u(__hmax2(u2b(a), u2b(b))); }
template <int HI> __device__ __forceinline__ bf2 bcast(uint32_t a) { return HI ? __high2bfloat162(u2b(a)) : __low2bfloat162(u2b(a)); }
template <int HI> __device__ __forceinline__ uint32_t hmul_b(uint32_t a, uint32_t s) { return b2u(__hmul2_rn(u2b(a), bcast<HI>(s))); }
template <int HI> __device__ __forceinline__ uint32_t hsub_b(uint32_t a, uint32_t s) { return b2u(__hsub2_rn(u2b(a), bcast<HI>(s))); }
__device__ __forceinline__ uint32_t hex2(uint32_t a) { uint32_t r; asm("ex2.approx.ftz.bf16x2 %0, %1;" : "=r"(r) : "r"(a)); return r; }
__device__ __forceinline__ uint32_t hex1(uint32_t a) {
  uint32_t r; asm("{\n.reg .b16 l, h, e;\nmov.b32 {l, h}, %1;\nex2.approx.ftz.bf16 e, l;\ncvt.u32.u16 %0, e;\n}\n" : "=r"(r) : "r"(a)); return r;
}
__device__ __forceinline__ float lo2f(uint32_t a) { return __uint_as_float(a << 16); }
__device__ __forceinline__ float hi2f(uint32_t a) { return __uint_as_float(a & 0xffff0000u); }

__device__ __forceinline__ void mbar_init(uint32_t bar, uint32_t cnt) { asm volatile("mbarrier.init.shared::cta.b64 [%0], %1;" :: "r"(bar), "r"(cnt) : "memory"); }
__device__ __forceinline__ void mbar_arrive(uint32_t bar) { asm volatile("mbarrier.arrive.shared::cta.b64 _, [%0];" :: "r"(bar) : "memory"); }
__device__ __forceinline__ void mbar_expect(uint32_t bar, uint32_t bytes) { asm volatile("mbarrier.arrive.expect_tx.shared::cta.b64 _, [%0], %1;" :: "r"(bar), "r"(bytes) : "memory"); }
template <int HINT>
__device__ __forceinline__ bool mbar_try(uint32_t bar, uint32_t parity) {
  uint32_t ok;
  if (HINT) asm volatile("{\n.reg .pred p;\nmbarrier.try_wait.parity.shared::cta.b64 p, [%1], %2, %3;\nselp.u32 %0, 1, 0, p;\n}\n" : "=r"(ok) : "r"(bar), "r"(parity), "n"(HINT) : "memory");
  else asm volatile("{\n.reg .pred p;\nmbarrier.try_wait.parity.shared::cta.b64 p, [%1], %2;\nselp.u32 %0, 1, 0, p;\n}\n" : "=r"(ok) : "r"(bar), "r"(parity) : "memory");
  return ok != 0;
}
__device__ __forceinline__ void mbar_wait(uint32_t bar, uint32_t parity) {
  if (__builtin_expect(!mbar_try<0>(bar, parity), 0)) {
    uint32_t n = 0;
    while (!mbar_try<4000>(bar, parity)) { if (++n > (1u << 20)) __trap(); }
  }
}
__device__ __forceinline__ void wg_fence() { asm volatile("wgmma.fence.sync.aligned;" ::: "memory"); }
__device__ __forceinline__ void wg_commit() { asm volatile("wgmma.commit_group.sync.aligned;" ::: "memory"); }
template <int N> __device__ __forceinline__ void wg_wait() { asm volatile("wgmma.wait_group.sync.aligned %0;" :: "n"(N) : "memory"); }
__device__ __forceinline__ void bar_sync(int id) { asm volatile("bar.sync %0, 128;" :: "r"(id) : "memory"); }
__device__ __forceinline__ void turn_wait(int wg) { asm volatile("bar.sync %0, 256;" :: "r"(3 + wg) : "memory"); }
__device__ __forceinline__ void turn_pass(int wg) { asm volatile("bar.arrive %0, 256;" :: "r"(4 - wg) : "memory"); }
__device__ __forceinline__ void stsm4(uint32_t addr, uint32_t a, uint32_t b, uint32_t c, uint32_t d) {
  asm volatile("stmatrix.sync.aligned.m8n8.x4.shared.b16 [%0], {%1,%2,%3,%4};" :: "r"(addr), "r"(a), "r"(b), "r"(c), "r"(d) : "memory");
}
template <int N> __device__ __forceinline__ void keep(float (&d)[N]) {
#pragma unroll
  for (int i = 0; i < N; i++) asm volatile("" : "+f"(d[i]) :: "memory");
}
__device__ __forceinline__ uint64_t mkdesc(uint32_t addr, uint32_t lbo, uint32_t sbo) {
  return ((uint64_t)(sbo >> 4) << 32) | (uint64_t)(((lbo >> 4) << 16) | ((addr & 0x3FFFF) >> 4));
}

template <int SCALE_D>
__device__ __forceinline__ void wgmma_n144(float (&d)[72], uint32_t a0, uint32_t a1, uint32_t a2, uint32_t a3, uint64_t descB) {
  if (SCALE_D == 0)
  asm volatile("wgmma.mma_async.sync.aligned.m64n144k16.f32.bf16.bf16 "
    "{%0, %1, %2, %3, %4, %5, %6, %7, %8, %9, %10, %11, %12, %13, %14, %15, "
    "%16, %17, %18, %19, %20, %21, %22, %23, %24, %25, %26, %27, %28, %29, %30, %31, "
    "%32, %33, %34, %35, %36, %37, %38, %39, %40, %41, %42, %43, %44, %45, %46, %47, "
    "%48, %49, %50, %51, %52, %53, %54, %55, %56, %57, %58, %59, %60, %61, %62, %63, "
    "%64, %65, %66, %67, %68, %69, %70, %71}, "
    "{%72, %73, %74, %75}, %76, 0, 1, 1, 0;\n"
    : "=f"(d[0]), "=f"(d[1]), "=f"(d[2]), "=f"(d[3]), "=f"(d[4]), "=f"(d[5]), "=f"(d[6]), "=f"(d[7]),
      "=f"(d[8]), "=f"(d[9]), "=f"(d[10]), "=f"(d[11]), "=f"(d[12]), "=f"(d[13]), "=f"(d[14]), "=f"(d[15]),
      "=f"(d[16]), "=f"(d[17]), "=f"(d[18]), "=f"(d[19]), "=f"(d[20]), "=f"(d[21]), "=f"(d[22]), "=f"(d[23]),
      "=f"(d[24]), "=f"(d[25]), "=f"(d[26]), "=f"(d[27]), "=f"(d[28]), "=f"(d[29]), "=f"(d[30]), "=f"(d[31]),
      "=f"(d[32]), "=f"(d[33]), "=f"(d[34]), "=f"(d[35]), "=f"(d[36]), "=f"(d[37]), "=f"(d[38]), "=f"(d[39]),
      "=f"(d[40]), "=f"(d[41]), "=f"(d[42]), "=f"(d[43]), "=f"(d[44]), "=f"(d[45]), "=f"(d[46]), "=f"(d[47]),
      "=f"(d[48]), "=f"(d[49]), "=f"(d[50]), "=f"(d[51]), "=f"(d[52]), "=f"(d[53]), "=f"(d[54]), "=f"(d[55]),
      "=f"(d[56]), "=f"(d[57]), "=f"(d[58]), "=f"(d[59]), "=f"(d[60]), "=f"(d[61]), "=f"(d[62]), "=f"(d[63]),
      "=f"(d[64]), "=f"(d[65]), "=f"(d[66]), "=f"(d[67]), "=f"(d[68]), "=f"(d[69]), "=f"(d[70]), "=f"(d[71])
    : "r"(a0), "r"(a1), "r"(a2), "r"(a3), "l"(descB));
  else
  asm volatile("wgmma.mma_async.sync.aligned.m64n144k16.f32.bf16.bf16 "
    "{%0, %1, %2, %3, %4, %5, %6, %7, %8, %9, %10, %11, %12, %13, %14, %15, "
    "%16, %17, %18, %19, %20, %21, %22, %23, %24, %25, %26, %27, %28, %29, %30, %31, "
    "%32, %33, %34, %35, %36, %37, %38, %39, %40, %41, %42, %43, %44, %45, %46, %47, "
    "%48, %49, %50, %51, %52, %53, %54, %55, %56, %57, %58, %59, %60, %61, %62, %63, "
    "%64, %65, %66, %67, %68, %69, %70, %71}, "
    "{%72, %73, %74, %75}, %76, 1, 1, 1, 0;\n"
    : "+f"(d[0]), "+f"(d[1]), "+f"(d[2]), "+f"(d[3]), "+f"(d[4]), "+f"(d[5]), "+f"(d[6]), "+f"(d[7]),
      "+f"(d[8]), "+f"(d[9]), "+f"(d[10]), "+f"(d[11]), "+f"(d[12]), "+f"(d[13]), "+f"(d[14]), "+f"(d[15]),
      "+f"(d[16]), "+f"(d[17]), "+f"(d[18]), "+f"(d[19]), "+f"(d[20]), "+f"(d[21]), "+f"(d[22]), "+f"(d[23]),
      "+f"(d[24]), "+f"(d[25]), "+f"(d[26]), "+f"(d[27]), "+f"(d[28]), "+f"(d[29]), "+f"(d[30]), "+f"(d[31]),
      "+f"(d[32]), "+f"(d[33]), "+f"(d[34]), "+f"(d[35]), "+f"(d[36]), "+f"(d[37]), "+f"(d[38]), "+f"(d[39]),
      "+f"(d[40]), "+f"(d[41]), "+f"(d[42]), "+f"(d[43]), "+f"(d[44]), "+f"(d[45]), "+f"(d[46]), "+f"(d[47]),
      "+f"(d[48]), "+f"(d[49]), "+f"(d[50]), "+f"(d[51]), "+f"(d[52]), "+f"(d[53]), "+f"(d[54]), "+f"(d[55]),
      "+f"(d[56]), "+f"(d[57]), "+f"(d[58]), "+f"(d[59]), "+f"(d[60]), "+f"(d[61]), "+f"(d[62]), "+f"(d[63]),
      "+f"(d[64]), "+f"(d[65]), "+f"(d[66]), "+f"(d[67]), "+f"(d[68]), "+f"(d[69]), "+f"(d[70]), "+f"(d[71])
    : "r"(a0), "r"(a1), "r"(a2), "r"(a3), "l"(descB));
}

template <int SCALE_D>
__device__ __forceinline__ void wgmma_n96(float (&d)[48], uint32_t a0, uint32_t a1, uint32_t a2, uint32_t a3, uint64_t descB) {
  if (SCALE_D == 0)
  asm volatile("wgmma.mma_async.sync.aligned.m64n96k16.f32.bf16.bf16 "
    "{%0, %1, %2, %3, %4, %5, %6, %7, %8, %9, %10, %11, %12, %13, %14, %15, "
    "%16, %17, %18, %19, %20, %21, %22, %23, %24, %25, %26, %27, %28, %29, %30, %31, "
    "%32, %33, %34, %35, %36, %37, %38, %39, %40, %41, %42, %43, %44, %45, %46, %47}, "
    "{%48, %49, %50, %51}, %52, 0, 1, 1, 0;\n"
    : "=f"(d[0]), "=f"(d[1]), "=f"(d[2]), "=f"(d[3]), "=f"(d[4]), "=f"(d[5]), "=f"(d[6]), "=f"(d[7]),
      "=f"(d[8]), "=f"(d[9]), "=f"(d[10]), "=f"(d[11]), "=f"(d[12]), "=f"(d[13]), "=f"(d[14]), "=f"(d[15]),
      "=f"(d[16]), "=f"(d[17]), "=f"(d[18]), "=f"(d[19]), "=f"(d[20]), "=f"(d[21]), "=f"(d[22]), "=f"(d[23]),
      "=f"(d[24]), "=f"(d[25]), "=f"(d[26]), "=f"(d[27]), "=f"(d[28]), "=f"(d[29]), "=f"(d[30]), "=f"(d[31]),
      "=f"(d[32]), "=f"(d[33]), "=f"(d[34]), "=f"(d[35]), "=f"(d[36]), "=f"(d[37]), "=f"(d[38]), "=f"(d[39]),
      "=f"(d[40]), "=f"(d[41]), "=f"(d[42]), "=f"(d[43]), "=f"(d[44]), "=f"(d[45]), "=f"(d[46]), "=f"(d[47])
    : "r"(a0), "r"(a1), "r"(a2), "r"(a3), "l"(descB));
  else
  asm volatile("wgmma.mma_async.sync.aligned.m64n96k16.f32.bf16.bf16 "
    "{%0, %1, %2, %3, %4, %5, %6, %7, %8, %9, %10, %11, %12, %13, %14, %15, "
    "%16, %17, %18, %19, %20, %21, %22, %23, %24, %25, %26, %27, %28, %29, %30, %31, "
    "%32, %33, %34, %35, %36, %37, %38, %39, %40, %41, %42, %43, %44, %45, %46, %47}, "
    "{%48, %49, %50, %51}, %52, 1, 1, 1, 0;\n"
    : "+f"(d[0]), "+f"(d[1]), "+f"(d[2]), "+f"(d[3]), "+f"(d[4]), "+f"(d[5]), "+f"(d[6]), "+f"(d[7]),
      "+f"(d[8]), "+f"(d[9]), "+f"(d[10]), "+f"(d[11]), "+f"(d[12]), "+f"(d[13]), "+f"(d[14]), "+f"(d[15]),
      "+f"(d[16]), "+f"(d[17]), "+f"(d[18]), "+f"(d[19]), "+f"(d[20]), "+f"(d[21]), "+f"(d[22]), "+f"(d[23]),
      "+f"(d[24]), "+f"(d[25]), "+f"(d[26]), "+f"(d[27]), "+f"(d[28]), "+f"(d[29]), "+f"(d[30]), "+f"(d[31]),
      "+f"(d[32]), "+f"(d[33]), "+f"(d[34]), "+f"(d[35]), "+f"(d[36]), "+f"(d[37]), "+f"(d[38]), "+f"(d[39]),
      "+f"(d[40]), "+f"(d[41]), "+f"(d[42]), "+f"(d[43]), "+f"(d[44]), "+f"(d[45]), "+f"(d[46]), "+f"(d[47])
    : "r"(a0), "r"(a1), "r"(a2), "r"(a3), "l"(descB));
}

template <int SCALE_D>
__device__ __forceinline__ void wgmma_n48(float (&d)[24], uint32_t a0, uint32_t a1, uint32_t a2, uint32_t a3, uint64_t descB) {
  if (SCALE_D == 0)
  asm volatile("wgmma.mma_async.sync.aligned.m64n48k16.f32.bf16.bf16 "
    "{%0, %1, %2, %3, %4, %5, %6, %7, %8, %9, %10, %11, %12, %13, %14, %15, "
    "%16, %17, %18, %19, %20, %21, %22, %23}, "
    "{%24, %25, %26, %27}, %28, 0, 1, 1, 0;\n"
    : "=f"(d[0]), "=f"(d[1]), "=f"(d[2]), "=f"(d[3]), "=f"(d[4]), "=f"(d[5]), "=f"(d[6]), "=f"(d[7]),
      "=f"(d[8]), "=f"(d[9]), "=f"(d[10]), "=f"(d[11]), "=f"(d[12]), "=f"(d[13]), "=f"(d[14]), "=f"(d[15]),
      "=f"(d[16]), "=f"(d[17]), "=f"(d[18]), "=f"(d[19]), "=f"(d[20]), "=f"(d[21]), "=f"(d[22]), "=f"(d[23])
    : "r"(a0), "r"(a1), "r"(a2), "r"(a3), "l"(descB));
  else
  asm volatile("wgmma.mma_async.sync.aligned.m64n48k16.f32.bf16.bf16 "
    "{%0, %1, %2, %3, %4, %5, %6, %7, %8, %9, %10, %11, %12, %13, %14, %15, "
    "%16, %17, %18, %19, %20, %21, %22, %23}, "
    "{%24, %25, %26, %27}, %28, 1, 1, 1, 0;\n"
    : "+f"(d[0]), "+f"(d[1]), "+f"(d[2]), "+f"(d[3]), "+f"(d[4]), "+f"(d[5]), "+f"(d[6]), "+f"(d[7]),
      "+f"(d[8]), "+f"(d[9]), "+f"(d[10]), "+f"(d[11]), "+f"(d[12]), "+f"(d[13]), "+f"(d[14]), "+f"(d[15]),
      "+f"(d[16]), "+f"(d[17]), "+f"(d[18]), "+f"(d[19]), "+f"(d[20]), "+f"(d[21]), "+f"(d[22]), "+f"(d[23])
    : "r"(a0), "r"(a1), "r"(a2), "r"(a3), "l"(descB));
}

template <int SCALE_D>
__device__ __forceinline__ void wgmma_n64(float (&d)[32], uint32_t a0, uint32_t a1, uint32_t a2, uint32_t a3, uint64_t descB) {
  if (SCALE_D == 0)
  asm volatile("wgmma.mma_async.sync.aligned.m64n64k16.f32.bf16.bf16 "
    "{%0, %1, %2, %3, %4, %5, %6, %7, %8, %9, %10, %11, %12, %13, %14, %15, "
    "%16, %17, %18, %19, %20, %21, %22, %23, %24, %25, %26, %27, %28, %29, %30, %31}, "
    "{%32, %33, %34, %35}, %36, 0, 1, 1, 0;\n"
    : "=f"(d[0]), "=f"(d[1]), "=f"(d[2]), "=f"(d[3]), "=f"(d[4]), "=f"(d[5]), "=f"(d[6]), "=f"(d[7]),
      "=f"(d[8]), "=f"(d[9]), "=f"(d[10]), "=f"(d[11]), "=f"(d[12]), "=f"(d[13]), "=f"(d[14]), "=f"(d[15]),
      "=f"(d[16]), "=f"(d[17]), "=f"(d[18]), "=f"(d[19]), "=f"(d[20]), "=f"(d[21]), "=f"(d[22]), "=f"(d[23]),
      "=f"(d[24]), "=f"(d[25]), "=f"(d[26]), "=f"(d[27]), "=f"(d[28]), "=f"(d[29]), "=f"(d[30]), "=f"(d[31])
    : "r"(a0), "r"(a1), "r"(a2), "r"(a3), "l"(descB));
  else if (SCALE_D == 2)
  asm volatile("wgmma.mma_async.sync.aligned.m64n64k16.f32.bf16.bf16 "
    "{%0, %1, %2, %3, %4, %5, %6, %7, %8, %9, %10, %11, %12, %13, %14, %15, "
    "%16, %17, %18, %19, %20, %21, %22, %23, %24, %25, %26, %27, %28, %29, %30, %31}, "
    "{%32, %33, %34, %35}, %36, 0, 1, 1, 0;\n"
    : "+f"(d[0]), "+f"(d[1]), "+f"(d[2]), "+f"(d[3]), "+f"(d[4]), "+f"(d[5]), "+f"(d[6]), "+f"(d[7]),
      "+f"(d[8]), "+f"(d[9]), "+f"(d[10]), "+f"(d[11]), "+f"(d[12]), "+f"(d[13]), "+f"(d[14]), "+f"(d[15]),
      "+f"(d[16]), "+f"(d[17]), "+f"(d[18]), "+f"(d[19]), "+f"(d[20]), "+f"(d[21]), "+f"(d[22]), "+f"(d[23]),
      "+f"(d[24]), "+f"(d[25]), "+f"(d[26]), "+f"(d[27]), "+f"(d[28]), "+f"(d[29]), "+f"(d[30]), "+f"(d[31])
    : "r"(a0), "r"(a1), "r"(a2), "r"(a3), "l"(descB));
  else
  asm volatile("wgmma.mma_async.sync.aligned.m64n64k16.f32.bf16.bf16 "
    "{%0, %1, %2, %3, %4, %5, %6, %7, %8, %9, %10, %11, %12, %13, %14, %15, "
    "%16, %17, %18, %19, %20, %21, %22, %23, %24, %25, %26, %27, %28, %29, %30, %31}, "
    "{%32, %33, %34, %35}, %36, 1, 1, 1, 0;\n"
    : "+f"(d[0]), "+f"(d[1]), "+f"(d[2]), "+f"(d[3]), "+f"(d[4]), "+f"(d[5]), "+f"(d[6]), "+f"(d[7]),
      "+f"(d[8]), "+f"(d[9]), "+f"(d[10]), "+f"(d[11]), "+f"(d[12]), "+f"(d[13]), "+f"(d[14]), "+f"(d[15]),
      "+f"(d[16]), "+f"(d[17]), "+f"(d[18]), "+f"(d[19]), "+f"(d[20]), "+f"(d[21]), "+f"(d[22]), "+f"(d[23]),
      "+f"(d[24]), "+f"(d[25]), "+f"(d[26]), "+f"(d[27]), "+f"(d[28]), "+f"(d[29]), "+f"(d[30]), "+f"(d[31])
    : "r"(a0), "r"(a1), "r"(a2), "r"(a3), "l"(descB));
}

template <int SCALE_D>
__device__ __forceinline__ void wgmma_n56(float (&d)[28], uint32_t a0, uint32_t a1, uint32_t a2, uint32_t a3, uint64_t descB) {
  if (SCALE_D == 0)
  asm volatile("wgmma.mma_async.sync.aligned.m64n56k16.f32.bf16.bf16 "
    "{%0, %1, %2, %3, %4, %5, %6, %7, %8, %9, %10, %11, %12, %13, %14, %15, "
    "%16, %17, %18, %19, %20, %21, %22, %23, %24, %25, %26, %27}, "
    "{%28, %29, %30, %31}, %32, 0, 1, 1, 0;\n"
    : "=f"(d[0]), "=f"(d[1]), "=f"(d[2]), "=f"(d[3]), "=f"(d[4]), "=f"(d[5]), "=f"(d[6]), "=f"(d[7]),
      "=f"(d[8]), "=f"(d[9]), "=f"(d[10]), "=f"(d[11]), "=f"(d[12]), "=f"(d[13]), "=f"(d[14]), "=f"(d[15]),
      "=f"(d[16]), "=f"(d[17]), "=f"(d[18]), "=f"(d[19]), "=f"(d[20]), "=f"(d[21]), "=f"(d[22]), "=f"(d[23]),
      "=f"(d[24]), "=f"(d[25]), "=f"(d[26]), "=f"(d[27])
    : "r"(a0), "r"(a1), "r"(a2), "r"(a3), "l"(descB));
  else
  asm volatile("wgmma.mma_async.sync.aligned.m64n56k16.f32.bf16.bf16 "
    "{%0, %1, %2, %3, %4, %5, %6, %7, %8, %9, %10, %11, %12, %13, %14, %15, "
    "%16, %17, %18, %19, %20, %21, %22, %23, %24, %25, %26, %27}, "
    "{%28, %29, %30, %31}, %32, 1, 1, 1, 0;\n"
    : "+f"(d[0]), "+f"(d[1]), "+f"(d[2]), "+f"(d[3]), "+f"(d[4]), "+f"(d[5]), "+f"(d[6]), "+f"(d[7]),
      "+f"(d[8]), "+f"(d[9]), "+f"(d[10]), "+f"(d[11]), "+f"(d[12]), "+f"(d[13]), "+f"(d[14]), "+f"(d[15]),
      "+f"(d[16]), "+f"(d[17]), "+f"(d[18]), "+f"(d[19]), "+f"(d[20]), "+f"(d[21]), "+f"(d[22]), "+f"(d[23]),
      "+f"(d[24]), "+f"(d[25]), "+f"(d[26]), "+f"(d[27])
    : "r"(a0), "r"(a1), "r"(a2), "r"(a3), "l"(descB));
}

template <int SCALE_D>
__device__ __forceinline__ void wgmma_n56t(float (&d)[28], uint32_t a0, uint32_t a1, uint32_t a2, uint32_t a3, uint64_t descB) {
  if (SCALE_D == 0)
  asm volatile("wgmma.mma_async.sync.aligned.m64n56k16.f32.bf16.bf16 "
    "{%0, %1, %2, %3, %4, %5, %6, %7, %8, %9, %10, %11, %12, %13, %14, %15, "
    "%16, %17, %18, %19, %20, %21, %22, %23, %24, %25, %26, %27}, "
    "{%28, %29, %30, %31}, %32, 0, 1, 1, 1;\n"
    : "=f"(d[0]), "=f"(d[1]), "=f"(d[2]), "=f"(d[3]), "=f"(d[4]), "=f"(d[5]), "=f"(d[6]), "=f"(d[7]),
      "=f"(d[8]), "=f"(d[9]), "=f"(d[10]), "=f"(d[11]), "=f"(d[12]), "=f"(d[13]), "=f"(d[14]), "=f"(d[15]),
      "=f"(d[16]), "=f"(d[17]), "=f"(d[18]), "=f"(d[19]), "=f"(d[20]), "=f"(d[21]), "=f"(d[22]), "=f"(d[23]),
      "=f"(d[24]), "=f"(d[25]), "=f"(d[26]), "=f"(d[27])
    : "r"(a0), "r"(a1), "r"(a2), "r"(a3), "l"(descB));
  else
  asm volatile("wgmma.mma_async.sync.aligned.m64n56k16.f32.bf16.bf16 "
    "{%0, %1, %2, %3, %4, %5, %6, %7, %8, %9, %10, %11, %12, %13, %14, %15, "
    "%16, %17, %18, %19, %20, %21, %22, %23, %24, %25, %26, %27}, "
    "{%28, %29, %30, %31}, %32, 1, 1, 1, 1;\n"
    : "+f"(d[0]), "+f"(d[1]), "+f"(d[2]), "+f"(d[3]), "+f"(d[4]), "+f"(d[5]), "+f"(d[6]), "+f"(d[7]),
      "+f"(d[8]), "+f"(d[9]), "+f"(d[10]), "+f"(d[11]), "+f"(d[12]), "+f"(d[13]), "+f"(d[14]), "+f"(d[15]),
      "+f"(d[16]), "+f"(d[17]), "+f"(d[18]), "+f"(d[19]), "+f"(d[20]), "+f"(d[21]), "+f"(d[22]), "+f"(d[23]),
      "+f"(d[24]), "+f"(d[25]), "+f"(d[26]), "+f"(d[27])
    : "r"(a0), "r"(a1), "r"(a2), "r"(a3), "l"(descB));
}

__global__ void __launch_bounds__(192) prepack_kernel(const __nv_bfloat16* __restrict__ wqkv, const __nv_bfloat16* __restrict__ wo) {
  __nv_bfloat16* dst = reinterpret_cast<__nv_bfloat16*>(g_wpack);
  const int c = threadIdx.x, nb = blockIdx.x;
  if (nb < 72) {
    __shared__ float red[6][8];
    const int h = nb / 18, j = nb % 18, part = j / 6;
    const int col = (part == 0 ? 192 : part == 1 ? 384 : 0) + h * 48 + (j % 6) * 8;
    uint4 raw = *reinterpret_cast<const uint4*>(wqkv + c * 576 + col);
    uint32_t u[4] = {raw.x, raw.y, raw.z, raw.w};
    float v[8];
#pragma unroll
    for (int i = 0; i < 4; i++) { v[2 * i] = lo2f(u[i]); v[2 * i + 1] = hi2f(u[i]); }
#pragma unroll
    for (int i = 0; i < 8; i++) {
      float s = v[i];
#pragma unroll
      for (int o = 16; o; o >>= 1) s += __shfl_xor_sync(~0u, s, o);
      if ((c & 31) == 0) red[c >> 5][i] = s;
    }
    __syncthreads();
    const int cc = c >> 5, q = (c >> 3) & 3, s1 = (c >> 2) & 1, hh = (c >> 1) & 1, e = c & 1;
    const int base = h * 27648 + (2 * cc + s1) * 2304 + j * 128 + hh * 64 + 2 * q + e;
#pragma unroll
    for (int n = 0; n < 8; n++) {
      float m = (red[0][n] + red[1][n] + red[2][n] + red[3][n] + red[4][n] + red[5][n]) * (1.0f / 192.0f);
      dst[base + n * 8] = __float2bfloat16(v[n] - m);
    }
  } else {
    const int jb = nb - 72, chunk = jb / 8, j = jb % 8;
    const int s = c >> 4, hh = (c >> 3) & 1, kk = c & 7;
    const int base = 110592 + (chunk * 12 + s) * 1024 + j * 128 + hh * 64 + kk;
#pragma unroll
    for (int n = 0; n < 8; n++) {
      const int ch = 32 * (jb >> 2) + 8 * (n >> 1) + 2 * (jb & 3) + (n & 1);
      dst[base + n * 8] = wo[c * 192 + ch];
    }
  }
}

__device__ __forceinline__ int window_of(int round, int nfull, int cta, int ncta, int wg) {
  if (round < nfull) return round * 2 * ncta + 2 * cta + wg;
  const int rem = NWIN - nfull * 2 * ncta;
  const int i = cta + wg * ncta;
  return i < rem ? nfull * 2 * ncta + i : -1;
}

__device__ __forceinline__ constexpr int qkv_off(int h, int s) { return ((3 * h + s / 4) % 8) * SLICE + (s % 4) * 4608; }
__device__ __forceinline__ constexpr int wo_off(int chunk, int s) { return 4 * SLICE + (chunk * 12 + s) * 2048; }

template <int H, int S0, int S1>
__device__ __forceinline__ void issue_qkv(float (&acc)[72], const uint32_t (&X)[48], uint64_t dW) {
  asm volatile("" : "+l"(dW));
#pragma unroll
  for (int s = S0; s < S1; s++) {
    if (s == 0) wgmma_n144<0>(acc, X[4 * s], X[4 * s + 1], X[4 * s + 2], X[4 * s + 3], dW + (qkv_off(H, s) >> 4));
    else        wgmma_n144<1>(acc, X[4 * s], X[4 * s + 1], X[4 * s + 2], X[4 * s + 3], dW + (qkv_off(H, s) >> 4));
  }
}
template <int H>
__device__ __forceinline__ void issue_kv(float (&acc)[48], const uint32_t (&X)[48], uint64_t dW) {
  asm volatile("" : "+l"(dW));
#pragma unroll
  for (int s = 0; s < 12; s++) {
    if (s == 0) wgmma_n96<0>(acc, X[4 * s], X[4 * s + 1], X[4 * s + 2], X[4 * s + 3], dW + (qkv_off(H, s) >> 4));
    else        wgmma_n96<1>(acc, X[4 * s], X[4 * s + 1], X[4 * s + 2], X[4 * s + 3], dW + (qkv_off(H, s) >> 4));
  }
}
template <int H>
__device__ __forceinline__ void issue_q(float (&acc)[24], const uint32_t (&X)[48], uint64_t dW) {
  asm volatile("" : "+l"(dW));
#pragma unroll
  for (int s = 0; s < 12; s++) {
    if (s == 0) wgmma_n48<0>(acc, X[4 * s], X[4 * s + 1], X[4 * s + 2], X[4 * s + 3], dW + ((qkv_off(H, s) + 3072) >> 4));
    else        wgmma_n48<1>(acc, X[4 * s], X[4 * s + 1], X[4 * s + 2], X[4 * s + 3], dW + ((qkv_off(H, s) + 3072) >> 4));
  }
}
template <int CHUNK, int S0, int S1>
__device__ __forceinline__ void issue_proj(float (&acc)[32], const uint32_t (&Of)[48], uint64_t dW) {
  asm volatile("" : "+l"(dW));
#pragma unroll
  for (int s = S0; s < S1; s++) {
    if (s == 0) wgmma_n64<(CHUNK == 2 ? 2 : 0)>(acc, Of[4 * s], Of[4 * s + 1], Of[4 * s + 2], Of[4 * s + 3], dW + (wo_off(CHUNK, s) >> 4));
    else        wgmma_n64<1>(acc, Of[4 * s], Of[4 * s + 1], Of[4 * s + 2], Of[4 * s + 3], dW + (wo_off(CHUNK, s) >> 4));
  }
}
__device__ __forceinline__ void store_kv(const float* a, uint32_t r, uint32_t addr) {
#pragma unroll
  for (int j = 0; j < 6; j += 2)
    stsm4(addr + j * KV_PITCH, hmul_b<0>(pack2(a[4 * j], a[4 * j + 1]), r), hmul_b<1>(pack2(a[4 * j + 2], a[4 * j + 3]), r),
          hmul_b<0>(pack2(a[4 * j + 4], a[4 * j + 5]), r), hmul_b<1>(pack2(a[4 * j + 6], a[4 * j + 7]), r));
}
__device__ __forceinline__ void pack_q(const float* a, uint32_t r, uint32_t (&Q)[12]) {
#pragma unroll
  for (int j = 0; j < 6; j++) {
    Q[2 * j] = hmul_b<0>(pack2(a[4 * j], a[4 * j + 1]), r);
    Q[2 * j + 1] = hmul_b<1>(pack2(a[4 * j + 2], a[4 * j + 3]), r);
  }
}
__device__ __forceinline__ void issue_s(float (&S)[28], const uint32_t (&Q)[12], uint64_t dK) {
  asm volatile("" : "+l"(dK));
  wgmma_n56<0>(S, Q[0], Q[1], Q[2], Q[3], dK);
  wgmma_n56<1>(S, Q[4], Q[5], Q[6], Q[7], dK + (2 * KV_PITCH >> 4));
  wgmma_n56<1>(S, Q[8], Q[9], Q[10], Q[11], dK + (4 * KV_PITCH >> 4));
}
__device__ __forceinline__ void softmax_pv(float (&S)[28], uint64_t dV) {
  uint32_t P[16];
#pragma unroll
  for (int j = 0; j < 14; j++) P[j] = pack2(S[2 * j], S[2 * j + 1]);
  const uint32_t m0 = hmax(hmax(hmax(hmax(P[0], P[2]), P[4]), hmax(hmax(P[6], P[8]), P[10])), P[12]);
  const uint32_t m1 = hmax(hmax(hmax(hmax(P[1], P[3]), P[5]), hmax(hmax(P[7], P[9]), P[11])), P[13]);
  uint32_t mx = hmax(__byte_perm(m0, m1, 0x5410), __byte_perm(m0, m1, 0x7632));
  mx = hmax(mx, __shfl_xor_sync(~0u, mx, 1));
  mx = hmax(mx, __shfl_xor_sync(~0u, mx, 2));
  P[12] = hex1(hsub_b<0>(P[12], mx)); P[13] = hex1(hsub_b<1>(P[13], mx)); P[14] = 0; P[15] = 0;
#pragma unroll
  for (int j = 0; j < 12; j++) P[j] = hex2((j & 1) ? hsub_b<1>(P[j], mx) : hsub_b<0>(P[j], mx));
  asm volatile("" : "+l"(dV));
  wg_fence();
  wgmma_n56t<0>(S, P[0], P[1], P[2], P[3], dV);
  wgmma_n56t<1>(S, P[4], P[5], P[6], P[7], dV + (256 >> 4));
  wgmma_n56t<1>(S, P[8], P[9], P[10], P[11], dV + (512 >> 4));
  wgmma_n56t<1>(S, P[12], P[13], P[14], P[15], dV + (768 >> 4));
  wg_commit();
}
template <int S0, int S1>
__device__ __forceinline__ void load_x(uint32_t (&X)[48], uint32_t t0) {
#pragma unroll
  for (int s = S0; s < S1; s++)
    asm volatile("ld.shared.v4.u32 {%0,%1,%2,%3}, [%4];" : "=r"(X[4 * s]), "=r"(X[4 * s + 1]), "=r"(X[4 * s + 2]), "=r"(X[4 * s + 3])
                 : "r"(((s & 1) ? (t0 ^ 16) : t0) + (s >> 1) * 128) : "memory");
}
__device__ __forceinline__ void proxy_fence() { asm volatile("fence.proxy.async.shared::cta;" ::: "memory"); }

template <int CHUNK>
__device__ __forceinline__ void store_out(const float (&p)[32], const uint32_t (&X)[48], uint8_t* o0, uint8_t* o1, bool v0, bool v1) {
#pragma unroll
  for (int c = 0; c < 2; c++) {
    const int cc = CHUNK * 2 + c;
    uint4 a, b;
    a.x = hadd(X[8 * cc],     pack2(p[16 * c],      p[16 * c + 1]));
    b.x = hadd(X[8 * cc + 1], pack2(p[16 * c + 2],  p[16 * c + 3]));
    a.y = hadd(X[8 * cc + 2], pack2(p[16 * c + 4],  p[16 * c + 5]));
    b.y = hadd(X[8 * cc + 3], pack2(p[16 * c + 6],  p[16 * c + 7]));
    a.z = hadd(X[8 * cc + 4], pack2(p[16 * c + 8],  p[16 * c + 9]));
    b.z = hadd(X[8 * cc + 5], pack2(p[16 * c + 10], p[16 * c + 11]));
    a.w = hadd(X[8 * cc + 6], pack2(p[16 * c + 12], p[16 * c + 13]));
    b.w = hadd(X[8 * cc + 7], pack2(p[16 * c + 14], p[16 * c + 15]));
    if (v0) asm volatile("st.global.v4.u32 [%0], {%1,%2,%3,%4};" :: "l"(o0 + cc * 64), "r"(a.x), "r"(a.y), "r"(a.z), "r"(a.w) : "memory");
    if (v1) asm volatile("st.global.v4.u32 [%0], {%1,%2,%3,%4};" :: "l"(o1 + cc * 64), "r"(b.x), "r"(b.y), "r"(b.z), "r"(b.w) : "memory");
  }
}

__device__ __forceinline__ void finish_o(const float (&o)[28], uint32_t* Of) {
  float i0, i1;
  asm("rcp.approx.ftz.f32 %0, %1;" : "=f"(i0) : "f"(o[24]));
  asm("rcp.approx.ftz.f32 %0, %1;" : "=f"(i1) : "f"(o[26]));
  const uint32_t inv = pack2(i0, i1);
#pragma unroll
  for (int j = 0; j < 6; j++) {
    Of[2 * j]     = hmul_b<0>(pack2(o[4 * j], o[4 * j + 1]), inv);
    Of[2 * j + 1] = hmul_b<1>(pack2(o[4 * j + 2], o[4 * j + 3]), inv);
  }
}

__global__ void __launch_bounds__(384, 1)
fused_kernel(const __grid_constant__ CUtensorMap tmx, const __nv_bfloat16* __restrict__ dw, __nv_bfloat16* __restrict__ out, const int never) {
  extern __shared__ __align__(1024) uint8_t smem[];
  const uint32_t sb = (uint32_t)__cvta_generic_to_shared(smem);
  const int tid = threadIdx.x, lane = tid & 31;
  const int warp = __shfl_sync(0xffffffffu, tid >> 5, 0);
  const int cta = blockIdx.x, ncta = gridDim.x;
  const int nfull = NWIN / (2 * ncta);
  const int nrounds = nfull + ((NWIN - nfull * 2 * ncta) > cta ? 1 : 0);

  if (tid == 0) {
    for (int i = 0; i < 6; i++) { mbar_init(sb + BAR_WFULL + 8 * i, 1); mbar_init(sb + BAR_WEMPTY + 8 * i, 8); }
    for (int i = 0; i < 9; i++) mbar_init(sb + BAR_XFULL + 8 * i, 1);
    mbar_init(sb + BAR_TFULL, 3);
    mbar_init(sb + BAR_TEMPTY, 8);
    asm volatile("fence.mbarrier_init.release.cluster;" ::: "memory");
  }
  if (tid < 128) {
    const uint32_t v = (tid & 63) < 49 ? 0x3f803f80u : 0u;
    *reinterpret_cast<uint4*>(smem + OFF_KV + (tid >> 6) * KV_BYTES + 6 * KV_PITCH + (tid & 63) * 16) = make_uint4(v, v, v, v);
    asm volatile("fence.proxy.async.shared::cta;" ::: "memory");
  }
  __syncthreads();

  if (warp >= 8) {
    asm volatile("setmaxnreg.dec.sync.aligned.u32 " PREGS ";");
    if (warp == 11) {
      if (lane == 0) {
        const uint8_t* wp = reinterpret_cast<const uint8_t*>(g_wpack);
        for (int r = 0; r < nrounds; r++) {
#pragma unroll
          for (int k = 0; k < 16; k++) {
            const int st = k < 12 ? k / 3 : 4 + (k - 12) / 2;
            const int kp = (k + 8) & 15;
            const int stp = kp < 12 ? kp / 3 : 4 + (kp - 12) / 2;
            const bool first_of_prev = (k == 0) || (stp != (((k + 7) & 15) < 12 ? ((k + 7) & 15) / 3 : 4 + (((k + 7) & 15) - 12) / 2));
            if (first_of_prev || k == 8) {
              if (k >= 8) mbar_wait(sb + BAR_WEMPTY + 8 * stp, r & 1);
              else if (r > 0) mbar_wait(sb + BAR_WEMPTY + 8 * stp, (r - 1) & 1);
            }
            const bool first = k < 12 ? (k % 3 == 0) : (k % 2 == 0);
            if (first) mbar_expect(sb + BAR_WFULL + 8 * st, (k < 12 ? 3 : 2) * SLICE);
            asm volatile("cp.async.bulk.shared::cluster.global.mbarrier::complete_tx::bytes [%0], [%1], %2, [%3];"
                         :: "r"(sb + OFF_W + (k & 7) * SLICE), "l"(wp + k * SLICE), "n"(SLICE), "r"(sb + BAR_WFULL + 8 * st) : "memory");
          }
        }
      }
    } else {
      const int cw = warp - 8;
      const int win = lane >> 4;
      const int ch0 = cw * 64 + (lane & 15) * 4;
      uint32_t wt[9][2];
#pragma unroll
      for (int t = 0; t < 9; t++) {
        uint2 v = *reinterpret_cast<const uint2*>(dw + t * CH + ch0);
        wt[t][0] = v.x; wt[t][1] = v.y;
      }
      const uint32_t xs = sb + OFF_X + cw * 3 * XSLOT;
      const uint32_t xld = xs + (lane >> 4) * 1152 + (lane & 15) * 8;
      const uint32_t xbar = sb + BAR_XFULL + cw * 24;
      const uint32_t st0 = sb + OFF_TILE + win * TILE_BYTES + ch0 * 4;
      const uint32_t st1 = sb + OFF_TILE + win * TILE_BYTES + ((ch0 * 4) ^ 16);
      const uint64_t tm = reinterpret_cast<uint64_t>(&tmx);
      int cx0, cy0, cx1, cy1;
      auto coords = [&](int r) {
        const int w0 = window_of(r, nfull, cta, ncta, 0);
        int w1 = window_of(r, nfull, cta, ncta, 1);
        if (w1 < 0) w1 = w0;
        const int a = w0 / NWX, b = w1 / NWX;
        cx0 = (w0 - a * NWX) * 7 - 1; cy0 = a * 7 - 1;
        cx1 = (w1 - b * NWX) * 7 - 1; cy1 = b * 7 - 1;
      };
      auto issue = [&](int slot, int dy) {
        asm volatile("{\n.reg .pred p;\nelect.sync _|p, 0xffffffff;\n"
                     "@p mbarrier.arrive.expect_tx.shared::cta.b64 _, [%2], %8;\n"
                     "@p cp.async.bulk.tensor.3d.shared::cluster.global.mbarrier::complete_tx::bytes [%0], [%1, {%3, %4, %5}], [%2];\n"
                     "@p cp.async.bulk.tensor.3d.shared::cluster.global.mbarrier::complete_tx::bytes [%0 + 1152], [%1, {%3, %6, %7}], [%2];\n}\n"
                     :: "r"(xs + slot * XSLOT), "l"(tm), "r"(xbar + slot * 8), "r"(cw * 64), "r"(cx0), "r"(cy0 + dy), "r"(cx1), "r"(cy1 + dy), "n"(XSLOT) : "memory");
      };
      coords(0);
      issue(0, 0); issue(1, 1); issue(2, 2);
      for (int r = 0; r < nrounds; r++) {
        const bool more = r + 1 < nrounds;
        uint32_t accA[7][2], accB[7][2], ctr[7][2], held[2];
#pragma unroll
        for (int i = 0; i < 9; i++) {
          mbar_wait(xbar + (i % 3) * 8, (r + i / 3) & 1);
          if (i == 7 && more) coords(r + 1);
          if (i == 0) { if (r > 0) issue(2, 2); }
          else if (i < 7) issue((i + 2) % 3, i + 2);
          else if (more) issue((i + 2) % 3, i - 7);
          if (i == 2 && r > 0) mbar_wait(sb + BAR_TEMPTY, (r - 1) & 1);
          if (i == 2) { TR(8); }
          uint32_t cur[9][2];
#pragma unroll
          for (int p = 0; p < 5; p++)
            asm volatile("ld.shared.v2.u32 {%0,%1}, [%2];" : "=r"(cur[p][0]), "=r"(cur[p][1]) : "r"(xld + (i % 3) * XSLOT + p * 128));
#pragma unroll
          for (int j = 0; j < 7; j++) {
            if (j >= 1 && j + 4 < 9)
              asm volatile("ld.shared.v2.u32 {%0,%1}, [%2];" : "=r"(cur[j + 4][0]), "=r"(cur[j + 4][1]) : "r"(xld + (i % 3) * XSLOT + (j + 4) * 128));
            if (i >= 2) {
              uint32_t o[2];
#pragma unroll
              for (int e = 0; e < 2; e++) {
                uint32_t a = hfma(cur[j][e], wt[6][e], accA[j][e]);
                a = hfma(cur[j + 1][e], wt[7][e], a);
                a = hfma(cur[j + 2][e], wt[8][e], a);
                o[e] = hadd(ctr[j][e], a);
              }
              const int tok = (i - 2) * 7 + j, ps = tok >> 1;
              if (!(tok & 1)) { held[0] = o[0]; held[1] = o[1]; }
              if ((tok & 1) || tok == 48)
                asm volatile("st.shared.v4.u32 [%0], {%1,%2,%3,%4};" :: "r"(((ps & 1) ? st1 : st0) + ps * 768), "r"(held[0]), "r"(o[0]), "r"(held[1]), "r"(o[1]) : "memory");
            }
#pragma unroll
            for (int e = 0; e < 2; e++) {
              if (i >= 1 && i <= 7) {
                uint32_t a = hfma(cur[j][e], wt[3][e], accB[j][e]);
                a = hfma(cur[j + 1][e], wt[4][e], a);
                accA[j][e] = hfma(cur[j + 2][e], wt[5][e], a);
                ctr[j][e] = cur[j + 1][e];
              }
              if (i <= 6) {
                uint32_t a = hmul(cur[j][e], wt[0][e]);
                a = hfma(cur[j + 1][e], wt[1][e], a);
                accB[j][e] = hfma(cur[j + 2][e], wt[2][e], a);
              }
            }
          }
        }
        __syncwarp();
        if (lane == 0) mbar_arrive(sb + BAR_TFULL);
        TR(27);
      }
    }
  } else {
    asm volatile("setmaxnreg.inc.sync.aligned.u32 " CREGS ";");
    const int wg = warp >> 2, w4 = warp & 3, g = lane >> 2, q = lane & 3;
    const int row0 = w4 * 16 + g, row1 = row0 + 8;
    const int ps = min(w4 * 8 + g, 24);
    const int tok0 = 2 * ps, tok1 = min(2 * ps + 1, 48);
    const uint32_t kv = sb + OFF_KV + wg * KV_BYTES;
    const int srow = w4 * 16 + (lane & 15);
    const uint32_t vst = kv + (lane >> 4) * KV_PITCH + srow * 16;
    const uint32_t kst = vst + (srow < 56 ? 1024 : 0);
    uint64_t dW = mkdesc(sb + OFF_W, 128, 256);
    uint64_t dK = mkdesc(kv + 1024, KV_PITCH, 128);
    uint64_t dV = mkdesc(kv, 128, KV_PITCH);
    const uint32_t vmask = (row0 < 49 ? 0xffffu : 0u) | (row1 < 49 ? 0xffff0000u : 0u);
    const float qscale = 0.14433756729740643f * 1.4426950408889634f;

    const uint32_t tx = sb + OFF_TILE + wg * TILE_BYTES + ps * 768 + q * 32 + (ps & 1) * 16;
    const int myrounds = window_of(nrounds - 1, nfull, cta, ncta, wg) < 0 ? nrounds - 1 : nrounds;

    if (never == 2) return;

    for (int r = 0;; r++) {
      const uint32_t par = r & 1;
      if (r == myrounds) {
        if (r < nrounds)
          for (int s = 0; s < 6; s++) { mbar_wait(sb + BAR_WFULL + 8 * s, par); if (lane == 0) mbar_arrive(sb + BAR_WEMPTY + 8 * s); }
        break;
      }
      TR(0);
      uint32_t X[48];
      float acc[72];
      mbar_wait(sb + BAR_TFULL, par);
      load_x<0, 12>(X, tx);
      __syncwarp();
      if (lane == 0) mbar_arrive(sb + BAR_TEMPTY);
      mbar_wait(sb + BAR_WFULL, par);
      wg_fence();
      issue_qkv<0, 0, 12>(acc, X, dW);
      wg_commit();
      sched_fence<1>(never);
      uint32_t rK, rV, rQ;
      {
        uint32_t sm[2];
#pragma unroll
        for (int a = 0; a < 2; a++) {
          uint32_t t[12];
#pragma unroll
          for (int i = 0; i < 12; i++) t[i] = hadd(X[4 * i + a], X[4 * i + 2 + a]);
#pragma unroll
          for (int i = 0; i < 6; i++) t[i] = hadd(t[i], t[i + 6]);
#pragma unroll
          for (int i = 0; i < 3; i++) t[i] = hadd(t[i], t[i + 3]);
          sm[a] = hadd(hadd(t[0], t[1]), t[2]);
        }
        uint32_t m = hadd(__byte_perm(sm[0], sm[1], 0x5410), __byte_perm(sm[0], sm[1], 0x7632));
        m = hadd(m, __shfl_xor_sync(~0u, m, 1));
        m = hadd(m, __shfl_xor_sync(~0u, m, 2));
        m = hmul(m, 0x3bab3babu);
        float var[2];
#pragma unroll
        for (int a = 0; a < 2; a++) {
          uint32_t t[4];
#pragma unroll
          for (int i = 0; i < 24; i++) {
            const uint32_t d = a ? hsub_b<1>(X[2 * i + 1], m) : hsub_b<0>(X[2 * i], m);
            t[i & 3] = i < 4 ? hmul(d, d) : hfma(d, d, t[i & 3]);
          }
          const uint32_t s = hadd(hadd(t[0], t[1]), hadd(t[2], t[3]));
          float v = lo2f(s) + hi2f(s);
          v += __shfl_xor_sync(~0u, v, 1);
          v += __shfl_xor_sync(~0u, v, 2);
          asm("rsqrt.approx.ftz.f32 %0, %1;" : "=f"(var[a]) : "f"(fmaf(v, 1.0f / 192.0f, 1e-5f)));
        }
        rK = pack2(var[0], var[1]);
        rV = rK & vmask;
        rQ = pack2(var[0] * qscale, var[1] * qscale);
        anchor(rQ);
      }
      uint32_t Of[48], Q[12];
      float S[28];
      TR(1);
      wg_wait<0>(); keep(acc);
      TR(2);
      if (lane == 0) mbar_arrive(sb + BAR_WEMPTY);
      store_kv(acc, rK, kst);
      store_kv(acc + 24, rV, vst);
      proxy_fence();
      pack_q(acc + 48, rQ, Q);
      mbar_wait(sb + BAR_WFULL + 8, par);
      bar_sync(1 + wg);
      TR(3);
      wg_fence();
      issue_s(S, Q, dK); wg_commit();
      issue_qkv<1, 0, 12>(acc, X, dW); wg_commit();
      wg_wait<1>(); keep(S);
      TR(4);
      softmax_pv(S, dV);
      TR(5);
      wg_wait<1>(); keep(acc);
      TR(6);
      if (lane == 0) mbar_arrive(sb + BAR_WEMPTY + 8);
      store_kv(acc, rK, kst);
      wg_wait<0>(); keep(S);
      bar_sync(1 + wg);
      store_kv(acc + 24, rV, vst);
      proxy_fence();
      pack_q(acc + 48, rQ, Q);
      finish_o(S, Of);
      mbar_wait(sb + BAR_WFULL + 16, par);
      bar_sync(1 + wg);
      TR(7);
      wg_fence();
      issue_s(S, Q, dK); wg_commit();
      issue_qkv<2, 0, 12>(acc, X, dW); wg_commit();
      wg_wait<1>(); keep(S);
      TR(8);
      softmax_pv(S, dV);
      TR(9);
      wg_wait<1>(); keep(acc);
      TR(10);
      if (lane == 0) mbar_arrive(sb + BAR_WEMPTY + 16);
      store_kv(acc, rK, kst);
      wg_wait<0>(); keep(S);
      bar_sync(1 + wg);
      store_kv(acc + 24, rV, vst);
      proxy_fence();
      pack_q(acc + 48, rQ, Q);
      finish_o(S, Of + 12);
      mbar_wait(sb + BAR_WFULL + 24, par);
      bar_sync(1 + wg);
      TR(11);
      {
        float kva[48], qa[24];
        wg_fence();
        issue_s(S, Q, dK); wg_commit();
        issue_kv<3>(kva, X, dW); wg_commit();
        wg_wait<1>(); keep(S);
        TR(12);
        softmax_pv(S, dV);
        TR(13);
        wg_wait<0>(); keep(S); keep(kva);
        TR(14);
        wg_fence();
        issue_q<3>(qa, X, dW); wg_commit();
        bar_sync(1 + wg);
        store_kv(kva, rK, kst);
        store_kv(kva + 24, rV, vst);
        proxy_fence();
        finish_o(S, Of + 24);
        anchor(Of[35]);
        wg_wait<0>(); keep(qa);
        TR(15);
        if (lane == 0) mbar_arrive(sb + BAR_WEMPTY + 24);
        pack_q(qa, rQ, Q);
      }
      mbar_wait(sb + BAR_WFULL + 32, par);
      bar_sync(1 + wg);
      TR(16);
      float pa[32], pb[32];
      wg_fence();
      issue_s(S, Q, dK); wg_commit();
      issue_proj<0, 0, 9>(pa, Of, dW); wg_commit();
      wg_wait<1>(); keep(S);
      TR(17);
      softmax_pv(S, dV);
      TR(18);
      mbar_wait(sb + BAR_WFULL + 40, par);
      wg_wait<0>(); keep(S); keep(pa);
      TR(19);
      finish_o(S, Of + 36);
      wg_fence();
      issue_proj<0, 9, 12>(pa, Of, dW); wg_commit();
      issue_proj<1, 0, 12>(pb, Of, dW); wg_commit();
      bar_sync(1 + wg);
      TR(20);
      const bool more = r + 1 < myrounds;
      const int w = window_of(r, nfull, cta, ncta, wg);
      const int wy = w / NWX, wx = w - wy * NWX;
      uint8_t* ob = reinterpret_cast<uint8_t*>(out) + (size_t)(wy * 7 * IMG + wx * 7) * 384 + q * 16;
      uint8_t* o0 = ob + ((tok0 / 7) * IMG + tok0 % 7) * 384;
      uint8_t* o1 = ob + ((tok1 / 7) * IMG + tok1 % 7) * 384;
      if (XWIN && more) mbar_wait(sb + BAR_TFULL, par ^ 1);
      wg_wait<1>(); keep(pa);
      TR(21);
      store_out<0>(pa, X, o0, o1, row0 < 49, row1 < 49);
      wg_fence();
      issue_proj<2, 0, 12>(pa, Of, dW); wg_commit();
      if (XWIN) load_x<0, 4>(X, tx);
      TR(22);
      wg_wait<1>(); keep(pb);
      TR(23);
      if (lane == 0) mbar_arrive(sb + BAR_WEMPTY + 32);
      store_out<1>(pb, X, o0, o1, row0 < 49, row1 < 49);
      if (XWIN) load_x<4, 8>(X, tx);
      if (XWIN && more) mbar_wait(sb + BAR_WFULL, par ^ 1);
      TR(24);
      wg_wait<0>(); keep(pa);
      TR(25);
      if (lane == 0) mbar_arrive(sb + BAR_WEMPTY + 40);
      store_out<2>(pa, X, o0, o1, row0 < 49, row1 < 49);
      TR(26);
    }
  }
}

typedef CUresult (*EncodeFn)(CUtensorMap*, CUtensorMapDataType, cuuint32_t, void*, const cuuint64_t*, const cuuint64_t*,
                             const cuuint32_t*, const cuuint32_t*, CUtensorMapInterleave, CUtensorMapSwizzle,
                             CUtensorMapL2promotion, CUtensorMapFloatOOBfill);

}

extern "C" void kernel_launch(void* const* d_in, const int* in_sizes, int n_in, void* d_out, int out_size) {
  const __nv_bfloat16* x = (const __nv_bfloat16*)d_in[0];
  const __nv_bfloat16* dw = (const __nv_bfloat16*)d_in[1];
  const __nv_bfloat16* wqkv = (const __nv_bfloat16*)d_in[2];
  const __nv_bfloat16* wo = (const __nv_bfloat16*)d_in[3];
  static EncodeFn encode = nullptr;
  static int nsm = 0;
  if (!encode) {
    void* fn = nullptr;
    cudaDriverEntryPointQueryResult qr;
    cudaGetDriverEntryPoint("cuTensorMapEncodeTiled", &fn, cudaEnableDefault, &qr);
    encode = (EncodeFn)fn;
    int dev = 0;
    cudaGetDevice(&dev);
    cudaDeviceGetAttribute(&nsm, cudaDevAttrMultiProcessorCount, dev);
    cudaFuncSetAttribute(fused_kernel, cudaFuncAttributeMaxDynamicSharedMemorySize, SMEM_BYTES);
  }
  CUtensorMap tmx;
  cuuint64_t gdim[3] = {CH, IMG, IMG};
  cuuint64_t gstr[2] = {CH * 2, (cuuint64_t)CH * 2 * IMG};
  cuuint32_t box[3] = {64, 9, 1};
  cuuint32_t estr[3] = {1, 1, 1};
  encode(&tmx, CU_TENSOR_MAP_DATA_TYPE_BFLOAT16, 3, (void*)x, gdim, gstr, box, estr, CU_TENSOR_MAP_INTERLEAVE_NONE,
         CU_TENSOR_MAP_SWIZZLE_NONE, CU_TENSOR_MAP_L2_PROMOTION_L2_128B, CU_TENSOR_MAP_FLOAT_OOB_FILL_NONE);
  prepack_kernel<<<96, 192>>>(wqkv, wo);
  fused_kernel<<<nsm, 384, SMEM_BYTES>>>(tmx, dw, (__nv_bfloat16*)d_out, 0);
}
```

```cpp
#include <cuda_runtime.h>
#include <cuda_bf16.h>
#include <cuda.h>
#include <stdint.h>

#define CREGS "208"
#define PREGS "88"
#define XWIN 1
namespace {

constexpr int IMG = 511;
constexpr int CH = 192;
constexpr int NWX = 73;
constexpr int NWIN = NWX * NWX;
constexpr int SLICE = 18432;
constexpr int OFF_W = 0;
constexpr int KV_BYTES = 12544, KV_PITCH = 1920;
constexpr int OFF_KV = 8 * SLICE;
constexpr int TILE_BYTES = 25 * 768;
constexpr int OFF_TILE = OFF_KV + 2 * KV_BYTES;
constexpr int XSLOT = 2304;
constexpr int OFF_X = OFF_TILE + 2 * TILE_BYTES;
constexpr int OFF_BAR = OFF_X + 9 * XSLOT;
constexpr int BAR_WFULL = OFF_BAR;
constexpr int BAR_WEMPTY = OFF_BAR + 48;
constexpr int BAR_XFULL = OFF_BAR + 96;
constexpr int BAR_TFULL = OFF_BAR + 168;
constexpr int BAR_TEMPTY = OFF_BAR + 176;
constexpr int SMEM_BYTES = OFF_BAR + 192;

constexpr int SMEM_BASE = 1024;
struct Descs { uint64_t w[12]; uint64_t k[2][4]; uint64_t v[2][4]; };

__device__ uint4 g_wpack[16 * SLICE / 16];
#define TR(id)
template <int ID> __device__ __forceinline__ void sched_fence(uint32_t v) {
  asm volatile("{\n.reg .pred p;\nsetp.ne.u32 p, %0, %1;\n@p bra.uni SF_%=;\ntrap;\nSF_%=:\n}\n" :: "r"(v), "n"(ID) : "memory");
}
__device__ __forceinline__ void anchor(uint32_t v) { sched_fence<0x7fc1ffc1>(v); }

typedef __nv_bfloat162 bf2;
__device__ __forceinline__ bf2 u2b(uint32_t u) { return *reinterpret_cast<bf2*>(&u); }
__device__ __forceinline__ uint32_t b2u(bf2 b) { return *reinterpret_cast<uint32_t*>(&b); }
__device__ __forceinline__ uint32_t pack2(float lo, float hi) {
  uint32_t r; asm("cvt.rn.bf16x2.f32 %0, %1, %2;" : "=r"(r) : "f"(hi), "f"(lo)); return r;
}
__device__ __forceinline__ uint32_t hadd(uint32_t a, uint32_t b) { return b2u(__hadd2_rn(u2b(a), u2b(b))); }
__device__ __forceinline__ uint32_t hmul(uint32_t a, uint32_t b) { return b2u(__hmul2_rn(u2b(a), u2b(b))); }
__device__ __forceinline__ uint32_t hfma(uint32_t a, uint32_t b, uint32_t c) { return b2u(__hfma2(u2b(a), u2b(b), u2b(c))); }
__device__ __forceinline__ uint32_t hmax(uint32_t a, uint32_t b) { return b2u(__hmax2(u2b(a), u2b(b))); }
template <int HI> __device__ __forceinline__ bf2 bcast(uint32_t a) { return HI ? __high2bfloat162(u2b(a)) : __low2bfloat162(u2b(a)); }
template <int HI> __device__ __forceinline__ uint32_t hmul_b(uint32_t a, uint32_t s) { return b2u(__hmul2_rn(u2b(a), bcast<HI>(s))); }
template <int HI> __device__ __forceinline__ uint32_t hsub_b(uint32_t a, uint32_t s) { return b2u(__hsub2_rn(u2b(a), bcast<HI>(s))); }
__device__ __forceinline__ uint32_t hex2(uint32_t a) { uint32_t r; asm("ex2.approx.ftz.bf16x2 %0, %1;" : "=r"(r) : "r"(a)); return r; }
__device__ __forceinline__ uint32_t hex1(uint32_t a) {
  uint32_t r; asm("{\n.reg .b16 l, h, e;\nmov.b32 {l, h}, %1;\nex2.approx.ftz.bf16 e, l;\ncvt.u32.u16 %0, e;\n}\n" : "=r"(r) : "r"(a)); return r;
}
__device__ __forceinline__ float lo2f(uint32_t a) { return __uint_as_float(a << 16); }
__device__ __forceinline__ float hi2f(uint32_t a) { return __uint_as_float(a & 0xffff0000u); }

__device__ __forceinline__ void mbar_init(uint32_t bar, uint32_t cnt) { asm volatile("mbarrier.init.shared::cta.b64 [%0], %1;" :: "r"(bar), "r"(cnt) : "memory"); }
__device__ __forceinline__ void mbar_arrive(uint32_t bar) { asm volatile("mbarrier.arrive.shared::cta.b64 _, [%0];" :: "r"(bar) : "memory"); }
__device__ __forceinline__ void mbar_expect(uint32_t bar, uint32_t bytes) { asm volatile("mbarrier.arrive.expect_tx.shared::cta.b64 _, [%0], %1;" :: "r"(bar), "r"(bytes) : "memory"); }
template <int HINT>
__device__ __forceinline__ bool mbar_try(uint32_t bar, uint32_t parity) {
  uint32_t ok;
  if (HINT) asm volatile("{\n.reg .pred p;\nmbarrier.try_wait.parity.shared::cta.b64 p, [%1], %2, %3;\nselp.u32 %0, 1, 0, p;\n}\n" : "=r"(ok) : "r"(bar), "r"(parity), "n"(HINT) : "memory");
  else asm volatile("{\n.reg .pred p;\nmbarrier.try_wait.parity.shared::cta.b64 p, [%1], %2;\nselp.u32 %0, 1, 0, p;\n}\n" : "=r"(ok) : "r"(bar), "r"(parity) : "memory");
  return ok != 0;
}
__device__ __forceinline__ void mbar_wait(uint32_t bar, uint32_t parity) {
  if (__builtin_expect(!mbar_try<0>(bar, parity), 0)) {
    uint32_t n = 0;
    while (!mbar_try<4000>(bar, parity)) { if (++n > (1u << 20)) __trap(); }
  }
}
__device__ __forceinline__ void wg_fence() { asm volatile("wgmma.fence.sync.aligned;" ::: "memory"); }
__device__ __forceinline__ void wg_commit() { asm volatile("wgmma.commit_group.sync.aligned;" ::: "memory"); }
template <int N> __device__ __forceinline__ void wg_wait() { asm volatile("wgmma.wait_group.sync.aligned %0;" :: "n"(N) : "memory"); }
__device__ __forceinline__ void bar_sync(int id) { asm volatile("bar.sync %0, 128;" :: "r"(id) : "memory"); }
__device__ __forceinline__ void turn_wait(int wg) { asm volatile("bar.sync %0, 256;" :: "r"(3 + wg) : "memory"); }
__device__ __forceinline__ void turn_pass(int wg) { asm volatile("bar.arrive %0, 256;" :: "r"(4 - wg) : "memory"); }
__device__ __forceinline__ void stsm4(uint32_t addr, uint32_t a, uint32_t b, uint32_t c, uint32_t d) {
  asm volatile("stmatrix.sync.aligned.m8n8.x4.shared.b16 [%0], {%1,%2,%3,%4};" :: "r"(addr), "r"(a), "r"(b), "r"(c), "r"(d) : "memory");
}
template <int N> __device__ __forceinline__ void keep(float (&d)[N]) {
#pragma unroll
  for (int i = 0; i < N; i++) asm volatile("" : "+f"(d[i]) :: "memory");
}
__host__ __device__ __forceinline__ uint64_t mkdesc(uint32_t addr, uint32_t lbo, uint32_t sbo) {
  return ((uint64_t)(sbo >> 4) << 32) | (uint64_t)(((lbo >> 4) << 16) | ((addr & 0x3FFFF) >> 4));
}

template <int SCALE_D>
__device__ __forceinline__ void wgmma_n144(float (&d)[72], uint32_t a0, uint32_t a1, uint32_t a2, uint32_t a3, uint64_t descB) {
  if (SCALE_D == 0)
  asm volatile("wgmma.mma_async.sync.aligned.m64n144k16.f32.bf16.bf16 "
    "{%0, %1, %2, %3, %4, %5, %6, %7, %8, %9, %10, %11, %12, %13, %14, %15, "
    "%16, %17, %18, %19, %20, %21, %22, %23, %24, %25, %26, %27, %28, %29, %30, %31, "
    "%32, %33, %34, %35, %36, %37, %38, %39, %40, %41, %42, %43, %44, %45, %46, %47, "
    "%48, %49, %50, %51, %52, %53, %54, %55, %56, %57, %58, %59, %60, %61, %62, %63, "
    "%64, %65, %66, %67, %68, %69, %70, %71}, "
    "{%72, %73, %74, %75}, %76, 0, 1, 1, 0;\n"
    : "=f"(d[0]), "=f"(d[1]), "=f"(d[2]), "=f"(d[3]), "=f"(d[4]), "=f"(d[5]), "=f"(d[6]), "=f"(d[7]),
      "=f"(d[8]), "=f"(d[9]), "=f"(d[10]), "=f"(d[11]), "=f"(d[12]), "=f"(d[13]), "=f"(d[14]), "=f"(d[15]),
      "=f"(d[16]), "=f"(d[17]), "=f"(d[18]), "=f"(d[19]), "=f"(d[20]), "=f"(d[21]), "=f"(d[22]), "=f"(d[23]),
      "=f"(d[24]), "=f"(d[25]), "=f"(d[26]), "=f"(d[27]), "=f"(d[28]), "=f"(d[29]), "=f"(d[30]), "=f"(d[31]),
      "=f"(d[32]), "=f"(d[33]), "=f"(d[34]), "=f"(d[35]), "=f"(d[36]), "=f"(d[37]), "=f"(d[38]), "=f"(d[39]),
      "=f"(d[40]), "=f"(d[41]), "=f"(d[42]), "=f"(d[43]), "=f"(d[44]), "=f"(d[45]), "=f"(d[46]), "=f"(d[47]),
      "=f"(d[48]), "=f"(d[49]), "=f"(d[50]), "=f"(d[51]), "=f"(d[52]), "=f"(d[53]), "=f"(d[54]), "=f"(d[55]),
      "=f"(d[56]), "=f"(d[57]), "=f"(d[58]), "=f"(d[59]), "=f"(d[60]), "=f"(d[61]), "=f"(d[62]), "=f"(d[63]),
      "=f"(d[64]), "=f"(d[65]), "=f"(d[66]), "=f"(d[67]), "=f"(d[68]), "=f"(d[69]), "=f"(d[70]), "=f"(d[71])
    : "r"(a0), "r"(a1), "r"(a2), "r"(a3), "l"(descB));
  else
  asm volatile("wgmma.mma_async.sync.aligned.m64n144k16.f32.bf16.bf16 "
    "{%0, %1, %2, %3, %4, %5, %6, %7, %8, %9, %10, %11, %12, %13, %14, %15, "
    "%16, %17, %18, %19, %20, %21, %22, %23, %24, %25, %26, %27, %28, %29, %30, %31, "
    "%32, %33, %34, %35, %36, %37, %38, %39, %40, %41, %42, %43, %44, %45, %46, %47, "
    "%48, %49, %50, %51, %52, %53, %54, %55, %56, %57, %58, %59, %60, %61, %62, %63, "
    "%64, %65, %66, %67, %68, %69, %70, %71}, "
    "{%72, %73, %74, %75}, %76, 1, 1, 1, 0;\n"
    : "+f"(d[0]), "+f"(d[1]), "+f"(d[2]), "+f"(d[3]), "+f"(d[4]), "+f"(d[5]), "+f"(d[6]), "+f"(d[7]),
      "+f"(d[8]), "+f"(d[9]), "+f"(d[10]), "+f"(d[11]), "+f"(d[12]), "+f"(d[13]), "+f"(d[14]), "+f"(d[15]),
      "+f"(d[16]), "+f"(d[17]), "+f"(d[18]), "+f"(d[19]), "+f"(d[20]), "+f"(d[21]), "+f"(d[22]), "+f"(d[23]),
      "+f"(d[24]), "+f"(d[25]), "+f"(d[26]), "+f"(d[27]), "+f"(d[28]), "+f"(d[29]), "+f"(d[30]), "+f"(d[31]),
      "+f"(d[32]), "+f"(d[33]), "+f"(d[34]), "+f"(d[35]), "+f"(d[36]), "+f"(d[37]), "+f"(d[38]), "+f"(d[39]),
      "+f"(d[40]), "+f"(d[41]), "+f"(d[42]), "+f"(d[43]), "+f"(d[44]), "+f"(d[45]), "+f"(d[46]), "+f"(d[47]),
      "+f"(d[48]), "+f"(d[49]), "+f"(d[50]), "+f"(d[51]), "+f"(d[52]), "+f"(d[53]), "+f"(d[54]), "+f"(d[55]),
      "+f"(d[56]), "+f"(d[57]), "+f"(d[58]), "+f"(d[59]), "+f"(d[60]), "+f"(d[61]), "+f"(d[62]), "+f"(d[63]),
      "+f"(d[64]), "+f"(d[65]), "+f"(d[66]), "+f"(d[67]), "+f"(d[68]), "+f"(d[69]), "+f"(d[70]), "+f"(d[71])
    : "r"(a0), "r"(a1), "r"(a2), "r"(a3), "l"(descB));
}

template <int SCALE_D>
__device__ __forceinline__ void wgmma_n96(float (&d)[48], uint32_t a0, uint32_t a1, uint32_t a2, uint32_t a3, uint64_t descB) {
  if (SCALE_D == 0)
  asm volatile("wgmma.mma_async.sync.aligned.m64n96k16.f32.bf16.bf16 "
    "{%0, %1, %2, %3, %4, %5, %6, %7, %8, %9, %10, %11, %12, %13, %14, %15, "
    "%16, %17, %18, %19, %20, %21, %22, %23, %24, %25, %26, %27, %28, %29, %30, %31, "
    "%32, %33, %34, %35, %36, %37, %38, %39, %40, %41, %42, %43, %44, %45, %46, %47}, "
    "{%48, %49, %50, %51}, %52, 0, 1, 1, 0;\n"
    : "=f"(d[0]), "=f"(d[1]), "=f"(d[2]), "=f"(d[3]), "=f"(d[4]), "=f"(d[5]), "=f"(d[6]), "=f"(d[7]),
      "=f"(d[8]), "=f"(d[9]), "=f"(d[10]), "=f"(d[11]), "=f"(d[12]), "=f"(d[13]), "=f"(d[14]), "=f"(d[15]),
      "=f"(d[16]), "=f"(d[17]), "=f"(d[18]), "=f"(d[19]), "=f"(d[20]), "=f"(d[21]), "=f"(d[22]), "=f"(d[23]),
      "=f"(d[24]), "=f"(d[25]), "=f"(d[26]), "=f"(d[27]), "=f"(d[28]), "=f"(d[29]), "=f"(d[30]), "=f"(d[31]),
      "=f"(d[32]), "=f"(d[33]), "=f"(d[34]), "=f"(d[35]), "=f"(d[36]), "=f"(d[37]), "=f"(d[38]), "=f"(d[39]),
      "=f"(d[40]), "=f"(d[41]), "=f"(d[42]), "=f"(d[43]), "=f"(d[44]), "=f"(d[45]), "=f"(d[46]), "=f"(d[47])
    : "r"(a0), "r"(a1), "r"(a2), "r"(a3), "l"(descB));
  else
  asm volatile("wgmma.mma_async.sync.aligned.m64n96k16.f32.bf16.bf16 "
    "{%0, %1, %2, %3, %4, %5, %6, %7, %8, %9, %10, %11, %12, %13, %14, %15, "
    "%16, %17, %18, %19, %20, %21, %22, %23, %24, %25, %26, %27, %28, %29, %30, %31, "
    "%32, %33, %34, %35, %36, %37, %38, %39, %40, %41, %42, %43, %44, %45, %46, %47}, "
    "{%48, %49, %50, %51}, %52, 1, 1, 1, 0;\n"
    : "+f"(d[0]), "+f"(d[1]), "+f"(d[2]), "+f"(d[3]), "+f"(d[4]), "+f"(d[5]), "+f"(d[6]), "+f"(d[7]),
      "+f"(d[8]), "+f"(d[9]), "+f"(d[10]), "+f"(d[11]), "+f"(d[12]), "+f"(d[13]), "+f"(d[14]), "+f"(d[15]),
      "+f"(d[16]), "+f"(d[17]), "+f"(d[18]), "+f"(d[19]), "+f"(d[20]), "+f"(d[21]), "+f"(d[22]), "+f"(d[23]),
      "+f"(d[24]), "+f"(d[25]), "+f"(d[26]), "+f"(d[27]), "+f"(d[28]), "+f"(d[29]), "+f"(d[30]), "+f"(d[31]),
      "+f"(d[32]), "+f"(d[33]), "+f"(d[34]), "+f"(d[35]), "+f"(d[36]), "+f"(d[37]), "+f"(d[38]), "+f"(d[39]),
      "+f"(d[40]), "+f"(d[41]), "+f"(d[42]), "+f"(d[43]), "+f"(d[44]), "+f"(d[45]), "+f"(d[46]), "+f"(d[47])
    : "r"(a0), "r"(a1), "r"(a2), "r"(a3), "l"(descB));
}

template <int SCALE_D>
__device__ __forceinline__ void wgmma_n48(float (&d)[24], uint32_t a0, uint32_t a1, uint32_t a2, uint32_t a3, uint64_t descB) {
  if (SCALE_D == 0)
  asm volatile("wgmma.mma_async.sync.aligned.m64n48k16.f32.bf16.bf16 "
    "{%0, %1, %2, %3, %4, %5, %6, %7, %8, %9, %10, %11, %12, %13, %14, %15, "
    "%16, %17, %18, %19, %20, %21, %22, %23}, "
    "{%24, %25, %26, %27}, %28, 0, 1, 1, 0;\n"
    : "=f"(d[0]), "=f"(d[1]), "=f"(d[2]), "=f"(d[3]), "=f"(d[4]), "=f"(d[5]), "=f"(d[6]), "=f"(d[7]),
      "=f"(d[8]), "=f"(d[9]), "=f"(d[10]), "=f"(d[11]), "=f"(d[12]), "=f"(d[13]), "=f"(d[14]), "=f"(d[15]),
      "=f"(d[16]), "=f"(d[17]), "=f"(d[18]), "=f"(d[19]), "=f"(d[20]), "=f"(d[21]), "=f"(d[22]), "=f"(d[23])
    : "r"(a0), "r"(a1), "r"(a2), "r"(a3), "l"(descB));
  else
  asm volatile("wgmma.mma_async.sync.aligned.m64n48k16.f32.bf16.bf16 "
    "{%0, %1, %2, %3, %4, %5, %6, %7, %8, %9, %10, %11, %12, %13, %14, %15, "
    "%16, %17, %18, %19, %20, %21, %22, %23}, "
    "{%24, %25, %26, %27}, %28, 1, 1, 1, 0;\n"
    : "+f"(d[0]), "+f"(d[1]), "+f"(d[2]), "+f"(d[3]), "+f"(d[4]), "+f"(d[5]), "+f"(d[6]), "+f"(d[7]),
      "+f"(d[8]), "+f"(d[9]), "+f"(d[10]), "+f"(d[11]), "+f"(d[12]), "+f"(d[13]), "+f"(d[14]), "+f"(d[15]),
      "+f"(d[16]), "+f"(d[17]), "+f"(d[18]), "+f"(d[19]), "+f"(d[20]), "+f"(d[21]), "+f"(d[22]), "+f"(d[23])
    : "r"(a0), "r"(a1), "r"(a2), "r"(a3), "l"(descB));
}

template <int SCALE_D>
__device__ __forceinline__ void wgmma_n64(float (&d)[32], uint32_t a0, uint32_t a1, uint32_t a2, uint32_t a3, uint64_t descB) {
  if (SCALE_D == 0)
  asm volatile("wgmma.mma_async.sync.aligned.m64n64k16.f32.bf16.bf16 "
    "{%0, %1, %2, %3, %4, %5, %6, %7, %8, %9, %10, %11, %12, %13, %14, %15, "
    "%16, %17, %18, %19, %20, %21, %22, %23, %24, %25, %26, %27, %28, %29, %30, %31}, "
    "{%32, %33, %34, %35}, %36, 0, 1, 1, 0;\n"
    : "=f"(d[0]), "=f"(d[1]), "=f"(d[2]), "=f"(d[3]), "=f"(d[4]), "=f"(d[5]), "=f"(d[6]), "=f"(d[7]),
      "=f"(d[8]), "=f"(d[9]), "=f"(d[10]), "=f"(d[11]), "=f"(d[12]), "=f"(d[13]), "=f"(d[14]), "=f"(d[15]),
      "=f"(d[16]), "=f"(d[17]), "=f"(d[18]), "=f"(d[19]), "=f"(d[20]), "=f"(d[21]), "=f"(d[22]), "=f"(d[23]),
      "=f"(d[24]), "=f"(d[25]), "=f"(d[26]), "=f"(d[27]), "=f"(d[28]), "=f"(d[29]), "=f"(d[30]), "=f"(d[31])
    : "r"(a0), "r"(a1), "r"(a2), "r"(a3), "l"(descB));
  else if (SCALE_D == 2)
  asm volatile("wgmma.mma_async.sync.aligned.m64n64k16.f32.bf16.bf16 "
    "{%0, %1, %2, %3, %4, %5, %6, %7, %8, %9, %10, %11, %12, %13, %14, %15, "
    "%16, %17, %18, %19, %20, %21, %22, %23, %24, %25, %26, %27, %28, %29, %30, %31}, "
    "{%32, %33, %34, %35}, %36, 0, 1, 1, 0;\n"
    : "+f"(d[0]), "+f"(d[1]), "+f"(d[2]), "+f"(d[3]), "+f"(d[4]), "+f"(d[5]), "+f"(d[6]), "+f"(d[7]),
      "+f"(d[8]), "+f"(d[9]), "+f"(d[10]), "+f"(d[11]), "+f"(d[12]), "+f"(d[13]), "+f"(d[14]), "+f"(d[15]),
      "+f"(d[16]), "+f"(d[17]), "+f"(d[18]), "+f"(d[19]), "+f"(d[20]), "+f"(d[21]), "+f"(d[22]), "+f"(d[23]),
      "+f"(d[24]), "+f"(d[25]), "+f"(d[26]), "+f"(d[27]), "+f"(d[28]), "+f"(d[29]), "+f"(d[30]), "+f"(d[31])
    : "r"(a0), "r"(a1), "r"(a2), "r"(a3), "l"(descB));
  else
  asm volatile("wgmma.mma_async.sync.aligned.m64n64k16.f32.bf16.bf16 "
    "{%0, %1, %2, %3, %4, %5, %6, %7, %8, %9, %10, %11, %12, %13, %14, %15, "
    "%16, %17, %18, %19, %20, %21, %22, %23, %24, %25, %26, %27, %28, %29, %30, %31}, "
    "{%32, %33, %34, %35}, %36, 1, 1, 1, 0;\n"
    : "+f"(d[0]), "+f"(d[1]), "+f"(d[2]), "+f"(d[3]), "+f"(d[4]), "+f"(d[5]), "+f"(d[6]), "+f"(d[7]),
      "+f"(d[8]), "+f"(d[9]), "+f"(d[10]), "+f"(d[11]), "+f"(d[12]), "+f"(d[13]), "+f"(d[14]), "+f"(d[15]),
      "+f"(d[16]), "+f"(d[17]), "+f"(d[18]), "+f"(d[19]), "+f"(d[20]), "+f"(d[21]), "+f"(d[22]), "+f"(d[23]),
      "+f"(d[24]), "+f"(d[25]), "+f"(d[26]), "+f"(d[27]), "+f"(d[28]), "+f"(d[29]), "+f"(d[30]), "+f"(d[31])
    : "r"(a0), "r"(a1), "r"(a2), "r"(a3), "l"(descB));
}

template <int SCALE_D>
__device__ __forceinline__ void wgmma_n56(float (&d)[28], uint32_t a0, uint32_t a1, uint32_t a2, uint32_t a3, uint64_t descB) {
  if (SCALE_D == 0)
  asm volatile("wgmma.mma_async.sync.aligned.m64n56k16.f32.bf16.bf16 "
    "{%0, %1, %2, %3, %4, %5, %6, %7, %8, %9, %10, %11, %12, %13, %14, %15, "
    "%16, %17, %18, %19, %20, %21, %22, %23, %24, %25, %26, %27}, "
    "{%28, %29, %30, %31}, %32, 0, 1, 1, 0;\n"
    : "=f"(d[0]), "=f"(d[1]), "=f"(d[2]), "=f"(d[3]), "=f"(d[4]), "=f"(d[5]), "=f"(d[6]), "=f"(d[7]),
      "=f"(d[8]), "=f"(d[9]), "=f"(d[10]), "=f"(d[11]), "=f"(d[12]), "=f"(d[13]), "=f"(d[14]), "=f"(d[15]),
      "=f"(d[16]), "=f"(d[17]), "=f"(d[18]), "=f"(d[19]), "=f"(d[20]), "=f"(d[21]), "=f"(d[22]), "=f"(d[23]),
      "=f"(d[24]), "=f"(d[25]), "=f"(d[26]), "=f"(d[27])
    : "r"(a0), "r"(a1), "r"(a2), "r"(a3), "l"(descB));
  else
  asm volatile("wgmma.mma_async.sync.aligned.m64n56k16.f32.bf16.bf16 "
    "{%0, %1, %2, %3, %4, %5, %6, %7, %8, %9, %10, %11, %12, %13, %14, %15, "
    "%16, %17, %18, %19, %20, %21, %22, %23, %24, %25, %26, %27}, "
    "{%28, %29, %30, %31}, %32, 1, 1, 1, 0;\n"
    : "+f"(d[0]), "+f"(d[1]), "+f"(d[2]), "+f"(d[3]), "+f"(d[4]), "+f"(d[5]), "+f"(d[6]), "+f"(d[7]),
      "+f"(d[8]), "+f"(d[9]), "+f"(d[10]), "+f"(d[11]), "+f"(d[12]), "+f"(d[13]), "+f"(d[14]), "+f"(d[15]),
      "+f"(d[16]), "+f"(d[17]), "+f"(d[18]), "+f"(d[19]), "+f"(d[20]), "+f"(d[21]), "+f"(d[22]), "+f"(d[23]),
      "+f"(d[24]), "+f"(d[25]), "+f"(d[26]), "+f"(d[27])
    : "r"(a0), "r"(a1), "r"(a2), "r"(a3), "l"(descB));
}

template <int SCALE_D>
__device__ __forceinline__ void wgmma_n56t(float (&d)[28], uint32_t a0, uint32_t a1, uint32_t a2, uint32_t a3, uint64_t descB) {
  if (SCALE_D == 0)
  asm volatile("wgmma.mma_async.sync.aligned.m64n56k16.f32.bf16.bf16 "
    "{%0, %1, %2, %3, %4, %5, %6, %7, %8, %9, %10, %11, %12, %13, %14, %15, "
    "%16, %17, %18, %19, %20, %21, %22, %23, %24, %25, %26, %27}, "
    "{%28, %29, %30, %31}, %32, 0, 1, 1, 1;\n"
    : "=f"(d[0]), "=f"(d[1]), "=f"(d[2]), "=f"(d[3]), "=f"(d[4]), "=f"(d[5]), "=f"(d[6]), "=f"(d[7]),
      "=f"(d[8]), "=f"(d[9]), "=f"(d[10]), "=f"(d[11]), "=f"(d[12]), "=f"(d[13]), "=f"(d[14]), "=f"(d[15]),
      "=f"(d[16]), "=f"(d[17]), "=f"(d[18]), "=f"(d[19]), "=f"(d[20]), "=f"(d[21]), "=f"(d[22]), "=f"(d[23]),
      "=f"(d[24]), "=f"(d[25]), "=f"(d[26]), "=f"(d[27])
    : "r"(a0), "r"(a1), "r"(a2), "r"(a3), "l"(descB));
  else
  asm volatile("wgmma.mma_async.sync.aligned.m64n56k16.f32.bf16.bf16 "
    "{%0, %1, %2, %3, %4, %5, %6, %7, %8, %9, %10, %11, %12, %13, %14, %15, "
    "%16, %17, %18, %19, %20, %21, %22, %23, %24, %25, %26, %27}, "
    "{%28, %29, %30, %31}, %32, 1, 1, 1, 1;\n"
    : "+f"(d[0]), "+f"(d[1]), "+f"(d[2]), "+f"(d[3]), "+f"(d[4]), "+f"(d[5]), "+f"(d[6]), "+f"(d[7]),
      "+f"(d[8]), "+f"(d[9]), "+f"(d[10]), "+f"(d[11]), "+f"(d[12]), "+f"(d[13]), "+f"(d[14]), "+f"(d[15]),
      "+f"(d[16]), "+f"(d[17]), "+f"(d[18]), "+f"(d[19]), "+f"(d[20]), "+f"(d[21]), "+f"(d[22]), "+f"(d[23]),
      "+f"(d[24]), "+f"(d[25]), "+f"(d[26]), "+f"(d[27])
    : "r"(a0), "r"(a1), "r"(a2), "r"(a3), "l"(descB));
}

__global__ void __launch_bounds__(192) prepack_kernel(const __nv_bfloat16* __restrict__ wqkv, const __nv_bfloat16* __restrict__ wo) {
  __nv_bfloat16* dst = reinterpret_cast<__nv_bfloat16*>(g_wpack);
  const int c = threadIdx.x, nb = blockIdx.x;
  if (nb < 72) {
    __shared__ float red[6][8];
    const int h = nb / 18, j = nb % 18, part = j / 6;
    const int col = (part == 0 ? 192 : part == 1 ? 384 : 0) + h * 48 + (j % 6) * 8;
    uint4 raw = *reinterpret_cast<const uint4*>(wqkv + c * 576 + col);
    uint32_t u[4] = {raw.x, raw.y, raw.z, raw.w};
    float v[8];
#pragma unroll
    for (int i = 0; i < 4; i++) { v[2 * i] = lo2f(u[i]); v[2 * i + 1] = hi2f(u[i]); }
#pragma unroll
    for (int i = 0; i < 8; i++) {
      float s = v[i];
#pragma unroll
      for (int o = 16; o; o >>= 1) s += __shfl_xor_sync(~0u, s, o);
      if ((c & 31) == 0) red[c >> 5][i] = s;
    }
    __syncthreads();
    const int cc = c >> 5, q = (c >> 3) & 3, s1 = (c >> 2) & 1, hh = (c >> 1) & 1, e = c & 1;
    const int base = h * 27648 + (2 * cc + s1) * 2304 + j * 128 + hh * 64 + 2 * q + e;
#pragma unroll
    for (int n = 0; n < 8; n++) {
      float m = (red[0][n] + red[1][n] + red[2][n] + red[3][n] + red[4][n] + red[5][n]) * (1.0f / 192.0f);
      dst[base + n * 8] = __float2bfloat16(v[n] - m);
    }
  } else {
    const int jb = nb - 72, chunk = jb / 8, j = jb % 8;
    const int s = c >> 4, hh = (c >> 3) & 1, kk = c & 7;
    const int base = 110592 + (chunk * 12 + s) * 1024 + j * 128 + hh * 64 + kk;
#pragma unroll
    for (int n = 0; n < 8; n++) {
      const int ch = 32 * (jb >> 2) + 8 * (n >> 1) + 2 * (jb & 3) + (n & 1);
      dst[base + n * 8] = wo[c * 192 + ch];
    }
  }
}

__device__ __forceinline__ int window_of(int round, int nfull, int cta, int ncta, int wg) {
  if (round < nfull) return round * 2 * ncta + 2 * cta + wg;
  const int rem = NWIN - nfull * 2 * ncta;
  const int i = cta + wg * ncta;
  return i < rem ? nfull * 2 * ncta + i : -1;
}

__device__ __forceinline__ constexpr int qkv_off(int h, int s) { return ((3 * h + s / 4) % 8) * SLICE + (s % 4) * 4608; }
__device__ __forceinline__ constexpr int wo_off(int chunk, int s) { return 4 * SLICE + (chunk * 12 + s) * 2048; }

template <int H, int S0, int S1>
__device__ __forceinline__ void issue_qkv(float (&acc)[72], const uint32_t (&X)[48], uint64_t dW) {
#pragma unroll
  for (int s = S0; s < S1; s++) {
    if (s == 0) wgmma_n144<0>(acc, X[4 * s], X[4 * s + 1], X[4 * s + 2], X[4 * s + 3], dW + (qkv_off(H, s) >> 4));
    else        wgmma_n144<1>(acc, X[4 * s], X[4 * s + 1], X[4 * s + 2], X[4 * s + 3], dW + (qkv_off(H, s) >> 4));
  }
}
template <int H>
__device__ __forceinline__ void issue_kv(float (&acc)[48], const uint32_t (&X)[48], uint64_t dW) {
#pragma unroll
  for (int s = 0; s < 12; s++) {
    if (s == 0) wgmma_n96<0>(acc, X[4 * s], X[4 * s + 1], X[4 * s + 2], X[4 * s + 3], dW + (qkv_off(H, s) >> 4));
    else        wgmma_n96<1>(acc, X[4 * s], X[4 * s + 1], X[4 * s + 2], X[4 * s + 3], dW + (qkv_off(H, s) >> 4));
  }
}
template <int H>
__device__ __forceinline__ void issue_q(float (&acc)[24], const uint32_t (&X)[48], uint64_t dW) {
#pragma unroll
  for (int s = 0; s < 12; s++) {
    if (s == 0) wgmma_n48<0>(acc, X[4 * s], X[4 * s + 1], X[4 * s + 2], X[4 * s + 3], dW + ((qkv_off(H, s) + 3072) >> 4));
    else        wgmma_n48<1>(acc, X[4 * s], X[4 * s + 1], X[4 * s + 2], X[4 * s + 3], dW + ((qkv_off(H, s) + 3072) >> 4));
  }
}
template <int CHUNK, int S0, int S1>
__device__ __forceinline__ void issue_proj(float (&acc)[32], const uint32_t (&Of)[48], uint64_t dW) {
#pragma unroll
  for (int s = S0; s < S1; s++) {
    if (s == 0) wgmma_n64<(CHUNK == 2 ? 2 : 0)>(acc, Of[4 * s], Of[4 * s + 1], Of[4 * s + 2], Of[4 * s + 3], dW + (wo_off(CHUNK, s) >> 4));
    else        wgmma_n64<1>(acc, Of[4 * s], Of[4 * s + 1], Of[4 * s + 2], Of[4 * s + 3], dW + (wo_off(CHUNK, s) >> 4));
  }
}
__device__ __forceinline__ void store_kv(const float* a, uint32_t r, uint32_t addr) {
#pragma unroll
  for (int j = 0; j < 6; j += 2)
    stsm4(addr + j * KV_PITCH, hmul_b<0>(pack2(a[4 * j], a[4 * j + 1]), r), hmul_b<1>(pack2(a[4 * j + 2], a[4 * j + 3]), r),
          hmul_b<0>(pack2(a[4 * j + 4], a[4 * j + 5]), r), hmul_b<1>(pack2(a[4 * j + 6], a[4 * j + 7]), r));
}
__device__ __forceinline__ void pack_q(const float* a, uint32_t r, uint32_t (&Q)[12]) {
#pragma unroll
  for (int j = 0; j < 6; j++) {
    Q[2 * j] = hmul_b<0>(pack2(a[4 * j], a[4 * j + 1]), r);
    Q[2 * j + 1] = hmul_b<1>(pack2(a[4 * j + 2], a[4 * j + 3]), r);
  }
}
__device__ __forceinline__ void issue_s(float (&S)[28], const uint32_t (&Q)[12], uint64_t dK) {
  wgmma_n56<0>(S, Q[0], Q[1], Q[2], Q[3], dK);
  wgmma_n56<1>(S, Q[4], Q[5], Q[6], Q[7], dK + (2 * KV_PITCH >> 4));
  wgmma_n56<1>(S, Q[8], Q[9], Q[10], Q[11], dK + (4 * KV_PITCH >> 4));
}
__device__ __forceinline__ void softmax_pv(float (&S)[28], uint64_t dV) {
  uint32_t P[16];
#pragma unroll
  for (int j = 0; j < 14; j++) P[j] = pack2(S[2 * j], S[2 * j + 1]);
  const uint32_t m0 = hmax(hmax(hmax(hmax(P[0], P[2]), P[4]), hmax(hmax(P[6], P[8]), P[10])), P[12]);
  const uint32_t m1 = hmax(hmax(hmax(hmax(P[1], P[3]), P[5]), hmax(hmax(P[7], P[9]), P[11])), P[13]);
  uint32_t mx = hmax(__byte_perm(m0, m1, 0x5410), __byte_perm(m0, m1, 0x7632));
  mx = hmax(mx, __shfl_xor_sync(~0u, mx, 1));
  mx = hmax(mx, __shfl_xor_sync(~0u, mx, 2));
  P[12] = hex1(hsub_b<0>(P[12], mx)); P[13] = hex1(hsub_b<1>(P[13], mx)); P[14] = 0; P[15] = 0;
#pragma unroll
  for (int j = 0; j < 12; j++) P[j] = hex2((j & 1) ? hsub_b<1>(P[j], mx) : hsub_b<0>(P[j], mx));
  wg_fence();
  wgmma_n56t<0>(S, P[0], P[1], P[2], P[3], dV);
  wgmma_n56t<1>(S, P[4], P[5], P[6], P[7], dV + (256 >> 4));
  wgmma_n56t<1>(S, P[8], P[9], P[10], P[11], dV + (512 >> 4));
  wgmma_n56t<1>(S, P[12], P[13], P[14], P[15], dV + (768 >> 4));
  wg_commit();
}
template <int S0, int S1>
__device__ __forceinline__ void load_x(uint32_t (&X)[48], uint32_t t0) {
#pragma unroll
  for (int s = S0; s < S1; s++)
    asm volatile("ld.shared.v4.u32 {%0,%1,%2,%3}, [%4];" : "=r"(X[4 * s]), "=r"(X[4 * s + 1]), "=r"(X[4 * s + 2]), "=r"(X[4 * s + 3])
                 : "r"(((s & 1) ? (t0 ^ 16) : t0) + (s >> 1) * 128) : "memory");
}
__device__ __forceinline__ void proxy_fence() { asm volatile("fence.proxy.async.shared::cta;" ::: "memory"); }

template <int CHUNK>
__device__ __forceinline__ void store_out(const float (&p)[32], const uint32_t (&X)[48], uint8_t* o0, uint8_t* o1) {
#pragma unroll
  for (int c = 0; c < 2; c++) {
    const int cc = CHUNK * 2 + c;
    uint4 a, b;
    a.x = hadd(X[8 * cc],     pack2(p[16 * c],      p[16 * c + 1]));
    b.x = hadd(X[8 * cc + 1], pack2(p[16 * c + 2],  p[16 * c + 3]));
    a.y = hadd(X[8 * cc + 2], pack2(p[16 * c + 4],  p[16 * c + 5]));
    b.y = hadd(X[8 * cc + 3], pack2(p[16 * c + 6],  p[16 * c + 7]));
    a.z = hadd(X[8 * cc + 4], pack2(p[16 * c + 8],  p[16 * c + 9]));
    b.z = hadd(X[8 * cc + 5], pack2(p[16 * c + 10], p[16 * c + 11]));
    a.w = hadd(X[8 * cc + 6], pack2(p[16 * c + 12], p[16 * c + 13]));
    b.w = hadd(X[8 * cc + 7], pack2(p[16 * c + 14], p[16 * c + 15]));
    asm volatile("st.global.v4.u32 [%0], {%1,%2,%3,%4};" :: "l"(o0 + cc * 64), "r"(a.x), "r"(a.y), "r"(a.z), "r"(a.w) : "memory");
    asm volatile("st.global.v4.u32 [%0], {%1,%2,%3,%4};" :: "l"(o1 + cc * 64), "r"(b.x), "r"(b.y), "r"(b.z), "r"(b.w) : "memory");
  }
}

__device__ __forceinline__ void finish_o(const float (&o)[28], uint32_t* Of) {
  float i0, i1;
  asm("rcp.approx.ftz.f32 %0, %1;" : "=f"(i0) : "f"(o[24]));
  asm("rcp.approx.ftz.f32 %0, %1;" : "=f"(i1) : "f"(o[26]));
  const uint32_t inv = pack2(i0, i1);
#pragma unroll
  for (int j = 0; j < 6; j++) {
    Of[2 * j]     = hmul_b<0>(pack2(o[4 * j], o[4 * j + 1]), inv);
    Of[2 * j + 1] = hmul_b<1>(pack2(o[4 * j + 2], o[4 * j + 3]), inv);
  }
}

__global__ void __launch_bounds__(384, 1)
fused_kernel(const __grid_constant__ CUtensorMap tmx, const __grid_constant__ Descs ds, const __nv_bfloat16* __restrict__ dw, __nv_bfloat16* __restrict__ out, const int never) {
  extern __shared__ __align__(1024) uint8_t smem[];
  const uint32_t sb = (uint32_t)__cvta_generic_to_shared(smem);
  const int tid = threadIdx.x, lane = tid & 31;
  const int warp = __shfl_sync(0xffffffffu, tid >> 5, 0);
  const int cta = blockIdx.x, ncta = gridDim.x;
  const int nfull = NWIN / (2 * ncta);
  const int nrounds = nfull + ((NWIN - nfull * 2 * ncta) > cta ? 1 : 0);

  if (tid == 0) {
    if ((sb & 0x3FFFF) != SMEM_BASE) __trap();
    for (int i = 0; i < 6; i++) { mbar_init(sb + BAR_WFULL + 8 * i, 1); mbar_init(sb + BAR_WEMPTY + 8 * i, 8); }
    for (int i = 0; i < 9; i++) mbar_init(sb + BAR_XFULL + 8 * i, 1);
    mbar_init(sb + BAR_TFULL, 3);
    mbar_init(sb + BAR_TEMPTY, 8);
    asm volatile("fence.mbarrier_init.release.cluster;" ::: "memory");
  }
  if (tid < 128) {
    const uint32_t v = (tid & 63) < 49 ? 0x3f803f80u : 0u;
    *reinterpret_cast<uint4*>(smem + OFF_KV + (tid >> 6) * KV_BYTES + 6 * KV_PITCH + (tid & 63) * 16) = make_uint4(v, v, v, v);
    asm volatile("fence.proxy.async.shared::cta;" ::: "memory");
  }
  __syncthreads();

  if (warp >= 8) {
    asm volatile("setmaxnreg.dec.sync.aligned.u32 " PREGS ";");
    if (warp == 11) {
      if (lane == 0) {
        const uint8_t* wp = reinterpret_cast<const uint8_t*>(g_wpack);
        for (int r = 0; r < nrounds; r++) {
#pragma unroll
          for (int k = 0; k < 16; k++) {
            const int st = k < 12 ? k / 3 : 4 + (k - 12) / 2;
            const int kp = (k + 8) & 15;
            const int stp = kp < 12 ? kp / 3 : 4 + (kp - 12) / 2;
            const bool first_of_prev = (k == 0) || (stp != (((k + 7) & 15) < 12 ? ((k + 7) & 15) / 3 : 4 + (((k + 7) & 15) - 12) / 2));
            if (first_of_prev || k == 8) {
              if (k >= 8) mbar_wait(sb + BAR_WEMPTY + 8 * stp, r & 1);
              else if (r > 0) mbar_wait(sb + BAR_WEMPTY + 8 * stp, (r - 1) & 1);
            }
            const bool first = k < 12 ? (k % 3 == 0) : (k % 2 == 0);
            if (first) mbar_expect(sb + BAR_WFULL + 8 * st, (k < 12 ? 3 : 2) * SLICE);
            asm volatile("cp.async.bulk.shared::cluster.global.mbarrier::complete_tx::bytes [%0], [%1], %2, [%3];"
                         :: "r"(sb + OFF_W + (k & 7) * SLICE), "l"(wp + k * SLICE), "n"(SLICE), "r"(sb + BAR_WFULL + 8 * st) : "memory");
          }
        }
      }
    } else {
      const int cw = warp - 8;
      const int win = lane >> 4;
      const int ch0 = cw * 64 + (lane & 15) * 4;
      uint32_t wt[9][2];
#pragma unroll
      for (int t = 0; t < 9; t++) {
        uint2 v = *reinterpret_cast<const uint2*>(dw + t * CH + ch0);
        wt[t][0] = v.x; wt[t][1] = v.y;
      }
      const uint32_t xs = sb + OFF_X + cw * 3 * XSLOT;
      const uint32_t xld = xs + (lane >> 4) * 1152 + (lane & 15) * 8;
      const uint32_t xbar = sb + BAR_XFULL + cw * 24;
      const uint32_t st0 = sb + OFF_TILE + win * TILE_BYTES + ch0 * 4;
      const uint32_t st1 = sb + OFF_TILE + win * TILE_BYTES + ((ch0 * 4) ^ 16);
      const uint64_t tm = reinterpret_cast<uint64_t>(&tmx);
      int cx0, cy0, cx1, cy1;
      auto coords = [&](int r) {
        const int w0 = window_of(r, nfull, cta, ncta, 0);
        int w1 = window_of(r, nfull, cta, ncta, 1);
        if (w1 < 0) w1 = w0;
        const int a = w0 / NWX, b = w1 / NWX;
        cx0 = (w0 - a * NWX) * 7 - 1; cy0 = a * 7 - 1;
        cx1 = (w1 - b * NWX) * 7 - 1; cy1 = b * 7 - 1;
      };
      auto issue = [&](int slot, int dy) {
        asm volatile("{\n.reg .pred p;\nelect.sync _|p, 0xffffffff;\n"
                     "@p mbarrier.arrive.expect_tx.shared::cta.b64 _, [%2], %8;\n"
                     "@p cp.async.bulk.tensor.3d.shared::cluster.global.mbarrier::complete_tx::bytes [%0], [%1, {%3, %4, %5}], [%2];\n"
                     "@p cp.async.bulk.tensor.3d.shared::cluster.global.mbarrier::complete_tx::bytes [%0 + 1152], [%1, {%3, %6, %7}], [%2];\n}\n"
                     :: "r"(xs + slot * XSLOT), "l"(tm), "r"(xbar + slot * 8), "r"(cw * 64), "r"(cx0), "r"(cy0 + dy), "r"(cx1), "r"(cy1 + dy), "n"(XSLOT) : "memory");
      };
      coords(0);
      issue(0, 0); issue(1, 1); issue(2, 2);
      for (int r = 0; r < nrounds; r++) {
        const bool more = r + 1 < nrounds;
        uint32_t accA[7][2], accB[7][2], ctr[7][2], held[2];
#pragma unroll
        for (int i = 0; i < 9; i++) {
          mbar_wait(xbar + (i % 3) * 8, (r + i / 3) & 1);
          if (i == 7 && more) coords(r + 1);
          if (i == 0) { if (r > 0) issue(2, 2); }
          else if (i < 7) issue((i + 2) % 3, i + 2);
          else if (more) issue((i + 2) % 3, i - 7);
          if (i == 2 && r > 0) mbar_wait(sb + BAR_TEMPTY, (r - 1) & 1);
          if (i == 2) { TR(8); }
          uint32_t cur[9][2];
#pragma unroll
          for (int p = 0; p < 5; p++)
            asm volatile("ld.shared.v2.u32 {%0,%1}, [%2];" : "=r"(cur[p][0]), "=r"(cur[p][1]) : "r"(xld + (i % 3) * XSLOT + p * 128));
#pragma unroll
          for (int j = 0; j < 7; j++) {
            if (j >= 1 && j + 4 < 9)
              asm volatile("ld.shared.v2.u32 {%0,%1}, [%2];" : "=r"(cur[j + 4][0]), "=r"(cur[j + 4][1]) : "r"(xld + (i % 3) * XSLOT + (j + 4) * 128));
            if (i >= 2) {
              uint32_t o[2];
#pragma unroll
              for (int e = 0; e < 2; e++) {
                uint32_t a = hfma(cur[j][e], wt[6][e], accA[j][e]);
                a = hfma(cur[j + 1][e], wt[7][e], a);
                a = hfma(cur[j + 2][e], wt[8][e], a);
                o[e] = hadd(ctr[j][e], a);
              }
              const int tok = (i - 2) * 7 + j, ps = tok >> 1;
              if (!(tok & 1)) { held[0] = o[0]; held[1] = o[1]; }
              if ((tok & 1) || tok == 48)
                asm volatile("st.shared.v4.u32 [%0], {%1,%2,%3,%4};" :: "r"(((ps & 1) ? st1 : st0) + ps * 768), "r"(held[0]), "r"(o[0]), "r"(held[1]), "r"(o[1]) : "memory");
            }
#pragma unroll
            for (int e = 0; e < 2; e++) {
              if (i >= 1 && i <= 7) {
                uint32_t a = hfma(cur[j][e], wt[3][e], accB[j][e]);
                a = hfma(cur[j + 1][e], wt[4][e], a);
                accA[j][e] = hfma(cur[j + 2][e], wt[5][e], a);
                ctr[j][e] = cur[j + 1][e];
              }
              if (i <= 6) {
                uint32_t a = hmul(cur[j][e], wt[0][e]);
                a = hfma(cur[j + 1][e], wt[1][e], a);
                accB[j][e] = hfma(cur[j + 2][e], wt[2][e], a);
              }
            }
          }
        }
        __syncwarp();
        if (lane == 0) mbar_arrive(sb + BAR_TFULL);
        TR(27);
      }
    }
  } else {
    asm volatile("setmaxnreg.inc.sync.aligned.u32 " CREGS ";");
    const int wg = warp >> 2, w4 = warp & 3, g = lane >> 2, q = lane & 3;
    const int row0 = w4 * 16 + g, row1 = row0 + 8;
    const int ps = min(w4 * 8 + g, 24);
    const int tok0 = 2 * ps, tok1 = min(2 * ps + 1, 48);
    const uint32_t kv = sb + OFF_KV + wg * KV_BYTES;
    const int srow = w4 * 16 + (lane & 15);
    const uint32_t vst = kv + (lane >> 4) * KV_PITCH + srow * 16;
    const uint32_t kst = vst + (srow < 56 ? 1024 : 0);
    const uint32_t off0 = ((tok0 / 7) * IMG + tok0 % 7) * 384 + q * 16, off1 = ((tok1 / 7) * IMG + tok1 % 7) * 384 + q * 16;
    const uint32_t vmask = (row0 < 49 ? 0xffffu : 0u) | (row1 < 49 ? 0xffff0000u : 0u);
    const float qscale = 0.14433756729740643f * 1.4426950408889634f;

    const uint32_t tx = sb + OFF_TILE + wg * TILE_BYTES + ps * 768 + q * 32 + (ps & 1) * 16;
    const int myrounds = window_of(nrounds - 1, nfull, cta, ncta, wg) < 0 ? nrounds - 1 : nrounds;

    if (never == 2) return;
    uint32_t X[48];
    float acc[72];
    mbar_wait(sb + BAR_TFULL, 0);
    load_x<0, 12>(X, tx);
    __syncwarp();
    if (lane == 0) mbar_arrive(sb + BAR_TEMPTY);
    mbar_wait(sb + BAR_WFULL, 0);
    wg_fence();
    issue_qkv<0, 0, 12>(acc, X, ds.w[0]);
    wg_commit();

    for (int r = 0;; r++) {
      const uint32_t par = r & 1;
      if (r == myrounds) {
        wg_wait<0>(); keep(acc);
        if (r < nrounds)
          for (int s = 0; s < 6; s++) { mbar_wait(sb + BAR_WFULL + 8 * s, par); if (lane == 0) mbar_arrive(sb + BAR_WEMPTY + 8 * s); }
        break;
      }
      TR(0);
      uint32_t rK, rV, rQ;
      {
        uint32_t sm[2];
#pragma unroll
        for (int a = 0; a < 2; a++) {
          uint32_t t[12];
#pragma unroll
          for (int i = 0; i < 12; i++) t[i] = hadd(X[4 * i + a], X[4 * i + 2 + a]);
#pragma unroll
          for (int i = 0; i < 6; i++) t[i] = hadd(t[i], t[i + 6]);
#pragma unroll
          for (int i = 0; i < 3; i++) t[i] = hadd(t[i], t[i + 3]);
          sm[a] = hadd(hadd(t[0], t[1]), t[2]);
        }
        uint32_t m = hadd(__byte_perm(sm[0], sm[1], 0x5410), __byte_perm(sm[0], sm[1], 0x7632));
        m = hadd(m, __shfl_xor_sync(~0u, m, 1));
        m = hadd(m, __shfl_xor_sync(~0u, m, 2));
        m = hmul(m, 0x3bab3babu);
        float var[2];
#pragma unroll
        for (int a = 0; a < 2; a++) {
          uint32_t t[4];
#pragma unroll
          for (int i = 0; i < 24; i++) {
            const uint32_t d = a ? hsub_b<1>(X[2 * i + 1], m) : hsub_b<0>(X[2 * i], m);
            t[i & 3] = i < 4 ? hmul(d, d) : hfma(d, d, t[i & 3]);
          }
          const uint32_t s = hadd(hadd(t[0], t[1]), hadd(t[2], t[3]));
          float v = lo2f(s) + hi2f(s);
          v += __shfl_xor_sync(~0u, v, 1);
          v += __shfl_xor_sync(~0u, v, 2);
          asm("rsqrt.approx.ftz.f32 %0, %1;" : "=f"(var[a]) : "f"(fmaf(v, 1.0f / 192.0f, 1e-5f)));
        }
        rK = pack2(var[0], var[1]);
        rV = rK & vmask;
        rQ = pack2(var[0] * qscale, var[1] * qscale);
        anchor(rQ);
      }
      uint32_t Of[48], Q[12];
      float S[28];
      TR(1);
      wg_wait<0>(); keep(acc);
      TR(2);
      if (lane == 0) mbar_arrive(sb + BAR_WEMPTY);
      store_kv(acc, rK, kst);
      store_kv(acc + 24, rV, vst);
      proxy_fence();
      pack_q(acc + 48, rQ, Q);
      mbar_wait(sb + BAR_WFULL + 8, par);
      bar_sync(1 + wg);
      TR(3);
      wg_fence();
      issue_s(S, Q, ds.k[wg][0]); wg_commit();
      issue_qkv<1, 0, 12>(acc, X, ds.w[2]); wg_commit();
      wg_wait<1>(); keep(S);
      TR(4);
      softmax_pv(S, ds.v[wg][0]);
      TR(5);
      wg_wait<1>(); keep(acc);
      TR(6);
      if (lane == 0) mbar_arrive(sb + BAR_WEMPTY + 8);
      store_kv(acc, rK, kst);
      wg_wait<0>(); keep(S);
      bar_sync(1 + wg);
      store_kv(acc + 24, rV, vst);
      proxy_fence();
      pack_q(acc + 48, rQ, Q);
      finish_o(S, Of);
      mbar_wait(sb + BAR_WFULL + 16, par);
      bar_sync(1 + wg);
      TR(7);
      wg_fence();
      issue_s(S, Q, ds.k[wg][1]); wg_commit();
      issue_qkv<2, 0, 12>(acc, X, ds.w[3]); wg_commit();
      wg_wait<1>(); keep(S);
      TR(8);
      softmax_pv(S, ds.v[wg][1]);
      TR(9);
      wg_wait<1>(); keep(acc);
      TR(10);
      if (lane == 0) mbar_arrive(sb + BAR_WEMPTY + 16);
      store_kv(acc, rK, kst);
      wg_wait<0>(); keep(S);
      bar_sync(1 + wg);
      store_kv(acc + 24, rV, vst);
      proxy_fence();
      pack_q(acc + 48, rQ, Q);
      finish_o(S, Of + 12);
      mbar_wait(sb + BAR_WFULL + 24, par);
      bar_sync(1 + wg);
      TR(11);
      {
        float kva[48], qa[24];
        wg_fence();
        issue_s(S, Q, ds.k[wg][2]); wg_commit();
        issue_kv<3>(kva, X, ds.w[4]); wg_commit();
        wg_wait<1>(); keep(S);
        TR(12);
        softmax_pv(S, ds.v[wg][2]);
        TR(13);
        wg_wait<0>(); keep(S); keep(kva);
        TR(14);
        wg_fence();
        issue_q<3>(qa, X, ds.w[5]); wg_commit();
        bar_sync(1 + wg);
        store_kv(kva, rK, kst);
        store_kv(kva + 24, rV, vst);
        proxy_fence();
        finish_o(S, Of + 24);
        anchor(Of[35]);
        wg_wait<0>(); keep(qa);
        TR(15);
        if (lane == 0) mbar_arrive(sb + BAR_WEMPTY + 24);
        pack_q(qa, rQ, Q);
      }
      mbar_wait(sb + BAR_WFULL + 32, par);
      bar_sync(1 + wg);
      TR(16);
      float pa[32], pb[32];
      wg_fence();
      issue_s(S, Q, ds.k[wg][3]); wg_commit();
      issue_proj<0, 0, 9>(pa, Of, ds.w[6]); wg_commit();
      wg_wait<1>(); keep(S);
      TR(17);
      softmax_pv(S, ds.v[wg][3]);
      TR(18);
      mbar_wait(sb + BAR_WFULL + 40, par);
      wg_wait<0>(); keep(S); keep(pa);
      TR(19);
      finish_o(S, Of + 36);
      wg_fence();
      issue_proj<0, 9, 12>(pa, Of, ds.w[7]); wg_commit();
      issue_proj<1, 0, 12>(pb, Of, ds.w[8]); wg_commit();
      bar_sync(1 + wg);
      TR(20);
      const bool more = r + 1 < myrounds;
      const int w = window_of(r, nfull, cta, ncta, wg);
      const int wy = w / NWX, wx = w - wy * NWX;
      const uint32_t wb = (uint32_t)(wy * 7 * IMG + wx * 7) * 384u;
      uint8_t* o0 = reinterpret_cast<uint8_t*>(out) + (wb + off0);
      uint8_t* o1 = reinterpret_cast<uint8_t*>(out) + (wb + off1);
      if (XWIN && more) mbar_wait(sb + BAR_TFULL, par ^ 1);
      wg_wait<1>(); keep(pa);
      TR(21);
      store_out<0>(pa, X, o0, o1);
      wg_fence();
      issue_proj<2, 0, 12>(pa, Of, ds.w[9]); wg_commit();
      if (XWIN) load_x<0, 4>(X, tx);
      TR(22);
      wg_wait<1>(); keep(pb);
      TR(23);
      if (lane == 0) mbar_arrive(sb + BAR_WEMPTY + 32);
      store_out<1>(pb, X, o0, o1);
      if (XWIN) load_x<4, 8>(X, tx);
      if (XWIN && more) mbar_wait(sb + BAR_WFULL, par ^ 1);
      TR(24);
      wg_wait<0>(); keep(pa);
      TR(25);
      if (lane == 0) mbar_arrive(sb + BAR_WEMPTY + 40);
      wg_fence();
      issue_qkv<0, 0, 8>(acc, X, ds.w[10]); wg_commit();
      sched_fence<1>(never);
      store_out<2>(pa, X, o0, o1);
      load_x<8, 12>(X, tx);
      __syncwarp();
      if (lane == 0) mbar_arrive(sb + BAR_TEMPTY);
      wg_fence();
      issue_qkv<0, 8, 12>(acc, X, ds.w[11]); wg_commit();
      TR(26);
    }
  }
}

typedef CUresult (*EncodeFn)(CUtensorMap*, CUtensorMapDataType, cuuint32_t, void*, const cuuint64_t*, const cuuint64_t*,
                             const cuuint32_t*, const cuuint32_t*, CUtensorMapInterleave, CUtensorMapSwizzle,
                             CUtensorMapL2promotion, CUtensorMapFloatOOBfill);

}

extern "C" void kernel_launch(void* const* d_in, const int* in_sizes, int n_in, void* d_out, int out_size) {
  const __nv_bfloat16* x = (const __nv_bfloat16*)d_in[0];
  const __nv_bfloat16* dw = (const __nv_bfloat16*)d_in[1];
  const __nv_bfloat16* wqkv = (const __nv_bfloat16*)d_in[2];
  const __nv_bfloat16* wo = (const __nv_bfloat16*)d_in[3];
  static EncodeFn encode = nullptr;
  static int nsm = 0;
  if (!encode) {
    void* fn = nullptr;
    cudaDriverEntryPointQueryResult qr;
    cudaGetDriverEntryPoint("cuTensorMapEncodeTiled", &fn, cudaEnableDefault, &qr);
    encode = (EncodeFn)fn;
    int dev = 0;
    cudaGetDevice(&dev);
    cudaDeviceGetAttribute(&nsm, cudaDevAttrMultiProcessorCount, dev);
    cudaFuncSetAttribute(fused_kernel, cudaFuncAttributeMaxDynamicSharedMemorySize, SMEM_BYTES);
  }
  CUtensorMap tmx;
  cuuint64_t gdim[3] = {CH, IMG, IMG};
  cuuint64_t gstr[2] = {CH * 2, (cuuint64_t)CH * 2 * IMG};
  cuuint32_t box[3] = {64, 9, 1};
  cuuint32_t estr[3] = {1, 1, 1};
  encode(&tmx, CU_TENSOR_MAP_DATA_TYPE_BFLOAT16, 3, (void*)x, gdim, gstr, box, estr, CU_TENSOR_MAP_INTERLEAVE_NONE,
         CU_TENSOR_MAP_SWIZZLE_NONE, CU_TENSOR_MAP_L2_PROMOTION_L2_128B, CU_TENSOR_MAP_FLOAT_OOB_FILL_NONE);
  Descs ds;
  for (int i = 0; i < 12; i++) ds.w[i] = mkdesc(SMEM_BASE + OFF_W, 128, 256);
  for (int g = 0; g < 2; g++)
    for (int i = 0; i < 4; i++) {
      ds.k[g][i] = mkdesc(SMEM_BASE + OFF_KV + g * KV_BYTES + 1024, KV_PITCH, 128);
      ds.v[g][i] = mkdesc(SMEM_BASE + OFF_KV + g * KV_BYTES, 128, KV_PITCH);
    }
  prepack_kernel<<<96, 192>>>(wqkv, wo);
  fused_kernel<<<nsm, 384, SMEM_BYTES>>>(tmx, ds, dw, (__nv_bfloat16*)d_out, 0);
}
```

```cpp
#include <cuda_runtime.h>
#include <cuda_bf16.h>
#include <cuda.h>
#include <stdint.h>

#define CREGS "208"
#define PREGS "88"
#define PP12 2
#define PP3 1
#define GA 2
#define GB 8
#define GC 12
#define GFENCE 1
namespace {

constexpr int IMG = 511;
constexpr int CH = 192;
constexpr int NWX = 73;
constexpr int NWIN = NWX * NWX;
constexpr int SLICE = 18432;
constexpr int OFF_W = 0;
constexpr int KV_BYTES = 12544, KV_PITCH = 1920;
constexpr int OFF_KV = 8 * SLICE;
constexpr int TILE_BYTES = 25 * 768;
constexpr int OFF_TILE = OFF_KV + 2 * KV_BYTES;
constexpr int XSLOT = 2304;
constexpr int OFF_X = OFF_TILE + 2 * TILE_BYTES;
constexpr int OFF_BAR = OFF_X + 9 * XSLOT;
constexpr int BAR_WFULL = OFF_BAR;
constexpr int CNT_WREL = OFF_BAR + 48;
constexpr int BAR_XFULL = OFF_BAR + 72;
constexpr int BAR_TFULL = OFF_BAR + 144;
constexpr int BAR_TEMPTY = OFF_BAR + 152;
constexpr int BAR_TPART = OFF_BAR + 160;
constexpr int BAR_SFULL = OFF_BAR + 176;
constexpr int OFF_RSTD = OFF_BAR + 192;
constexpr int OFF_DUMMY = OFF_RSTD + 200;
constexpr int OFF_TRACE = OFF_DUMMY + 152;
constexpr int SMEM_BYTES = OFF_TRACE;

constexpr int SMEM_BASE = 1024;
struct Descs { uint64_t w[12]; uint64_t k[2][4]; uint64_t v[2][4]; const uint8_t* src[16]; };

__device__ uint4 g_wpack[16 * SLICE / 16];
#define TR(id)
template <int ID> __device__ __forceinline__ void sched_fence(uint32_t v) {
  asm volatile("{\n.reg .pred p;\nsetp.ne.u32 p, %0, %1;\n@p bra.uni SF_%=;\ntrap;\nSF_%=:\n}\n" :: "r"(v), "n"(ID) : "memory");
}
__device__ __forceinline__ void anchor(uint32_t v) { sched_fence<0x7fc1ffc1>(v); }

template <int V> struct IC { static constexpr int v = V; };
typedef __nv_bfloat162 bf2;
__device__ __forceinline__ bf2 u2b(uint32_t u) { return *reinterpret_cast<bf2*>(&u); }
__device__ __forceinline__ uint32_t b2u(bf2 b) { return *reinterpret_cast<uint32_t*>(&b); }
__device__ __forceinline__ uint32_t pack2(float lo, float hi) {
  uint32_t r; asm("cvt.rn.bf16x2.f32 %0, %1, %2;" : "=r"(r) : "f"(hi), "f"(lo)); return r;
}
__device__ __forceinline__ uint32_t hadd(uint32_t a, uint32_t b) { return b2u(__hadd2_rn(u2b(a), u2b(b))); }
__device__ __forceinline__ uint32_t hmul(uint32_t a, uint32_t b) { return b2u(__hmul2_rn(u2b(a), u2b(b))); }
__device__ __forceinline__ uint32_t hfma(uint32_t a, uint32_t b, uint32_t c) { return b2u(__hfma2(u2b(a), u2b(b), u2b(c))); }
__device__ __forceinline__ uint32_t hmax(uint32_t a, uint32_t b) { return b2u(__hmax2(u2b(a), u2b(b))); }
template <int HI> __device__ __forceinline__ bf2 bcast(uint32_t a) { return HI ? __high2bfloat162(u2b(a)) : __low2bfloat162(u2b(a)); }
template <int HI> __device__ __forceinline__ uint32_t hmul_b(uint32_t a, uint32_t s) { return b2u(__hmul2_rn(u2b(a), bcast<HI>(s))); }
template <int HI> __device__ __forceinline__ uint32_t hsub_b(uint32_t a, uint32_t s) { return b2u(__hsub2_rn(u2b(a), bcast<HI>(s))); }
__device__ __forceinline__ uint32_t hex2(uint32_t a) { uint32_t r; asm("ex2.approx.ftz.bf16x2 %0, %1;" : "=r"(r) : "r"(a)); return r; }
__device__ __forceinline__ uint32_t hex1(uint32_t a) {
  uint32_t r; asm("{\n.reg .b16 l, h, e;\nmov.b32 {l, h}, %1;\nex2.approx.ftz.bf16 e, l;\ncvt.u32.u16 %0, e;\n}\n" : "=r"(r) : "r"(a)); return r;
}
__device__ __forceinline__ float lo2f(uint32_t a) { return __uint_as_float(a << 16); }
__device__ __forceinline__ float hi2f(uint32_t a) { return __uint_as_float(a & 0xffff0000u); }

__device__ __forceinline__ void mbar_init(uint32_t bar, uint32_t cnt) { asm volatile("mbarrier.init.shared::cta.b64 [%0], %1;" :: "r"(bar), "r"(cnt) : "memory"); }
__device__ __forceinline__ void mbar_arrive(uint32_t bar) { asm volatile("mbarrier.arrive.shared::cta.b64 _, [%0];" :: "r"(bar) : "memory"); }
__device__ __forceinline__ void mbar_expect(uint32_t bar, uint32_t bytes) { asm volatile("mbarrier.arrive.expect_tx.shared::cta.b64 _, [%0], %1;" :: "r"(bar), "r"(bytes) : "memory"); }
template <int HINT>
__device__ __forceinline__ bool mbar_try(uint32_t bar, uint32_t parity) {
  uint32_t ok;
  if (HINT) asm volatile("{\n.reg .pred p;\nmbarrier.try_wait.parity.shared::cta.b64 p, [%1], %2, %3;\nselp.u32 %0, 1, 0, p;\n}\n" : "=r"(ok) : "r"(bar), "r"(parity), "n"(HINT) : "memory");
  else asm volatile("{\n.reg .pred p;\nmbarrier.try_wait.parity.shared::cta.b64 p, [%1], %2;\nselp.u32 %0, 1, 0, p;\n}\n" : "=r"(ok) : "r"(bar), "r"(parity) : "memory");
  return ok != 0;
}
__device__ __forceinline__ void mbar_wait(uint32_t bar, uint32_t parity) {
  if (__builtin_expect(!mbar_try<0>(bar, parity), 0)) {
    uint32_t n = 0;
    while (!mbar_try<4000>(bar, parity)) { if (++n > (1u << 20)) __trap(); }
  }
}
__device__ __forceinline__ void wg_fence() { asm volatile("wgmma.fence.sync.aligned;" ::: "memory"); }
__device__ __forceinline__ void wg_commit() { asm volatile("wgmma.commit_group.sync.aligned;" ::: "memory"); }
template <int N> __device__ __forceinline__ void wg_wait() { asm volatile("wgmma.wait_group.sync.aligned %0;" :: "n"(N) : "memory"); }
__device__ __forceinline__ void bar_sync(int id) { asm volatile("bar.sync %0, 128;" :: "r"(id) : "memory"); }
__device__ __forceinline__ void turn_wait(int wg) { bar_sync(1 + wg); }
__device__ __forceinline__ void turn_pass(int wg) {}
__device__ __forceinline__ void stsm4(uint32_t addr, uint32_t a, uint32_t b, uint32_t c, uint32_t d) {
  asm volatile("stmatrix.sync.aligned.m8n8.x4.shared.b16 [%0], {%1,%2,%3,%4};" :: "r"(addr), "r"(a), "r"(b), "r"(c), "r"(d) : "memory");
}
template <int N> __device__ __forceinline__ void keep(float (&d)[N]) {
#pragma unroll
  for (int i = 0; i < N; i++) asm volatile("" : "+f"(d[i]) :: "memory");
}
__host__ __device__ __forceinline__ uint64_t mkdesc(uint32_t addr, uint32_t lbo, uint32_t sbo) {
  return ((uint64_t)(sbo >> 4) << 32) | (uint64_t)(((lbo >> 4) << 16) | ((addr & 0x3FFFF) >> 4));
}

template <int SCALE_D>
__device__ __forceinline__ void wgmma_n144(float (&d)[72], uint32_t a0, uint32_t a1, uint32_t a2, uint32_t a3, uint64_t descB) {
  if (SCALE_D == 0)
  asm volatile("wgmma.mma_async.sync.aligned.m64n144k16.f32.bf16.bf16 "
    "{%0, %1, %2, %3, %4, %5, %6, %7, %8, %9, %10, %11, %12, %13, %14, %15, "
    "%16, %17, %18, %19, %20, %21, %22, %23, %24, %25, %26, %27, %28, %29, %30, %31, "
    "%32, %33, %34, %35, %36, %37, %38, %39, %40, %41, %42, %43, %44, %45, %46, %47, "
    "%48, %49, %50, %51, %52, %53, %54, %55, %56, %57, %58, %59, %60, %61, %62, %63, "
    "%64, %65, %66, %67, %68, %69, %70, %71}, "
    "{%72, %73, %74, %75}, %76, 0, 1, 1, 0;\n"
    : "=f"(d[0]), "=f"(d[1]), "=f"(d[2]), "=f"(d[3]), "=f"(d[4]), "=f"(d[5]), "=f"(d[6]), "=f"(d[7]),
      "=f"(d[8]), "=f"(d[9]), "=f"(d[10]), "=f"(d[11]), "=f"(d[12]), "=f"(d[13]), "=f"(d[14]), "=f"(d[15]),
      "=f"(d[16]), "=f"(d[17]), "=f"(d[18]), "=f"(d[19]), "=f"(d[20]), "=f"(d[21]), "=f"(d[22]), "=f"(d[23]),
      "=f"(d[24]), "=f"(d[25]), "=f"(d[26]), "=f"(d[27]), "=f"(d[28]), "=f"(d[29]), "=f"(d[30]), "=f"(d[31]),
      "=f"(d[32]), "=f"(d[33]), "=f"(d[34]), "=f"(d[35]), "=f"(d[36]), "=f"(d[37]), "=f"(d[38]), "=f"(d[39]),
      "=f"(d[40]), "=f"(d[41]), "=f"(d[42]), "=f"(d[43]), "=f"(d[44]), "=f"(d[45]), "=f"(d[46]), "=f"(d[47]),
      "=f"(d[48]), "=f"(d[49]), "=f"(d[50]), "=f"(d[51]), "=f"(d[52]), "=f"(d[53]), "=f"(d[54]), "=f"(d[55]),
      "=f"(d[56]), "=f"(d[57]), "=f"(d[58]), "=f"(d[59]), "=f"(d[60]), "=f"(d[61]), "=f"(d[62]), "=f"(d[63]),
      "=f"(d[64]), "=f"(d[65]), "=f"(d[66]), "=f"(d[67]), "=f"(d[68]), "=f"(d[69]), "=f"(d[70]), "=f"(d[71])
    : "r"(a0), "r"(a1), "r"(a2), "r"(a3), "l"(descB));
  else
  asm volatile("wgmma.mma_async.sync.aligned.m64n144k16.f32.bf16.bf16 "
    "{%0, %1, %2, %3, %4, %5, %6, %7, %8, %9, %10, %11, %12, %13, %14, %15, "
    "%16, %17, %18, %19, %20, %21, %22, %23, %24, %25, %26, %27, %28, %29, %30, %31, "
    "%32, %33, %34, %35, %36, %37, %38, %39, %40, %41, %42, %43, %44, %45, %46, %47, "
    "%48, %49, %50, %51, %52, %53, %54, %55, %56, %57, %58, %59, %60, %61, %62, %63, "
    "%64, %65, %66, %67, %68, %69, %70, %71}, "
    "{%72, %73, %74, %75}, %76, 1, 1, 1, 0;\n"
    : "+f"(d[0]), "+f"(d[1]), "+f"(d[2]), "+f"(d[3]), "+f"(d[4]), "+f"(d[5]), "+f"(d[6]), "+f"(d[7]),
      "+f"(d[8]), "+f"(d[9]), "+f"(d[10]), "+f"(d[11]), "+f"(d[12]), "+f"(d[13]), "+f"(d[14]), "+f"(d[15]),
      "+f"(d[16]), "+f"(d[17]), "+f"(d[18]), "+f"(d[19]), "+f"(d[20]), "+f"(d[21]), "+f"(d[22]), "+f"(d[23]),
      "+f"(d[24]), "+f"(d[25]), "+f"(d[26]), "+f"(d[27]), "+f"(d[28]), "+f"(d[29]), "+f"(d[30]), "+f"(d[31]),
      "+f"(d[32]), "+f"(d[33]), "+f"(d[34]), "+f"(d[35]), "+f"(d[36]), "+f"(d[37]), "+f"(d[38]), "+f"(d[39]),
      "+f"(d[40]), "+f"(d[41]), "+f"(d[42]), "+f"(d[43]), "+f"(d[44]), "+f"(d[45]), "+f"(d[46]), "+f"(d[47]),
      "+f"(d[48]), "+f"(d[49]), "+f"(d[50]), "+f"(d[51]), "+f"(d[52]), "+f"(d[53]), "+f"(d[54]), "+f"(d[55]),
      "+f"(d[56]), "+f"(d[57]), "+f"(d[58]), "+f"(d[59]), "+f"(d[60]), "+f"(d[61]), "+f"(d[62]), "+f"(d[63]),
      "+f"(d[64]), "+f"(d[65]), "+f"(d[66]), "+f"(d[67]), "+f"(d[68]), "+f"(d[69]), "+f"(d[70]), "+f"(d[71])
    : "r"(a0), "r"(a1), "r"(a2), "r"(a3), "l"(descB));
}

template <int SCALE_D>
__device__ __forceinline__ void wgmma_n96(float (&d)[48], uint32_t a0, uint32_t a1, uint32_t a2, uint32_t a3, uint64_t descB) {
  if (SCALE_D == 0)
  asm volatile("wgmma.mma_async.sync.aligned.m64n96k16.f32.bf16.bf16 "
    "{%0, %1, %2, %3, %4, %5, %6, %7, %8, %9, %10, %11, %12, %13, %14, %15, "
    "%16, %17, %18, %19, %20, %21, %22, %23, %24, %25, %26, %27, %28, %29, %30, %31, "
    "%32, %33, %34, %35, %36, %37, %38, %39, %40, %41, %42, %43, %44, %45, %46, %47}, "
    "{%48, %49, %50, %51}, %52, 0, 1, 1, 0;\n"
    : "=f"(d[0]), "=f"(d[1]), "=f"(d[2]), "=f"(d[3]), "=f"(d[4]), "=f"(d[5]), "=f"(d[6]), "=f"(d[7]),
      "=f"(d[8]), "=f"(d[9]), "=f"(d[10]), "=f"(d[11]), "=f"(d[12]), "=f"(d[13]), "=f"(d[14]), "=f"(d[15]),
      "=f"(d[16]), "=f"(d[17]), "=f"(d[18]), "=f"(d[19]), "=f"(d[20]), "=f"(d[21]), "=f"(d[22]), "=f"(d[23]),
      "=f"(d[24]), "=f"(d[25]), "=f"(d[26]), "=f"(d[27]), "=f"(d[28]), "=f"(d[29]), "=f"(d[30]), "=f"(d[31]),
      "=f"(d[32]), "=f"(d[33]), "=f"(d[34]), "=f"(d[35]), "=f"(d[36]), "=f"(d[37]), "=f"(d[38]), "=f"(d[39]),
      "=f"(d[40]), "=f"(d[41]), "=f"(d[42]), "=f"(d[43]), "=f"(d[44]), "=f"(d[45]), "=f"(d[46]), "=f"(d[47])
    : "r"(a0), "r"(a1), "r"(a2), "r"(a3), "l"(descB));
  else
  asm volatile("wgmma.mma_async.sync.aligned.m64n96k16.f32.bf16.bf16 "
    "{%0, %1, %2, %3, %4, %5, %6, %7, %8, %9, %10, %11, %12, %13, %14, %15, "
    "%16, %17, %18, %19, %20, %21, %22, %23, %24, %25, %26, %27, %28, %29, %30, %31, "
    "%32, %33, %34, %35, %36, %37, %38, %39, %40, %41, %42, %43, %44, %45, %46, %47}, "
    "{%48, %49, %50, %51}, %52, 1, 1, 1, 0;\n"
    : "+f"(d[0]), "+f"(d[1]), "+f"(d[2]), "+f"(d[3]), "+f"(d[4]), "+f"(d[5]), "+f"(d[6]), "+f"(d[7]),
      "+f"(d[8]), "+f"(d[9]), "+f"(d[10]), "+f"(d[11]), "+f"(d[12]), "+f"(d[13]), "+f"(d[14]), "+f"(d[15]),
      "+f"(d[16]), "+f"(d[17]), "+f"(d[18]), "+f"(d[19]), "+f"(d[20]), "+f"(d[21]), "+f"(d[22]), "+f"(d[23]),
      "+f"(d[24]), "+f"(d[25]), "+f"(d[26]), "+f"(d[27]), "+f"(d[28]), "+f"(d[29]), "+f"(d[30]), "+f"(d[31]),
      "+f"(d[32]), "+f"(d[33]), "+f"(d[34]), "+f"(d[35]), "+f"(d[36]), "+f"(d[37]), "+f"(d[38]), "+f"(d[39]),
      "+f"(d[40]), "+f"(d[41]), "+f"(d[42]), "+f"(d[43]), "+f"(d[44]), "+f"(d[45]), "+f"(d[46]), "+f"(d[47])
    : "r"(a0), "r"(a1), "r"(a2), "r"(a3), "l"(descB));
}

template <int SCALE_D>
__device__ __forceinline__ void wgmma_n48(float (&d)[24], uint32_t a0, uint32_t a1, uint32_t a2, uint32_t a3, uint64_t descB) {
  if (SCALE_D == 0)
  asm volatile("wgmma.mma_async.sync.aligned.m64n48k16.f32.bf16.bf16 "
    "{%0, %1, %2, %3, %4, %5, %6, %7, %8, %9, %10, %11, %12, %13, %14, %15, "
    "%16, %17, %18, %19, %20, %21, %22, %23}, "
    "{%24, %25, %26, %27}, %28, 0, 1, 1, 0;\n"
    : "=f"(d[0]), "=f"(d[1]), "=f"(d[2]), "=f"(d[3]), "=f"(d[4]), "=f"(d[5]), "=f"(d[6]), "=f"(d[7]),
      "=f"(d[8]), "=f"(d[9]), "=f"(d[10]), "=f"(d[11]), "=f"(d[12]), "=f"(d[13]), "=f"(d[14]), "=f"(d[15]),
      "=f"(d[16]), "=f"(d[17]), "=f"(d[18]), "=f"(d[19]), "=f"(d[20]), "=f"(d[21]), "=f"(d[22]), "=f"(d[23])
    : "r"(a0), "r"(a1), "r"(a2), "r"(a3), "l"(descB));
  else
  asm volatile("wgmma.mma_async.sync.aligned.m64n48k16.f32.bf16.bf16 "
    "{%0, %1, %2, %3, %4, %5, %6, %7, %8, %9, %10, %11, %12, %13, %14, %15, "
    "%16, %17, %18, %19, %20, %21, %22, %23}, "
    "{%24, %25, %26, %27}, %28, 1, 1, 1, 0;\n"
    : "+f"(d[0]), "+f"(d[1]), "+f"(d[2]), "+f"(d[3]), "+f"(d[4]), "+f"(d[5]), "+f"(d[6]), "+f"(d[7]),
      "+f"(d[8]), "+f"(d[9]), "+f"(d[10]), "+f"(d[11]), "+f"(d[12]), "+f"(d[13]), "+f"(d[14]), "+f"(d[15]),
      "+f"(d[16]), "+f"(d[17]), "+f"(d[18]), "+f"(d[19]), "+f"(d[20]), "+f"(d[21]), "+f"(d[22]), "+f"(d[23])
    : "r"(a0), "r"(a1), "r"(a2), "r"(a3), "l"(descB));
}

template <int SCALE_D>
__device__ __forceinline__ void wgmma_n64(float (&d)[32], uint32_t a0, uint32_t a1, uint32_t a2, uint32_t a3, uint64_t descB) {
  if (SCALE_D == 0)
  asm volatile("wgmma.mma_async.sync.aligned.m64n64k16.f32.bf16.bf16 "
    "{%0, %1, %2, %3, %4, %5, %6, %7, %8, %9, %10, %11, %12, %13, %14, %15, "
    "%16, %17, %18, %19, %20, %21, %22, %23, %24, %25, %26, %27, %28, %29, %30, %31}, "
    "{%32, %33, %34, %35}, %36, 0, 1, 1, 0;\n"
    : "=f"(d[0]), "=f"(d[1]), "=f"(d[2]), "=f"(d[3]), "=f"(d[4]), "=f"(d[5]), "=f"(d[6]), "=f"(d[7]),
      "=f"(d[8]), "=f"(d[9]), "=f"(d[10]), "=f"(d[11]), "=f"(d[12]), "=f"(d[13]), "=f"(d[14]), "=f"(d[15]),
      "=f"(d[16]), "=f"(d[17]), "=f"(d[18]), "=f"(d[19]), "=f"(d[20]), "=f"(d[21]), "=f"(d[22]), "=f"(d[23]),
      "=f"(d[24]), "=f"(d[25]), "=f"(d[26]), "=f"(d[27]), "=f"(d[28]), "=f"(d[29]), "=f"(d[30]), "=f"(d[31])
    : "r"(a0), "r"(a1), "r"(a2), "r"(a3), "l"(descB));
  else if (SCALE_D == 2)
  asm volatile("wgmma.mma_async.sync.aligned.m64n64k16.f32.bf16.bf16 "
    "{%0, %1, %2, %3, %4, %5, %6, %7, %8, %9, %10, %11, %12, %13, %14, %15, "
    "%16, %17, %18, %19, %20, %21, %22, %23, %24, %25, %26, %27, %28, %29, %30, %31}, "
    "{%32, %33, %34, %35}, %36, 0, 1, 1, 0;\n"
    : "+f"(d[0]), "+f"(d[1]), "+f"(d[2]), "+f"(d[3]), "+f"(d[4]), "+f"(d[5]), "+f"(d[6]), "+f"(d[7]),
      "+f"(d[8]), "+f"(d[9]), "+f"(d[10]), "+f"(d[11]), "+f"(d[12]), "+f"(d[13]), "+f"(d[14]), "+f"(d[15]),
      "+f"(d[16]), "+f"(d[17]), "+f"(d[18]), "+f"(d[19]), "+f"(d[20]), "+f"(d[21]), "+f"(d[22]), "+f"(d[23]),
      "+f"(d[24]), "+f"(d[25]), "+f"(d[26]), "+f"(d[27]), "+f"(d[28]), "+f"(d[29]), "+f"(d[30]), "+f"(d[31])
    : "r"(a0), "r"(a1), "r"(a2), "r"(a3), "l"(descB));
  else
  asm volatile("wgmma.mma_async.sync.aligned.m64n64k16.f32.bf16.bf16 "
    "{%0, %1, %2, %3, %4, %5, %6, %7, %8, %9, %10, %11, %12, %13, %14, %15, "
    "%16, %17, %18, %19, %20, %21, %22, %23, %24, %25, %26, %27, %28, %29, %30, %31}, "
    "{%32, %33, %34, %35}, %36, 1, 1, 1, 0;\n"
    : "+f"(d[0]), "+f"(d[1]), "+f"(d[2]), "+f"(d[3]), "+f"(d[4]), "+f"(d[5]), "+f"(d[6]), "+f"(d[7]),
      "+f"(d[8]), "+f"(d[9]), "+f"(d[10]), "+f"(d[11]), "+f"(d[12]), "+f"(d[13]), "+f"(d[14]), "+f"(d[15]),
      "+f"(d[16]), "+f"(d[17]), "+f"(d[18]), "+f"(d[19]), "+f"(d[20]), "+f"(d[21]), "+f"(d[22]), "+f"(d[23]),
      "+f"(d[24]), "+f"(d[25]), "+f"(d[26]), "+f"(d[27]), "+f"(d[28]), "+f"(d[29]), "+f"(d[30]), "+f"(d[31])
    : "r"(a0), "r"(a1), "r"(a2), "r"(a3), "l"(descB));
}

template <int SCALE_D>
__device__ __forceinline__ void wgmma_n56(float (&d)[28], uint32_t a0, uint32_t a1, uint32_t a2, uint32_t a3, uint64_t descB) {
  if (SCALE_D == 0)
  asm volatile("wgmma.mma_async.sync.aligned.m64n56k16.f32.bf16.bf16 "
    "{%0, %1, %2, %3, %4, %5, %6, %7, %8, %9, %10, %11, %12, %13, %14, %15, "
    "%16, %17, %18, %19, %20, %21, %22, %23, %24, %25, %26, %27}, "
    "{%28, %29, %30, %31}, %32, 0, 1, 1, 0;\n"
    : "=f"(d[0]), "=f"(d[1]), "=f"(d[2]), "=f"(d[3]), "=f"(d[4]), "=f"(d[5]), "=f"(d[6]), "=f"(d[7]),
      "=f"(d[8]), "=f"(d[9]), "=f"(d[10]), "=f"(d[11]), "=f"(d[12]), "=f"(d[13]), "=f"(d[14]), "=f"(d[15]),
      "=f"(d[16]), "=f"(d[17]), "=f"(d[18]), "=f"(d[19]), "=f"(d[20]), "=f"(d[21]), "=f"(d[22]), "=f"(d[23]),
      "=f"(d[24]), "=f"(d[25]), "=f"(d[26]), "=f"(d[27])
    : "r"(a0), "r"(a1), "r"(a2), "r"(a3), "l"(descB));
  else
  asm volatile("wgmma.mma_async.sync.aligned.m64n56k16.f32.bf16.bf16 "
    "{%0, %1, %2, %3, %4, %5, %6, %7, %8, %9, %10, %11, %12, %13, %14, %15, "
    "%16, %17, %18, %19, %20, %21, %22, %23, %24, %25, %26, %27}, "
    "{%28, %29, %30, %31}, %32, 1, 1, 1, 0;\n"
    : "+f"(d[0]), "+f"(d[1]), "+f"(d[2]), "+f"(d[3]), "+f"(d[4]), "+f"(d[5]), "+f"(d[6]), "+f"(d[7]),
      "+f"(d[8]), "+f"(d[9]), "+f"(d[10]), "+f"(d[11]), "+f"(d[12]), "+f"(d[13]), "+f"(d[14]), "+f"(d[15]),
      "+f"(d[16]), "+f"(d[17]), "+f"(d[18]), "+f"(d[19]), "+f"(d[20]), "+f"(d[21]), "+f"(d[22]), "+f"(d[23]),
      "+f"(d[24]), "+f"(d[25]), "+f"(d[26]), "+f"(d[27])
    : "r"(a0), "r"(a1), "r"(a2), "r"(a3), "l"(descB));
}

template <int SCALE_D>
__device__ __forceinline__ void wgmma_n56t(float (&d)[28], uint32_t a0, uint32_t a1, uint32_t a2, uint32_t a3, uint64_t descB) {
  if (SCALE_D == 0)
  asm volatile("wgmma.mma_async.sync.aligned.m64n56k16.f32.bf16.bf16 "
    "{%0, %1, %2, %3, %4, %5, %6, %7, %8, %9, %10, %11, %12, %13, %14, %15, "
    "%16, %17, %18, %19, %20, %21, %22, %23, %24, %25, %26, %27}, "
    "{%28, %29, %30, %31}, %32, 0, 1, 1, 1;\n"
    : "=f"(d[0]), "=f"(d[1]), "=f"(d[2]), "=f"(d[3]), "=f"(d[4]), "=f"(d[5]), "=f"(d[6]), "=f"(d[7]),
      "=f"(d[8]), "=f"(d[9]), "=f"(d[10]), "=f"(d[11]), "=f"(d[12]), "=f"(d[13]), "=f"(d[14]), "=f"(d[15]),
      "=f"(d[16]), "=f"(d[17]), "=f"(d[18]), "=f"(d[19]), "=f"(d[20]), "=f"(d[21]), "=f"(d[22]), "=f"(d[23]),
      "=f"(d[24]), "=f"(d[25]), "=f"(d[26]), "=f"(d[27])
    : "r"(a0), "r"(a1), "r"(a2), "r"(a3), "l"(descB));
  else
  asm volatile("wgmma.mma_async.sync.aligned.m64n56k16.f32.bf16.bf16 "
    "{%0, %1, %2, %3, %4, %5, %6, %7, %8, %9, %10, %11, %12, %13, %14, %15, "
    "%16, %17, %18, %19, %20, %21, %22, %23, %24, %25, %26, %27}, "
    "{%28, %29, %30, %31}, %32, 1, 1, 1, 1;\n"
    : "+f"(d[0]), "+f"(d[1]), "+f"(d[2]), "+f"(d[3]), "+f"(d[4]), "+f"(d[5]), "+f"(d[6]), "+f"(d[7]),
      "+f"(d[8]), "+f"(d[9]), "+f"(d[10]), "+f"(d[11]), "+f"(d[12]), "+f"(d[13]), "+f"(d[14]), "+f"(d[15]),
      "+f"(d[16]), "+f"(d[17]), "+f"(d[18]), "+f"(d[19]), "+f"(d[20]), "+f"(d[21]), "+f"(d[22]), "+f"(d[23]),
      "+f"(d[24]), "+f"(d[25]), "+f"(d[26]), "+f"(d[27])
    : "r"(a0), "r"(a1), "r"(a2), "r"(a3), "l"(descB));
}

__global__ void __launch_bounds__(192) prepack_kernel(const __nv_bfloat16* __restrict__ wqkv, const __nv_bfloat16* __restrict__ wo) {
  __nv_bfloat16* dst = reinterpret_cast<__nv_bfloat16*>(g_wpack);
  const int c = threadIdx.x, nb = blockIdx.x;
  if (nb < 72) {
    __shared__ float red[6][8];
    const int h = nb / 18, j = nb % 18, part = j / 6;
    const int col = (part == 0 ? 192 : part == 1 ? 384 : 0) + h * 48 + (j % 6) * 8;
    uint4 raw = *reinterpret_cast<const uint4*>(wqkv + c * 576 + col);
    uint32_t u[4] = {raw.x, raw.y, raw.z, raw.w};
    float v[8];
#pragma unroll
    for (int i = 0; i < 4; i++) { v[2 * i] = lo2f(u[i]); v[2 * i + 1] = hi2f(u[i]); }
#pragma unroll
    for (int i = 0; i < 8; i++) {
      float s = v[i];
#pragma unroll
      for (int o = 16; o; o >>= 1) s += __shfl_xor_sync(~0u, s, o);
      if ((c & 31) == 0) red[c >> 5][i] = s;
    }
    __syncthreads();
    const int cc = c >> 5, q = (c >> 3) & 3, s1 = (c >> 2) & 1, hh = (c >> 1) & 1, e = c & 1;
    const int base = h * 27648 + (2 * cc + s1) * 2304 + j * 128 + hh * 64 + 2 * q + e;
#pragma unroll
    for (int n = 0; n < 8; n++) {
      float m = (red[0][n] + red[1][n] + red[2][n] + red[3][n] + red[4][n] + red[5][n]) * (1.0f / 192.0f);
      dst[base + n * 8] = __float2bfloat16((v[n] - m) * (part == 2 ? 0.14433756729740643f * 1.4426950408889634f : 1.0f));
    }
  } else {
    const int jb = nb - 72, chunk = jb / 8, j = jb % 8;
    const int s = c >> 4, hh = (c >> 3) & 1, kk = c & 7;
    const int base = 110592 + (chunk * 12 + s) * 1024 + j * 128 + hh * 64 + kk;
#pragma unroll
    for (int n = 0; n < 8; n++) {
      const int ch = 32 * (jb >> 2) + 8 * (n >> 1) + 2 * (jb & 3) + (n & 1);
      dst[base + n * 8] = wo[c * 192 + ch];
    }
  }
}

__device__ __forceinline__ int window_of(int round, int nfull, int cta, int ncta, int wg) {
  if (round < nfull) return round * 2 * ncta + 2 * cta + wg;
  const int rem = NWIN - nfull * 2 * ncta;
  const int i = cta + wg * ncta;
  return i < rem ? nfull * 2 * ncta + i : -1;
}

__device__ __forceinline__ constexpr int qkv_off(int h, int s) { return ((3 * h + s / 4) % 8) * SLICE + (s % 4) * 4608; }
__device__ __forceinline__ constexpr int wo_off(int chunk, int s) { return 4 * SLICE + (chunk * 12 + s) * 2048; }

template <int H, int S0, int S1>
__device__ __forceinline__ void issue_qkv(float (&acc)[72], const uint32_t (&X)[48], uint64_t dW) {
#pragma unroll
  for (int s = S0; s < S1; s++) {
    if (s == 0) wgmma_n144<0>(acc, X[4 * s], X[4 * s + 1], X[4 * s + 2], X[4 * s + 3], dW + (qkv_off(H, s) >> 4));
    else        wgmma_n144<1>(acc, X[4 * s], X[4 * s + 1], X[4 * s + 2], X[4 * s + 3], dW + (qkv_off(H, s) >> 4));
  }
}
template <int H, int S0, int S1>
__device__ __forceinline__ void issue_kv(float (&acc)[48], const uint32_t (&X)[48], uint64_t dW) {
#pragma unroll
  for (int s = S0; s < S1; s++) {
    if (s == 0) wgmma_n96<0>(acc, X[4 * s], X[4 * s + 1], X[4 * s + 2], X[4 * s + 3], dW + (qkv_off(H, s) >> 4));
    else        wgmma_n96<1>(acc, X[4 * s], X[4 * s + 1], X[4 * s + 2], X[4 * s + 3], dW + (qkv_off(H, s) >> 4));
  }
}
template <int H>
__device__ __forceinline__ void issue_q(float (&acc)[24], const uint32_t (&X)[48], uint64_t dW) {
#pragma unroll
  for (int s = 0; s < 12; s++) {
    if (s == 0) wgmma_n48<0>(acc, X[4 * s], X[4 * s + 1], X[4 * s + 2], X[4 * s + 3], dW + ((qkv_off(H, s) + 3072) >> 4));
    else        wgmma_n48<1>(acc, X[4 * s], X[4 * s + 1], X[4 * s + 2], X[4 * s + 3], dW + ((qkv_off(H, s) + 3072) >> 4));
  }
}
template <int CHUNK, int S0, int S1>
__device__ __forceinline__ void issue_proj(float (&acc)[32], const uint32_t (&Of)[48], uint64_t dW) {
#pragma unroll
  for (int s = S0; s < S1; s++) {
    if (s == 0) wgmma_n64<(CHUNK == 2 ? 2 : 0)>(acc, Of[4 * s], Of[4 * s + 1], Of[4 * s + 2], Of[4 * s + 3], dW + (wo_off(CHUNK, s) >> 4));
    else        wgmma_n64<1>(acc, Of[4 * s], Of[4 * s + 1], Of[4 * s + 2], Of[4 * s + 3], dW + (wo_off(CHUNK, s) >> 4));
  }
}
__device__ __forceinline__ void store_kv(const float* a, uint32_t r, uint32_t addr) {
#pragma unroll
  for (int j = 0; j < 6; j += 2)
    stsm4(addr + j * KV_PITCH, hmul_b<0>(pack2(a[4 * j], a[4 * j + 1]), r), hmul_b<1>(pack2(a[4 * j + 2], a[4 * j + 3]), r),
          hmul_b<0>(pack2(a[4 * j + 4], a[4 * j + 5]), r), hmul_b<1>(pack2(a[4 * j + 6], a[4 * j + 7]), r));
}
__device__ __forceinline__ void pack_q(const float* a, uint32_t r, uint32_t (&Q)[12]) {
#pragma unroll
  for (int j = 0; j < 6; j++) {
    Q[2 * j] = hmul_b<0>(pack2(a[4 * j], a[4 * j + 1]), r);
    Q[2 * j + 1] = hmul_b<1>(pack2(a[4 * j + 2], a[4 * j + 3]), r);
  }
}
__device__ __forceinline__ void issue_s(float (&S)[28], const uint32_t (&Q)[12], uint64_t dK) {
  wgmma_n56<0>(S, Q[0], Q[1], Q[2], Q[3], dK);
  wgmma_n56<1>(S, Q[4], Q[5], Q[6], Q[7], dK + (2 * KV_PITCH >> 4));
  wgmma_n56<1>(S, Q[8], Q[9], Q[10], Q[11], dK + (4 * KV_PITCH >> 4));
}
#define PIN() asm volatile("pmevent 0;" ::: "memory")
template <int NK, class G>
__device__ __forceinline__ void attention(float (&S)[28], const uint32_t (&Q)[12], uint64_t dK, uint64_t dV, G g) {
#define GK(k) if ((k) < NK) { if ((k) >= 2) wg_fence(); g(IC<((k) < NK ? (k) : 0)>{}, IC<((k) < NK ? (k) + 1 : 0)>{}); if ((k) >= 2) wg_commit(); }
  wg_fence();
  issue_s(S, Q, dK); wg_commit();
  GK(0) GK(1) wg_commit(); wg_wait<1>();
  keep(S);
  uint32_t P[16];
  GK(2)
#pragma unroll
  for (int j = 0; j < 4; j++) P[j] = pack2(S[2 * j], S[2 * j + 1]);
  asm volatile("" : "+r"(P[0]), "+r"(P[1]), "+r"(P[2]), "+r"(P[3])); PIN();
  GK(3)
#pragma unroll
  for (int j = 4; j < 9; j++) P[j] = pack2(S[2 * j], S[2 * j + 1]);
  asm volatile("" : "+r"(P[4]), "+r"(P[5]), "+r"(P[6]), "+r"(P[7]), "+r"(P[8])); PIN();
  GK(4)
#pragma unroll
  for (int j = 9; j < 14; j++) P[j] = pack2(S[2 * j], S[2 * j + 1]);
  asm volatile("" : "+r"(P[9]), "+r"(P[10]), "+r"(P[11]), "+r"(P[12]), "+r"(P[13])); PIN();
  GK(5)
  uint32_t m0 = hmax(hmax(hmax(hmax(P[0], P[2]), P[4]), hmax(hmax(P[6], P[8]), P[10])), P[12]);
  uint32_t m1 = hmax(hmax(hmax(hmax(P[1], P[3]), P[5]), hmax(hmax(P[7], P[9]), P[11])), P[13]);
  asm volatile("" : "+r"(m0), "+r"(m1)); PIN();
  GK(6)
  uint32_t mx = hmax(__byte_perm(m0, m1, 0x5410), __byte_perm(m0, m1, 0x7632));
  uint32_t sh = __shfl_xor_sync(~0u, mx, 1);
  PIN();
  GK(7)
  mx = hmax(mx, sh);
  sh = __shfl_xor_sync(~0u, mx, 2);
  PIN();
  GK(8)
  mx = hmax(mx, sh);
#pragma unroll
  for (int j = 0; j < 14; j++) P[j] = (j & 1) ? hsub_b<1>(P[j], mx) : hsub_b<0>(P[j], mx);
  P[12] = hex1(P[12]); P[13] = hex1(P[13]); P[14] = 0; P[15] = 0;
  P[0] = hex2(P[0]); P[1] = hex2(P[1]);
  asm volatile("" : "+r"(P[0]), "+r"(P[1]), "+r"(P[12]), "+r"(P[13])); PIN();
  GK(9)
  P[2] = hex2(P[2]); P[3] = hex2(P[3]);
  asm volatile("" : "+r"(P[2]), "+r"(P[3])); PIN();
  GK(10)
  P[4] = hex2(P[4]); P[5] = hex2(P[5]);
  asm volatile("" : "+r"(P[4]), "+r"(P[5])); PIN();
  GK(11)
#pragma unroll
  for (int j = 6; j < 12; j++) P[j] = hex2(P[j]);
  wg_fence();
  wgmma_n56t<0>(S, P[0], P[1], P[2], P[3], dV);
  wgmma_n56t<1>(S, P[4], P[5], P[6], P[7], dV + (256 >> 4));
  wgmma_n56t<1>(S, P[8], P[9], P[10], P[11], dV + (512 >> 4));
  wgmma_n56t<1>(S, P[12], P[13], P[14], P[15], dV + (768 >> 4));
  wg_commit();
#undef GK
}
template <int S0, int S1>
__device__ __forceinline__ void load_x(uint32_t (&X)[48], uint32_t t0) {
#pragma unroll
  for (int s = S0; s < S1; s++)
    asm volatile("ld.shared.v4.u32 {%0,%1,%2,%3}, [%4];" : "=r"(X[4 * s]), "=r"(X[4 * s + 1]), "=r"(X[4 * s + 2]), "=r"(X[4 * s + 3])
                 : "r"(((s & 1) ? (t0 ^ 16) : t0) + (s >> 1) * 128) : "memory");
}
__device__ __forceinline__ void proxy_fence() { asm volatile("fence.proxy.async.shared::cta;" ::: "memory"); }

template <int CHUNK>
__device__ __forceinline__ void store_out(const float (&p)[32], const uint32_t (&X)[48], uint8_t* o0, uint8_t* o1) {
#pragma unroll
  for (int c = 0; c < 2; c++) {
    const int cc = CHUNK * 2 + c;
    uint4 a, b;
    a.x = hadd(X[8 * cc],     pack2(p[16 * c],      p[16 * c + 1]));
    b.x = hadd(X[8 * cc + 1], pack2(p[16 * c + 2],  p[16 * c + 3]));
    a.y = hadd(X[8 * cc + 2], pack2(p[16 * c + 4],  p[16 * c + 5]));
    b.y = hadd(X[8 * cc + 3], pack2(p[16 * c + 6],  p[16 * c + 7]));
    a.z = hadd(X[8 * cc + 4], pack2(p[16 * c + 8],  p[16 * c + 9]));
    b.z = hadd(X[8 * cc + 5], pack2(p[16 * c + 10], p[16 * c + 11]));
    a.w = hadd(X[8 * cc + 6], pack2(p[16 * c + 12], p[16 * c + 13]));
    b.w = hadd(X[8 * cc + 7], pack2(p[16 * c + 14], p[16 * c + 15]));
    asm volatile("st.global.v4.u32 [%0], {%1,%2,%3,%4};" :: "l"(o0 + cc * 64), "r"(a.x), "r"(a.y), "r"(a.z), "r"(a.w) : "memory");
    asm volatile("st.global.v4.u32 [%0], {%1,%2,%3,%4};" :: "l"(o1 + cc * 64), "r"(b.x), "r"(b.y), "r"(b.z), "r"(b.w) : "memory");
  }
}

__device__ __forceinline__ void finish_o(const float (&o)[28], uint32_t* Of) {
  float i0, i1;
  asm("rcp.approx.ftz.f32 %0, %1;" : "=f"(i0) : "f"(o[24]));
  asm("rcp.approx.ftz.f32 %0, %1;" : "=f"(i1) : "f"(o[26]));
  const uint32_t inv = pack2(i0, i1);
#pragma unroll
  for (int j = 0; j < 6; j++) {
    Of[2 * j]     = hmul_b<0>(pack2(o[4 * j], o[4 * j + 1]), inv);
    Of[2 * j + 1] = hmul_b<1>(pack2(o[4 * j + 2], o[4 * j + 3]), inv);
  }
}

template <int K> __device__ __forceinline__ void load_slice(uint32_t sb, const Descs& ds) {
  constexpr int st = K < 12 ? K / 3 : 4 + (K - 12) / 2;
  constexpr bool first = K < 12 ? (K % 3 == 0) : (K % 2 == 0);
  if (first) mbar_expect(sb + BAR_WFULL + 8 * st, (K < 12 ? 3 : 2) * SLICE);
  asm volatile("cp.async.bulk.shared::cluster.global.mbarrier::complete_tx::bytes [%0], [%1], %2, [%3];"
               :: "r"(sb + OFF_W + (K & 7) * SLICE), "l"(ds.src[K]), "n"(SLICE),
                  "r"(sb + BAR_WFULL + 8 * st) : "memory");
}
template <int STAGE> __device__ __forceinline__ uint32_t release_begin(uint32_t cnt) {
  uint32_t old;
  asm volatile("atom.shared.inc.u32 %0, [%1 + %2], 7;" : "=r"(old) : "r"(cnt), "n"(4 * STAGE) : "memory");
  return old;
}
template <int STAGE> __device__ __forceinline__ void release_end(uint32_t sb, const Descs& ds, uint32_t old, int lane, bool next_round) {
  if (old == 7 && lane == 0) {
    if (STAGE == 0) { load_slice<8>(sb, ds); load_slice<9>(sb, ds); load_slice<10>(sb, ds); }
    if (STAGE == 1) { load_slice<11>(sb, ds); load_slice<12>(sb, ds); load_slice<13>(sb, ds); }
    if (STAGE == 2) { load_slice<14>(sb, ds); load_slice<15>(sb, ds); if (next_round) load_slice<0>(sb, ds); }
    if (STAGE == 3 && next_round) { load_slice<1>(sb, ds); load_slice<2>(sb, ds); load_slice<3>(sb, ds); }
    if (STAGE == 4 && next_round) { load_slice<4>(sb, ds); load_slice<5>(sb, ds); }
    if (STAGE == 5 && next_round) { load_slice<6>(sb, ds); load_slice<7>(sb, ds); }
  }
}

__device__ __forceinline__ uint32_t ln_rstd(const uint32_t (&X)[48]) {
  uint32_t sm[2];
#pragma unroll
  for (int a = 0; a < 2; a++) {
    uint32_t t[12];
#pragma unroll
    for (int i = 0; i < 12; i++) t[i] = hadd(X[4 * i + a], X[4 * i + 2 + a]);
#pragma unroll
    for (int i = 0; i < 6; i++) t[i] = hadd(t[i], t[i + 6]);
#pragma unroll
    for (int i = 0; i < 3; i++) t[i] = hadd(t[i], t[i + 3]);
    sm[a] = hadd(hadd(t[0], t[1]), t[2]);
  }
  uint32_t m = hadd(__byte_perm(sm[0], sm[1], 0x5410), __byte_perm(sm[0], sm[1], 0x7632));
  m = hadd(m, __shfl_xor_sync(~0u, m, 1));
  m = hadd(m, __shfl_xor_sync(~0u, m, 2));
  m = hmul(m, 0x3bab3babu);
  float var[2];
#pragma unroll
  for (int a = 0; a < 2; a++) {
    uint32_t t[4];
#pragma unroll
    for (int i = 0; i < 24; i++) {
      const uint32_t d = a ? hsub_b<1>(X[2 * i + 1], m) : hsub_b<0>(X[2 * i], m);
      t[i & 3] = i < 4 ? hmul(d, d) : hfma(d, d, t[i & 3]);
    }
    const uint32_t s = hadd(hadd(t[0], t[1]), hadd(t[2], t[3]));
    float v = lo2f(s) + hi2f(s);
    v += __shfl_xor_sync(~0u, v, 1);
    v += __shfl_xor_sync(~0u, v, 2);
    asm("rsqrt.approx.ftz.f32 %0, %1;" : "=f"(var[a]) : "f"(fmaf(v, 1.0f / 192.0f, 1e-5f)));
  }
  return pack2(var[0], var[1]);
}

__device__ __forceinline__ void stats_pass(uint32_t sb, int pass, int lane) {
  const int g = lane >> 2, q = lane & 3;
  const int tile = pass < 6 ? (pass & 1) : (g & 1);
  const int ps = pass < 6 ? (pass >> 1) * 8 + g : 24;
  uint32_t X[48];
  load_x<0, 12>(X, sb + OFF_TILE + tile * TILE_BYTES + ps * 768 + q * 32 + (ps & 1) * 16);
  const uint32_t rs = ln_rstd(X);
  asm volatile("st.shared.u32 [%0], %1;" :: "r"(sb + OFF_RSTD + tile * 100 + ps * 4), "r"(rs) : "memory");
}

__global__ void __launch_bounds__(384, 1)
fused_kernel(const __grid_constant__ CUtensorMap tmx, const __grid_constant__ Descs ds, const __nv_bfloat16* __restrict__ dw, __nv_bfloat16* __restrict__ out, const int never) {
  extern __shared__ __align__(1024) uint8_t smem[];
  const uint32_t sb = (uint32_t)__cvta_generic_to_shared(smem);
  const int tid = threadIdx.x, lane = tid & 31;
  const int warp = __shfl_sync(0xffffffffu, tid >> 5, 0);
  const int cta = blockIdx.x, ncta = gridDim.x;
  const int nfull = NWIN / (2 * ncta);
  const int nrounds = nfull + ((NWIN - nfull * 2 * ncta) > cta ? 1 : 0);

  if (tid == 0) {
    if ((sb & 0x3FFFF) != SMEM_BASE) __trap();
    for (int i = 0; i < 6; i++) { mbar_init(sb + BAR_WFULL + 8 * i, 1); *reinterpret_cast<uint32_t*>(smem + CNT_WREL + 4 * i) = 0; }
    for (int i = 0; i < 9; i++) mbar_init(sb + BAR_XFULL + 8 * i, 1);
    mbar_init(sb + BAR_TFULL, 3);
    mbar_init(sb + BAR_TEMPTY, 8);
    mbar_init(sb + BAR_TPART, 3);
    mbar_init(sb + BAR_TPART + 8, 3);
    mbar_init(sb + BAR_SFULL, 4);
    asm volatile("fence.mbarrier_init.release.cluster;" ::: "memory");
  }
  if (tid < 128) {
    const uint32_t v = (tid & 63) < 49 ? 0x3f803f80u : 0u;
    *reinterpret_cast<uint4*>(smem + OFF_KV + (tid >> 6) * KV_BYTES + 6 * KV_PITCH + (tid & 63) * 16) = make_uint4(v, v, v, v);
    asm volatile("fence.proxy.async.shared::cta;" ::: "memory");
  }
  __syncthreads();

  if (warp >= 8) {
    asm volatile("setmaxnreg.dec.sync.aligned.u32 " PREGS ";");
    if (warp == 11) {
      if (lane == 0) {
        load_slice<0>(sb, ds); load_slice<1>(sb, ds); load_slice<2>(sb, ds); load_slice<3>(sb, ds);
        load_slice<4>(sb, ds); load_slice<5>(sb, ds); load_slice<6>(sb, ds); load_slice<7>(sb, ds);
      }
      __syncwarp();
      for (int r = 0; r < nrounds; r++) {
#pragma unroll 1
        for (int pass = 0; pass < 4; pass++) {
          if (!(pass & 1)) mbar_wait(sb + BAR_TPART + 4 * pass, r & 1);
          stats_pass(sb, pass, lane);
        }
        __syncwarp();
        if (lane == 0) mbar_arrive(sb + BAR_SFULL);
        TR(2);
      }
    } else {
      const int cw = warp - 8;
      const int win = lane >> 4;
      const int ch0 = cw * 64 + (lane & 15) * 4;
      uint32_t wt[9][2];
#pragma unroll
      for (int t = 0; t < 9; t++) {
        uint2 v = *reinterpret_cast<const uint2*>(dw + t * CH + ch0);
        wt[t][0] = v.x; wt[t][1] = v.y;
      }
      const uint32_t xs = sb + OFF_X + cw * 3 * XSLOT;
      const uint32_t xld = xs + (lane >> 4) * 1152 + (lane & 15) * 8;
      const uint32_t xbar = sb + BAR_XFULL + cw * 24;
      const uint32_t st0 = sb + OFF_TILE + win * TILE_BYTES + ch0 * 4;
      const uint32_t st1 = sb + OFF_TILE + win * TILE_BYTES + ((ch0 * 4) ^ 16);
      const uint64_t tm = reinterpret_cast<uint64_t>(&tmx);
      int cx0, cy0, cx1, cy1;
      auto coords = [&](int r) {
        const int w0 = window_of(r, nfull, cta, ncta, 0);
        int w1 = window_of(r, nfull, cta, ncta, 1);
        if (w1 < 0) w1 = w0;
        const int a = w0 / NWX, b = w1 / NWX;
        cx0 = (w0 - a * NWX) * 7 - 1; cy0 = a * 7 - 1;
        cx1 = (w1 - b * NWX) * 7 - 1; cy1 = b * 7 - 1;
      };
      auto issue = [&](int slot, int dy) {
        asm volatile("{\n.reg .pred p;\nelect.sync _|p, 0xffffffff;\n"
                     "@p mbarrier.arrive.expect_tx.shared::cta.b64 _, [%2], %8;\n"
                     "@p cp.async.bulk.tensor.3d.shared::cluster.global.mbarrier::complete_tx::bytes [%0], [%1, {%3, %4, %5}], [%2];\n"
                     "@p cp.async.bulk.tensor.3d.shared::cluster.global.mbarrier::complete_tx::bytes [%0 + 1152], [%1, {%3, %6, %7}], [%2];\n}\n"
                     :: "r"(xs + slot * XSLOT), "l"(tm), "r"(xbar + slot * 8), "r"(cw * 64), "r"(cx0), "r"(cy0 + dy), "r"(cx1), "r"(cy1 + dy), "n"(XSLOT) : "memory");
      };
      coords(0);
      issue(0, 0); issue(1, 1); issue(2, 2);
      for (int r = 0; r < nrounds; r++) {
        const bool more = r + 1 < nrounds;
        uint32_t accA[7][2], accB[7][2], ctr[7][2], held[2];
#pragma unroll
        for (int i = 0; i < 9; i++) {
          mbar_wait(xbar + (i % 3) * 8, (r + i / 3) & 1);
          if (i == 5 || i == 7) { __syncwarp(); if (lane == 0) mbar_arrive(sb + BAR_TPART + (i == 5 ? 0 : 8)); }
          if (i == 7 && more) coords(r + 1);
          if (i == 0) { if (r > 0) issue(2, 2); }
          else if (i < 7) issue((i + 2) % 3, i + 2);
          else if (more) issue((i + 2) % 3, i - 7);
          if (i == 2 && r > 0) mbar_wait(sb + BAR_TEMPTY, (r - 1) & 1);
          if (i == 2) { TR(0); }
          uint32_t cur[9][2];
#pragma unroll
          for (int p = 0; p < 5; p++)
            asm volatile("ld.shared.v2.u32 {%0,%1}, [%2];" : "=r"(cur[p][0]), "=r"(cur[p][1]) : "r"(xld + (i % 3) * XSLOT + p * 128));
#pragma unroll
          for (int j = 0; j < 7; j++) {
            if (j >= 1 && j + 4 < 9)
              asm volatile("ld.shared.v2.u32 {%0,%1}, [%2];" : "=r"(cur[j + 4][0]), "=r"(cur[j + 4][1]) : "r"(xld + (i % 3) * XSLOT + (j + 4) * 128));
            if (i >= 2) {
              uint32_t o[2];
#pragma unroll
              for (int e = 0; e < 2; e++) {
                uint32_t a = hfma(cur[j][e], wt[6][e], accA[j][e]);
                a = hfma(cur[j + 1][e], wt[7][e], a);
                a = hfma(cur[j + 2][e], wt[8][e], a);
                o[e] = hadd(ctr[j][e], a);
              }
              const int tok = (i - 2) * 7 + j, ps = tok >> 1;
              if (!(tok & 1)) { held[0] = o[0]; held[1] = o[1]; }
              if ((tok & 1) || tok == 48)
                asm volatile("st.shared.v4.u32 [%0], {%1,%2,%3,%4};" :: "r"(((ps & 1) ? st1 : st0) + ps * 768), "r"(held[0]), "r"(o[0]), "r"(held[1]), "r"(o[1]) : "memory");
            }
#pragma unroll
            for (int e = 0; e < 2; e++) {
              if (i >= 1 && i <= 7) {
                uint32_t a = hfma(cur[j][e], wt[3][e], accB[j][e]);
                a = hfma(cur[j + 1][e], wt[4][e], a);
                accA[j][e] = hfma(cur[j + 2][e], wt[5][e], a);
                ctr[j][e] = cur[j + 1][e];
              }
              if (i <= 6) {
                uint32_t a = hmul(cur[j][e], wt[0][e]);
                a = hfma(cur[j + 1][e], wt[1][e], a);
                accB[j][e] = hfma(cur[j + 2][e], wt[2][e], a);
              }
            }
          }
        }
        __syncwarp();
        if (lane == 0) mbar_arrive(sb + BAR_TFULL);
        TR(1);
        mbar_wait(sb + BAR_TFULL, r & 1);
        stats_pass(sb, 4 + cw, lane);
        __syncwarp();
        if (lane == 0) mbar_arrive(sb + BAR_SFULL);
      }
    }
  } else {
    asm volatile("setmaxnreg.inc.sync.aligned.u32 " CREGS ";");
    const int wg = warp >> 2, w4 = warp & 3, g = lane >> 2, q = lane & 3;
    const int row0 = w4 * 16 + g, row1 = row0 + 8;
    const int ps = min(w4 * 8 + g, 24);
    const int tok0 = 2 * ps, tok1 = min(2 * ps + 1, 48);
    const uint32_t kv = sb + OFF_KV + wg * KV_BYTES;
    const int srow = w4 * 16 + (lane & 15);
    const uint32_t vst = kv + (lane >> 4) * KV_PITCH + srow * 16;
    const uint32_t kst = vst + (srow < 56 ? 1024 : 0);
    const uint32_t off0 = ((tok0 / 7) * IMG + tok0 % 7) * 384 + q * 16, off1 = ((tok1 / 7) * IMG + tok1 % 7) * 384 + q * 16;
    const uint32_t cnt = lane == 0 ? sb + CNT_WREL : sb + OFF_DUMMY + lane * 4;
    const uint32_t vmask = (row0 < 49 ? 0xffffu : 0u) | (row1 < 49 ? 0xffff0000u : 0u);

    const uint32_t tx = sb + OFF_TILE + wg * TILE_BYTES + ps * 768 + q * 32 + (ps & 1) * 16;
    const int myrounds = window_of(nrounds - 1, nfull, cta, ncta, wg) < 0 ? nrounds - 1 : nrounds;

    if (never == 2) return;
    uint32_t X[48];
    float acc[72];
    mbar_wait(sb + BAR_TFULL, 0);
    load_x<0, 12>(X, tx);
    mbar_wait(sb + BAR_WFULL, 0);
    wg_fence();
    issue_qkv<0, 0, 12>(acc, X, ds.w[0]);
    wg_commit();
    uint32_t rK;
    mbar_wait(sb + BAR_SFULL, 0);
    asm volatile("ld.shared.u32 %0, [%1];" : "=r"(rK) : "r"(sb + OFF_RSTD + wg * 100 + ps * 4) : "memory");
    __syncwarp();
    if (lane == 0) mbar_arrive(sb + BAR_TEMPTY);

    if (wg == 1) turn_pass(1);
    for (int r = 0;; r++) {
      const uint32_t par = r & 1;
      if (r == myrounds) {
        wg_wait<0>(); keep(acc);
        if (r < nrounds)
        {
          mbar_wait(sb + BAR_WFULL, par);      release_end<0>(sb, ds, release_begin<0>(cnt), lane, false);
          mbar_wait(sb + BAR_WFULL + 8, par);  release_end<1>(sb, ds, release_begin<1>(cnt), lane, false);
          turn_wait(wg); turn_pass(wg);
          mbar_wait(sb + BAR_WFULL + 16, par); release_end<2>(sb, ds, release_begin<2>(cnt), lane, false);
          for (int i = 0; i < 5; i++) { turn_wait(wg); if (i < 4) turn_pass(wg); }
        }
        break;
      }
      TR(0);
      const bool next_round = r + 1 < nrounds;
      const uint32_t rV = rK & vmask;
      uint32_t rel;
      uint32_t Of[48], Q[12];
      float S[28];
      wg_wait<0>(); keep(acc);
      TR(2);
      rel = release_begin<0>(cnt);
      store_kv(acc, rK, kst);
      release_end<0>(sb, ds, rel, lane, next_round);
      store_kv(acc + 24, rV, vst);
      proxy_fence();
      pack_q(acc + 48, rK, Q);
      mbar_wait(sb + BAR_WFULL + 8, par);
      turn_wait(wg);
      TR(3);
      attention<12>(S, Q, ds.k[wg][0], ds.v[wg][0], [&](auto a, auto b) { issue_qkv<1, a.v, b.v>(acc, X, ds.w[2]); });
      TR(5);
      wg_wait<1>(); keep(acc);
      TR(6);
      rel = release_begin<1>(cnt);
      store_kv(acc, rK, kst);
      release_end<1>(sb, ds, rel, lane, next_round);
      wg_wait<0>(); keep(S);
      bar_sync(1 + wg);
      store_kv(acc + 24, rV, vst);
      proxy_fence();
      pack_q(acc + 48, rK, Q);
      finish_o(S, Of);
      mbar_wait(sb + BAR_WFULL + 16, par);
      turn_wait(wg);
      TR(7);
      attention<12>(S, Q, ds.k[wg][1], ds.v[wg][1], [&](auto a, auto b) { issue_qkv<2, a.v, b.v>(acc, X, ds.w[3]); });
      TR(9);
      wg_wait<1>(); keep(acc);
      TR(10);
      rel = release_begin<2>(cnt);
      store_kv(acc, rK, kst);
      release_end<2>(sb, ds, rel, lane, next_round);
      wg_wait<0>(); keep(S);
      bar_sync(1 + wg);
      store_kv(acc + 24, rV, vst);
      proxy_fence();
      pack_q(acc + 48, rK, Q);
      finish_o(S, Of + 12);
      mbar_wait(sb + BAR_WFULL + 24, par);
      turn_wait(wg);
      TR(11);
      {
        float kva[48], qa[24];
        attention<12>(S, Q, ds.k[wg][2], ds.v[wg][2], [&](auto a, auto b) { issue_kv<3, a.v, b.v>(kva, X, ds.w[4]); });
        TR(13);
        wg_wait<0>(); keep(S); keep(kva);
        TR(14);
        wg_fence();
        issue_q<3>(qa, X, ds.w[5]); wg_commit();
        bar_sync(1 + wg);
        store_kv(kva, rK, kst);
        store_kv(kva + 24, rV, vst);
        proxy_fence();
        finish_o(S, Of + 24);
        anchor(Of[35]);
        wg_wait<0>(); keep(qa);
        TR(15);
        rel = release_begin<3>(cnt);
        pack_q(qa, rK, Q);
        release_end<3>(sb, ds, rel, lane, next_round);
      }
      mbar_wait(sb + BAR_WFULL + 32, par);
      turn_wait(wg);
      TR(16);
      float pa[32], pb[32];
      attention<9>(S, Q, ds.k[wg][3], ds.v[wg][3], [&](auto a, auto b) { issue_proj<0, a.v, b.v>(pa, Of, ds.w[6]); });
      TR(18);
      mbar_wait(sb + BAR_WFULL + 40, par);
      wg_wait<0>(); keep(S); keep(pa);
      TR(19);
      finish_o(S, Of + 36);
      turn_wait(wg);
      wg_fence();
      issue_proj<0, 9, 12>(pa, Of, ds.w[7]); wg_commit();
      issue_proj<1, 0, 12>(pb, Of, ds.w[8]); wg_commit();
      TR(20);
      const bool more = r + 1 < myrounds;
      const int w = window_of(r, nfull, cta, ncta, wg);
      const int wy = w / NWX, wx = w - wy * NWX;
      const uint32_t wb = (uint32_t)(wy * 7 * IMG + wx * 7) * 384u;
      uint8_t* o0 = reinterpret_cast<uint8_t*>(out) + (wb + off0);
      uint8_t* o1 = reinterpret_cast<uint8_t*>(out) + (wb + off1);
      if (more) mbar_wait(sb + BAR_TFULL, par ^ 1);
      wg_wait<1>(); keep(pa);
      TR(21);
      store_out<0>(pa, X, o0, o1);
      wg_fence();
      issue_proj<2, 0, 12>(pa, Of, ds.w[9]); wg_commit();
      load_x<0, 4>(X, tx);
      TR(22);
      wg_wait<1>(); keep(pb);
      turn_pass(wg);
      TR(23);
      rel = release_begin<4>(cnt);
      store_out<1>(pb, X, o0, o1);
      load_x<4, 8>(X, tx);
      release_end<4>(sb, ds, rel, lane, next_round);
      if (more) mbar_wait(sb + BAR_WFULL, par ^ 1);
      TR(24);
      wg_wait<0>(); keep(pa);
      TR(25);
      rel = release_begin<5>(cnt);
      turn_wait(wg);
      wg_fence();
      issue_qkv<0, 0, 8>(acc, X, ds.w[10]); wg_commit();
      sched_fence<1>(never);
      store_out<2>(pa, X, o0, o1);
      load_x<8, 12>(X, tx);
      release_end<5>(sb, ds, rel, lane, next_round);
      wg_fence();
      issue_qkv<0, 8, 12>(acc, X, ds.w[11]); wg_commit();
      if (wg == 0 || next_round) turn_pass(wg);
      if (more) mbar_wait(sb + BAR_SFULL, par ^ 1);
      asm volatile("ld.shared.u32 %0, [%1];" : "=r"(rK) : "r"(sb + OFF_RSTD + wg * 100 + ps * 4) : "memory");
      __syncwarp();
      if (lane == 0) mbar_arrive(sb + BAR_TEMPTY);
      TR(1);
    }
  }
}

typedef CUresult (*EncodeFn)(CUtensorMap*, CUtensorMapDataType, cuuint32_t, void*, const cuuint64_t*, const cuuint64_t*,
                             const cuuint32_t*, const cuuint32_t*, CUtensorMapInterleave, CUtensorMapSwizzle,
                             CUtensorMapL2promotion, CUtensorMapFloatOOBfill);

}

extern "C" void kernel_launch(void* const* d_in, const int* in_sizes, int n_in, void* d_out, int out_size) {
  const __nv_bfloat16* x = (const __nv_bfloat16*)d_in[0];
  const __nv_bfloat16* dw = (const __nv_bfloat16*)d_in[1];
  const __nv_bfloat16* wqkv = (const __nv_bfloat16*)d_in[2];
  const __nv_bfloat16* wo = (const __nv_bfloat16*)d_in[3];
  static EncodeFn encode = nullptr;
  static int nsm = 0;
  static void* wpack = nullptr;
  if (!encode) {
    void* fn = nullptr;
    cudaDriverEntryPointQueryResult qr;
    cudaGetDriverEntryPoint("cuTensorMapEncodeTiled", &fn, cudaEnableDefault, &qr);
    encode = (EncodeFn)fn;
    int dev = 0;
    cudaGetDevice(&dev);
    cudaDeviceGetAttribute(&nsm, cudaDevAttrMultiProcessorCount, dev);
    cudaGetSymbolAddress(&wpack, g_wpack);
    cudaFuncSetAttribute(fused_kernel, cudaFuncAttributeMaxDynamicSharedMemorySize, SMEM_BYTES);
  }
  CUtensorMap tmx;
  cuuint64_t gdim[3] = {CH, IMG, IMG};
  cuuint64_t gstr[2] = {CH * 2, (cuuint64_t)CH * 2 * IMG};
  cuuint32_t box[3] = {64, 9, 1};
  cuuint32_t estr[3] = {1, 1, 1};
  encode(&tmx, CU_TENSOR_MAP_DATA_TYPE_BFLOAT16, 3, (void*)x, gdim, gstr, box, estr, CU_TENSOR_MAP_INTERLEAVE_NONE,
         CU_TENSOR_MAP_SWIZZLE_NONE, CU_TENSOR_MAP_L2_PROMOTION_L2_128B, CU_TENSOR_MAP_FLOAT_OOB_FILL_NONE);
  Descs ds;
  for (int i = 0; i < 12; i++) ds.w[i] = mkdesc(SMEM_BASE + OFF_W, 128, 256);
  for (int i = 0; i < 16; i++) ds.src[i] = (const uint8_t*)wpack + i * SLICE;
  for (int g = 0; g < 2; g++)
    for (int i = 0; i < 4; i++) {
      ds.k[g][i] = mkdesc(SMEM_BASE + OFF_KV + g * KV_BYTES + 1024, KV_PITCH, 128);
      ds.v[g][i] = mkdesc(SMEM_BASE + OFF_KV + g * KV_BYTES, 128, KV_PITCH);
    }
  prepack_kernel<<<96, 192>>>(wqkv, wo);
  fused_kernel<<<nsm, 384, SMEM_BYTES>>>(tmx, ds, dw, (__nv_bfloat16*)d_out, 0);
}
```

```cpp
#include <cuda_runtime.h>
#include <cuda_bf16.h>
#include <cuda.h>
#include <stdint.h>

#define CREGS "208"
#define PREGS "88"
namespace {

constexpr int IMG = 511;
constexpr int CH = 192;
constexpr int NWX = 73;
constexpr int NWIN = NWX * NWX;
constexpr int SLICE = 18432;
constexpr int OFF_W = 0;
constexpr int KV_BYTES = 12544, KV_PITCH = 1920;
constexpr int OFF_KV = 8 * SLICE;
constexpr int TILE_BYTES = 25 * 768;
constexpr int OFF_TILE = OFF_KV + 2 * KV_BYTES;
constexpr int XSLOT = 2304;
constexpr int OFF_X = OFF_TILE + 2 * TILE_BYTES;
constexpr int OFF_BAR = OFF_X + 9 * XSLOT;
constexpr int BAR_WFULL = OFF_BAR;
constexpr int CNT_WREL = OFF_BAR + 48;
constexpr int BAR_XFULL = OFF_BAR + 72;
constexpr int BAR_TFULL = OFF_BAR + 144;
constexpr int BAR_TEMPTY = OFF_BAR + 152;
constexpr int BAR_TPART = OFF_BAR + 160;
constexpr int BAR_SFULL = OFF_BAR + 176;
constexpr int OFF_RSTD = OFF_BAR + 192;
constexpr int OFF_DUMMY = OFF_RSTD + 200;
constexpr int OFF_TRACE = OFF_DUMMY + 152;
constexpr int SMEM_BYTES = OFF_TRACE;

constexpr int SMEM_BASE = 1024;
struct Descs { uint64_t q[4][12]; uint64_t v3[12]; uint64_t p[36]; uint64_t kv[2][8]; const uint8_t* src[16]; };

__device__ uint4 g_wpack[16 * SLICE / 16];
#define TR(id)
template <int ID> __device__ __forceinline__ void sched_fence(uint32_t v) {
  asm volatile("{\n.reg .pred p;\nsetp.ne.u32 p, %0, %1;\n@p bra.uni SF_%=;\ntrap;\nSF_%=:\n}\n" :: "r"(v), "n"(ID) : "memory");
}
__device__ __forceinline__ void anchor(uint32_t v) { sched_fence<0x7fc1ffc1>(v); }

template <int V> struct IC { static constexpr int v = V; };
typedef __nv_bfloat162 bf2;
__device__ __forceinline__ bf2 u2b(uint32_t u) { return *reinterpret_cast<bf2*>(&u); }
__device__ __forceinline__ uint32_t b2u(bf2 b) { return *reinterpret_cast<uint32_t*>(&b); }
__device__ __forceinline__ uint32_t pack2(float lo, float hi) {
  uint32_t r; asm("cvt.rn.bf16x2.f32 %0, %1, %2;" : "=r"(r) : "f"(hi), "f"(lo)); return r;
}
__device__ __forceinline__ uint32_t hadd(uint32_t a, uint32_t b) { return b2u(__hadd2_rn(u2b(a), u2b(b))); }
__device__ __forceinline__ uint32_t hmul(uint32_t a, uint32_t b) { return b2u(__hmul2_rn(u2b(a), u2b(b))); }
__device__ __forceinline__ uint32_t hfma(uint32_t a, uint32_t b, uint32_t c) { return b2u(__hfma2(u2b(a), u2b(b), u2b(c))); }
__device__ __forceinline__ uint32_t hmax(uint32_t a, uint32_t b) { return b2u(__hmax2(u2b(a), u2b(b))); }
template <int HI> __device__ __forceinline__ bf2 bcast(uint32_t a) { return HI ? __high2bfloat162(u2b(a)) : __low2bfloat162(u2b(a)); }
template <int HI> __device__ __forceinline__ uint32_t hmul_b(uint32_t a, uint32_t s) { return b2u(__hmul2_rn(u2b(a), bcast<HI>(s))); }
template <int HI> __device__ __forceinline__ uint32_t hsub_b(uint32_t a, uint32_t s) { return b2u(__hsub2_rn(u2b(a), bcast<HI>(s))); }
__device__ __forceinline__ uint32_t hex2(uint32_t a) { uint32_t r; asm("ex2.approx.ftz.bf16x2 %0, %1;" : "=r"(r) : "r"(a)); return r; }
__device__ __forceinline__ uint32_t hex1(uint32_t a) {
  uint32_t r; asm("{\n.reg .b16 l, h, e;\nmov.b32 {l, h}, %1;\nex2.approx.ftz.bf16 e, l;\ncvt.u32.u16 %0, e;\n}\n" : "=r"(r) : "r"(a)); return r;
}
__device__ __forceinline__ float lo2f(uint32_t a) { return __uint_as_float(a << 16); }
__device__ __forceinline__ float hi2f(uint32_t a) { return __uint_as_float(a & 0xffff0000u); }

__device__ __forceinline__ void mbar_init(uint32_t bar, uint32_t cnt) { asm volatile("mbarrier.init.shared::cta.b64 [%0], %1;" :: "r"(bar), "r"(cnt) : "memory"); }
__device__ __forceinline__ void mbar_arrive(uint32_t bar) { asm volatile("mbarrier.arrive.shared::cta.b64 _, [%0];" :: "r"(bar) : "memory"); }
__device__ __forceinline__ void mbar_expect(uint32_t bar, uint32_t bytes) { asm volatile("mbarrier.arrive.expect_tx.shared::cta.b64 _, [%0], %1;" :: "r"(bar), "r"(bytes) : "memory"); }
template <int HINT>
__device__ __forceinline__ bool mbar_try(uint32_t bar, uint32_t parity) {
  uint32_t ok;
  if (HINT) asm volatile("{\n.reg .pred p;\nmbarrier.try_wait.parity.shared::cta.b64 p, [%1], %2, %3;\nselp.u32 %0, 1, 0, p;\n}\n" : "=r"(ok) : "r"(bar), "r"(parity), "n"(HINT) : "memory");
  else asm volatile("{\n.reg .pred p;\nmbarrier.try_wait.parity.shared::cta.b64 p, [%1], %2;\nselp.u32 %0, 1, 0, p;\n}\n" : "=r"(ok) : "r"(bar), "r"(parity) : "memory");
  return ok != 0;
}
__device__ __forceinline__ void mbar_wait(uint32_t bar, uint32_t parity) {
  if (__builtin_expect(!mbar_try<0>(bar, parity), 0)) {
    uint32_t n = 0;
    while (!mbar_try<4000>(bar, parity)) { if (++n > (1u << 20)) __trap(); }
  }
}
__device__ __forceinline__ void wg_fence() { asm volatile("wgmma.fence.sync.aligned;" ::: "memory"); }
__device__ __forceinline__ void wg_commit() { asm volatile("wgmma.commit_group.sync.aligned;" ::: "memory"); }
template <int N> __device__ __forceinline__ void wg_wait() { asm volatile("wgmma.wait_group.sync.aligned %0;" :: "n"(N) : "memory"); }
__device__ __forceinline__ void bar_sync(int id) { asm volatile("bar.sync %0, 128;" :: "r"(id) : "memory"); }
__device__ __forceinline__ void stsm4(uint32_t addr, uint32_t a, uint32_t b, uint32_t c, uint32_t d) {
  asm volatile("stmatrix.sync.aligned.m8n8.x4.shared.b16 [%0], {%1,%2,%3,%4};" :: "r"(addr), "r"(a), "r"(b), "r"(c), "r"(d) : "memory");
}
template <int N> __device__ __forceinline__ void keep(float (&d)[N]) {
#pragma unroll
  for (int i = 0; i < N; i++) asm volatile("" : "+f"(d[i]) :: "memory");
}
__host__ __device__ __forceinline__ uint64_t mkdesc(uint32_t addr, uint32_t lbo, uint32_t sbo) {
  return ((uint64_t)(sbo >> 4) << 32) | (uint64_t)(((lbo >> 4) << 16) | ((addr & 0x3FFFF) >> 4));
}

template <int SCALE_D>
__device__ __forceinline__ void wgmma_n144(float (&d)[72], uint32_t a0, uint32_t a1, uint32_t a2, uint32_t a3, uint64_t descB) {
  if (SCALE_D == 0)
  asm volatile("wgmma.mma_async.sync.aligned.m64n144k16.f32.bf16.bf16 "
    "{%0, %1, %2, %3, %4, %5, %6, %7, %8, %9, %10, %11, %12, %13, %14, %15, "
    "%16, %17, %18, %19, %20, %21, %22, %23, %24, %25, %26, %27, %28, %29, %30, %31, "
    "%32, %33, %34, %35, %36, %37, %38, %39, %40, %41, %42, %43, %44, %45, %46, %47, "
    "%48, %49, %50, %51, %52, %53, %54, %55, %56, %57, %58, %59, %60, %61, %62, %63, "
    "%64, %65, %66, %67, %68, %69, %70, %71}, "
    "{%72, %73, %74, %75}, %76, 0, 1, 1, 0;\n"
    : "=f"(d[0]), "=f"(d[1]), "=f"(d[2]), "=f"(d[3]), "=f"(d[4]), "=f"(d[5]), "=f"(d[6]), "=f"(d[7]),
      "=f"(d[8]), "=f"(d[9]), "=f"(d[10]), "=f"(d[11]), "=f"(d[12]), "=f"(d[13]), "=f"(d[14]), "=f"(d[15]),
      "=f"(d[16]), "=f"(d[17]), "=f"(d[18]), "=f"(d[19]), "=f"(d[20]), "=f"(d[21]), "=f"(d[22]), "=f"(d[23]),
      "=f"(d[24]), "=f"(d[25]), "=f"(d[26]), "=f"(d[27]), "=f"(d[28]), "=f"(d[29]), "=f"(d[30]), "=f"(d[31]),
      "=f"(d[32]), "=f"(d[33]), "=f"(d[34]), "=f"(d[35]), "=f"(d[36]), "=f"(d[37]), "=f"(d[38]), "=f"(d[39]),
      "=f"(d[40]), "=f"(d[41]), "=f"(d[42]), "=f"(d[43]), "=f"(d[44]), "=f"(d[45]), "=f"(d[46]), "=f"(d[47]),
      "=f"(d[48]), "=f"(d[49]), "=f"(d[50]), "=f"(d[51]), "=f"(d[52]), "=f"(d[53]), "=f"(d[54]), "=f"(d[55]),
      "=f"(d[56]), "=f"(d[57]), "=f"(d[58]), "=f"(d[59]), "=f"(d[60]), "=f"(d[61]), "=f"(d[62]), "=f"(d[63]),
      "=f"(d[64]), "=f"(d[65]), "=f"(d[66]), "=f"(d[67]), "=f"(d[68]), "=f"(d[69]), "=f"(d[70]), "=f"(d[71])
    : "r"(a0), "r"(a1), "r"(a2), "r"(a3), "l"(descB));
  else
  asm volatile("wgmma.mma_async.sync.aligned.m64n144k16.f32.bf16.bf16 "
    "{%0, %1, %2, %3, %4, %5, %6, %7, %8, %9, %10, %11, %12, %13, %14, %15, "
    "%16, %17, %18, %19, %20, %21, %22, %23, %24, %25, %26, %27, %28, %29, %30, %31, "
    "%32, %33, %34, %35, %36, %37, %38, %39, %40, %41, %42, %43, %44, %45, %46, %47, "
    "%48, %49, %50, %51, %52, %53, %54, %55, %56, %57, %58, %59, %60, %61, %62, %63, "
    "%64, %65, %66, %67, %68, %69, %70, %71}, "
    "{%72, %73, %74, %75}, %76, 1, 1, 1, 0;\n"
    : "+f"(d[0]), "+f"(d[1]), "+f"(d[2]), "+f"(d[3]), "+f"(d[4]), "+f"(d[5]), "+f"(d[6]), "+f"(d[7]),
      "+f"(d[8]), "+f"(d[9]), "+f"(d[10]), "+f"(d[11]), "+f"(d[12]), "+f"(d[13]), "+f"(d[14]), "+f"(d[15]),
      "+f"(d[16]), "+f"(d[17]), "+f"(d[18]), "+f"(d[19]), "+f"(d[20]), "+f"(d[21]), "+f"(d[22]), "+f"(d[23]),
      "+f"(d[24]), "+f"(d[25]), "+f"(d[26]), "+f"(d[27]), "+f"(d[28]), "+f"(d[29]), "+f"(d[30]), "+f"(d[31]),
      "+f"(d[32]), "+f"(d[33]), "+f"(d[34]), "+f"(d[35]), "+f"(d[36]), "+f"(d[37]), "+f"(d[38]), "+f"(d[39]),
      "+f"(d[40]), "+f"(d[41]), "+f"(d[42]), "+f"(d[43]), "+f"(d[44]), "+f"(d[45]), "+f"(d[46]), "+f"(d[47]),
      "+f"(d[48]), "+f"(d[49]), "+f"(d[50]), "+f"(d[51]), "+f"(d[52]), "+f"(d[53]), "+f"(d[54]), "+f"(d[55]),
      "+f"(d[56]), "+f"(d[57]), "+f"(d[58]), "+f"(d[59]), "+f"(d[60]), "+f"(d[61]), "+f"(d[62]), "+f"(d[63]),
      "+f"(d[64]), "+f"(d[65]), "+f"(d[66]), "+f"(d[67]), "+f"(d[68]), "+f"(d[69]), "+f"(d[70]), "+f"(d[71])
    : "r"(a0), "r"(a1), "r"(a2), "r"(a3), "l"(descB));
}

template <int SCALE_D>
__device__ __forceinline__ void wgmma_n96(float (&d)[48], uint32_t a0, uint32_t a1, uint32_t a2, uint32_t a3, uint64_t descB) {
  if (SCALE_D == 0)
  asm volatile("wgmma.mma_async.sync.aligned.m64n96k16.f32.bf16.bf16 "
    "{%0, %1, %2, %3, %4, %5, %6, %7, %8, %9, %10, %11, %12, %13, %14, %15, "
    "%16, %17, %18, %19, %20, %21, %22, %23, %24, %25, %26, %27, %28, %29, %30, %31, "
    "%32, %33, %34, %35, %36, %37, %38, %39, %40, %41, %42, %43, %44, %45, %46, %47}, "
    "{%48, %49, %50, %51}, %52, 0, 1, 1, 0;\n"
    : "=f"(d[0]), "=f"(d[1]), "=f"(d[2]), "=f"(d[3]), "=f"(d[4]), "=f"(d[5]), "=f"(d[6]), "=f"(d[7]),
      "=f"(d[8]), "=f"(d[9]), "=f"(d[10]), "=f"(d[11]), "=f"(d[12]), "=f"(d[13]), "=f"(d[14]), "=f"(d[15]),
      "=f"(d[16]), "=f"(d[17]), "=f"(d[18]), "=f"(d[19]), "=f"(d[20]), "=f"(d[21]), "=f"(d[22]), "=f"(d[23]),
      "=f"(d[24]), "=f"(d[25]), "=f"(d[26]), "=f"(d[27]), "=f"(d[28]), "=f"(d[29]), "=f"(d[30]), "=f"(d[31]),
      "=f"(d[32]), "=f"(d[33]), "=f"(d[34]), "=f"(d[35]), "=f"(d[36]), "=f"(d[37]), "=f"(d[38]), "=f"(d[39]),
      "=f"(d[40]), "=f"(d[41]), "=f"(d[42]), "=f"(d[43]), "=f"(d[44]), "=f"(d[45]), "=f"(d[46]), "=f"(d[47])
    : "r"(a0), "r"(a1), "r"(a2), "r"(a3), "l"(descB));
  else
  asm volatile("wgmma.mma_async.sync.aligned.m64n96k16.f32.bf16.bf16 "
    "{%0, %1, %2, %3, %4, %5, %6, %7, %8, %9, %10, %11, %12, %13, %14, %15, "
    "%16, %17, %18, %19, %20, %21, %22, %23, %24, %25, %26, %27, %28, %29, %30, %31, "
    "%32, %33, %34, %35, %36, %37, %38, %39, %40, %41, %42, %43, %44, %45, %46, %47}, "
    "{%48, %49, %50, %51}, %52, 1, 1, 1, 0;\n"
    : "+f"(d[0]), "+f"(d[1]), "+f"(d[2]), "+f"(d[3]), "+f"(d[4]), "+f"(d[5]), "+f"(d[6]), "+f"(d[7]),
      "+f"(d[8]), "+f"(d[9]), "+f"(d[10]), "+f"(d[11]), "+f"(d[12]), "+f"(d[13]), "+f"(d[14]), "+f"(d[15]),
      "+f"(d[16]), "+f"(d[17]), "+f"(d[18]), "+f"(d[19]), "+f"(d[20]), "+f"(d[21]), "+f"(d[22]), "+f"(d[23]),
      "+f"(d[24]), "+f"(d[25]), "+f"(d[26]), "+f"(d[27]), "+f"(d[28]), "+f"(d[29]), "+f"(d[30]), "+f"(d[31]),
      "+f"(d[32]), "+f"(d[33]), "+f"(d[34]), "+f"(d[35]), "+f"(d[36]), "+f"(d[37]), "+f"(d[38]), "+f"(d[39]),
      "+f"(d[40]), "+f"(d[41]), "+f"(d[42]), "+f"(d[43]), "+f"(d[44]), "+f"(d[45]), "+f"(d[46]), "+f"(d[47])
    : "r"(a0), "r"(a1), "r"(a2), "r"(a3), "l"(descB));
}

template <int SCALE_D>
__device__ __forceinline__ void wgmma_n48(float (&d)[24], uint32_t a0, uint32_t a1, uint32_t a2, uint32_t a3, uint64_t descB) {
  if (SCALE_D == 0)
  asm volatile("wgmma.mma_async.sync.aligned.m64n48k16.f32.bf16.bf16 "
    "{%0, %1, %2, %3, %4, %5, %6, %7, %8, %9, %10, %11, %12, %13, %14, %15, "
    "%16, %17, %18, %19, %20, %21, %22, %23}, "
    "{%24, %25, %26, %27}, %28, 0, 1, 1, 0;\n"
    : "=f"(d[0]), "=f"(d[1]), "=f"(d[2]), "=f"(d[3]), "=f"(d[4]), "=f"(d[5]), "=f"(d[6]), "=f"(d[7]),
      "=f"(d[8]), "=f"(d[9]), "=f"(d[10]), "=f"(d[11]), "=f"(d[12]), "=f"(d[13]), "=f"(d[14]), "=f"(d[15]),
      "=f"(d[16]), "=f"(d[17]), "=f"(d[18]), "=f"(d[19]), "=f"(d[20]), "=f"(d[21]), "=f"(d[22]), "=f"(d[23])
    : "r"(a0), "r"(a1), "r"(a2), "r"(a3), "l"(descB));
  else
  asm volatile("wgmma.mma_async.sync.aligned.m64n48k16.f32.bf16.bf16 "
    "{%0, %1, %2, %3, %4, %5, %6, %7, %8, %9, %10, %11, %12, %13, %14, %15, "
    "%16, %17, %18, %19, %20, %21, %22, %23}, "
    "{%24, %25, %26, %27}, %28, 1, 1, 1, 0;\n"
    : "+f"(d[0]), "+f"(d[1]), "+f"(d[2]), "+f"(d[3]), "+f"(d[4]), "+f"(d[5]), "+f"(d[6]), "+f"(d[7]),
      "+f"(d[8]), "+f"(d[9]), "+f"(d[10]), "+f"(d[11]), "+f"(d[12]), "+f"(d[13]), "+f"(d[14]), "+f"(d[15]),
      "+f"(d[16]), "+f"(d[17]), "+f"(d[18]), "+f"(d[19]), "+f"(d[20]), "+f"(d[21]), "+f"(d[22]), "+f"(d[23])
    : "r"(a0), "r"(a1), "r"(a2), "r"(a3), "l"(descB));
}

template <int SCALE_D>
__device__ __forceinline__ void wgmma_n64(float (&d)[32], uint32_t a0, uint32_t a1, uint32_t a2, uint32_t a3, uint64_t descB) {
  if (SCALE_D == 0)
  asm volatile("wgmma.mma_async.sync.aligned.m64n64k16.f32.bf16.bf16 "
    "{%0, %1, %2, %3, %4, %5, %6, %7, %8, %9, %10, %11, %12, %13, %14, %15, "
    "%16, %17, %18, %19, %20, %21, %22, %23, %24, %25, %26, %27, %28, %29, %30, %31}, "
    "{%32, %33, %34, %35}, %36, 0, 1, 1, 0;\n"
    : "=f"(d[0]), "=f"(d[1]), "=f"(d[2]), "=f"(d[3]), "=f"(d[4]), "=f"(d[5]), "=f"(d[6]), "=f"(d[7]),
      "=f"(d[8]), "=f"(d[9]), "=f"(d[10]), "=f"(d[11]), "=f"(d[12]), "=f"(d[13]), "=f"(d[14]), "=f"(d[15]),
      "=f"(d[16]), "=f"(d[17]), "=f"(d[18]), "=f"(d[19]), "=f"(d[20]), "=f"(d[21]), "=f"(d[22]), "=f"(d[23]),
      "=f"(d[24]), "=f"(d[25]), "=f"(d[26]), "=f"(d[27]), "=f"(d[28]), "=f"(d[29]), "=f"(d[30]), "=f"(d[31])
    : "r"(a0), "r"(a1), "r"(a2), "r"(a3), "l"(descB));
  else if (SCALE_D == 2)
  asm volatile("wgmma.mma_async.sync.aligned.m64n64k16.f32.bf16.bf16 "
    "{%0, %1, %2, %3, %4, %5, %6, %7, %8, %9, %10, %11, %12, %13, %14, %15, "
    "%16, %17, %18, %19, %20, %21, %22, %23, %24, %25, %26, %27, %28, %29, %30, %31}, "
    "{%32, %33, %34, %35}, %36, 0, 1, 1, 0;\n"
    : "+f"(d[0]), "+f"(d[1]), "+f"(d[2]), "+f"(d[3]), "+f"(d[4]), "+f"(d[5]), "+f"(d[6]), "+f"(d[7]),
      "+f"(d[8]), "+f"(d[9]), "+f"(d[10]), "+f"(d[11]), "+f"(d[12]), "+f"(d[13]), "+f"(d[14]), "+f"(d[15]),
      "+f"(d[16]), "+f"(d[17]), "+f"(d[18]), "+f"(d[19]), "+f"(d[20]), "+f"(d[21]), "+f"(d[22]), "+f"(d[23]),
      "+f"(d[24]), "+f"(d[25]), "+f"(d[26]), "+f"(d[27]), "+f"(d[28]), "+f"(d[29]), "+f"(d[30]), "+f"(d[31])
    : "r"(a0), "r"(a1), "r"(a2), "r"(a3), "l"(descB));
  else
  asm volatile("wgmma.mma_async.sync.aligned.m64n64k16.f32.bf16.bf16 "
    "{%0, %1, %2, %3, %4, %5, %6, %7, %8, %9, %10, %11, %12, %13, %14, %15, "
    "%16, %17, %18, %19, %20, %21, %22, %23, %24, %25, %26, %27, %28, %29, %30, %31}, "
    "{%32, %33, %34, %35}, %36, 1, 1, 1, 0;\n"
    : "+f"(d[0]), "+f"(d[1]), "+f"(d[2]), "+f"(d[3]), "+f"(d[4]), "+f"(d[5]), "+f"(d[6]), "+f"(d[7]),
      "+f"(d[8]), "+f"(d[9]), "+f"(d[10]), "+f"(d[11]), "+f"(d[12]), "+f"(d[13]), "+f"(d[14]), "+f"(d[15]),
      "+f"(d[16]), "+f"(d[17]), "+f"(d[18]), "+f"(d[19]), "+f"(d[20]), "+f"(d[21]), "+f"(d[22]), "+f"(d[23]),
      "+f"(d[24]), "+f"(d[25]), "+f"(d[26]), "+f"(d[27]), "+f"(d[28]), "+f"(d[29]), "+f"(d[30]), "+f"(d[31])
    : "r"(a0), "r"(a1), "r"(a2), "r"(a3), "l"(descB));
}

template <int SCALE_D>
__device__ __forceinline__ void wgmma_n56(float (&d)[28], uint32_t a0, uint32_t a1, uint32_t a2, uint32_t a3, uint64_t descB) {
  if (SCALE_D == 0)
  asm volatile("wgmma.mma_async.sync.aligned.m64n56k16.f32.bf16.bf16 "
    "{%0, %1, %2, %3, %4, %5, %6, %7, %8, %9, %10, %11, %12, %13, %14, %15, "
    "%16, %17, %18, %19, %20, %21, %22, %23, %24, %25, %26, %27}, "
    "{%28, %29, %30, %31}, %32, 0, 1, 1, 0;\n"
    : "=f"(d[0]), "=f"(d[1]), "=f"(d[2]), "=f"(d[3]), "=f"(d[4]), "=f"(d[5]), "=f"(d[6]), "=f"(d[7]),
      "=f"(d[8]), "=f"(d[9]), "=f"(d[10]), "=f"(d[11]), "=f"(d[12]), "=f"(d[13]), "=f"(d[14]), "=f"(d[15]),
      "=f"(d[16]), "=f"(d[17]), "=f"(d[18]), "=f"(d[19]), "=f"(d[20]), "=f"(d[21]), "=f"(d[22]), "=f"(d[23]),
      "=f"(d[24]), "=f"(d[25]), "=f"(d[26]), "=f"(d[27])
    : "r"(a0), "r"(a1), "r"(a2), "r"(a3), "l"(descB));
  else
  asm volatile("wgmma.mma_async.sync.aligned.m64n56k16.f32.bf16.bf16 "
    "{%0, %1, %2, %3, %4, %5, %6, %7, %8, %9, %10, %11, %12, %13, %14, %15, "
    "%16, %17, %18, %19, %20, %21, %22, %23, %24, %25, %26, %27}, "
    "{%28, %29, %30, %31}, %32, 1, 1, 1, 0;\n"
    : "+f"(d[0]), "+f"(d[1]), "+f"(d[2]), "+f"(d[3]), "+f"(d[4]), "+f"(d[5]), "+f"(d[6]), "+f"(d[7]),
      "+f"(d[8]), "+f"(d[9]), "+f"(d[10]), "+f"(d[11]), "+f"(d[12]), "+f"(d[13]), "+f"(d[14]), "+f"(d[15]),
      "+f"(d[16]), "+f"(d[17]), "+f"(d[18]), "+f"(d[19]), "+f"(d[20]), "+f"(d[21]), "+f"(d[22]), "+f"(d[23]),
      "+f"(d[24]), "+f"(d[25]), "+f"(d[26]), "+f"(d[27])
    : "r"(a0), "r"(a1), "r"(a2), "r"(a3), "l"(descB));
}

template <int SCALE_D>
__device__ __forceinline__ void wgmma_n56t(float (&d)[28], uint32_t a0, uint32_t a1, uint32_t a2, uint32_t a3, uint64_t descB) {
  if (SCALE_D == 0)
  asm volatile("wgmma.mma_async.sync.aligned.m64n56k16.f32.bf16.bf16 "
    "{%0, %1, %2, %3, %4, %5, %6, %7, %8, %9, %10, %11, %12, %13, %14, %15, "
    "%16, %17, %18, %19, %20, %21, %22, %23, %24, %25, %26, %27}, "
    "{%28, %29, %30, %31}, %32, 0, 1, 1, 1;\n"
    : "=f"(d[0]), "=f"(d[1]), "=f"(d[2]), "=f"(d[3]), "=f"(d[4]), "=f"(d[5]), "=f"(d[6]), "=f"(d[7]),
      "=f"(d[8]), "=f"(d[9]), "=f"(d[10]), "=f"(d[11]), "=f"(d[12]), "=f"(d[13]), "=f"(d[14]), "=f"(d[15]),
      "=f"(d[16]), "=f"(d[17]), "=f"(d[18]), "=f"(d[19]), "=f"(d[20]), "=f"(d[21]), "=f"(d[22]), "=f"(d[23]),
      "=f"(d[24]), "=f"(d[25]), "=f"(d[26]), "=f"(d[27])
    : "r"(a0), "r"(a1), "r"(a2), "r"(a3), "l"(descB));
  else
  asm volatile("wgmma.mma_async.sync.aligned.m64n56k16.f32.bf16.bf16 "
    "{%0, %1, %2, %3, %4, %5, %6, %7, %8, %9, %10, %11, %12, %13, %14, %15, "
    "%16, %17, %18, %19, %20, %21, %22, %23, %24, %25, %26, %27}, "
    "{%28, %29, %30, %31}, %32, 1, 1, 1, 1;\n"
    : "+f"(d[0]), "+f"(d[1]), "+f"(d[2]), "+f"(d[3]), "+f"(d[4]), "+f"(d[5]), "+f"(d[6]), "+f"(d[7]),
      "+f"(d[8]), "+f"(d[9]), "+f"(d[10]), "+f"(d[11]), "+f"(d[12]), "+f"(d[13]), "+f"(d[14]), "+f"(d[15]),
      "+f"(d[16]), "+f"(d[17]), "+f"(d[18]), "+f"(d[19]), "+f"(d[20]), "+f"(d[21]), "+f"(d[22]), "+f"(d[23]),
      "+f"(d[24]), "+f"(d[25]), "+f"(d[26]), "+f"(d[27])
    : "r"(a0), "r"(a1), "r"(a2), "r"(a3), "l"(descB));
}

__global__ void __launch_bounds__(192) prepack_kernel(const __nv_bfloat16* __restrict__ wqkv, const __nv_bfloat16* __restrict__ wo) {
  __nv_bfloat16* dst = reinterpret_cast<__nv_bfloat16*>(g_wpack);
  const int c = threadIdx.x, nb = blockIdx.x;
  if (nb < 72) {
    __shared__ float red[6][8];
    const int h = nb / 18, j = nb % 18, part = j / 6;
    const int col = (part == 0 ? 192 : part == 1 ? 0 : 384) + h * 48 + (j % 6) * 8;
    uint4 raw = *reinterpret_cast<const uint4*>(wqkv + c * 576 + col);
    uint32_t u[4] = {raw.x, raw.y, raw.z, raw.w};
    float v[8];
#pragma unroll
    for (int i = 0; i < 4; i++) { v[2 * i] = lo2f(u[i]); v[2 * i + 1] = hi2f(u[i]); }
#pragma unroll
    for (int i = 0; i < 8; i++) {
      float s = v[i];
#pragma unroll
      for (int o = 16; o; o >>= 1) s += __shfl_xor_sync(~0u, s, o);
      if ((c & 31) == 0) red[c >> 5][i] = s;
    }
    __syncthreads();
    const int cc = c >> 5, q = (c >> 3) & 3, s1 = (c >> 2) & 1, hh = (c >> 1) & 1, e = c & 1;
    const int base = h * 27648 + (2 * cc + s1) * 2304 + j * 128 + hh * 64 + 2 * q + e;
#pragma unroll
    for (int n = 0; n < 8; n++) {
      float m = (red[0][n] + red[1][n] + red[2][n] + red[3][n] + red[4][n] + red[5][n]) * (1.0f / 192.0f);
      dst[base + n * 8] = __float2bfloat16((v[n] - m) * (part == 1 ? 0.14433756729740643f * 1.4426950408889634f : 1.0f));
    }
  } else {
    const int jb = nb - 72, chunk = jb / 8, j = jb % 8;
    const int s = c >> 4, hh = (c >> 3) & 1, kk = c & 7;
    const int base = 110592 + (chunk * 12 + s) * 1024 + j * 128 + hh * 64 + kk;
#pragma unroll
    for (int n = 0; n < 8; n++) {
      const int ch = 32 * (jb >> 2) + 8 * (n >> 1) + 2 * (jb & 3) + (n & 1);
      dst[base + n * 8] = wo[c * 192 + ch];
    }
  }
}

__device__ __forceinline__ int window_of(int round, int nfull, int cta, int ncta, int wg) {
  if (round < nfull) return round * 2 * ncta + 2 * cta + wg;
  const int rem = NWIN - nfull * 2 * ncta;
  const int i = cta + wg * ncta;
  return i < rem ? nfull * 2 * ncta + i : -1;
}

__host__ __device__ constexpr int qkv_off(int h, int s) { return ((3 * h + s / 4) % 8) * SLICE + (s % 4) * 4608; }
__host__ __device__ constexpr int wo_off(int chunk, int s) { return 4 * SLICE + (chunk * 12 + s) * 2048; }

#define DEF_ISSUE(NAME, NREG, FN, FIRST)                                                                          \
  template <int S0, int S1, int INIT = FIRST>                                                                     \
  __device__ __forceinline__ void NAME(float (&acc)[NREG], const uint32_t (&A)[48], const uint64_t* d) {          \
    wg_fence();                                                                                                   \
    _Pragma("unroll") for (int s = S0; s < S1; s++) {                                                             \
      if (s == 0) FN<INIT>(acc, A[4 * s], A[4 * s + 1], A[4 * s + 2], A[4 * s + 3], d[s]);                        \
      else        FN<1>(acc, A[4 * s], A[4 * s + 1], A[4 * s + 2], A[4 * s + 3], d[s]);                           \
    }                                                                                                             \
    wg_commit();                                                                                                  \
  }
DEF_ISSUE(mma144, 72, wgmma_n144, 0)
DEF_ISSUE(mma96, 48, wgmma_n96, 0)
DEF_ISSUE(mma64, 32, wgmma_n64, 0)
DEF_ISSUE(mma48, 24, wgmma_n48, 0)
#undef DEF_ISSUE

#define PIN() asm volatile("pmevent 0;" ::: "memory")
template <int A, int B> __device__ __forceinline__ void hold(uint32_t* v) {
#pragma unroll
  for (int i = A; i < B; i++) asm volatile("" : "+r"(v[i]));
}
template <int A, int B> __device__ __forceinline__ void packn(uint32_t* d, const float* a) {
#pragma unroll
  for (int i = A; i < B; i++) d[i] = pack2(a[2 * i], a[2 * i + 1]);
}
template <int A, int B> __device__ __forceinline__ void scalen(uint32_t* d, uint32_t r) {
#pragma unroll
  for (int i = A; i < B; i++) d[i] = (i & 1) ? hmul_b<1>(d[i], r) : hmul_b<0>(d[i], r);
}
__device__ __forceinline__ void stsm12(const uint32_t* v, uint32_t addr) {
#pragma unroll
  for (int j = 0; j < 3; j++) stsm4(addr + 2 * j * KV_PITCH, v[4 * j], v[4 * j + 1], v[4 * j + 2], v[4 * j + 3]);
}
__device__ __forceinline__ uint32_t inv_sum(const float (&o)[28]) {
  float i0, i1;
  asm("rcp.approx.ftz.f32 %0, %1;" : "=f"(i0) : "f"(o[24]));
  asm("rcp.approx.ftz.f32 %0, %1;" : "=f"(i1) : "f"(o[26]));
  return pack2(i0, i1);
}
__device__ __forceinline__ void proxy_fence() { asm volatile("fence.proxy.async.shared::cta;" ::: "memory"); }
__device__ __forceinline__ void issue_s(float (&S)[28], const uint32_t (&Q)[12], const uint64_t* d) {
  wg_fence();
  wgmma_n56<0>(S, Q[0], Q[1], Q[2], Q[3], d[0]);
  wgmma_n56<1>(S, Q[4], Q[5], Q[6], Q[7], d[1]);
  wgmma_n56<1>(S, Q[8], Q[9], Q[10], Q[11], d[2]);
  wg_commit();
}
struct H2 { uint16_t l, h; };
__device__ __forceinline__ H2 exp_halves(uint32_t a) {
  H2 r;
  asm("{\n.reg .b16 l, h;\nmov.b32 {l, h}, %2;\nex2.approx.ftz.bf16 %0, l;\nex2.approx.ftz.bf16 %1, h;\n}\n" : "=h"(r.l), "=h"(r.h) : "r"(a));
  return r;
}
__device__ __forceinline__ uint32_t join(H2 v) { uint32_t r; asm("mov.b32 %0, {%1, %2};" : "=r"(r) : "h"(v.l), "h"(v.h)); return r; }
__device__ __forceinline__ void hold(H2& v) { asm volatile("" : "+h"(v.l), "+h"(v.h)); }

template <int NK, bool PREV, class G>
__device__ __forceinline__ void softmax_pv(float (&S)[28], const uint64_t* dV, uint32_t* Op, uint32_t inv, int wg, G g) {
#define GK(k) if ((k) < NK) g(IC<((k) < NK ? (k) : 0)>{}, IC<((k) < NK ? (k) + 1 : 0)>{});
  uint32_t P[16];
  GK(2) packn<0, 4>(P, S);  if (PREV) { scalen<0, 4>(Op, inv); hold<0, 4>(Op); }   hold<0, 4>(P); PIN();
  GK(3) packn<4, 9>(P, S);  if (PREV) { scalen<4, 8>(Op, inv); hold<4, 8>(Op); }   hold<4, 9>(P); PIN();
  GK(4) packn<9, 14>(P, S); if (PREV) { scalen<8, 12>(Op, inv); hold<8, 12>(Op); } hold<9, 14>(P); PIN();
  GK(5)
  uint32_t m0 = hmax(hmax(hmax(hmax(P[0], P[2]), P[4]), hmax(hmax(P[6], P[8]), P[10])), P[12]);
  uint32_t m1 = hmax(hmax(hmax(hmax(P[1], P[3]), P[5]), hmax(hmax(P[7], P[9]), P[11])), P[13]);
  uint32_t mx = hmax(__byte_perm(m0, m1, 0x5410), __byte_perm(m0, m1, 0x7632));
  uint32_t sh = __shfl_xor_sync(~0u, mx, 1);
  PIN();
  GK(6)
  PIN();
  mx = hmax(mx, sh);
  sh = __shfl_xor_sync(~0u, mx, 2);
  PIN();
  GK(7)
  bar_sync(1 + wg);
  PIN();
  mx = hmax(mx, sh);
#pragma unroll
  for (int j = 0; j < 14; j++) P[j] = (j & 1) ? hsub_b<1>(P[j], mx) : hsub_b<0>(P[j], mx);
  H2 e0 = exp_halves(P[0]), e1 = exp_halves(P[1]);
  GK(8)
  hold<2, 14>(P); hold(e0); hold(e1); PIN();
  GK(9)
  H2 e2 = exp_halves(P[2]), e3 = exp_halves(P[3]);
  P[0] = join(e0); P[1] = join(e1);
  hold<0, 2>(P); hold(e2); hold(e3); PIN();
  GK(10)
  e0 = exp_halves(P[4]); e1 = exp_halves(P[5]);
  P[2] = join(e2); P[3] = join(e3);
  hold<2, 4>(P); hold(e0); hold(e1); PIN();
  GK(11)
  P[12] = hex1(P[12]); P[13] = hex1(P[13]); P[14] = 0; P[15] = 0;
  P[4] = join(e0); P[5] = join(e1);
#pragma unroll
  for (int j = 6; j < 12; j++) P[j] = hex2(P[j]);
  wg_fence();
  wgmma_n56t<0>(S, P[0], P[1], P[2], P[3], dV[0]);
  wgmma_n56t<1>(S, P[4], P[5], P[6], P[7], dV[1]);
  wgmma_n56t<1>(S, P[12], P[13], P[14], P[15], dV[3]);
  wgmma_n56t<1>(S, P[8], P[9], P[10], P[11], dV[2]);
  wg_commit();
#undef GK
}
template <int S0, int S1>
__device__ __forceinline__ void load_x(uint32_t (&X)[48], uint32_t t0) {
#pragma unroll
  for (int s = S0; s < S1; s++)
    asm volatile("ld.shared.v4.u32 {%0,%1,%2,%3}, [%4];" : "=r"(X[4 * s]), "=r"(X[4 * s + 1]), "=r"(X[4 * s + 2]), "=r"(X[4 * s + 3])
                 : "r"(((s & 1) ? (t0 ^ 16) : t0) + (s >> 1) * 128) : "memory");
}

template <int CC>
__device__ __forceinline__ void store_out(const uint32_t* T, const uint32_t (&X)[48], uint8_t* o0, uint8_t* o1) {
  asm volatile("st.global.v4.u32 [%0], {%1,%2,%3,%4};" :: "l"(o0 + CC * 64), "r"(hadd(X[8 * CC], T[0])), "r"(hadd(X[8 * CC + 2], T[2])),
               "r"(hadd(X[8 * CC + 4], T[4])), "r"(hadd(X[8 * CC + 6], T[6])) : "memory");
  asm volatile("st.global.v4.u32 [%0], {%1,%2,%3,%4};" :: "l"(o1 + CC * 64), "r"(hadd(X[8 * CC + 1], T[1])), "r"(hadd(X[8 * CC + 3], T[3])),
               "r"(hadd(X[8 * CC + 5], T[5])), "r"(hadd(X[8 * CC + 7], T[7])) : "memory");
}

template <int K, int CNT> __device__ __forceinline__ void load_slices(uint32_t sb, const Descs& ds) {
  constexpr int st = K < 12 ? K / 3 : 4 + (K - 12) / 2;
  constexpr bool first = K < 12 ? (K % 3 == 0) : (K % 2 == 0);
  if (first)
    asm volatile("{\n.reg .pred p;\nelect.sync _|p, 0xffffffff;\n@p mbarrier.arrive.expect_tx.shared::cta.b64 _, [%0], %1;\n}\n"
                 :: "r"(sb + BAR_WFULL + 8 * st), "n"((K < 12 ? 3 : 2) * SLICE) : "memory");
  asm volatile("{\n.reg .pred p;\nelect.sync _|p, 0xffffffff;\n"
               "@p cp.async.bulk.shared::cluster.global.mbarrier::complete_tx::bytes [%0], [%1], %2, [%3];\n}\n"
               :: "r"(sb + OFF_W + (K & 7) * SLICE), "l"(ds.src[K]), "n"(CNT * SLICE), "r"(sb + BAR_WFULL + 8 * st) : "memory");
}
template <int STAGE> __device__ __forceinline__ uint32_t release_begin(uint32_t cnt) {
  uint32_t old;
  asm volatile("atom.shared.inc.u32 %0, [%1 + %2], 7;" : "=r"(old) : "r"(cnt), "n"(4 * STAGE) : "memory");
  return old;
}
template <int STAGE> __device__ __forceinline__ void release_end(uint32_t sb, const Descs& ds, uint32_t old, int lane, bool next_round) {
  if (__any_sync(0xffffffffu, old == 7 && lane == 0)) {
    if (STAGE == 0) { load_slices<8, 1>(sb, ds); load_slices<9, 2>(sb, ds); }
    if (STAGE == 1) { load_slices<11, 1>(sb, ds); load_slices<12, 2>(sb, ds); }
    if (STAGE == 2) { load_slices<14, 2>(sb, ds); if (next_round) load_slices<0, 1>(sb, ds); }
    if (STAGE == 3 && next_round) { load_slices<1, 2>(sb, ds); load_slices<3, 1>(sb, ds); }
    if (STAGE == 4 && next_round) load_slices<4, 2>(sb, ds);
    if (STAGE == 5 && next_round) load_slices<6, 2>(sb, ds);
  }
}

__device__ __forceinline__ uint32_t ln_rstd(const uint32_t (&X)[48]) {
  uint32_t sm[2];
#pragma unroll
  for (int a = 0; a < 2; a++) {
    uint32_t t[12];
#pragma unroll
    for (int i = 0; i < 12; i++) t[i] = hadd(X[4 * i + a], X[4 * i + 2 + a]);
#pragma unroll
    for (int i = 0; i < 6; i++) t[i] = hadd(t[i], t[i + 6]);
#pragma unroll
    for (int i = 0; i < 3; i++) t[i] = hadd(t[i], t[i + 3]);
    sm[a] = hadd(hadd(t[0], t[1]), t[2]);
  }
  uint32_t m = hadd(__byte_perm(sm[0], sm[1], 0x5410), __byte_perm(sm[0], sm[1], 0x7632));
  m = hadd(m, __shfl_xor_sync(~0u, m, 1));
  m = hadd(m, __shfl_xor_sync(~0u, m, 2));
  m = hmul(m, 0x3bab3babu);
  float var[2];
#pragma unroll
  for (int a = 0; a < 2; a++) {
    uint32_t t[4];
#pragma unroll
    for (int i = 0; i < 24; i++) {
      const uint32_t d = a ? hsub_b<1>(X[2 * i + 1], m) : hsub_b<0>(X[2 * i], m);
      t[i & 3] = i < 4 ? hmul(d, d) : hfma(d, d, t[i & 3]);
    }
    const uint32_t s = hadd(hadd(t[0], t[1]), hadd(t[2], t[3]));
    float v = lo2f(s) + hi2f(s);
    v += __shfl_xor_sync(~0u, v, 1);
    v += __shfl_xor_sync(~0u, v, 2);
    asm("rsqrt.approx.ftz.f32 %0, %1;" : "=f"(var[a]) : "f"(fmaf(v, 1.0f / 192.0f, 1e-5f)));
  }
  return pack2(var[0], var[1]);
}

__device__ __forceinline__ void stats_pass(uint32_t sb, int pass, int lane) {
  const int g = lane >> 2, q = lane & 3;
  const int tile = pass < 6 ? (pass & 1) : (g & 1);
  const int ps = pass < 6 ? (pass >> 1) * 8 + g : 24;
  uint32_t X[48];
  load_x<0, 12>(X, sb + OFF_TILE + tile * TILE_BYTES + ps * 768 + q * 32 + (ps & 1) * 16);
  const uint32_t rs = ln_rstd(X);
  asm volatile("st.shared.u32 [%0], %1;" :: "r"(sb + OFF_RSTD + tile * 100 + ps * 4), "r"(rs) : "memory");
}

__global__ void __launch_bounds__(384, 1)
fused_kernel(const __grid_constant__ CUtensorMap tmx, const __grid_constant__ Descs ds, const __nv_bfloat16* __restrict__ dw, __nv_bfloat16* __restrict__ out, const int never) {
  extern __shared__ __align__(1024) uint8_t smem[];
  const uint32_t sb = (uint32_t)__cvta_generic_to_shared(smem);
  const int tid = threadIdx.x, lane = tid & 31;
  const int warp = __shfl_sync(0xffffffffu, tid >> 5, 0);
  const int cta = blockIdx.x, ncta = gridDim.x;
  const int nfull = NWIN / (2 * ncta);
  const int nrounds = nfull + ((NWIN - nfull * 2 * ncta) > cta ? 1 : 0);

  if (tid == 0) {
    if ((sb & 0x3FFFF) != SMEM_BASE) __trap();
    for (int i = 0; i < 6; i++) { mbar_init(sb + BAR_WFULL + 8 * i, 1); *reinterpret_cast<uint32_t*>(smem + CNT_WREL + 4 * i) = 0; }
    for (int i = 0; i < 9; i++) mbar_init(sb + BAR_XFULL + 8 * i, 1);
    mbar_init(sb + BAR_TFULL, 3);
    mbar_init(sb + BAR_TEMPTY, 8);
    mbar_init(sb + BAR_TPART, 3);
    mbar_init(sb + BAR_TPART + 8, 3);
    mbar_init(sb + BAR_SFULL, 4);
    asm volatile("fence.mbarrier_init.release.cluster;" ::: "memory");
  }
  if (tid < 128) {
    const uint32_t v = (tid & 63) < 49 ? 0x3f803f80u : 0u;
    *reinterpret_cast<uint4*>(smem + OFF_KV + (tid >> 6) * KV_BYTES + 6 * KV_PITCH + (tid & 63) * 16) = make_uint4(v, v, v, v);
    asm volatile("fence.proxy.async.shared::cta;" ::: "memory");
  }
  __syncthreads();

  if (warp >= 8) {
    asm volatile("setmaxnreg.dec.sync.aligned.u32 " PREGS ";");
    if (warp == 11) {
      load_slices<0, 3>(sb, ds); load_slices<3, 3>(sb, ds); load_slices<6, 2>(sb, ds);
      for (int r = 0; r < nrounds; r++) {
#pragma unroll 1
        for (int pass = 0; pass < 4; pass++) {
          if (!(pass & 1)) mbar_wait(sb + BAR_TPART + 4 * pass, r & 1);
          stats_pass(sb, pass, lane);
        }
        __syncwarp();
        if (lane == 0) mbar_arrive(sb + BAR_SFULL);
        TR(2);
      }
    } else {
      const int cw = warp - 8;
      const int win = lane >> 4;
      const int ch0 = cw * 64 + (lane & 15) * 4;
      uint32_t wt[9][2];
#pragma unroll
      for (int t = 0; t < 9; t++) {
        uint2 v = *reinterpret_cast<const uint2*>(dw + t * CH + ch0);
        wt[t][0] = v.x; wt[t][1] = v.y;
      }
      const uint32_t xs = sb + OFF_X + cw * 3 * XSLOT;
      const uint32_t xld = xs + (lane >> 4) * 1152 + (lane & 15) * 8;
      const uint32_t xbar = sb + BAR_XFULL + cw * 24;
      const uint32_t st0 = sb + OFF_TILE + win * TILE_BYTES + ch0 * 4;
      const uint32_t st1 = sb + OFF_TILE + win * TILE_BYTES + ((ch0 * 4) ^ 16);
      const uint64_t tm = reinterpret_cast<uint64_t>(&tmx);
      int cx0, cy0, cx1, cy1;
      auto coords = [&](int r) {
        const int w0 = window_of(r, nfull, cta, ncta, 0);
        int w1 = window_of(r, nfull, cta, ncta, 1);
        if (w1 < 0) w1 = w0;
        const int a = w0 / NWX, b = w1 / NWX;
        cx0 = (w0 - a * NWX) * 7 - 1; cy0 = a * 7 - 1;
        cx1 = (w1 - b * NWX) * 7 - 1; cy1 = b * 7 - 1;
      };
      auto issue = [&](int slot, int dy) {
        asm volatile("{\n.reg .pred p;\nelect.sync _|p, 0xffffffff;\n"
                     "@p mbarrier.arrive.expect_tx.shared::cta.b64 _, [%2], %8;\n"
                     "@p cp.async.bulk.tensor.3d.shared::cluster.global.mbarrier::complete_tx::bytes [%0], [%1, {%3, %4, %5}], [%2];\n"
                     "@p cp.async.bulk.tensor.3d.shared::cluster.global.mbarrier::complete_tx::bytes [%0 + 1152], [%1, {%3, %6, %7}], [%2];\n}\n"
                     :: "r"(xs + slot * XSLOT), "l"(tm), "r"(xbar + slot * 8), "r"(cw * 64), "r"(cx0), "r"(cy0 + dy), "r"(cx1), "r"(cy1 + dy), "n"(XSLOT) : "memory");
      };
      coords(0);
      issue(0, 0); issue(1, 1); issue(2, 2);
      for (int r = 0; r < nrounds; r++) {
        const bool more = r + 1 < nrounds;
        uint32_t accA[7][2], accB[7][2], ctr[7][2], held[2];
#pragma unroll
        for (int i = 0; i < 9; i++) {
          mbar_wait(xbar + (i % 3) * 8, (r + i / 3) & 1);
          if (i == 5 || i == 7) { __syncwarp(); if (lane == 0) mbar_arrive(sb + BAR_TPART + (i == 5 ? 0 : 8)); }
          if (i == 7 && more) coords(r + 1);
          if (i == 0) { if (r > 0) issue(2, 2); }
          else if (i < 7) issue((i + 2) % 3, i + 2);
          else if (more) issue((i + 2) % 3, i - 7);
          if (i == 2 && r > 0) mbar_wait(sb + BAR_TEMPTY, (r - 1) & 1);
          if (i == 2) { TR(0); }
          uint32_t cur[9][2];
#pragma unroll
          for (int p = 0; p < 5; p++)
            asm volatile("ld.shared.v2.u32 {%0,%1}, [%2];" : "=r"(cur[p][0]), "=r"(cur[p][1]) : "r"(xld + (i % 3) * XSLOT + p * 128));
#pragma unroll
          for (int j = 0; j < 7; j++) {
            if (j >= 1 && j + 4 < 9)
              asm volatile("ld.shared.v2.u32 {%0,%1}, [%2];" : "=r"(cur[j + 4][0]), "=r"(cur[j + 4][1]) : "r"(xld + (i % 3) * XSLOT + (j + 4) * 128));
            if (i >= 2) {
              uint32_t o[2];
#pragma unroll
              for (int e = 0; e < 2; e++) {
                uint32_t a = hfma(cur[j][e], wt[6][e], accA[j][e]);
                a = hfma(cur[j + 1][e], wt[7][e], a);
                a = hfma(cur[j + 2][e], wt[8][e], a);
                o[e] = hadd(ctr[j][e], a);
              }
              const int tok = (i - 2) * 7 + j, ps = tok >> 1;
              if (!(tok & 1)) { held[0] = o[0]; held[1] = o[1]; }
              if ((tok & 1) || tok == 48)
                asm volatile("st.shared.v4.u32 [%0], {%1,%2,%3,%4};" :: "r"(((ps & 1) ? st1 : st0) + ps * 768), "r"(held[0]), "r"(o[0]), "r"(held[1]), "r"(o[1]) : "memory");
            }
#pragma unroll
            for (int e = 0; e < 2; e++) {
              if (i >= 1 && i <= 7) {
                uint32_t a = hfma(cur[j][e], wt[3][e], accB[j][e]);
                a = hfma(cur[j + 1][e], wt[4][e], a);
                accA[j][e] = hfma(cur[j + 2][e], wt[5][e], a);
                ctr[j][e] = cur[j + 1][e];
              }
              if (i <= 6) {
                uint32_t a = hmul(cur[j][e], wt[0][e]);
                a = hfma(cur[j + 1][e], wt[1][e], a);
                accB[j][e] = hfma(cur[j + 2][e], wt[2][e], a);
              }
            }
          }
        }
        __syncwarp();
        if (lane == 0) mbar_arrive(sb + BAR_TFULL);
        TR(1);
        mbar_wait(sb + BAR_TFULL, r & 1);
        stats_pass(sb, 4 + cw, lane);
        __syncwarp();
        if (lane == 0) mbar_arrive(sb + BAR_SFULL);
      }
    }
  } else {
    asm volatile("setmaxnreg.inc.sync.aligned.u32 " CREGS ";");
    const int wg = warp >> 2, w4 = warp & 3, g = lane >> 2, q = lane & 3;
    const int row0 = w4 * 16 + g, row1 = row0 + 8;
    const int ps = min(w4 * 8 + g, 24);
    const int tok0 = 2 * ps, tok1 = min(2 * ps + 1, 48);
    const uint32_t kv = sb + OFF_KV + wg * KV_BYTES;
    const int srow = w4 * 16 + (lane & 15);
    const uint32_t vst = kv + (lane >> 4) * KV_PITCH + srow * 16;
    const uint32_t kst = vst + (srow < 56 ? 1024 : 0);
    const uint32_t off0 = ((tok0 / 7) * IMG + tok0 % 7) * 384 + q * 16, off1 = ((tok1 / 7) * IMG + tok1 % 7) * 384 + q * 16;
    const uint32_t cnt = lane == 0 ? sb + CNT_WREL : sb + OFF_DUMMY + lane * 4;
    const uint32_t vmask = (row0 < 49 ? 0xffffu : 0u) | (row1 < 49 ? 0xffff0000u : 0u);

    const uint32_t tx = sb + OFF_TILE + wg * TILE_BYTES + ps * 768 + q * 32 + (ps & 1) * 16;
    const int myrounds = window_of(nrounds - 1, nfull, cta, ncta, wg) < 0 ? nrounds - 1 : nrounds;

    if (never == 2) return;
    uint32_t X[48];
    float acc[72];
    mbar_wait(sb + BAR_TFULL, 0);
    load_x<0, 12>(X, tx);
    mbar_wait(sb + BAR_WFULL, 0);
    mma144<0, 12>(acc, X, ds.q[0]);
    uint32_t rK;
    mbar_wait(sb + BAR_SFULL, 0);
    asm volatile("ld.shared.u32 %0, [%1];" : "=r"(rK) : "r"(sb + OFF_RSTD + wg * 100 + ps * 4) : "memory");
    __syncwarp();
    if (lane == 0) mbar_arrive(sb + BAR_TEMPTY);

    for (int r = 0;; r++) {
      const uint32_t par = r & 1;
      if (r == myrounds) {
        wg_wait<0>(); keep(acc);
        if (r < nrounds)
        {
          mbar_wait(sb + BAR_WFULL, par);      release_end<0>(sb, ds, release_begin<0>(cnt), lane, false);
          mbar_wait(sb + BAR_WFULL + 8, par);  release_end<1>(sb, ds, release_begin<1>(cnt), lane, false);
          mbar_wait(sb + BAR_WFULL + 16, par); release_end<2>(sb, ds, release_begin<2>(cnt), lane, false);
        }
        break;
      }
      TR(0);
      const bool next_round = r + 1 < nrounds;
      const uint32_t rV = rK & vmask;
      uint32_t rel;
      uint32_t Of[48], Q[12], T[16], inv = 0;
      float S[28];
      const uint64_t* dkv = ds.kv[wg];

#define PRE(H, ACC)                                                                     \
      packn<0, 12>(T, ACC); scalen<0, 12>(T, rK); stsm12(T, kst);                       \
      packn<0, 12>(T, ACC + 24); hold<0, 12>(T);                                        \
      if (H > 0) { PIN(); wg_wait<0>(); keep(S); }                                      \
      _Pragma("unroll") for (int i = 0; i < 12; i++) Q[i] = T[i];                       \
      scalen<0, 12>(Q, rK); hold<0, 12>(Q);
#define PRE2(H)                                                                         \
      if (H > 0) { inv = inv_sum(S); packn<0, 12>(Of + 12 * (H > 0 ? H - 1 : 0), S);    \
                   hold<0, 12>(Of + 12 * (H > 0 ? H - 1 : 0)); hold<0, 1>(&inv); }      \
      PIN();                                                                            \
      proxy_fence();
#define MID(VACC, FIRST2)                                                               \
      PIN();                                                                            \
      packn<0, 12>(T, VACC); hold<0, 12>(T); PIN();                                     \
      FIRST2;                                                                           \
      scalen<0, 12>(T, rV); stsm12(T, vst); proxy_fence();                              \
      PIN();                                                                            \
      wg_wait<1>(); keep(S);

      wg_wait<0>(); keep(acc);
      TR(2);
      rel = release_begin<0>(cnt);
      PRE(0, acc) PRE2(0)
      release_end<0>(sb, ds, rel, lane, next_round);
      mbar_wait(sb + BAR_WFULL + 8, par);
      bar_sync(1 + wg);
      TR(3);
      issue_s(S, Q, dkv);
      MID(acc + 48, (mma144<0, 2>(acc, X, ds.q[1])))
      TR(4);
      softmax_pv<12, false>(S, dkv + 4, Of, inv, wg, [&](auto a, auto b) { mma144<a.v, b.v>(acc, X, ds.q[1]); });
      TR(5);
      wg_wait<1>(); keep(acc);
      TR(6);
      rel = release_begin<1>(cnt);
      PRE(1, acc) PRE2(1)
      release_end<1>(sb, ds, rel, lane, next_round);
      mbar_wait(sb + BAR_WFULL + 16, par);
      bar_sync(1 + wg);
      TR(7);
      issue_s(S, Q, dkv);
      MID(acc + 48, (mma144<0, 2>(acc, X, ds.q[2])))
      TR(8);
      softmax_pv<12, true>(S, dkv + 4, Of, inv, wg, [&](auto a, auto b) { mma144<a.v, b.v>(acc, X, ds.q[2]); });
      TR(9);
      float kq[48], va[24], pa[32], pb[32];
      wg_wait<1>(); keep(acc);
      TR(10);
      rel = release_begin<2>(cnt);
      PRE(2, acc) PRE2(2)
      release_end<2>(sb, ds, rel, lane, next_round);
      mbar_wait(sb + BAR_WFULL + 24, par);
      bar_sync(1 + wg);
      TR(11);
      issue_s(S, Q, dkv);
      MID(acc + 48, (mma96<0, 2>(kq, X, ds.q[3])))
      TR(12);
      softmax_pv<12, true>(S, dkv + 4, Of + 12, inv, wg, [&](auto a, auto b) { mma96<a.v, b.v>(kq, X, ds.q[3]); });
      TR(13);
      wg_wait<1>(); keep(kq);
      TR(14);
      packn<0, 12>(T, kq); hold<0, 12>(T); PIN();
      mma48<0, 4>(va, X, ds.v3);
      scalen<0, 12>(T, rK); stsm12(T, kst); PIN();
      mma48<4, 8>(va, X, ds.v3);
      packn<0, 12>(Q, kq + 24); scalen<0, 12>(Q, rK); hold<0, 12>(Q); PIN();
      mma48<8, 12>(va, X, ds.v3);
      PIN();
      wg_wait<3>(); keep(S);
      PRE2(3)
      mbar_wait(sb + BAR_WFULL + 32, par);
      bar_sync(1 + wg);
      TR(15);
      issue_s(S, Q, dkv);
      wg_wait<1>(); keep(va);
      rel = release_begin<3>(cnt);
      MID(va, (mma64<0, 2>(pa, Of, ds.p)))
      release_end<3>(sb, ds, rel, lane, next_round);
      TR(16);
      softmax_pv<9, true>(S, dkv + 4, Of + 24, inv, wg, [&](auto a, auto b) { mma64<a.v, b.v>(pa, Of, ds.p); });
      TR(17);
#undef PRE
#undef PRE2
#undef MID
      const bool more = r + 1 < myrounds;
      const int w = window_of(r, nfull, cta, ncta, wg);
      const int wy = w / NWX, wx = w - wy * NWX;
      const uint32_t wb = (uint32_t)(wy * 7 * IMG + wx * 7) * 384u;
      uint8_t* o0 = reinterpret_cast<uint8_t*>(out) + (wb + off0);
      uint8_t* o1 = reinterpret_cast<uint8_t*>(out) + (wb + off1);
      mbar_wait(sb + BAR_WFULL + 40, par);
      wg_wait<0>(); keep(S); keep(pa);
      TR(18);
      inv = inv_sum(S); packn<0, 12>(Of + 36, S); hold<36, 48>(Of); PIN();
      mma64<0, 5>(pb, Of, ds.p + 12);
      scalen<36, 48>(Of, inv); hold<36, 48>(Of); PIN();
      mma64<9, 12>(pa, Of, ds.p);
      mma64<5, 12>(pb, Of, ds.p + 12);
      bar_sync(1 + wg);
      if (more) mbar_wait(sb + BAR_TFULL, par ^ 1);
      TR(19);
      wg_wait<1>(); keep(pa);
      TR(20);
      packn<0, 16>(T, pa); hold<0, 16>(T); PIN();
      mma64<0, 4, 2>(pa, Of, ds.p + 24);
      store_out<0>(T, X, o0, o1); load_x<0, 2>(X, tx); PIN();
      mma64<4, 8>(pa, Of, ds.p + 24);
      store_out<1>(T + 8, X, o0, o1); load_x<2, 4>(X, tx); PIN();
      mma64<8, 12>(pa, Of, ds.p + 24);
      PIN();
      TR(21);
      wg_wait<3>(); keep(pb);
      rel = release_begin<4>(cnt);
      packn<0, 16>(T, pb);
      store_out<2>(T, X, o0, o1); store_out<3>(T + 8, X, o0, o1); load_x<4, 8>(X, tx);
      release_end<4>(sb, ds, rel, lane, next_round);
      if (more) mbar_wait(sb + BAR_WFULL, par ^ 1);
      TR(22);
      wg_wait<0>(); keep(pa);
      TR(23);
      rel = release_begin<5>(cnt);
      mma144<0, 1>(acc, X, ds.q[0]);
      packn<0, 8>(T, pa); hold<0, 8>(T); PIN();
      mma144<1, 2>(acc, X, ds.q[0]);
      store_out<4>(T, X, o0, o1); load_x<8, 10>(X, tx); PIN();
      mma144<2, 3>(acc, X, ds.q[0]);
      packn<8, 16>(T, pa); hold<8, 16>(T); PIN();
      mma144<3, 4>(acc, X, ds.q[0]);
      store_out<5>(T + 8, X, o0, o1); load_x<10, 12>(X, tx); PIN();
      mma144<4, 8>(acc, X, ds.q[0]);
      release_end<5>(sb, ds, rel, lane, next_round);
      if (more) mbar_wait(sb + BAR_SFULL, par ^ 1);
      asm volatile("ld.shared.u32 %0, [%1];" : "=r"(rK) : "r"(sb + OFF_RSTD + wg * 100 + ps * 4) : "memory");
      mma144<8, 12>(acc, X, ds.q[0]);
      __syncwarp();
      if (lane == 0) mbar_arrive(sb + BAR_TEMPTY);
      TR(1);
    }
  }
}

typedef CUresult (*EncodeFn)(CUtensorMap*, CUtensorMapDataType, cuuint32_t, void*, const cuuint64_t*, const cuuint64_t*,
                             const cuuint32_t*, const cuuint32_t*, CUtensorMapInterleave, CUtensorMapSwizzle,
                             CUtensorMapL2promotion, CUtensorMapFloatOOBfill);

}

extern "C" void kernel_launch(void* const* d_in, const int* in_sizes, int n_in, void* d_out, int out_size) {
  const __nv_bfloat16* x = (const __nv_bfloat16*)d_in[0];
  const __nv_bfloat16* dw = (const __nv_bfloat16*)d_in[1];
  const __nv_bfloat16* wqkv = (const __nv_bfloat16*)d_in[2];
  const __nv_bfloat16* wo = (const __nv_bfloat16*)d_in[3];
  static EncodeFn encode = nullptr;
  static int nsm = 0;
  static void* wpack = nullptr;
  if (!encode) {
    void* fn = nullptr;
    cudaDriverEntryPointQueryResult qr;
    cudaGetDriverEntryPoint("cuTensorMapEncodeTiled", &fn, cudaEnableDefault, &qr);
    encode = (EncodeFn)fn;
    int dev = 0;
    cudaGetDevice(&dev);
    cudaDeviceGetAttribute(&nsm, cudaDevAttrMultiProcessorCount, dev);
    cudaGetSymbolAddress(&wpack, g_wpack);
    cudaFuncSetAttribute(fused_kernel, cudaFuncAttributeMaxDynamicSharedMemorySize, SMEM_BYTES);
  }
  CUtensorMap tmx;
  cuuint64_t gdim[3] = {CH, IMG, IMG};
  cuuint64_t gstr[2] = {CH * 2, (cuuint64_t)CH * 2 * IMG};
  cuuint32_t box[3] = {64, 9, 1};
  cuuint32_t estr[3] = {1, 1, 1};
  encode(&tmx, CU_TENSOR_MAP_DATA_TYPE_BFLOAT16, 3, (void*)x, gdim, gstr, box, estr, CU_TENSOR_MAP_INTERLEAVE_NONE,
         CU_TENSOR_MAP_SWIZZLE_NONE, CU_TENSOR_MAP_L2_PROMOTION_L2_128B, CU_TENSOR_MAP_FLOAT_OOB_FILL_NONE);
  Descs ds;
  for (int i = 0; i < 12; i++) {
    for (int h = 0; h < 4; h++) ds.q[h][i] = mkdesc(SMEM_BASE + OFF_W + qkv_off(h, i), 128, 256);
    ds.v3[i] = mkdesc(SMEM_BASE + OFF_W + qkv_off(3, i) + 3072, 128, 256);
    for (int c = 0; c < 3; c++) ds.p[c * 12 + i] = mkdesc(SMEM_BASE + OFF_W + wo_off(c, i), 128, 256);
  }
  for (int i = 0; i < 16; i++) ds.src[i] = (const uint8_t*)wpack + i * SLICE;
  for (int g = 0; g < 2; g++)
    for (int i = 0; i < 4; i++) {
      ds.kv[g][i] = mkdesc(SMEM_BASE + OFF_KV + g * KV_BYTES + 1024 + 2 * i * KV_PITCH, KV_PITCH, 128);
      ds.kv[g][4 + i] = mkdesc(SMEM_BASE + OFF_KV + g * KV_BYTES + 256 * i, 128, KV_PITCH);
    }
  prepack_kernel<<<96, 192>>>(wqkv, wo);
  fused_kernel<<<nsm, 384, SMEM_BYTES>>>(tmx, ds, dw, (__nv_bfloat16*)d_out, 0);
}
```

```cpp
#include <cuda_runtime.h>
#include <cuda_bf16.h>
#include <cuda.h>
#include <stdint.h>

#define CREGS "208"
#define PREGS "88"
namespace {

constexpr int IMG = 511;
constexpr int CH = 192;
constexpr int NWX = 73;
constexpr int NWIN = NWX * NWX;
constexpr int SLICE = 18432;
constexpr int OFF_W = 0;
constexpr int KV_BYTES = 12544, KV_PITCH = 1920;
constexpr int OFF_KV = 8 * SLICE;
constexpr int TILE_BYTES = 25 * 768;
constexpr int OFF_TILE = OFF_KV + 2 * KV_BYTES;
constexpr int XSLOT = 2304;
constexpr int OFF_X = OFF_TILE + 2 * TILE_BYTES;
constexpr int OFF_BAR = OFF_X + 9 * XSLOT;
constexpr int BAR_WFULL = OFF_BAR;
constexpr int CNT_WREL = OFF_BAR + 48;
constexpr int BAR_XFULL = OFF_BAR + 72;
constexpr int BAR_TFULL = OFF_BAR + 144;
constexpr int BAR_TEMPTY = OFF_BAR + 152;
constexpr int BAR_TPART = OFF_BAR + 160;
constexpr int BAR_SFULL = OFF_BAR + 176;
constexpr int OFF_RSTD = OFF_BAR + 192;
constexpr int OFF_DUMMY = OFF_RSTD + 200;
constexpr int OFF_TRACE = OFF_DUMMY + 152;
constexpr int SMEM_BYTES = OFF_TRACE;

constexpr int SMEM_BASE = 1024;
struct Descs { uint64_t q[4][12]; uint64_t v3[12]; uint64_t p[36]; uint64_t kv[2][8]; const uint8_t* src[16]; };

__device__ uint4 g_wpack[16 * SLICE / 16];
#define TR(id)
template <int ID> __device__ __forceinline__ void sched_fence(uint32_t v) {
  asm volatile("{\n.reg .pred p;\nsetp.ne.u32 p, %0, %1;\n@p bra.uni SF_%=;\ntrap;\nSF_%=:\n}\n" :: "r"(v), "n"(ID) : "memory");
}
__device__ __forceinline__ void anchor(uint32_t v) { sched_fence<0x7fc1ffc1>(v); }

template <int V> struct IC { static constexpr int v = V; };
typedef __nv_bfloat162 bf2;
__device__ __forceinline__ bf2 u2b(uint32_t u) { return *reinterpret_cast<bf2*>(&u); }
__device__ __forceinline__ uint32_t b2u(bf2 b) { return *reinterpret_cast<uint32_t*>(&b); }
__device__ __forceinline__ uint32_t pack2(float lo, float hi) {
  uint32_t r; asm("cvt.rn.bf16x2.f32 %0, %1, %2;" : "=r"(r) : "f"(hi), "f"(lo)); return r;
}
__device__ __forceinline__ uint32_t hadd(uint32_t a, uint32_t b) { return b2u(__hadd2_rn(u2b(a), u2b(b))); }
__device__ __forceinline__ uint32_t hmul(uint32_t a, uint32_t b) { return b2u(__hmul2_rn(u2b(a), u2b(b))); }
__device__ __forceinline__ uint32_t hfma(uint32_t a, uint32_t b, uint32_t c) { return b2u(__hfma2(u2b(a), u2b(b), u2b(c))); }
__device__ __forceinline__ uint32_t hmax(uint32_t a, uint32_t b) { return b2u(__hmax2(u2b(a), u2b(b))); }
template <int HI> __device__ __forceinline__ bf2 bcast(uint32_t a) { return HI ? __high2bfloat162(u2b(a)) : __low2bfloat162(u2b(a)); }
template <int HI> __device__ __forceinline__ uint32_t hmul_b(uint32_t a, uint32_t s) { return b2u(__hmul2_rn(u2b(a), bcast<HI>(s))); }
template <int HI> __device__ __forceinline__ uint32_t hsub_b(uint32_t a, uint32_t s) { return b2u(__hsub2_rn(u2b(a), bcast<HI>(s))); }
__device__ __forceinline__ uint32_t hex2(uint32_t a) { uint32_t r; asm("ex2.approx.ftz.bf16x2 %0, %1;" : "=r"(r) : "r"(a)); return r; }
__device__ __forceinline__ uint32_t hex1(uint32_t a) {
  uint32_t r; asm("{\n.reg .b16 l, h, e;\nmov.b32 {l, h}, %1;\nex2.approx.ftz.bf16 e, l;\ncvt.u32.u16 %0, e;\n}\n" : "=r"(r) : "r"(a)); return r;
}
__device__ __forceinline__ float lo2f(uint32_t a) { return __uint_as_float(a << 16); }
__device__ __forceinline__ float hi2f(uint32_t a) { return __uint_as_float(a & 0xffff0000u); }

__device__ __forceinline__ void mbar_init(uint32_t bar, uint32_t cnt) { asm volatile("mbarrier.init.shared::cta.b64 [%0], %1;" :: "r"(bar), "r"(cnt) : "memory"); }
__device__ __forceinline__ void mbar_arrive(uint32_t bar) { asm volatile("mbarrier.arrive.shared::cta.b64 _, [%0];" :: "r"(bar) : "memory"); }
__device__ __forceinline__ void mbar_expect(uint32_t bar, uint32_t bytes) { asm volatile("mbarrier.arrive.expect_tx.shared::cta.b64 _, [%0], %1;" :: "r"(bar), "r"(bytes) : "memory"); }
template <int HINT>
__device__ __forceinline__ bool mbar_try(uint32_t bar, uint32_t parity) {
  uint32_t ok;
  if (HINT) asm volatile("{\n.reg .pred p;\nmbarrier.try_wait.parity.shared::cta.b64 p, [%1], %2, %3;\nselp.u32 %0, 1, 0, p;\n}\n" : "=r"(ok) : "r"(bar), "r"(parity), "n"(HINT) : "memory");
  else asm volatile("{\n.reg .pred p;\nmbarrier.try_wait.parity.shared::cta.b64 p, [%1], %2;\nselp.u32 %0, 1, 0, p;\n}\n" : "=r"(ok) : "r"(bar), "r"(parity) : "memory");
  return ok != 0;
}
__device__ __forceinline__ void mbar_wait(uint32_t bar, uint32_t parity) {
  if (__builtin_expect(!mbar_try<0>(bar, parity), 0)) {
    uint32_t n = 0;
    while (!mbar_try<4000>(bar, parity)) { if (++n > (1u << 20)) __trap(); }
  }
}
__device__ __forceinline__ void wg_fence() { asm volatile("wgmma.fence.sync.aligned;" ::: "memory"); }
__device__ __forceinline__ void wg_commit() { asm volatile("wgmma.commit_group.sync.aligned;" ::: "memory"); }
template <int N> __device__ __forceinline__ void wg_wait() { asm volatile("wgmma.wait_group.sync.aligned %0;" :: "n"(N) : "memory"); }
__device__ __forceinline__ void bar_sync(int id) { asm volatile("bar.sync %0, 128;" :: "r"(id) : "memory"); }
__device__ __forceinline__ void stsm4(uint32_t addr, uint32_t a, uint32_t b, uint32_t c, uint32_t d) {
  asm volatile("stmatrix.sync.aligned.m8n8.x4.shared.b16 [%0], {%1,%2,%3,%4};" :: "r"(addr), "r"(a), "r"(b), "r"(c), "r"(d) : "memory");
}
template <int N> __device__ __forceinline__ void keep(float (&d)[N]) {
#pragma unroll
  for (int i = 0; i < N; i++) asm volatile("" : "+f"(d[i]) :: "memory");
}
__host__ __device__ __forceinline__ uint64_t mkdesc(uint32_t addr, uint32_t lbo, uint32_t sbo) {
  return ((uint64_t)(sbo >> 4) << 32) | (uint64_t)(((lbo >> 4) << 16) | ((addr & 0x3FFFF) >> 4));
}

template <int SCALE_D>
__device__ __forceinline__ void wgmma_n144(float (&d)[72], uint32_t a0, uint32_t a1, uint32_t a2, uint32_t a3, uint64_t descB) {
  if (SCALE_D == 0)
  asm volatile("wgmma.mma_async.sync.aligned.m64n144k16.f32.bf16.bf16 "
    "{%0, %1, %2, %3, %4, %5, %6, %7, %8, %9, %10, %11, %12, %13, %14, %15, "
    "%16, %17, %18, %19, %20, %21, %22, %23, %24, %25, %26, %27, %28, %29, %30, %31, "
    "%32, %33, %34, %35, %36, %37, %38, %39, %40, %41, %42, %43, %44, %45, %46, %47, "
    "%48, %49, %50, %51, %52, %53, %54, %55, %56, %57, %58, %59, %60, %61, %62, %63, "
    "%64, %65, %66, %67, %68, %69, %70, %71}, "
    "{%72, %73, %74, %75}, %76, 0, 1, 1, 0;\n"
    : "=f"(d[0]), "=f"(d[1]), "=f"(d[2]), "=f"(d[3]), "=f"(d[4]), "=f"(d[5]), "=f"(d[6]), "=f"(d[7]),
      "=f"(d[8]), "=f"(d[9]), "=f"(d[10]), "=f"(d[11]), "=f"(d[12]), "=f"(d[13]), "=f"(d[14]), "=f"(d[15]),
      "=f"(d[16]), "=f"(d[17]), "=f"(d[18]), "=f"(d[19]), "=f"(d[20]), "=f"(d[21]), "=f"(d[22]), "=f"(d[23]),
      "=f"(d[24]), "=f"(d[25]), "=f"(d[26]), "=f"(d[27]), "=f"(d[28]), "=f"(d[29]), "=f"(d[30]), "=f"(d[31]),
      "=f"(d[32]), "=f"(d[33]), "=f"(d[34]), "=f"(d[35]), "=f"(d[36]), "=f"(d[37]), "=f"(d[38]), "=f"(d[39]),
      "=f"(d[40]), "=f"(d[41]), "=f"(d[42]), "=f"(d[43]), "=f"(d[44]), "=f"(d[45]), "=f"(d[46]), "=f"(d[47]),
      "=f"(d[48]), "=f"(d[49]), "=f"(d[50]), "=f"(d[51]), "=f"(d[52]), "=f"(d[53]), "=f"(d[54]), "=f"(d[55]),
      "=f"(d[56]), "=f"(d[57]), "=f"(d[58]), "=f"(d[59]), "=f"(d[60]), "=f"(d[61]), "=f"(d[62]), "=f"(d[63]),
      "=f"(d[64]), "=f"(d[65]), "=f"(d[66]), "=f"(d[67]), "=f"(d[68]), "=f"(d[69]), "=f"(d[70]), "=f"(d[71])
    : "r"(a0), "r"(a1), "r"(a2), "r"(a3), "l"(descB));
  else
  asm volatile("wgmma.mma_async.sync.aligned.m64n144k16.f32.bf16.bf16 "
    "{%0, %1, %2, %3, %4, %5, %6, %7, %8, %9, %10, %11, %12, %13, %14, %15, "
    "%16, %17, %18, %19, %20, %21, %22, %23, %24, %25, %26, %27, %28, %29, %30, %31, "
    "%32, %33, %34, %35, %36, %37, %38, %39, %40, %41, %42, %43, %44, %45, %46, %47, "
    "%48, %49, %50, %51, %52, %53, %54, %55, %56, %57, %58, %59, %60, %61, %62, %63, "
    "%64, %65, %66, %67, %68, %69, %70, %71}, "
    "{%72, %73, %74, %75}, %76, 1, 1, 1, 0;\n"
    : "+f"(d[0]), "+f"(d[1]), "+f"(d[2]), "+f"(d[3]), "+f"(d[4]), "+f"(d[5]), "+f"(d[6]), "+f"(d[7]),
      "+f"(d[8]), "+f"(d[9]), "+f"(d[10]), "+f"(d[11]), "+f"(d[12]), "+f"(d[13]), "+f"(d[14]), "+f"(d[15]),
      "+f"(d[16]), "+f"(d[17]), "+f"(d[18]), "+f"(d[19]), "+f"(d[20]), "+f"(d[21]), "+f"(d[22]), "+f"(d[23]),
      "+f"(d[24]), "+f"(d[25]), "+f"(d[26]), "+f"(d[27]), "+f"(d[28]), "+f"(d[29]), "+f"(d[30]), "+f"(d[31]),
      "+f"(d[32]), "+f"(d[33]), "+f"(d[34]), "+f"(d[35]), "+f"(d[36]), "+f"(d[37]), "+f"(d[38]), "+f"(d[39]),
      "+f"(d[40]), "+f"(d[41]), "+f"(d[42]), "+f"(d[43]), "+f"(d[44]), "+f"(d[45]), "+f"(d[46]), "+f"(d[47]),
      "+f"(d[48]), "+f"(d[49]), "+f"(d[50]), "+f"(d[51]), "+f"(d[52]), "+f"(d[53]), "+f"(d[54]), "+f"(d[55]),
      "+f"(d[56]), "+f"(d[57]), "+f"(d[58]), "+f"(d[59]), "+f"(d[60]), "+f"(d[61]), "+f"(d[62]), "+f"(d[63]),
      "+f"(d[64]), "+f"(d[65]), "+f"(d[66]), "+f"(d[67]), "+f"(d[68]), "+f"(d[69]), "+f"(d[70]), "+f"(d[71])
    : "r"(a0), "r"(a1), "r"(a2), "r"(a3), "l"(descB));
}

template <int SCALE_D>
__device__ __forceinline__ void wgmma_n96(float (&d)[48], uint32_t a0, uint32_t a1, uint32_t a2, uint32_t a3, uint64_t descB) {
  if (SCALE_D == 0)
  asm volatile("wgmma.mma_async.sync.aligned.m64n96k16.f32.bf16.bf16 "
    "{%0, %1, %2, %3, %4, %5, %6, %7, %8, %9, %10, %11, %12, %13, %14, %15, "
    "%16, %17, %18, %19, %20, %21, %22, %23, %24, %25, %26, %27, %28, %29, %30, %31, "
    "%32, %33, %34, %35, %36, %37, %38, %39, %40, %41, %42, %43, %44, %45, %46, %47}, "
    "{%48, %49, %50, %51}, %52, 0, 1, 1, 0;\n"
    : "=f"(d[0]), "=f"(d[1]), "=f"(d[2]), "=f"(d[3]), "=f"(d[4]), "=f"(d[5]), "=f"(d[6]), "=f"(d[7]),
      "=f"(d[8]), "=f"(d[9]), "=f"(d[10]), "=f"(d[11]), "=f"(d[12]), "=f"(d[13]), "=f"(d[14]), "=f"(d[15]),
      "=f"(d[16]), "=f"(d[17]), "=f"(d[18]), "=f"(d[19]), "=f"(d[20]), "=f"(d[21]), "=f"(d[22]), "=f"(d[23]),
      "=f"(d[24]), "=f"(d[25]), "=f"(d[26]), "=f"(d[27]), "=f"(d[28]), "=f"(d[29]), "=f"(d[30]), "=f"(d[31]),
      "=f"(d[32]), "=f"(d[33]), "=f"(d[34]), "=f"(d[35]), "=f"(d[36]), "=f"(d[37]), "=f"(d[38]), "=f"(d[39]),
      "=f"(d[40]), "=f"(d[41]), "=f"(d[42]), "=f"(d[43]), "=f"(d[44]), "=f"(d[45]), "=f"(d[46]), "=f"(d[47])
    : "r"(a0), "r"(a1), "r"(a2), "r"(a3), "l"(descB));
  else
  asm volatile("wgmma.mma_async.sync.aligned.m64n96k16.f32.bf16.bf16 "
    "{%0, %1, %2, %3, %4, %5, %6, %7, %8, %9, %10, %11, %12, %13, %14, %15, "
    "%16, %17, %18, %19, %20, %21, %22, %23, %24, %25, %26, %27, %28, %29, %30, %31, "
    "%32, %33, %34, %35, %36, %37, %38, %39, %40, %41, %42, %43, %44, %45, %46, %47}, "
    "{%48, %49, %50, %51}, %52, 1, 1, 1, 0;\n"
    : "+f"(d[0]), "+f"(d[1]), "+f"(d[2]), "+f"(d[3]), "+f"(d[4]), "+f"(d[5]), "+f"(d[6]), "+f"(d[7]),
      "+f"(d[8]), "+f"(d[9]), "+f"(d[10]), "+f"(d[11]), "+f"(d[12]), "+f"(d[13]), "+f"(d[14]), "+f"(d[15]),
      "+f"(d[16]), "+f"(d[17]), "+f"(d[18]), "+f"(d[19]), "+f"(d[20]), "+f"(d[21]), "+f"(d[22]), "+f"(d[23]),
      "+f"(d[24]), "+f"(d[25]), "+f"(d[26]), "+f"(d[27]), "+f"(d[28]), "+f"(d[29]), "+f"(d[30]), "+f"(d[31]),
      "+f"(d[32]), "+f"(d[33]), "+f"(d[34]), "+f"(d[35]), "+f"(d[36]), "+f"(d[37]), "+f"(d[38]), "+f"(d[39]),
      "+f"(d[40]), "+f"(d[41]), "+f"(d[42]), "+f"(d[43]), "+f"(d[44]), "+f"(d[45]), "+f"(d[46]), "+f"(d[47])
    : "r"(a0), "r"(a1), "r"(a2), "r"(a3), "l"(descB));
}

template <int SCALE_D>
__device__ __forceinline__ void wgmma_n48(float (&d)[24], uint32_t a0, uint32_t a1, uint32_t a2, uint32_t a3, uint64_t descB) {
  if (SCALE_D == 0)
  asm volatile("wgmma.mma_async.sync.aligned.m64n48k16.f32.bf16.bf16 "
    "{%0, %1, %2, %3, %4, %5, %6, %7, %8, %9, %10, %11, %12, %13, %14, %15, "
    "%16, %17, %18, %19, %20, %21, %22, %23}, "
    "{%24, %25, %26, %27}, %28, 0, 1, 1, 0;\n"
    : "=f"(d[0]), "=f"(d[1]), "=f"(d[2]), "=f"(d[3]), "=f"(d[4]), "=f"(d[5]), "=f"(d[6]), "=f"(d[7]),
      "=f"(d[8]), "=f"(d[9]), "=f"(d[10]), "=f"(d[11]), "=f"(d[12]), "=f"(d[13]), "=f"(d[14]), "=f"(d[15]),
      "=f"(d[16]), "=f"(d[17]), "=f"(d[18]), "=f"(d[19]), "=f"(d[20]), "=f"(d[21]), "=f"(d[22]), "=f"(d[23])
    : "r"(a0), "r"(a1), "r"(a2), "r"(a3), "l"(descB));
  else
  asm volatile("wgmma.mma_async.sync.aligned.m64n48k16.f32.bf16.bf16 "
    "{%0, %1, %2, %3, %4, %5, %6, %7, %8, %9, %10, %11, %12, %13, %14, %15, "
    "%16, %17, %18, %19, %20, %21, %22, %23}, "
    "{%24, %25, %26, %27}, %28, 1, 1, 1, 0;\n"
    : "+f"(d[0]), "+f"(d[1]), "+f"(d[2]), "+f"(d[3]), "+f"(d[4]), "+f"(d[5]), "+f"(d[6]), "+f"(d[7]),
      "+f"(d[8]), "+f"(d[9]), "+f"(d[10]), "+f"(d[11]), "+f"(d[12]), "+f"(d[13]), "+f"(d[14]), "+f"(d[15]),
      "+f"(d[16]), "+f"(d[17]), "+f"(d[18]), "+f"(d[19]), "+f"(d[20]), "+f"(d[21]), "+f"(d[22]), "+f"(d[23])
    : "r"(a0), "r"(a1), "r"(a2), "r"(a3), "l"(descB));
}

template <int SCALE_D>
__device__ __forceinline__ void wgmma_n64(float (&d)[32], uint32_t a0, uint32_t a1, uint32_t a2, uint32_t a3, uint64_t descB) {
  if (SCALE_D == 0)
  asm volatile("wgmma.mma_async.sync.aligned.m64n64k16.f32.bf16.bf16 "
    "{%0, %1, %2, %3, %4, %5, %6, %7, %8, %9, %10, %11, %12, %13, %14, %15, "
    "%16, %17, %18, %19, %20, %21, %22, %23, %24, %25, %26, %27, %28, %29, %30, %31}, "
    "{%32, %33, %34, %35}, %36, 0, 1, 1, 0;\n"
    : "=f"(d[0]), "=f"(d[1]), "=f"(d[2]), "=f"(d[3]), "=f"(d[4]), "=f"(d[5]), "=f"(d[6]), "=f"(d[7]),
      "=f"(d[8]), "=f"(d[9]), "=f"(d[10]), "=f"(d[11]), "=f"(d[12]), "=f"(d[13]), "=f"(d[14]), "=f"(d[15]),
      "=f"(d[16]), "=f"(d[17]), "=f"(d[18]), "=f"(d[19]), "=f"(d[20]), "=f"(d[21]), "=f"(d[22]), "=f"(d[23]),
      "=f"(d[24]), "=f"(d[25]), "=f"(d[26]), "=f"(d[27]), "=f"(d[28]), "=f"(d[29]), "=f"(d[30]), "=f"(d[31])
    : "r"(a0), "r"(a1), "r"(a2), "r"(a3), "l"(descB));
  else if (SCALE_D == 2)
  asm volatile("wgmma.mma_async.sync.aligned.m64n64k16.f32.bf16.bf16 "
    "{%0, %1, %2, %3, %4, %5, %6, %7, %8, %9, %10, %11, %12, %13, %14, %15, "
    "%16, %17, %18, %19, %20, %21, %22, %23, %24, %25, %26, %27, %28, %29, %30, %31}, "
    "{%32, %33, %34, %35}, %36, 0, 1, 1, 0;\n"
    : "+f"(d[0]), "+f"(d[1]), "+f"(d[2]), "+f"(d[3]), "+f"(d[4]), "+f"(d[5]), "+f"(d[6]), "+f"(d[7]),
      "+f"(d[8]), "+f"(d[9]), "+f"(d[10]), "+f"(d[11]), "+f"(d[12]), "+f"(d[13]), "+f"(d[14]), "+f"(d[15]),
      "+f"(d[16]), "+f"(d[17]), "+f"(d[18]), "+f"(d[19]), "+f"(d[20]), "+f"(d[21]), "+f"(d[22]), "+f"(d[23]),
      "+f"(d[24]), "+f"(d[25]), "+f"(d[26]), "+f"(d[27]), "+f"(d[28]), "+f"(d[29]), "+f"(d[30]), "+f"(d[31])
    : "r"(a0), "r"(a1), "r"(a2), "r"(a3), "l"(descB));
  else
  asm volatile("wgmma.mma_async.sync.aligned.m64n64k16.f32.bf16.bf16 "
    "{%0, %1, %2, %3, %4, %5, %6, %7, %8, %9, %10, %11, %12, %13, %14, %15, "
    "%16, %17, %18, %19, %20, %21, %22, %23, %24, %25, %26, %27, %28, %29, %30, %31}, "
    "{%32, %33, %34, %35}, %36, 1, 1, 1, 0;\n"
    : "+f"(d[0]), "+f"(d[1]), "+f"(d[2]), "+f"(d[3]), "+f"(d[4]), "+f"(d[5]), "+f"(d[6]), "+f"(d[7]),
      "+f"(d[8]), "+f"(d[9]), "+f"(d[10]), "+f"(d[11]), "+f"(d[12]), "+f"(d[13]), "+f"(d[14]), "+f"(d[15]),
      "+f"(d[16]), "+f"(d[17]), "+f"(d[18]), "+f"(d[19]), "+f"(d[20]), "+f"(d[21]), "+f"(d[22]), "+f"(d[23]),
      "+f"(d[24]), "+f"(d[25]), "+f"(d[26]), "+f"(d[27]), "+f"(d[28]), "+f"(d[29]), "+f"(d[30]), "+f"(d[31])
    : "r"(a0), "r"(a1), "r"(a2), "r"(a3), "l"(descB));
}

template <int SCALE_D>
__device__ __forceinline__ void wgmma_n56(float (&d)[28], uint32_t a0, uint32_t a1, uint32_t a2, uint32_t a3, uint64_t descB) {
  if (SCALE_D == 0)
  asm volatile("wgmma.mma_async.sync.aligned.m64n56k16.f32.bf16.bf16 "
    "{%0, %1, %2, %3, %4, %5, %6, %7, %8, %9, %10, %11, %12, %13, %14, %15, "
    "%16, %17, %18, %19, %20, %21, %22, %23, %24, %25, %26, %27}, "
    "{%28, %29, %30, %31}, %32, 0, 1, 1, 0;\n"
    : "=f"(d[0]), "=f"(d[1]), "=f"(d[2]), "=f"(d[3]), "=f"(d[4]), "=f"(d[5]), "=f"(d[6]), "=f"(d[7]),
      "=f"(d[8]), "=f"(d[9]), "=f"(d[10]), "=f"(d[11]), "=f"(d[12]), "=f"(d[13]), "=f"(d[14]), "=f"(d[15]),
      "=f"(d[16]), "=f"(d[17]), "=f"(d[18]), "=f"(d[19]), "=f"(d[20]), "=f"(d[21]), "=f"(d[22]), "=f"(d[23]),
      "=f"(d[24]), "=f"(d[25]), "=f"(d[26]), "=f"(d[27])
    : "r"(a0), "r"(a1), "r"(a2), "r"(a3), "l"(descB));
  else
  asm volatile("wgmma.mma_async.sync.aligned.m64n56k16.f32.bf16.bf16 "
    "{%0, %1, %2, %3, %4, %5, %6, %7, %8, %9, %10, %11, %12, %13, %14, %15, "
    "%16, %17, %18, %19, %20, %21, %22, %23, %24, %25, %26, %27}, "
    "{%28, %29, %30, %31}, %32, 1, 1, 1, 0;\n"
    : "+f"(d[0]), "+f"(d[1]), "+f"(d[2]), "+f"(d[3]), "+f"(d[4]), "+f"(d[5]), "+f"(d[6]), "+f"(d[7]),
      "+f"(d[8]), "+f"(d[9]), "+f"(d[10]), "+f"(d[11]), "+f"(d[12]), "+f"(d[13]), "+f"(d[14]), "+f"(d[15]),
      "+f"(d[16]), "+f"(d[17]), "+f"(d[18]), "+f"(d[19]), "+f"(d[20]), "+f"(d[21]), "+f"(d[22]), "+f"(d[23]),
      "+f"(d[24]), "+f"(d[25]), "+f"(d[26]), "+f"(d[27])
    : "r"(a0), "r"(a1), "r"(a2), "r"(a3), "l"(descB));
}

template <int SCALE_D>
__device__ __forceinline__ void wgmma_n56t(float (&d)[28], uint32_t a0, uint32_t a1, uint32_t a2, uint32_t a3, uint64_t descB) {
  if (SCALE_D == 0)
  asm volatile("wgmma.mma_async.sync.aligned.m64n56k16.f32.bf16.bf16 "
    "{%0, %1, %2, %3, %4, %5, %6, %7, %8, %9, %10, %11, %12, %13, %14, %15, "
    "%16, %17, %18, %19, %20, %21, %22, %23, %24, %25, %26, %27}, "
    "{%28, %29, %30, %31}, %32, 0, 1, 1, 1;\n"
    : "=f"(d[0]), "=f"(d[1]), "=f"(d[2]), "=f"(d[3]), "=f"(d[4]), "=f"(d[5]), "=f"(d[6]), "=f"(d[7]),
      "=f"(d[8]), "=f"(d[9]), "=f"(d[10]), "=f"(d[11]), "=f"(d[12]), "=f"(d[13]), "=f"(d[14]), "=f"(d[15]),
      "=f"(d[16]), "=f"(d[17]), "=f"(d[18]), "=f"(d[19]), "=f"(d[20]), "=f"(d[21]), "=f"(d[22]), "=f"(d[23]),
      "=f"(d[24]), "=f"(d[25]), "=f"(d[26]), "=f"(d[27])
    : "r"(a0), "r"(a1), "r"(a2), "r"(a3), "l"(descB));
  else
  asm volatile("wgmma.mma_async.sync.aligned.m64n56k16.f32.bf16.bf16 "
    "{%0, %1, %2, %3, %4, %5, %6, %7, %8, %9, %10, %11, %12, %13, %14, %15, "
    "%16, %17, %18, %19, %20, %21, %22, %23, %24, %25, %26, %27}, "
    "{%28, %29, %30, %31}, %32, 1, 1, 1, 1;\n"
    : "+f"(d[0]), "+f"(d[1]), "+f"(d[2]), "+f"(d[3]), "+f"(d[4]), "+f"(d[5]), "+f"(d[6]), "+f"(d[7]),
      "+f"(d[8]), "+f"(d[9]), "+f"(d[10]), "+f"(d[11]), "+f"(d[12]), "+f"(d[13]), "+f"(d[14]), "+f"(d[15]),
      "+f"(d[16]), "+f"(d[17]), "+f"(d[18]), "+f"(d[19]), "+f"(d[20]), "+f"(d[21]), "+f"(d[22]), "+f"(d[23]),
      "+f"(d[24]), "+f"(d[25]), "+f"(d[26]), "+f"(d[27])
    : "r"(a0), "r"(a1), "r"(a2), "r"(a3), "l"(descB));
}

__global__ void __launch_bounds__(192) prepack_kernel(const __nv_bfloat16* __restrict__ wqkv, const __nv_bfloat16* __restrict__ wo) {
  __nv_bfloat16* dst = reinterpret_cast<__nv_bfloat16*>(g_wpack);
  const int c = threadIdx.x, nb = blockIdx.x;
  if (nb < 72) {
    __shared__ float red[6][8];
    const int h = nb / 18, j = nb % 18, part = j / 6;
    const int col = (part == 0 ? 192 : part == 1 ? 0 : 384) + h * 48 + (j % 6) * 8;
    uint4 raw = *reinterpret_cast<const uint4*>(wqkv + c * 576 + col);
    uint32_t u[4] = {raw.x, raw.y, raw.z, raw.w};
    float v[8];
#pragma unroll
    for (int i = 0; i < 4; i++) { v[2 * i] = lo2f(u[i]); v[2 * i + 1] = hi2f(u[i]); }
#pragma unroll
    for (int i = 0; i < 8; i++) {
      float s = v[i];
#pragma unroll
      for (int o = 16; o; o >>= 1) s += __shfl_xor_sync(~0u, s, o);
      if ((c & 31) == 0) red[c >> 5][i] = s;
    }
    __syncthreads();
    const int cc = c >> 5, q = (c >> 3) & 3, s1 = (c >> 2) & 1, hh = (c >> 1) & 1, e = c & 1;
    const int base = h * 27648 + (2 * cc + s1) * 2304 + j * 128 + hh * 64 + 2 * q + e;
#pragma unroll
    for (int n = 0; n < 8; n++) {
      float m = (red[0][n] + red[1][n] + red[2][n] + red[3][n] + red[4][n] + red[5][n]) * (1.0f / 192.0f);
      dst[base + n * 8] = __float2bfloat16((v[n] - m) * (part == 1 ? 0.14433756729740643f * 1.4426950408889634f : 1.0f));
    }
  } else {
    const int jb = nb - 72, chunk = jb / 8, j = jb % 8;
    const int s = c >> 4, hh = (c >> 3) & 1, kk = c & 7;
    const int base = 110592 + (chunk * 12 + s) * 1024 + j * 128 + hh * 64 + kk;
#pragma unroll
    for (int n = 0; n < 8; n++) {
      const int ch = 32 * (jb >> 2) + 8 * (n >> 1) + 2 * (jb & 3) + (n & 1);
      dst[base + n * 8] = wo[c * 192 + ch];
    }
  }
}

__device__ __forceinline__ int window_of(int round, int nfull, int cta, int ncta, int wg) {
  if (round < nfull) return round * 2 * ncta + 2 * cta + wg;
  const int rem = NWIN - nfull * 2 * ncta;
  const int i = cta + wg * ncta;
  return i < rem ? nfull * 2 * ncta + i : -1;
}

__host__ __device__ constexpr int qkv_off(int h, int s) { return ((3 * h + s / 4) % 8) * SLICE + (s % 4) * 4608; }
__host__ __device__ constexpr int wo_off(int chunk, int s) { return 4 * SLICE + (chunk * 12 + s) * 2048; }

#define DEF_ISSUE(NAME, NREG, FN, FIRST)                                                                          \
  template <int S0, int S1, int INIT = FIRST>                                                                     \
  __device__ __forceinline__ void NAME(float (&acc)[NREG], const uint32_t (&A)[48], const uint64_t* d) {          \
    wg_fence();                                                                                                   \
    _Pragma("unroll") for (int s = S0; s < S1; s++) {                                                             \
      if (s == 0) FN<INIT>(acc, A[4 * s], A[4 * s + 1], A[4 * s + 2], A[4 * s + 3], d[s]);                        \
      else        FN<1>(acc, A[4 * s], A[4 * s + 1], A[4 * s + 2], A[4 * s + 3], d[s]);                           \
    }                                                                                                             \
    wg_commit();                                                                                                  \
  }
DEF_ISSUE(mma144, 72, wgmma_n144, 0)
DEF_ISSUE(mma96, 48, wgmma_n96, 0)
DEF_ISSUE(mma64, 32, wgmma_n64, 0)
DEF_ISSUE(mma48, 24, wgmma_n48, 0)
#undef DEF_ISSUE

#define PIN() asm volatile("pmevent 0;" ::: "memory")
template <int A, int B> __device__ __forceinline__ void hold(uint32_t* v) {
#pragma unroll
  for (int i = A; i < B; i++) asm volatile("" : "+r"(v[i]));
}
template <int A, int B> __device__ __forceinline__ void packn(uint32_t* d, const float* a) {
#pragma unroll
  for (int i = A; i < B; i++) d[i] = pack2(a[2 * i], a[2 * i + 1]);
}
template <int A, int B> __device__ __forceinline__ void scalen(uint32_t* d, uint32_t r) {
#pragma unroll
  for (int i = A; i < B; i++) d[i] = (i & 1) ? hmul_b<1>(d[i], r) : hmul_b<0>(d[i], r);
}
__device__ __forceinline__ void stsm12(const uint32_t* v, uint32_t addr) {
#pragma unroll
  for (int j = 0; j < 3; j++) stsm4(addr + 2 * j * KV_PITCH, v[4 * j], v[4 * j + 1], v[4 * j + 2], v[4 * j + 3]);
}
__device__ __forceinline__ uint32_t inv_sum(const float (&o)[28]) {
  float i0, i1;
  asm("rcp.approx.ftz.f32 %0, %1;" : "=f"(i0) : "f"(o[24]));
  asm("rcp.approx.ftz.f32 %0, %1;" : "=f"(i1) : "f"(o[26]));
  return pack2(i0, i1);
}
__device__ __forceinline__ void proxy_fence() { asm volatile("fence.proxy.async.shared::cta;" ::: "memory"); }
__device__ __forceinline__ void issue_s(float (&S)[28], const uint32_t (&Q)[12], const uint64_t* d) {
  wg_fence();
  wgmma_n56<0>(S, Q[0], Q[1], Q[2], Q[3], d[0]);
  wgmma_n56<1>(S, Q[4], Q[5], Q[6], Q[7], d[1]);
  wgmma_n56<1>(S, Q[8], Q[9], Q[10], Q[11], d[2]);
  wg_commit();
}
struct H2 { uint16_t l, h; };
__device__ __forceinline__ H2 exp_halves(uint32_t a) {
  H2 r;
  asm("{\n.reg .b16 l, h;\nmov.b32 {l, h}, %2;\nex2.approx.ftz.bf16 %0, l;\nex2.approx.ftz.bf16 %1, h;\n}\n" : "=h"(r.l), "=h"(r.h) : "r"(a));
  return r;
}
__device__ __forceinline__ uint32_t join(H2 v) { uint32_t r; asm("mov.b32 %0, {%1, %2};" : "=r"(r) : "h"(v.l), "h"(v.h)); return r; }
__device__ __forceinline__ void hold(H2& v) { asm volatile("" : "+h"(v.l), "+h"(v.h)); }

template <int NK, bool PREV, class G>
__device__ __forceinline__ void softmax_pv(float (&S)[28], const uint64_t* dV, uint32_t* Op, uint32_t inv, int wg, G g) {
#define GK(k) if ((k) < NK) g(IC<((k) < NK ? (k) : 0)>{}, IC<((k) < NK ? (k) + 1 : 0)>{});
  uint32_t P[16];
  GK(2) packn<0, 4>(P, S);  if (PREV) { scalen<0, 4>(Op, inv); hold<0, 4>(Op); }   hold<0, 4>(P); PIN();
  GK(3) packn<4, 9>(P, S);  if (PREV) { scalen<4, 8>(Op, inv); hold<4, 8>(Op); }   hold<4, 9>(P); PIN();
  GK(4) packn<9, 14>(P, S); if (PREV) { scalen<8, 12>(Op, inv); hold<8, 12>(Op); } hold<9, 14>(P); PIN();
  GK(5)
  uint32_t m0 = hmax(hmax(hmax(hmax(P[0], P[2]), P[4]), hmax(hmax(P[6], P[8]), P[10])), P[12]);
  uint32_t m1 = hmax(hmax(hmax(hmax(P[1], P[3]), P[5]), hmax(hmax(P[7], P[9]), P[11])), P[13]);
  uint32_t mx = hmax(__byte_perm(m0, m1, 0x5410), __byte_perm(m0, m1, 0x7632));
  uint32_t sh = __shfl_xor_sync(~0u, mx, 1);
  PIN();
  GK(6)
  PIN();
  mx = hmax(mx, sh);
  sh = __shfl_xor_sync(~0u, mx, 2);
  PIN();
  GK(7)
  bar_sync(1 + wg);
  PIN();
  mx = hmax(mx, sh);
#pragma unroll
  for (int j = 0; j < 14; j++) P[j] = (j & 1) ? hsub_b<1>(P[j], mx) : hsub_b<0>(P[j], mx);
  H2 e0 = exp_halves(P[0]), e1 = exp_halves(P[1]);
  GK(8)
  hold<2, 14>(P); hold(e0); hold(e1); PIN();
  GK(9)
  H2 e2 = exp_halves(P[2]), e3 = exp_halves(P[3]);
  P[0] = join(e0); P[1] = join(e1);
  hold<0, 2>(P); hold(e2); hold(e3); PIN();
  GK(10)
  e0 = exp_halves(P[4]); e1 = exp_halves(P[5]);
  P[2] = join(e2); P[3] = join(e3);
  hold<2, 4>(P); hold(e0); hold(e1); PIN();
  GK(11)
  P[12] = hex1(P[12]); P[13] = hex1(P[13]); P[14] = 0; P[15] = 0;
  P[4] = join(e0); P[5] = join(e1);
#pragma unroll
  for (int j = 6; j < 12; j++) P[j] = hex2(P[j]);
  wg_fence();
  wgmma_n56t<0>(S, P[0], P[1], P[2], P[3], dV[0]);
  wgmma_n56t<1>(S, P[4], P[5], P[6], P[7], dV[1]);
  wgmma_n56t<1>(S, P[12], P[13], P[14], P[15], dV[3]);
  wgmma_n56t<1>(S, P[8], P[9], P[10], P[11], dV[2]);
  wg_commit();
#undef GK
}
template <int S0, int S1>
__device__ __forceinline__ void load_x(uint32_t (&X)[48], uint32_t t0) {
#pragma unroll
  for (int s = S0; s < S1; s++)
    asm volatile("ld.shared.v4.u32 {%0,%1,%2,%3}, [%4];" : "=r"(X[4 * s]), "=r"(X[4 * s + 1]), "=r"(X[4 * s + 2]), "=r"(X[4 * s + 3])
                 : "r"(((s & 1) ? (t0 ^ 16) : t0) + (s >> 1) * 128) : "memory");
}

template <int CC>
__device__ __forceinline__ void store_out(const uint32_t* T, const uint32_t (&X)[48], uint8_t* o0, uint8_t* o1) {
  asm volatile("st.global.v4.u32 [%0], {%1,%2,%3,%4};" :: "l"(o0 + CC * 64), "r"(hadd(X[8 * CC], T[0])), "r"(hadd(X[8 * CC + 2], T[2])),
               "r"(hadd(X[8 * CC + 4], T[4])), "r"(hadd(X[8 * CC + 6], T[6])) : "memory");
  asm volatile("st.global.v4.u32 [%0], {%1,%2,%3,%4};" :: "l"(o1 + CC * 64), "r"(hadd(X[8 * CC + 1], T[1])), "r"(hadd(X[8 * CC + 3], T[3])),
               "r"(hadd(X[8 * CC + 5], T[5])), "r"(hadd(X[8 * CC + 7], T[7])) : "memory");
}

template <int K, int CNT> __device__ __forceinline__ void load_slices(uint32_t sb, const Descs& ds) {
  constexpr int st = K < 12 ? K / 3 : 4 + (K - 12) / 2;
  constexpr bool first = K < 12 ? (K % 3 == 0) : (K % 2 == 0);
  if (first)
    asm volatile("{\n.reg .pred p;\nelect.sync _|p, 0xffffffff;\n@p mbarrier.arrive.expect_tx.shared::cta.b64 _, [%0], %1;\n}\n"
                 :: "r"(sb + BAR_WFULL + 8 * st), "n"((K < 12 ? 3 : 2) * SLICE) : "memory");
  asm volatile("{\n.reg .pred p;\nelect.sync _|p, 0xffffffff;\n"
               "@p cp.async.bulk.shared::cluster.global.mbarrier::complete_tx::bytes [%0], [%1], %2, [%3];\n}\n"
               :: "r"(sb + OFF_W + (K & 7) * SLICE), "l"(ds.src[K]), "n"(CNT * SLICE), "r"(sb + BAR_WFULL + 8 * st) : "memory");
}
template <int STAGE> __device__ __forceinline__ uint32_t release_begin(uint32_t cnt) {
  uint32_t old;
  asm volatile("atom.shared.inc.u32 %0, [%1 + %2], 7;" : "=r"(old) : "r"(cnt), "n"(4 * STAGE) : "memory");
  return old;
}
template <int STAGE> __device__ __forceinline__ void release_end(uint32_t sb, const Descs& ds, uint32_t old, int lane, bool next_round) {
  if (__any_sync(0xffffffffu, old == 7 && lane == 0)) {
    if (STAGE == 0) { load_slices<8, 1>(sb, ds); load_slices<9, 2>(sb, ds); }
    if (STAGE == 1) { load_slices<11, 1>(sb, ds); load_slices<12, 2>(sb, ds); }
    if (STAGE == 2) { load_slices<14, 2>(sb, ds); if (next_round) load_slices<0, 1>(sb, ds); }
    if (STAGE == 3 && next_round) { load_slices<1, 2>(sb, ds); load_slices<3, 1>(sb, ds); }
    if (STAGE == 4 && next_round) load_slices<4, 2>(sb, ds);
    if (STAGE == 5 && next_round) load_slices<6, 2>(sb, ds);
  }
}

__device__ __forceinline__ uint32_t ln_rstd(const uint32_t (&X)[48]) {
  uint32_t sm[2];
#pragma unroll
  for (int a = 0; a < 2; a++) {
    uint32_t t[12];
#pragma unroll
    for (int i = 0; i < 12; i++) t[i] = hadd(X[4 * i + a], X[4 * i + 2 + a]);
#pragma unroll
    for (int i = 0; i < 6; i++) t[i] = hadd(t[i], t[i + 6]);
#pragma unroll
    for (int i = 0; i < 3; i++) t[i] = hadd(t[i], t[i + 3]);
    sm[a] = hadd(hadd(t[0], t[1]), t[2]);
  }
  uint32_t m = hadd(__byte_perm(sm[0], sm[1], 0x5410), __byte_perm(sm[0], sm[1], 0x7632));
  m = hadd(m, __shfl_xor_sync(~0u, m, 1));
  m = hadd(m, __shfl_xor_sync(~0u, m, 2));
  m = hmul(m, 0x3bab3babu);
  float var[2];
#pragma unroll
  for (int a = 0; a < 2; a++) {
    uint32_t t[4];
#pragma unroll
    for (int i = 0; i < 24; i++) {
      const uint32_t d = a ? hsub_b<1>(X[2 * i + 1], m) : hsub_b<0>(X[2 * i], m);
      t[i & 3] = i < 4 ? hmul(d, d) : hfma(d, d, t[i & 3]);
    }
    const uint32_t s = hadd(hadd(t[0], t[1]), hadd(t[2], t[3]));
    float v = lo2f(s) + hi2f(s);
    v += __shfl_xor_sync(~0u, v, 1);
    v += __shfl_xor_sync(~0u, v, 2);
    asm("rsqrt.approx.ftz.f32 %0, %1;" : "=f"(var[a]) : "f"(fmaf(v, 1.0f / 192.0f, 1e-5f)));
  }
  return pack2(var[0], var[1]);
}

__device__ __forceinline__ void stats_pass(uint32_t sb, int pass, int lane) {
  const int g = lane >> 2, q = lane & 3;
  const int tile = pass < 6 ? (pass & 1) : (g & 1);
  const int ps = pass < 6 ? (pass >> 1) * 8 + g : 24;
  uint32_t X[48];
  load_x<0, 12>(X, sb + OFF_TILE + tile * TILE_BYTES + ps * 768 + q * 32 + (ps & 1) * 16);
  const uint32_t rs = ln_rstd(X);
  asm volatile("st.shared.u32 [%0], %1;" :: "r"(sb + OFF_RSTD + tile * 100 + ps * 4), "r"(rs) : "memory");
}

__global__ void __launch_bounds__(384, 1)
fused_kernel(const __grid_constant__ CUtensorMap tmx, const __grid_constant__ Descs ds, const __nv_bfloat16* __restrict__ dw, __nv_bfloat16* __restrict__ out, const int never) {
  extern __shared__ __align__(1024) uint8_t smem[];
  const uint32_t sb = (uint32_t)__cvta_generic_to_shared(smem);
  const int tid = threadIdx.x, lane = tid & 31;
  const int warp = __shfl_sync(0xffffffffu, tid >> 5, 0);
  const int cta = blockIdx.x, ncta = gridDim.x;
  const int nfull = NWIN / (2 * ncta);
  const int nrounds = nfull + ((NWIN - nfull * 2 * ncta) > cta ? 1 : 0);

  if (tid == 0) {
    if ((sb & 0x3FFFF) != SMEM_BASE) __trap();
    for (int i = 0; i < 6; i++) { mbar_init(sb + BAR_WFULL + 8 * i, 1); *reinterpret_cast<uint32_t*>(smem + CNT_WREL + 4 * i) = 0; }
    for (int i = 0; i < 9; i++) mbar_init(sb + BAR_XFULL + 8 * i, 1);
    mbar_init(sb + BAR_TFULL, 3);
    mbar_init(sb + BAR_TEMPTY, 8);
    mbar_init(sb + BAR_TPART, 3);
    mbar_init(sb + BAR_TPART + 8, 3);
    mbar_init(sb + BAR_SFULL, 4);
    asm volatile("fence.mbarrier_init.release.cluster;" ::: "memory");
  }
  if (tid < 128) {
    const uint32_t v = (tid & 63) < 49 ? 0x3f803f80u : 0u;
    *reinterpret_cast<uint4*>(smem + OFF_KV + (tid >> 6) * KV_BYTES + 6 * KV_PITCH + (tid & 63) * 16) = make_uint4(v, v, v, v);
    asm volatile("fence.proxy.async.shared::cta;" ::: "memory");
  }
  __syncthreads();

  if (warp >= 8) {
    asm volatile("setmaxnreg.dec.sync.aligned.u32 " PREGS ";");
    if (warp == 11) {
      load_slices<0, 3>(sb, ds); load_slices<3, 3>(sb, ds); load_slices<6, 2>(sb, ds);
      for (int r = 0; r < nrounds; r++) {
#pragma unroll 1
        for (int pass = 0; pass < 4; pass++) {
          if (!(pass & 1)) mbar_wait(sb + BAR_TPART + 4 * pass, r & 1);
          stats_pass(sb, pass, lane);
        }
        __syncwarp();
        if (lane == 0) mbar_arrive(sb + BAR_SFULL);
        TR(2);
      }
    } else {
      const int cw = warp - 8;
      const int win = lane >> 4;
      const int ch0 = cw * 64 + (lane & 15) * 4;
      uint32_t wt[9][2];
#pragma unroll
      for (int t = 0; t < 9; t++) {
        uint2 v = *reinterpret_cast<const uint2*>(dw + t * CH + ch0);
        wt[t][0] = v.x; wt[t][1] = v.y;
      }
      const uint32_t xs = sb + OFF_X + cw * 3 * XSLOT;
      const uint32_t xld = xs + (lane >> 4) * 1152 + (lane & 15) * 8;
      const uint32_t xbar = sb + BAR_XFULL + cw * 24;
      const uint32_t st0 = sb + OFF_TILE + win * TILE_BYTES + ch0 * 4;
      const uint32_t st1 = sb + OFF_TILE + win * TILE_BYTES + ((ch0 * 4) ^ 16);
      const uint64_t tm = reinterpret_cast<uint64_t>(&tmx);
      int cx0, cy0, cx1, cy1;
      auto coords = [&](int r) {
        const int w0 = window_of(r, nfull, cta, ncta, 0);
        int w1 = window_of(r, nfull, cta, ncta, 1);
        if (w1 < 0) w1 = w0;
        const int a = w0 / NWX, b = w1 / NWX;
        cx0 = (w0 - a * NWX) * 7 - 1; cy0 = a * 7 - 1;
        cx1 = (w1 - b * NWX) * 7 - 1; cy1 = b * 7 - 1;
      };
      auto issue = [&](int slot, int dy) {
        asm volatile("{\n.reg .pred p;\nelect.sync _|p, 0xffffffff;\n"
                     "@p mbarrier.arrive.expect_tx.shared::cta.b64 _, [%2], %8;\n"
                     "@p cp.async.bulk.tensor.3d.shared::cluster.global.mbarrier::complete_tx::bytes [%0], [%1, {%3, %4, %5}], [%2];\n"
                     "@p cp.async.bulk.tensor.3d.shared::cluster.global.mbarrier::complete_tx::bytes [%0 + 1152], [%1, {%3, %6, %7}], [%2];\n}\n"
                     :: "r"(xs + slot * XSLOT), "l"(tm), "r"(xbar + slot * 8), "r"(cw * 64), "r"(cx0), "r"(cy0 + dy), "r"(cx1), "r"(cy1 + dy), "n"(XSLOT) : "memory");
      };
      coords(0);
      issue(0, 0); issue(1, 1); issue(2, 2);
      for (int r = 0; r < nrounds; r++) {
        const bool more = r + 1 < nrounds;
        uint32_t accA[7][2], accB[7][2], ctr[7][2], held[2];
#pragma unroll
        for (int i = 0; i < 9; i++) {
          mbar_wait(xbar + (i % 3) * 8, (r + i / 3) & 1);
          if (i == 5 || i == 7) { __syncwarp(); if (lane == 0) mbar_arrive(sb + BAR_TPART + (i == 5 ? 0 : 8)); }
          if (i == 7 && more) coords(r + 1);
          if (i == 0) { if (r > 0) issue(2, 2); }
          else if (i < 7) issue((i + 2) % 3, i + 2);
          else if (more) issue((i + 2) % 3, i - 7);
          if (i == 2 && r > 0) mbar_wait(sb + BAR_TEMPTY, (r - 1) & 1);
          if (i == 2) { TR(0); }
          uint32_t cur[9][2];
#pragma unroll
          for (int p = 0; p < 5; p++)
            asm volatile("ld.shared.v2.u32 {%0,%1}, [%2];" : "=r"(cur[p][0]), "=r"(cur[p][1]) : "r"(xld + (i % 3) * XSLOT + p * 128));
#pragma unroll
          for (int j = 0; j < 7; j++) {
            if (j >= 1 && j + 4 < 9)
              asm volatile("ld.shared.v2.u32 {%0,%1}, [%2];" : "=r"(cur[j + 4][0]), "=r"(cur[j + 4][1]) : "r"(xld + (i % 3) * XSLOT + (j + 4) * 128));
            if (i >= 2) {
              uint32_t o[2];
#pragma unroll
              for (int e = 0; e < 2; e++) {
                uint32_t a = hfma(cur[j][e], wt[6][e], accA[j][e]);
                a = hfma(cur[j + 1][e], wt[7][e], a);
                a = hfma(cur[j + 2][e], wt[8][e], a);
                o[e] = hadd(ctr[j][e], a);
              }
              const int tok = (i - 2) * 7 + j, ps = tok >> 1;
              if (!(tok & 1)) { held[0] = o[0]; held[1] = o[1]; }
              if ((tok & 1) || tok == 48)
                asm volatile("st.shared.v4.u32 [%0], {%1,%2,%3,%4};" :: "r"(((ps & 1) ? st1 : st0) + ps * 768), "r"(held[0]), "r"(o[0]), "r"(held[1]), "r"(o[1]) : "memory");
            }
#pragma unroll
            for (int e = 0; e < 2; e++) {
              if (i >= 1 && i <= 7) {
                uint32_t a = hfma(cur[j][e], wt[3][e], accB[j][e]);
                a = hfma(cur[j + 1][e], wt[4][e], a);
                accA[j][e] = hfma(cur[j + 2][e], wt[5][e], a);
                ctr[j][e] = cur[j + 1][e];
              }
              if (i <= 6) {
                uint32_t a = hmul(cur[j][e], wt[0][e]);
                a = hfma(cur[j + 1][e], wt[1][e], a);
                accB[j][e] = hfma(cur[j + 2][e], wt[2][e], a);
              }
            }
          }
        }
        __syncwarp();
        if (lane == 0) mbar_arrive(sb + BAR_TFULL);
        TR(1);
        mbar_wait(sb + BAR_TFULL, r & 1);
        stats_pass(sb, 4 + cw, lane);
        __syncwarp();
        if (lane == 0) mbar_arrive(sb + BAR_SFULL);
      }
    }
  } else {
    asm volatile("setmaxnreg.inc.sync.aligned.u32 " CREGS ";");
    const int wg = warp >> 2, w4 = warp & 3, g = lane >> 2, q = lane & 3;
    const int row0 = w4 * 16 + g, row1 = row0 + 8;
    const int ps = min(w4 * 8 + g, 24);
    const int tok0 = 2 * ps, tok1 = min(2 * ps + 1, 48);
    const uint32_t kv = sb + OFF_KV + wg * KV_BYTES;
    const int srow = w4 * 16 + (lane & 15);
    const uint32_t vst = kv + (lane >> 4) * KV_PITCH + srow * 16;
    const uint32_t kst = vst + (srow < 56 ? 1024 : 0);
    const uint32_t off0 = ((tok0 / 7) * IMG + tok0 % 7) * 384 + q * 16, off1 = ((tok1 / 7) * IMG + tok1 % 7) * 384 + q * 16;
    const uint32_t cnt = lane == 0 ? sb + CNT_WREL : sb + OFF_DUMMY + lane * 4;
    const uint32_t vmask = (row0 < 49 ? 0xffffu : 0u) | (row1 < 49 ? 0xffff0000u : 0u);

    const uint32_t tx = sb + OFF_TILE + wg * TILE_BYTES + ps * 768 + q * 32 + (ps & 1) * 16;
    const int myrounds = window_of(nrounds - 1, nfull, cta, ncta, wg) < 0 ? nrounds - 1 : nrounds;

    if (never == 2) return;
    uint32_t X[48];
    float acc[72];
    mbar_wait(sb + BAR_TFULL, 0);
    load_x<0, 12>(X, tx);
    mbar_wait(sb + BAR_WFULL, 0);
    mma144<0, 12>(acc, X, ds.q[0]);
    uint32_t rK;
    mbar_wait(sb + BAR_SFULL, 0);
    asm volatile("ld.shared.u32 %0, [%1];" : "=r"(rK) : "r"(sb + OFF_RSTD + wg * 100 + ps * 4) : "memory");
    __syncwarp();
    if (lane == 0) mbar_arrive(sb + BAR_TEMPTY);

    for (int r = 0;; r++) {
      const uint32_t par = r & 1;
      if (r == myrounds) {
        wg_wait<0>(); keep(acc);
        if (r < nrounds)
        {
          mbar_wait(sb + BAR_WFULL, par);      release_end<0>(sb, ds, release_begin<0>(cnt), lane, false);
          mbar_wait(sb + BAR_WFULL + 8, par);  release_end<1>(sb, ds, release_begin<1>(cnt), lane, false);
          mbar_wait(sb + BAR_WFULL + 16, par); release_end<2>(sb, ds, release_begin<2>(cnt), lane, false);
        }
        break;
      }
      TR(0);
      const bool next_round = r + 1 < nrounds;
      const uint32_t rV = rK & vmask;
      uint32_t rel;
      uint32_t Of[48], Q[12], T[16], inv = 0;
      float S[28];
      const uint64_t* dkv = ds.kv[wg];

#define PRE(H, ACC)                                                                     \
      packn<0, 12>(T, ACC); scalen<0, 12>(T, rK); stsm12(T, kst);                       \
      packn<0, 12>(T, ACC + 24); hold<0, 12>(T);                                        \
      if (H > 0) { PIN(); wg_wait<0>(); keep(S); }                                      \
      _Pragma("unroll") for (int i = 0; i < 12; i++) Q[i] = T[i];                       \
      scalen<0, 12>(Q, rK); hold<0, 12>(Q);
#define PRE2(H)                                                                         \
      if (H > 0) { inv = inv_sum(S); packn<0, 12>(Of + 12 * (H > 0 ? H - 1 : 0), S);    \
                   hold<0, 12>(Of + 12 * (H > 0 ? H - 1 : 0)); hold<0, 1>(&inv); }      \
      PIN();                                                                            \
      proxy_fence();
#define MID(VACC, FIRST2)                                                               \
      PIN();                                                                            \
      packn<0, 12>(T, VACC); hold<0, 12>(T); PIN();                                     \
      FIRST2;                                                                           \
      scalen<0, 12>(T, rV); stsm12(T, vst); proxy_fence();                              \
      PIN();                                                                            \
      wg_wait<1>(); keep(S);

      wg_wait<0>(); keep(acc);
      TR(2);
      rel = release_begin<0>(cnt);
      PRE(0, acc) PRE2(0)
      release_end<0>(sb, ds, rel, lane, next_round);
      mbar_wait(sb + BAR_WFULL + 8, par);
      bar_sync(1 + wg);
      TR(3);
      issue_s(S, Q, dkv);
      MID(acc + 48, (mma144<0, 2>(acc, X, ds.q[1])))
      TR(4);
      softmax_pv<12, false>(S, dkv + 4, Of, inv, wg, [&](auto a, auto b) { mma144<a.v, b.v>(acc, X, ds.q[1]); });
      TR(5);
      wg_wait<1>(); keep(acc);
      TR(6);
      rel = release_begin<1>(cnt);
      PRE(1, acc) PRE2(1)
      release_end<1>(sb, ds, rel, lane, next_round);
      mbar_wait(sb + BAR_WFULL + 16, par);
      bar_sync(1 + wg);
      TR(7);
      issue_s(S, Q, dkv);
      MID(acc + 48, (mma144<0, 2>(acc, X, ds.q[2])))
      TR(8);
      softmax_pv<12, true>(S, dkv + 4, Of, inv, wg, [&](auto a, auto b) { mma144<a.v, b.v>(acc, X, ds.q[2]); });
      TR(9);
      float kq[48], va[24], pa[32], pb[32];
      wg_wait<1>(); keep(acc);
      TR(10);
      rel = release_begin<2>(cnt);
      PRE(2, acc) PRE2(2)
      release_end<2>(sb, ds, rel, lane, next_round);
      mbar_wait(sb + BAR_WFULL + 24, par);
      bar_sync(1 + wg);
      TR(11);
      issue_s(S, Q, dkv);
      MID(acc + 48, (mma96<0, 2>(kq, X, ds.q[3])))
      TR(12);
      softmax_pv<12, true>(S, dkv + 4, Of + 12, inv, wg, [&](auto a, auto b) { mma96<a.v, b.v>(kq, X, ds.q[3]); });
      TR(13);
      wg_wait<1>(); keep(kq);
      TR(14);
      packn<0, 12>(T, kq); scalen<0, 12>(T, rK); stsm12(T, kst); PIN();
      wg_wait<0>(); keep(S);
      mma48<0, 4>(va, X, ds.v3);
      packn<0, 6>(Q, kq + 24); scalen<0, 6>(Q, rK); hold<0, 6>(Q); PIN();
      mma48<4, 8>(va, X, ds.v3);
      packn<6, 12>(Q, kq + 24); scalen<6, 12>(Q, rK); hold<6, 12>(Q); PIN();
      mma48<8, 12>(va, X, ds.v3);
      PRE2(3)
      mbar_wait(sb + BAR_WFULL + 32, par);
      bar_sync(1 + wg);
      TR(15);
      issue_s(S, Q, dkv);
      wg_wait<1>(); keep(va);
      rel = release_begin<3>(cnt);
      MID(va, (mma64<0, 2>(pa, Of, ds.p)))
      release_end<3>(sb, ds, rel, lane, next_round);
      TR(16);
      softmax_pv<9, true>(S, dkv + 4, Of + 24, inv, wg, [&](auto a, auto b) { mma64<a.v, b.v>(pa, Of, ds.p); });
      TR(17);
#undef PRE
#undef PRE2
#undef MID
      const bool more = r + 1 < myrounds;
      const int w = window_of(r, nfull, cta, ncta, wg);
      const int wy = w / NWX, wx = w - wy * NWX;
      const uint32_t wb = (uint32_t)(wy * 7 * IMG + wx * 7) * 384u;
      uint8_t* o0 = reinterpret_cast<uint8_t*>(out) + (wb + off0);
      uint8_t* o1 = reinterpret_cast<uint8_t*>(out) + (wb + off1);
      mbar_wait(sb + BAR_WFULL + 40, par);
      wg_wait<0>(); keep(S); keep(pa);
      TR(18);
      inv = inv_sum(S); packn<0, 12>(Of + 36, S); hold<36, 48>(Of); PIN();
      mma64<0, 5>(pb, Of, ds.p + 12);
      scalen<36, 48>(Of, inv); hold<36, 48>(Of); PIN();
      mma64<9, 12>(pa, Of, ds.p);
      mma64<5, 12>(pb, Of, ds.p + 12);
      bar_sync(1 + wg);
      if (more) mbar_wait(sb + BAR_TFULL, par ^ 1);
      TR(19);
      wg_wait<1>(); keep(pa);
      TR(20);
      packn<0, 16>(T, pa); hold<0, 16>(T); PIN();
      mma64<0, 4, 2>(pa, Of, ds.p + 24);
      store_out<0>(T, X, o0, o1); load_x<0, 2>(X, tx); PIN();
      mma64<4, 8>(pa, Of, ds.p + 24);
      store_out<1>(T + 8, X, o0, o1); load_x<2, 4>(X, tx); PIN();
      mma64<8, 12>(pa, Of, ds.p + 24);
      PIN();
      TR(21);
      wg_wait<3>(); keep(pb);
      rel = release_begin<4>(cnt);
      packn<0, 16>(T, pb);
      store_out<2>(T, X, o0, o1); store_out<3>(T + 8, X, o0, o1); load_x<4, 8>(X, tx);
      release_end<4>(sb, ds, rel, lane, next_round);
      if (more) mbar_wait(sb + BAR_WFULL, par ^ 1);
      TR(22);
      wg_wait<0>(); keep(pa);
      TR(23);
      rel = release_begin<5>(cnt);
      mma144<0, 1>(acc, X, ds.q[0]);
      packn<0, 8>(T, pa); hold<0, 8>(T); PIN();
      mma144<1, 2>(acc, X, ds.q[0]);
      store_out<4>(T, X, o0, o1); load_x<8, 10>(X, tx); PIN();
      mma144<2, 3>(acc, X, ds.q[0]);
      packn<8, 16>(T, pa); hold<8, 16>(T); PIN();
      mma144<3, 4>(acc, X, ds.q[0]);
      store_out<5>(T + 8, X, o0, o1); load_x<10, 12>(X, tx); PIN();
      mma144<4, 8>(acc, X, ds.q[0]);
      release_end<5>(sb, ds, rel, lane, next_round);
      if (more) mbar_wait(sb + BAR_SFULL, par ^ 1);
      asm volatile("ld.shared.u32 %0, [%1];" : "=r"(rK) : "r"(sb + OFF_RSTD + wg * 100 + ps * 4) : "memory");
      mma144<8, 12>(acc, X, ds.q[0]);
      __syncwarp();
      if (lane == 0) mbar_arrive(sb + BAR_TEMPTY);
      TR(1);
    }
  }
}

typedef CUresult (*EncodeFn)(CUtensorMap*, CUtensorMapDataType, cuuint32_t, void*, const cuuint64_t*, const cuuint64_t*,
                             const cuuint32_t*, const cuuint32_t*, CUtensorMapInterleave, CUtensorMapSwizzle,
                             CUtensorMapL2promotion, CUtensorMapFloatOOBfill);

}

extern "C" void kernel_launch(void* const* d_in, const int* in_sizes, int n_in, void* d_out, int out_size) {
  const __nv_bfloat16* x = (const __nv_bfloat16*)d_in[0];
  const __nv_bfloat16* dw = (const __nv_bfloat16*)d_in[1];
  const __nv_bfloat16* wqkv = (const __nv_bfloat16*)d_in[2];
  const __nv_bfloat16* wo = (const __nv_bfloat16*)d_in[3];
  static EncodeFn encode = nullptr;
  static int nsm = 0;
  static void* wpack = nullptr;
  if (!encode) {
    void* fn = nullptr;
    cudaDriverEntryPointQueryResult qr;
    cudaGetDriverEntryPoint("cuTensorMapEncodeTiled", &fn, cudaEnableDefault, &qr);
    encode = (EncodeFn)fn;
    int dev = 0;
    cudaGetDevice(&dev);
    cudaDeviceGetAttribute(&nsm, cudaDevAttrMultiProcessorCount, dev);
    cudaGetSymbolAddress(&wpack, g_wpack);
    cudaFuncSetAttribute(fused_kernel, cudaFuncAttributeMaxDynamicSharedMemorySize, SMEM_BYTES);
  }
  CUtensorMap tmx;
  cuuint64_t gdim[3] = {CH, IMG, IMG};
  cuuint64_t gstr[2] = {CH * 2, (cuuint64_t)CH * 2 * IMG};
  cuuint32_t box[3] = {64, 9, 1};
  cuuint32_t estr[3] = {1, 1, 1};
  encode(&tmx, CU_TENSOR_MAP_DATA_TYPE_BFLOAT16, 3, (void*)x, gdim, gstr, box, estr, CU_TENSOR_MAP_INTERLEAVE_NONE,
         CU_TENSOR_MAP_SWIZZLE_NONE, CU_TENSOR_MAP_L2_PROMOTION_L2_128B, CU_TENSOR_MAP_FLOAT_OOB_FILL_NONE);
  Descs ds;
  for (int i = 0; i < 12; i++) {
    for (int h = 0; h < 4; h++) ds.q[h][i] = mkdesc(SMEM_BASE + OFF_W + qkv_off(h, i), 128, 256);
    ds.v3[i] = mkdesc(SMEM_BASE + OFF_W + qkv_off(3, i) + 3072, 128, 256);
    for (int c = 0; c < 3; c++) ds.p[c * 12 + i] = mkdesc(SMEM_BASE + OFF_W + wo_off(c, i), 128, 256);
  }
  for (int i = 0; i < 16; i++) ds.src[i] = (const uint8_t*)wpack + i * SLICE;
  for (int g = 0; g < 2; g++)
    for (int i = 0; i < 4; i++) {
      ds.kv[g][i] = mkdesc(SMEM_BASE + OFF_KV + g * KV_BYTES + 1024 + 2 * i * KV_PITCH, KV_PITCH, 128);
      ds.kv[g][4 + i] = mkdesc(SMEM_BASE + OFF_KV + g * KV_BYTES + 256 * i, 128, KV_PITCH);
    }
  prepack_kernel<<<96, 192>>>(wqkv, wo);
  fused_kernel<<<nsm, 384, SMEM_BYTES>>>(tmx, ds, dw, (__nv_bfloat16*)d_out, 0);
}
```

```cpp
#include <cuda_runtime.h>
#include <cuda_bf16.h>
#include <cuda.h>
#include <stdint.h>

#define CREGS "208"
#define PREGS "88"
namespace {

constexpr int IMG = 511;
constexpr int CH = 192;
constexpr int NWX = 73;
constexpr int NWIN = NWX * NWX;
constexpr int SLICE = 18432;
constexpr int OFF_W = 0;
constexpr int KV_PITCH = 1792, KV_KOFF = 896, KV_BYTES = 6 * KV_PITCH + 1024;
constexpr int OFF_KV = 8 * SLICE;
constexpr int TILE_BYTES = 25 * 768;
constexpr int OFF_TILE = OFF_KV + 2 * KV_BYTES;
constexpr int XSLOT = 2304;
constexpr int OFF_X = OFF_TILE + 2 * TILE_BYTES;
constexpr int OFF_BAR = OFF_X + 9 * XSLOT;
constexpr int BAR_WFULL = OFF_BAR;
constexpr int BAR_XFULL = OFF_BAR + 72;
constexpr int BAR_TFULL = OFF_BAR + 144;
constexpr int BAR_TEMPTY = OFF_BAR + 152;
constexpr int BAR_TPART = OFF_BAR + 160;
constexpr int BAR_SFULL = OFF_BAR + 176;
constexpr int OFF_RSTD = OFF_BAR + 192;
constexpr int CNT_WREL = OFF_RSTD + 208;
constexpr int OFF_TRACE = CNT_WREL + 768;
constexpr int SMEM_BYTES = OFF_TRACE;

constexpr int SMEM_BASE = 1024;
struct Descs { uint64_t q[4][12]; uint64_t v3[12]; uint64_t p[36]; uint64_t kv[2][8]; const uint8_t* src[16]; };

__device__ uint4 g_wpack[16 * SLICE / 16];
#define TR(id)
template <int ID> __device__ __forceinline__ void sched_fence(uint32_t v) {
  asm volatile("{\n.reg .pred p;\nsetp.ne.u32 p, %0, %1;\n@p bra.uni SF_%=;\ntrap;\nSF_%=:\n}\n" :: "r"(v), "n"(ID) : "memory");
}
__device__ __forceinline__ void anchor(uint32_t v) { sched_fence<0x7fc1ffc1>(v); }

template <int V> struct IC { static constexpr int v = V; };
typedef __nv_bfloat162 bf2;
__device__ __forceinline__ bf2 u2b(uint32_t u) { return *reinterpret_cast<bf2*>(&u); }
__device__ __forceinline__ uint32_t b2u(bf2 b) { return *reinterpret_cast<uint32_t*>(&b); }
__device__ __forceinline__ uint32_t pack2(float lo, float hi) {
  uint32_t r; asm("cvt.rn.bf16x2.f32 %0, %1, %2;" : "=r"(r) : "f"(hi), "f"(lo)); return r;
}
__device__ __forceinline__ uint32_t hadd(uint32_t a, uint32_t b) { return b2u(__hadd2_rn(u2b(a), u2b(b))); }
__device__ __forceinline__ uint32_t hmul(uint32_t a, uint32_t b) { return b2u(__hmul2_rn(u2b(a), u2b(b))); }
__device__ __forceinline__ uint32_t hfma(uint32_t a, uint32_t b, uint32_t c) { return b2u(__hfma2(u2b(a), u2b(b), u2b(c))); }
__device__ __forceinline__ uint32_t hmax(uint32_t a, uint32_t b) { return b2u(__hmax2(u2b(a), u2b(b))); }
template <int HI> __device__ __forceinline__ bf2 bcast(uint32_t a) { return HI ? __high2bfloat162(u2b(a)) : __low2bfloat162(u2b(a)); }
template <int HI> __device__ __forceinline__ uint32_t hmul_b(uint32_t a, uint32_t s) { return b2u(__hmul2_rn(u2b(a), bcast<HI>(s))); }
template <int HI> __device__ __forceinline__ uint32_t hsub_b(uint32_t a, uint32_t s) { return b2u(__hsub2_rn(u2b(a), bcast<HI>(s))); }
__device__ __forceinline__ uint32_t hex2(uint32_t a) { uint32_t r; asm("ex2.approx.ftz.bf16x2 %0, %1;" : "=r"(r) : "r"(a)); return r; }
__device__ __forceinline__ uint32_t hex1(uint32_t a) {
  uint32_t r; asm("{\n.reg .b16 l, h, e;\nmov.b32 {l, h}, %1;\nex2.approx.ftz.bf16 e, l;\ncvt.u32.u16 %0, e;\n}\n" : "=r"(r) : "r"(a)); return r;
}
__device__ __forceinline__ float lo2f(uint32_t a) { return __uint_as_float(a << 16); }
__device__ __forceinline__ float hi2f(uint32_t a) { return __uint_as_float(a & 0xffff0000u); }

__device__ __forceinline__ void mbar_init(uint32_t bar, uint32_t cnt) { asm volatile("mbarrier.init.shared::cta.b64 [%0], %1;" :: "r"(bar), "r"(cnt) : "memory"); }
__device__ __forceinline__ void mbar_arrive(uint32_t bar) { asm volatile("mbarrier.arrive.shared::cta.b64 _, [%0];" :: "r"(bar) : "memory"); }
__device__ __forceinline__ void mbar_expect(uint32_t bar, uint32_t bytes) { asm volatile("mbarrier.arrive.expect_tx.shared::cta.b64 _, [%0], %1;" :: "r"(bar), "r"(bytes) : "memory"); }
template <int HINT>
__device__ __forceinline__ bool mbar_try(uint32_t bar, uint32_t parity) {
  uint32_t ok;
  if (HINT) asm volatile("{\n.reg .pred p;\nmbarrier.try_wait.parity.shared::cta.b64 p, [%1], %2, %3;\nselp.u32 %0, 1, 0, p;\n}\n" : "=r"(ok) : "r"(bar), "r"(parity), "n"(HINT) : "memory");
  else asm volatile("{\n.reg .pred p;\nmbarrier.try_wait.parity.shared::cta.b64 p, [%1], %2;\nselp.u32 %0, 1, 0, p;\n}\n" : "=r"(ok) : "r"(bar), "r"(parity) : "memory");
  return ok != 0;
}
__device__ __forceinline__ void mbar_wait(uint32_t bar, uint32_t parity) {
  if (__builtin_expect(!mbar_try<0>(bar, parity), 0)) {
    uint32_t n = 0;
    while (!mbar_try<4000>(bar, parity)) { if (++n > (1u << 20)) __trap(); }
  }
}
__device__ __forceinline__ void wg_fence() { asm volatile("wgmma.fence.sync.aligned;" ::: "memory"); }
__device__ __forceinline__ void wg_commit() { asm volatile("wgmma.commit_group.sync.aligned;" ::: "memory"); }
template <int N> __device__ __forceinline__ void wg_wait() { asm volatile("wgmma.wait_group.sync.aligned %0;" :: "n"(N) : "memory"); }
__device__ __forceinline__ void bar_sync(int id) { asm volatile("bar.sync %0, 128;" :: "r"(id) : "memory"); }
__device__ __forceinline__ void stsm4(uint32_t addr, uint32_t a, uint32_t b, uint32_t c, uint32_t d) {
  asm volatile("stmatrix.sync.aligned.m8n8.x4.shared.b16 [%0], {%1,%2,%3,%4};" :: "r"(addr), "r"(a), "r"(b), "r"(c), "r"(d) : "memory");
}
template <int N> __device__ __forceinline__ void keep(float (&d)[N]) {
#pragma unroll
  for (int i = 0; i < N; i++) asm volatile("" : "+f"(d[i]) :: "memory");
}
__host__ __device__ __forceinline__ uint64_t mkdesc(uint32_t addr, uint32_t lbo, uint32_t sbo) {
  return ((uint64_t)(sbo >> 4) << 32) | (uint64_t)(((lbo >> 4) << 16) | ((addr & 0x3FFFF) >> 4));
}

template <int SCALE_D>
__device__ __forceinline__ void wgmma_n144(float (&d)[72], uint32_t a0, uint32_t a1, uint32_t a2, uint32_t a3, uint64_t descB) {
  if (SCALE_D == 0)
  asm volatile("wgmma.mma_async.sync.aligned.m64n144k16.f32.bf16.bf16 "
    "{%0, %1, %2, %3, %4, %5, %6, %7, %8, %9, %10, %11, %12, %13, %14, %15, "
    "%16, %17, %18, %19, %20, %21, %22, %23, %24, %25, %26, %27, %28, %29, %30, %31, "
    "%32, %33, %34, %35, %36, %37, %38, %39, %40, %41, %42, %43, %44, %45, %46, %47, "
    "%48, %49, %50, %51, %52, %53, %54, %55, %56, %57, %58, %59, %60, %61, %62, %63, "
    "%64, %65, %66, %67, %68, %69, %70, %71}, "
    "{%72, %73, %74, %75}, %76, 0, 1, 1, 0;\n"
    : "=f"(d[0]), "=f"(d[1]), "=f"(d[2]), "=f"(d[3]), "=f"(d[4]), "=f"(d[5]), "=f"(d[6]), "=f"(d[7]),
      "=f"(d[8]), "=f"(d[9]), "=f"(d[10]), "=f"(d[11]), "=f"(d[12]), "=f"(d[13]), "=f"(d[14]), "=f"(d[15]),
      "=f"(d[16]), "=f"(d[17]), "=f"(d[18]), "=f"(d[19]), "=f"(d[20]), "=f"(d[21]), "=f"(d[22]), "=f"(d[23]),
      "=f"(d[24]), "=f"(d[25]), "=f"(d[26]), "=f"(d[27]), "=f"(d[28]), "=f"(d[29]), "=f"(d[30]), "=f"(d[31]),
      "=f"(d[32]), "=f"(d[33]), "=f"(d[34]), "=f"(d[35]), "=f"(d[36]), "=f"(d[37]), "=f"(d[38]), "=f"(d[39]),
      "=f"(d[40]), "=f"(d[41]), "=f"(d[42]), "=f"(d[43]), "=f"(d[44]), "=f"(d[45]), "=f"(d[46]), "=f"(d[47]),
      "=f"(d[48]), "=f"(d[49]), "=f"(d[50]), "=f"(d[51]), "=f"(d[52]), "=f"(d[53]), "=f"(d[54]), "=f"(d[55]),
      "=f"(d[56]), "=f"(d[57]), "=f"(d[58]), "=f"(d[59]), "=f"(d[60]), "=f"(d[61]), "=f"(d[62]), "=f"(d[63]),
      "=f"(d[64]), "=f"(d[65]), "=f"(d[66]), "=f"(d[67]), "=f"(d[68]), "=f"(d[69]), "=f"(d[70]), "=f"(d[71])
    : "r"(a0), "r"(a1), "r"(a2), "r"(a3), "l"(descB));
  else
  asm volatile("wgmma.mma_async.sync.aligned.m64n144k16.f32.bf16.bf16 "
    "{%0, %1, %2, %3, %4, %5, %6, %7, %8, %9, %10, %11, %12, %13, %14, %15, "
    "%16, %17, %18, %19, %20, %21, %22, %23, %24, %25, %26, %27, %28, %29, %30, %31, "
    "%32, %33, %34, %35, %36, %37, %38, %39, %40, %41, %42, %43, %44, %45, %46, %47, "
    "%48, %49, %50, %51, %52, %53, %54, %55, %56, %57, %58, %59, %60, %61, %62, %63, "
    "%64, %65, %66, %67, %68, %69, %70, %71}, "
    "{%72, %73, %74, %75}, %76, 1, 1, 1, 0;\n"
    : "+f"(d[0]), "+f"(d[1]), "+f"(d[2]), "+f"(d[3]), "+f"(d[4]), "+f"(d[5]), "+f"(d[6]), "+f"(d[7]),
      "+f"(d[8]), "+f"(d[9]), "+f"(d[10]), "+f"(d[11]), "+f"(d[12]), "+f"(d[13]), "+f"(d[14]), "+f"(d[15]),
      "+f"(d[16]), "+f"(d[17]), "+f"(d[18]), "+f"(d[19]), "+f"(d[20]), "+f"(d[21]), "+f"(d[22]), "+f"(d[23]),
      "+f"(d[24]), "+f"(d[25]), "+f"(d[26]), "+f"(d[27]), "+f"(d[28]), "+f"(d[29]), "+f"(d[30]), "+f"(d[31]),
      "+f"(d[32]), "+f"(d[33]), "+f"(d[34]), "+f"(d[35]), "+f"(d[36]), "+f"(d[37]), "+f"(d[38]), "+f"(d[39]),
      "+f"(d[40]), "+f"(d[41]), "+f"(d[42]), "+f"(d[43]), "+f"(d[44]), "+f"(d[45]), "+f"(d[46]), "+f"(d[47]),
      "+f"(d[48]), "+f"(d[49]), "+f"(d[50]), "+f"(d[51]), "+f"(d[52]), "+f"(d[53]), "+f"(d[54]), "+f"(d[55]),
      "+f"(d[56]), "+f"(d[57]), "+f"(d[58]), "+f"(d[59]), "+f"(d[60]), "+f"(d[61]), "+f"(d[62]), "+f"(d[63]),
      "+f"(d[64]), "+f"(d[65]), "+f"(d[66]), "+f"(d[67]), "+f"(d[68]), "+f"(d[69]), "+f"(d[70]), "+f"(d[71])
    : "r"(a0), "r"(a1), "r"(a2), "r"(a3), "l"(descB));
}

template <int SCALE_D>
__device__ __forceinline__ void wgmma_n96(float (&d)[48], uint32_t a0, uint32_t a1, uint32_t a2, uint32_t a3, uint64_t descB) {
  if (SCALE_D == 0)
  asm volatile("wgmma.mma_async.sync.aligned.m64n96k16.f32.bf16.bf16 "
    "{%0, %1, %2, %3, %4, %5, %6, %7, %8, %9, %10, %11, %12, %13, %14, %15, "
    "%16, %17, %18, %19, %20, %21, %22, %23, %24, %25, %26, %27, %28, %29, %30, %31, "
    "%32, %33, %34, %35, %36, %37, %38, %39, %40, %41, %42, %43, %44, %45, %46, %47}, "
    "{%48, %49, %50, %51}, %52, 0, 1, 1, 0;\n"
    : "=f"(d[0]), "=f"(d[1]), "=f"(d[2]), "=f"(d[3]), "=f"(d[4]), "=f"(d[5]), "=f"(d[6]), "=f"(d[7]),
      "=f"(d[8]), "=f"(d[9]), "=f"(d[10]), "=f"(d[11]), "=f"(d[12]), "=f"(d[13]), "=f"(d[14]), "=f"(d[15]),
      "=f"(d[16]), "=f"(d[17]), "=f"(d[18]), "=f"(d[19]), "=f"(d[20]), "=f"(d[21]), "=f"(d[22]), "=f"(d[23]),
      "=f"(d[24]), "=f"(d[25]), "=f"(d[26]), "=f"(d[27]), "=f"(d[28]), "=f"(d[29]), "=f"(d[30]), "=f"(d[31]),
      "=f"(d[32]), "=f"(d[33]), "=f"(d[34]), "=f"(d[35]), "=f"(d[36]), "=f"(d[37]), "=f"(d[38]), "=f"(d[39]),
      "=f"(d[40]), "=f"(d[41]), "=f"(d[42]), "=f"(d[43]), "=f"(d[44]), "=f"(d[45]), "=f"(d[46]), "=f"(d[47])
    : "r"(a0), "r"(a1), "r"(a2), "r"(a3), "l"(descB));
  else
  asm volatile("wgmma.mma_async.sync.aligned.m64n96k16.f32.bf16.bf16 "
    "{%0, %1, %2, %3, %4, %5, %6, %7, %8, %9, %10, %11, %12, %13, %14, %15, "
    "%16, %17, %18, %19, %20, %21, %22, %23, %24, %25, %26, %27, %28, %29, %30, %31, "
    "%32, %33, %34, %35, %36, %37, %38, %39, %40, %41, %42, %43, %44, %45, %46, %47}, "
    "{%48, %49, %50, %51}, %52, 1, 1, 1, 0;\n"
    : "+f"(d[0]), "+f"(d[1]), "+f"(d[2]), "+f"(d[3]), "+f"(d[4]), "+f"(d[5]), "+f"(d[6]), "+f"(d[7]),
      "+f"(d[8]), "+f"(d[9]), "+f"(d[10]), "+f"(d[11]), "+f"(d[12]), "+f"(d[13]), "+f"(d[14]), "+f"(d[15]),
      "+f"(d[16]), "+f"(d[17]), "+f"(d[18]), "+f"(d[19]), "+f"(d[20]), "+f"(d[21]), "+f"(d[22]), "+f"(d[23]),
      "+f"(d[24]), "+f"(d[25]), "+f"(d[26]), "+f"(d[27]), "+f"(d[28]), "+f"(d[29]), "+f"(d[30]), "+f"(d[31]),
      "+f"(d[32]), "+f"(d[33]), "+f"(d[34]), "+f"(d[35]), "+f"(d[36]), "+f"(d[37]), "+f"(d[38]), "+f"(d[39]),
      "+f"(d[40]), "+f"(d[41]), "+f"(d[42]), "+f"(d[43]), "+f"(d[44]), "+f"(d[45]), "+f"(d[46]), "+f"(d[47])
    : "r"(a0), "r"(a1), "r"(a2), "r"(a3), "l"(descB));
}

template <int SCALE_D>
__device__ __forceinline__ void wgmma_n48(float (&d)[24], uint32_t a0, uint32_t a1, uint32_t a2, uint32_t a3, uint64_t descB) {
  if (SCALE_D == 0)
  asm volatile("wgmma.mma_async.sync.aligned.m64n48k16.f32.bf16.bf16 "
    "{%0, %1, %2, %3, %4, %5, %6, %7, %8, %9, %10, %11, %12, %13, %14, %15, "
    "%16, %17, %18, %19, %20, %21, %22, %23}, "
    "{%24, %25, %26, %27}, %28, 0, 1, 1, 0;\n"
    : "=f"(d[0]), "=f"(d[1]), "=f"(d[2]), "=f"(d[3]), "=f"(d[4]), "=f"(d[5]), "=f"(d[6]), "=f"(d[7]),
      "=f"(d[8]), "=f"(d[9]), "=f"(d[10]), "=f"(d[11]), "=f"(d[12]), "=f"(d[13]), "=f"(d[14]), "=f"(d[15]),
      "=f"(d[16]), "=f"(d[17]), "=f"(d[18]), "=f"(d[19]), "=f"(d[20]), "=f"(d[21]), "=f"(d[22]), "=f"(d[23])
    : "r"(a0), "r"(a1), "r"(a2), "r"(a3), "l"(descB));
  else
  asm volatile("wgmma.mma_async.sync.aligned.m64n48k16.f32.bf16.bf16 "
    "{%0, %1, %2, %3, %4, %5, %6, %7, %8, %9, %10, %11, %12, %13, %14, %15, "
    "%16, %17, %18, %19, %20, %21, %22, %23}, "
    "{%24, %25, %26, %27}, %28, 1, 1, 1, 0;\n"
    : "+f"(d[0]), "+f"(d[1]), "+f"(d[2]), "+f"(d[3]), "+f"(d[4]), "+f"(d[5]), "+f"(d[6]), "+f"(d[7]),
      "+f"(d[8]), "+f"(d[9]), "+f"(d[10]), "+f"(d[11]), "+f"(d[12]), "+f"(d[13]), "+f"(d[14]), "+f"(d[15]),
      "+f"(d[16]), "+f"(d[17]), "+f"(d[18]), "+f"(d[19]), "+f"(d[20]), "+f"(d[21]), "+f"(d[22]), "+f"(d[23])
    : "r"(a0), "r"(a1), "r"(a2), "r"(a3), "l"(descB));
}

template <int SCALE_D>
__device__ __forceinline__ void wgmma_n64(float (&d)[32], uint32_t a0, uint32_t a1, uint32_t a2, uint32_t a3, uint64_t descB) {
  if (SCALE_D == 0)
  asm volatile("wgmma.mma_async.sync.aligned.m64n64k16.f32.bf16.bf16 "
    "{%0, %1, %2, %3, %4, %5, %6, %7, %8, %9, %10, %11, %12, %13, %14, %15, "
    "%16, %17, %18, %19, %20, %21, %22, %23, %24, %25, %26, %27, %28, %29, %30, %31}, "
    "{%32, %33, %34, %35}, %36, 0, 1, 1, 0;\n"
    : "=f"(d[0]), "=f"(d[1]), "=f"(d[2]), "=f"(d[3]), "=f"(d[4]), "=f"(d[5]), "=f"(d[6]), "=f"(d[7]),
      "=f"(d[8]), "=f"(d[9]), "=f"(d[10]), "=f"(d[11]), "=f"(d[12]), "=f"(d[13]), "=f"(d[14]), "=f"(d[15]),
      "=f"(d[16]), "=f"(d[17]), "=f"(d[18]), "=f"(d[19]), "=f"(d[20]), "=f"(d[21]), "=f"(d[22]), "=f"(d[23]),
      "=f"(d[24]), "=f"(d[25]), "=f"(d[26]), "=f"(d[27]), "=f"(d[28]), "=f"(d[29]), "=f"(d[30]), "=f"(d[31])
    : "r"(a0), "r"(a1), "r"(a2), "r"(a3), "l"(descB));
  else if (SCALE_D == 2)
  asm volatile("wgmma.mma_async.sync.aligned.m64n64k16.f32.bf16.bf16 "
    "{%0, %1, %2, %3, %4, %5, %6, %7, %8, %9, %10, %11, %12, %13, %14, %15, "
    "%16, %17, %18, %19, %20, %21, %22, %23, %24, %25, %26, %27, %28, %29, %30, %31}, "
    "{%32, %33, %34, %35}, %36, 0, 1, 1, 0;\n"
    : "+f"(d[0]), "+f"(d[1]), "+f"(d[2]), "+f"(d[3]), "+f"(d[4]), "+f"(d[5]), "+f"(d[6]), "+f"(d[7]),
      "+f"(d[8]), "+f"(d[9]), "+f"(d[10]), "+f"(d[11]), "+f"(d[12]), "+f"(d[13]), "+f"(d[14]), "+f"(d[15]),
      "+f"(d[16]), "+f"(d[17]), "+f"(d[18]), "+f"(d[19]), "+f"(d[20]), "+f"(d[21]), "+f"(d[22]), "+f"(d[23]),
      "+f"(d[24]), "+f"(d[25]), "+f"(d[26]), "+f"(d[27]), "+f"(d[28]), "+f"(d[29]), "+f"(d[30]), "+f"(d[31])
    : "r"(a0), "r"(a1), "r"(a2), "r"(a3), "l"(descB));
  else
  asm volatile("wgmma.mma_async.sync.aligned.m64n64k16.f32.bf16.bf16 "
    "{%0, %1, %2, %3, %4, %5, %6, %7, %8, %9, %10, %11, %12, %13, %14, %15, "
    "%16, %17, %18, %19, %20, %21, %22, %23, %24, %25, %26, %27, %28, %29, %30, %31}, "
    "{%32, %33, %34, %35}, %36, 1, 1, 1, 0;\n"
    : "+f"(d[0]), "+f"(d[1]), "+f"(d[2]), "+f"(d[3]), "+f"(d[4]), "+f"(d[5]), "+f"(d[6]), "+f"(d[7]),
      "+f"(d[8]), "+f"(d[9]), "+f"(d[10]), "+f"(d[11]), "+f"(d[12]), "+f"(d[13]), "+f"(d[14]), "+f"(d[15]),
      "+f"(d[16]), "+f"(d[17]), "+f"(d[18]), "+f"(d[19]), "+f"(d[20]), "+f"(d[21]), "+f"(d[22]), "+f"(d[23]),
      "+f"(d[24]), "+f"(d[25]), "+f"(d[26]), "+f"(d[27]), "+f"(d[28]), "+f"(d[29]), "+f"(d[30]), "+f"(d[31])
    : "r"(a0), "r"(a1), "r"(a2), "r"(a3), "l"(descB));
}

template <int SCALE_D>
__device__ __forceinline__ void wgmma_n56(float (&d)[28], uint32_t a0, uint32_t a1, uint32_t a2, uint32_t a3, uint64_t descB) {
  if (SCALE_D == 0)
  asm volatile("wgmma.mma_async.sync.aligned.m64n56k16.f32.bf16.bf16 "
    "{%0, %1, %2, %3, %4, %5, %6, %7, %8, %9, %10, %11, %12, %13, %14, %15, "
    "%16, %17, %18, %19, %20, %21, %22, %23, %24, %25, %26, %27}, "
    "{%28, %29, %30, %31}, %32, 0, 1, 1, 0;\n"
    : "=f"(d[0]), "=f"(d[1]), "=f"(d[2]), "=f"(d[3]), "=f"(d[4]), "=f"(d[5]), "=f"(d[6]), "=f"(d[7]),
      "=f"(d[8]), "=f"(d[9]), "=f"(d[10]), "=f"(d[11]), "=f"(d[12]), "=f"(d[13]), "=f"(d[14]), "=f"(d[15]),
      "=f"(d[16]), "=f"(d[17]), "=f"(d[18]), "=f"(d[19]), "=f"(d[20]), "=f"(d[21]), "=f"(d[22]), "=f"(d[23]),
      "=f"(d[24]), "=f"(d[25]), "=f"(d[26]), "=f"(d[27])
    : "r"(a0), "r"(a1), "r"(a2), "r"(a3), "l"(descB));
  else
  asm volatile("wgmma.mma_async.sync.aligned.m64n56k16.f32.bf16.bf16 "
    "{%0, %1, %2, %3, %4, %5, %6, %7, %8, %9, %10, %11, %12, %13, %14, %15, "
    "%16, %17, %18, %19, %20, %21, %22, %23, %24, %25, %26, %27}, "
    "{%28, %29, %30, %31}, %32, 1, 1, 1, 0;\n"
    : "+f"(d[0]), "+f"(d[1]), "+f"(d[2]), "+f"(d[3]), "+f"(d[4]), "+f"(d[5]), "+f"(d[6]), "+f"(d[7]),
      "+f"(d[8]), "+f"(d[9]), "+f"(d[10]), "+f"(d[11]), "+f"(d[12]), "+f"(d[13]), "+f"(d[14]), "+f"(d[15]),
      "+f"(d[16]), "+f"(d[17]), "+f"(d[18]), "+f"(d[19]), "+f"(d[20]), "+f"(d[21]), "+f"(d[22]), "+f"(d[23]),
      "+f"(d[24]), "+f"(d[25]), "+f"(d[26]), "+f"(d[27])
    : "r"(a0), "r"(a1), "r"(a2), "r"(a3), "l"(descB));
}

template <int SCALE_D>
__device__ __forceinline__ void wgmma_n56t(float (&d)[28], uint32_t a0, uint32_t a1, uint32_t a2, uint32_t a3, uint64_t descB) {
  if (SCALE_D == 0)
  asm volatile("wgmma.mma_async.sync.aligned.m64n56k16.f32.bf16.bf16 "
    "{%0, %1, %2, %3, %4, %5, %6, %7, %8, %9, %10, %11, %12, %13, %14, %15, "
    "%16, %17, %18, %19, %20, %21, %22, %23, %24, %25, %26, %27}, "
    "{%28, %29, %30, %31}, %32, 0, 1, 1, 1;\n"
    : "=f"(d[0]), "=f"(d[1]), "=f"(d[2]), "=f"(d[3]), "=f"(d[4]), "=f"(d[5]), "=f"(d[6]), "=f"(d[7]),
      "=f"(d[8]), "=f"(d[9]), "=f"(d[10]), "=f"(d[11]), "=f"(d[12]), "=f"(d[13]), "=f"(d[14]), "=f"(d[15]),
      "=f"(d[16]), "=f"(d[17]), "=f"(d[18]), "=f"(d[19]), "=f"(d[20]), "=f"(d[21]), "=f"(d[22]), "=f"(d[23]),
      "=f"(d[24]), "=f"(d[25]), "=f"(d[26]), "=f"(d[27])
    : "r"(a0), "r"(a1), "r"(a2), "r"(a3), "l"(descB));
  else
  asm volatile("wgmma.mma_async.sync.aligned.m64n56k16.f32.bf16.bf16 "
    "{%0, %1, %2, %3, %4, %5, %6, %7, %8, %9, %10, %11, %12, %13, %14, %15, "
    "%16, %17, %18, %19, %20, %21, %22, %23, %24, %25, %26, %27}, "
    "{%28, %29, %30, %31}, %32, 1, 1, 1, 1;\n"
    : "+f"(d[0]), "+f"(d[1]), "+f"(d[2]), "+f"(d[3]), "+f"(d[4]), "+f"(d[5]), "+f"(d[6]), "+f"(d[7]),
      "+f"(d[8]), "+f"(d[9]), "+f"(d[10]), "+f"(d[11]), "+f"(d[12]), "+f"(d[13]), "+f"(d[14]), "+f"(d[15]),
      "+f"(d[16]), "+f"(d[17]), "+f"(d[18]), "+f"(d[19]), "+f"(d[20]), "+f"(d[21]), "+f"(d[22]), "+f"(d[23]),
      "+f"(d[24]), "+f"(d[25]), "+f"(d[26]), "+f"(d[27])
    : "r"(a0), "r"(a1), "r"(a2), "r"(a3), "l"(descB));
}

__global__ void __launch_bounds__(192) prepack_kernel(const __nv_bfloat16* __restrict__ wqkv, const __nv_bfloat16* __restrict__ wo) {
  __nv_bfloat16* dst = reinterpret_cast<__nv_bfloat16*>(g_wpack);
  const int c = threadIdx.x, nb = blockIdx.x;
  if (nb < 72) {
    __shared__ float red[6][8];
    const int h = nb / 18, j = nb % 18, part = j / 6;
    const int col = (part == 0 ? 192 : part == 1 ? 0 : 384) + h * 48 + (j % 6) * 8;
    uint4 raw = *reinterpret_cast<const uint4*>(wqkv + c * 576 + col);
    uint32_t u[4] = {raw.x, raw.y, raw.z, raw.w};
    float v[8];
#pragma unroll
    for (int i = 0; i < 4; i++) { v[2 * i] = lo2f(u[i]); v[2 * i + 1] = hi2f(u[i]); }
#pragma unroll
    for (int i = 0; i < 8; i++) {
      float s = v[i];
#pragma unroll
      for (int o = 16; o; o >>= 1) s += __shfl_xor_sync(~0u, s, o);
      if ((c & 31) == 0) red[c >> 5][i] = s;
    }
    __syncthreads();
    const int cc = c >> 5, q = (c >> 3) & 3, s1 = (c >> 2) & 1, hh = (c >> 1) & 1, e = c & 1;
    const int base = h * 27648 + (2 * cc + s1) * 2304 + j * 128 + hh * 64 + 2 * q + e;
#pragma unroll
    for (int n = 0; n < 8; n++) {
      float m = (red[0][n] + red[1][n] + red[2][n] + red[3][n] + red[4][n] + red[5][n]) * (1.0f / 192.0f);
      dst[base + n * 8] = __float2bfloat16((v[n] - m) * (part == 1 ? 0.14433756729740643f * 1.4426950408889634f : 1.0f));
    }
  } else {
    const int jb = nb - 72, chunk = jb / 8, j = jb % 8;
    const int s = c >> 4, hh = (c >> 3) & 1, kk = c & 7;
    const int base = 110592 + (chunk * 12 + s) * 1024 + j * 128 + hh * 64 + kk;
#pragma unroll
    for (int n = 0; n < 8; n++) {
      const int ch = 32 * (jb >> 2) + 8 * (n >> 1) + 2 * (jb & 3) + (n & 1);
      dst[base + n * 8] = wo[c * 192 + ch];
    }
  }
}

__device__ __forceinline__ int window_of(int round, int nfull, int cta, int ncta, int wg) {
  if (round < nfull) return round * 2 * ncta + 2 * cta + wg;
  const int rem = NWIN - nfull * 2 * ncta;
  const int i = cta + wg * ncta;
  return i < rem ? nfull * 2 * ncta + i : -1;
}

__host__ __device__ constexpr int qkv_off(int h, int s) { return ((3 * h + s / 4) % 8) * SLICE + (s % 4) * 4608; }
__host__ __device__ constexpr int wo_off(int chunk, int s) { return 4 * SLICE + (chunk * 12 + s) * 2048; }

#define DEF_ISSUE(NAME, NREG, FN, FIRST)                                                                          \
  template <int S0, int S1, int INIT = FIRST>                                                                     \
  __device__ __forceinline__ void NAME(float (&acc)[NREG], const uint32_t (&A)[48], const uint64_t* d) {          \
    wg_fence();                                                                                                   \
    _Pragma("unroll") for (int s = S0; s < S1; s++) {                                                             \
      if (s == 0) FN<INIT>(acc, A[4 * s], A[4 * s + 1], A[4 * s + 2], A[4 * s + 3], d[s]);                        \
      else        FN<1>(acc, A[4 * s], A[4 * s + 1], A[4 * s + 2], A[4 * s + 3], d[s]);                           \
    }                                                                                                             \
    wg_commit();                                                                                                  \
  }
DEF_ISSUE(mma144, 72, wgmma_n144, 0)
DEF_ISSUE(mma96, 48, wgmma_n96, 0)
DEF_ISSUE(mma64, 32, wgmma_n64, 0)
DEF_ISSUE(mma48, 24, wgmma_n48, 0)
#undef DEF_ISSUE

#define PIN() asm volatile("pmevent 0;" ::: "memory")
template <int A, int B> __device__ __forceinline__ void hold(uint32_t* v) {
#pragma unroll
  for (int i = A; i < B; i++) asm volatile("" : "+r"(v[i]));
}
template <int A, int B> __device__ __forceinline__ void packn(uint32_t* d, const float* a) {
#pragma unroll
  for (int i = A; i < B; i++) d[i] = pack2(a[2 * i], a[2 * i + 1]);
}
template <int A, int B> __device__ __forceinline__ void scalen(uint32_t* d, uint32_t r) {
#pragma unroll
  for (int i = A; i < B; i++) d[i] = (i & 1) ? hmul_b<1>(d[i], r) : hmul_b<0>(d[i], r);
}
__device__ __forceinline__ void stsm12(const uint32_t* v, uint32_t addr) {
#pragma unroll
  for (int j = 0; j < 3; j++) stsm4(addr + 2 * j * KV_PITCH, v[4 * j], v[4 * j + 1], v[4 * j + 2], v[4 * j + 3]);
}
__device__ __forceinline__ uint32_t inv_sum(const float (&o)[28]) {
  float i0, i1;
  asm("rcp.approx.ftz.f32 %0, %1;" : "=f"(i0) : "f"(o[24]));
  asm("rcp.approx.ftz.f32 %0, %1;" : "=f"(i1) : "f"(o[26]));
  return pack2(i0, i1);
}
__device__ __forceinline__ void proxy_fence() { asm volatile("fence.proxy.async.shared::cta;" ::: "memory"); }
__device__ __forceinline__ void issue_s(float (&S)[28], const uint32_t (&Q)[12], const uint64_t* d) {
  wg_fence();
  wgmma_n56<0>(S, Q[0], Q[1], Q[2], Q[3], d[0]);
  wgmma_n56<1>(S, Q[4], Q[5], Q[6], Q[7], d[1]);
  wgmma_n56<1>(S, Q[8], Q[9], Q[10], Q[11], d[2]);
  wg_commit();
}
struct H2 { uint16_t l, h; };
__device__ __forceinline__ H2 exp_halves(uint32_t a) {
  H2 r;
  asm("{\n.reg .b16 l, h;\nmov.b32 {l, h}, %2;\nex2.approx.ftz.bf16 %0, l;\nex2.approx.ftz.bf16 %1, h;\n}\n" : "=h"(r.l), "=h"(r.h) : "r"(a));
  return r;
}
__device__ __forceinline__ uint32_t join(H2 v) { uint32_t r; asm("mov.b32 %0, {%1, %2};" : "=r"(r) : "h"(v.l), "h"(v.h)); return r; }
__device__ __forceinline__ void hold(H2& v) { asm volatile("" : "+h"(v.l), "+h"(v.h)); }

template <int NK, bool PREV, class G>
__device__ __forceinline__ void softmax_pv(float (&S)[28], const uint64_t* dV, uint32_t* Op, uint32_t inv, int wg, G g) {
#define GK(k) if ((k) < NK) g(IC<((k) < NK ? (k) : 0)>{}, IC<((k) < NK ? (k) + 1 : 0)>{});
  uint32_t P[16];
  GK(2) packn<0, 4>(P, S);  if (PREV) { scalen<0, 4>(Op, inv); hold<0, 4>(Op); }   hold<0, 4>(P); PIN();
  GK(3) packn<4, 9>(P, S);  if (PREV) { scalen<4, 8>(Op, inv); hold<4, 8>(Op); }   hold<4, 9>(P); PIN();
  GK(4) packn<9, 14>(P, S); if (PREV) { scalen<8, 12>(Op, inv); hold<8, 12>(Op); } hold<9, 14>(P); PIN();
  GK(5)
  uint32_t m0 = hmax(hmax(hmax(hmax(P[0], P[2]), P[4]), hmax(hmax(P[6], P[8]), P[10])), P[12]);
  uint32_t m1 = hmax(hmax(hmax(hmax(P[1], P[3]), P[5]), hmax(hmax(P[7], P[9]), P[11])), P[13]);
  uint32_t mx = hmax(__byte_perm(m0, m1, 0x5410), __byte_perm(m0, m1, 0x7632));
  uint32_t sh = __shfl_xor_sync(~0u, mx, 1);
  PIN();
  GK(6)
  PIN();
  mx = hmax(mx, sh);
  sh = __shfl_xor_sync(~0u, mx, 2);
  PIN();
  GK(7)
  PIN();
  mx = hmax(mx, sh);
#pragma unroll
  for (int j = 0; j < 14; j++) P[j] = (j & 1) ? hsub_b<1>(P[j], mx) : hsub_b<0>(P[j], mx);
  H2 e0 = exp_halves(P[0]), e1 = exp_halves(P[1]);
  GK(8)
  hold<2, 14>(P); hold(e0); hold(e1); PIN();
  GK(9)
  H2 e2 = exp_halves(P[2]), e3 = exp_halves(P[3]);
  P[0] = join(e0); P[1] = join(e1);
  hold<0, 2>(P); hold(e2); hold(e3); PIN();
  GK(10)
  e0 = exp_halves(P[4]); e1 = exp_halves(P[5]);
  P[2] = join(e2); P[3] = join(e3);
  hold<2, 4>(P); hold(e0); hold(e1); PIN();
  GK(11)
  PIN();
  proxy_fence();
  P[12] = hex1(P[12]); P[13] = hex1(P[13]); P[14] = 0; P[15] = 0;
  P[4] = join(e0); P[5] = join(e1);
#pragma unroll
  for (int j = 6; j < 12; j++) P[j] = hex2(P[j]);
  bar_sync(1 + wg);
  wg_fence();
  wgmma_n56t<0>(S, P[0], P[1], P[2], P[3], dV[0]);
  wgmma_n56t<1>(S, P[4], P[5], P[6], P[7], dV[1]);
  wgmma_n56t<1>(S, P[12], P[13], P[14], P[15], dV[3]);
  wgmma_n56t<1>(S, P[8], P[9], P[10], P[11], dV[2]);
  wg_commit();
#undef GK
}
template <int S0, int S1>
__device__ __forceinline__ void load_x(uint32_t (&X)[48], uint32_t t0) {
#pragma unroll
  for (int s = S0; s < S1; s++)
    asm volatile("ld.shared.v4.u32 {%0,%1,%2,%3}, [%4];" : "=r"(X[4 * s]), "=r"(X[4 * s + 1]), "=r"(X[4 * s + 2]), "=r"(X[4 * s + 3])
                 : "r"(((s & 1) ? (t0 ^ 16) : t0) + (s >> 1) * 128) : "memory");
}

template <int C, int A, int B> __device__ __forceinline__ void add_res(uint32_t* T, const uint32_t (&X)[48]) {
#pragma unroll
  for (int i = A; i < B; i++) T[i] = hadd(X[16 * C + i], T[i]);
}
template <int C>
__device__ __forceinline__ void store_out(const uint32_t* T, uint8_t* o0, uint8_t* o1) {
#pragma unroll
  for (int c = 0; c < 2; c++) {
    asm volatile("st.global.v4.u32 [%0], {%1,%2,%3,%4};" :: "l"(o0 + C * 128 + c * 64), "r"(T[8 * c]), "r"(T[8 * c + 2]), "r"(T[8 * c + 4]), "r"(T[8 * c + 6]) : "memory");
    asm volatile("st.global.v4.u32 [%0], {%1,%2,%3,%4};" :: "l"(o1 + C * 128 + c * 64), "r"(T[8 * c + 1]), "r"(T[8 * c + 3]), "r"(T[8 * c + 5]), "r"(T[8 * c + 7]) : "memory");
  }
}

template <int K, int CNT> __device__ __forceinline__ void load_slices(uint32_t sb, const Descs& ds) {
  constexpr int st = K < 12 ? K / 3 : 4 + (K - 12) / 2;
  constexpr bool first = K < 12 ? (K % 3 == 0) : (K % 2 == 0);
  if (first)
    asm volatile("{\n.reg .pred p;\nelect.sync _|p, 0xffffffff;\n@p mbarrier.arrive.expect_tx.shared::cta.b64 _, [%0], %1;\n}\n"
                 :: "r"(sb + BAR_WFULL + 8 * st), "n"((K < 12 ? 3 : 2) * SLICE) : "memory");
  asm volatile("{\n.reg .pred p;\nelect.sync _|p, 0xffffffff;\n"
               "@p cp.async.bulk.shared::cluster.global.mbarrier::complete_tx::bytes [%0], [%1], %2, [%3];\n}\n"
               :: "r"(sb + OFF_W + (K & 7) * SLICE), "l"(ds.src[K]), "n"(CNT * SLICE), "r"(sb + BAR_WFULL + 8 * st) : "memory");
}
template <int STAGE> __device__ __forceinline__ uint32_t release_begin(uint32_t sb) {
  uint32_t old;
  asm volatile("{\n.reg .b32 a;\nmov.u32 a, %%laneid;\nmad.lo.u32 a, a, 4, %1;\natom.shared.inc.u32 %0, [a + %2], 7;\n}\n"
               : "=r"(old) : "r"(sb), "n"(CNT_WREL + 128 * STAGE) : "memory");
  return old;
}
template <int STAGE> __device__ __forceinline__ void release_end(uint32_t sb, const Descs& ds, uint32_t old, bool next_round) {
  if (__ballot_sync(0xffffffffu, old == 7) & 1) {
    if (STAGE == 0) { load_slices<8, 1>(sb, ds); load_slices<9, 2>(sb, ds); }
    if (STAGE == 1) { load_slices<11, 1>(sb, ds); load_slices<12, 2>(sb, ds); }
    if (STAGE == 2) { load_slices<14, 2>(sb, ds); if (next_round) load_slices<0, 1>(sb, ds); }
    if (STAGE == 3 && next_round) { load_slices<1, 2>(sb, ds); load_slices<3, 1>(sb, ds); }
    if (STAGE == 4 && next_round) load_slices<4, 2>(sb, ds);
    if (STAGE == 5 && next_round) load_slices<6, 2>(sb, ds);
  }
}

__device__ __forceinline__ uint32_t ln_rstd(const uint32_t (&X)[48]) {
  uint32_t sm[2];
#pragma unroll
  for (int a = 0; a < 2; a++) {
    uint32_t t[12];
#pragma unroll
    for (int i = 0; i < 12; i++) t[i] = hadd(X[4 * i + a], X[4 * i + 2 + a]);
#pragma unroll
    for (int i = 0; i < 6; i++) t[i] = hadd(t[i], t[i + 6]);
#pragma unroll
    for (int i = 0; i < 3; i++) t[i] = hadd(t[i], t[i + 3]);
    sm[a] = hadd(hadd(t[0], t[1]), t[2]);
  }
  uint32_t m = hadd(__byte_perm(sm[0], sm[1], 0x5410), __byte_perm(sm[0], sm[1], 0x7632));
  m = hadd(m, __shfl_xor_sync(~0u, m, 1));
  m = hadd(m, __shfl_xor_sync(~0u, m, 2));
  m = hmul(m, 0x3bab3babu);
  float var[2];
#pragma unroll
  for (int a = 0; a < 2; a++) {
    uint32_t t[4];
#pragma unroll
    for (int i = 0; i < 24; i++) {
      const uint32_t d = a ? hsub_b<1>(X[2 * i + 1], m) : hsub_b<0>(X[2 * i], m);
      t[i & 3] = i < 4 ? hmul(d, d) : hfma(d, d, t[i & 3]);
    }
    const uint32_t s = hadd(hadd(t[0], t[1]), hadd(t[2], t[3]));
    float v = lo2f(s) + hi2f(s);
    v += __shfl_xor_sync(~0u, v, 1);
    v += __shfl_xor_sync(~0u, v, 2);
    asm("rsqrt.approx.ftz.f32 %0, %1;" : "=f"(var[a]) : "f"(fmaf(v, 1.0f / 192.0f, 1e-5f)));
  }
  return pack2(var[0], var[1]);
}

__device__ __forceinline__ void stats_pass(uint32_t sb, int pass, int lane) {
  const int g = lane >> 2, q = lane & 3;
  const int tile = pass < 6 ? (pass & 1) : (g & 1);
  const int ps = pass < 6 ? (pass >> 1) * 8 + g : 24;
  uint32_t X[48];
  load_x<0, 12>(X, sb + OFF_TILE + tile * TILE_BYTES + ps * 768 + q * 32 + (ps & 1) * 16);
  const uint32_t rs = ln_rstd(X);
  asm volatile("st.shared.u32 [%0], %1;" :: "r"(sb + OFF_RSTD + tile * 100 + ps * 4), "r"(rs) : "memory");
}

__global__ void __launch_bounds__(384, 1)
fused_kernel(const __grid_constant__ CUtensorMap tmx, const __grid_constant__ Descs ds, const __nv_bfloat16* __restrict__ dw, __nv_bfloat16* __restrict__ out, const int never) {
  extern __shared__ __align__(1024) uint8_t smem[];
  const uint32_t sb = (uint32_t)__cvta_generic_to_shared(smem);
  const int tid = threadIdx.x, lane = tid & 31;
  const int warp = __shfl_sync(0xffffffffu, tid >> 5, 0);
  const int cta = blockIdx.x, ncta = gridDim.x;
  const int nfull = NWIN / (2 * ncta);
  const int nrounds = nfull + ((NWIN - nfull * 2 * ncta) > cta ? 1 : 0);

  if (tid == 0) {
    if ((sb & 0x3FFFF) != SMEM_BASE) __trap();
    for (int i = 0; i < 6; i++) { mbar_init(sb + BAR_WFULL + 8 * i, 1); }
    for (int i = 0; i < 9; i++) mbar_init(sb + BAR_XFULL + 8 * i, 1);
    mbar_init(sb + BAR_TFULL, 3);
    mbar_init(sb + BAR_TEMPTY, 8);
    mbar_init(sb + BAR_TPART, 3);
    mbar_init(sb + BAR_TPART + 8, 3);
    mbar_init(sb + BAR_SFULL, 4);
    asm volatile("fence.mbarrier_init.release.cluster;" ::: "memory");
  }
  if (tid >= 128 && tid < 320) *reinterpret_cast<uint32_t*>(smem + CNT_WREL + (tid - 128) * 4) = 0;
  if (tid < 128) {
    const uint32_t v = (tid & 63) < 49 ? 0x3f803f80u : 0u;
    *reinterpret_cast<uint4*>(smem + OFF_KV + (tid >> 6) * KV_BYTES + 6 * KV_PITCH + (tid & 63) * 16) = make_uint4(v, v, v, v);
    asm volatile("fence.proxy.async.shared::cta;" ::: "memory");
  }
  __syncthreads();

  if (warp >= 8) {
    asm volatile("setmaxnreg.dec.sync.aligned.u32 " PREGS ";");
    if (warp == 11) {
      load_slices<0, 3>(sb, ds); load_slices<3, 3>(sb, ds); load_slices<6, 2>(sb, ds);
      for (int r = 0; r < nrounds; r++) {
#pragma unroll 1
        for (int pass = 0; pass < 4; pass++) {
          if (!(pass & 1)) mbar_wait(sb + BAR_TPART + 4 * pass, r & 1);
          stats_pass(sb, pass, lane);
        }
        __syncwarp();
        if (lane == 0) mbar_arrive(sb + BAR_SFULL);
        TR(2);
      }
    } else {
      const int cw = warp - 8;
      const int win = lane >> 4;
      const int ch0 = cw * 64 + (lane & 15) * 4;
      uint32_t wt[9][2];
#pragma unroll
      for (int t = 0; t < 9; t++) {
        uint2 v = *reinterpret_cast<const uint2*>(dw + t * CH + ch0);
        wt[t][0] = v.x; wt[t][1] = v.y;
      }
      const uint32_t xs = sb + OFF_X + cw * 3 * XSLOT;
      const uint32_t xld = xs + (lane >> 4) * 1152 + (lane & 15) * 8;
      const uint32_t xbar = sb + BAR_XFULL + cw * 24;
      const uint32_t st0 = sb + OFF_TILE + win * TILE_BYTES + ch0 * 4;
      const uint32_t st1 = sb + OFF_TILE + win * TILE_BYTES + ((ch0 * 4) ^ 16);
      const uint64_t tm = reinterpret_cast<uint64_t>(&tmx);
      int cx0, cy0, cx1, cy1;
      auto coords = [&](int r) {
        const int w0 = window_of(r, nfull, cta, ncta, 0);
        int w1 = window_of(r, nfull, cta, ncta, 1);
        if (w1 < 0) w1 = w0;
        const int a = w0 / NWX, b = w1 / NWX;
        cx0 = (w0 - a * NWX) * 7 - 1; cy0 = a * 7 - 1;
        cx1 = (w1 - b * NWX) * 7 - 1; cy1 = b * 7 - 1;
      };
      auto issue = [&](int slot, int dy) {
        asm volatile("{\n.reg .pred p;\nelect.sync _|p, 0xffffffff;\n"
                     "@p mbarrier.arrive.expect_tx.shared::cta.b64 _, [%2], %8;\n"
                     "@p cp.async.bulk.tensor.3d.shared::cluster.global.mbarrier::complete_tx::bytes [%0], [%1, {%3, %4, %5}], [%2];\n"
                     "@p cp.async.bulk.tensor.3d.shared::cluster.global.mbarrier::complete_tx::bytes [%0 + 1152], [%1, {%3, %6, %7}], [%2];\n}\n"
                     :: "r"(xs + slot * XSLOT), "l"(tm), "r"(xbar + slot * 8), "r"(cw * 64), "r"(cx0), "r"(cy0 + dy), "r"(cx1), "r"(cy1 + dy), "n"(XSLOT) : "memory");
      };
      coords(0);
      issue(0, 0); issue(1, 1); issue(2, 2);
      for (int r = 0; r < nrounds; r++) {
        const bool more = r + 1 < nrounds;
        uint32_t accA[7][2], accB[7][2], ctr[7][2], held[2];
#pragma unroll
        for (int i = 0; i < 9; i++) {
          mbar_wait(xbar + (i % 3) * 8, (r + i / 3) & 1);
          if (i == 5 || i == 7) { __syncwarp(); if (lane == 0) mbar_arrive(sb + BAR_TPART + (i == 5 ? 0 : 8)); }
          if (i == 7 && more) coords(r + 1);
          if (i == 0) { if (r > 0) issue(2, 2); }
          else if (i < 7) issue((i + 2) % 3, i + 2);
          else if (more) issue((i + 2) % 3, i - 7);
          if (i == 2 && r > 0) mbar_wait(sb + BAR_TEMPTY, (r - 1) & 1);
          if (i == 2) { TR(0); }
          uint32_t cur[9][2];
#pragma unroll
          for (int p = 0; p < 5; p++)
            asm volatile("ld.shared.v2.u32 {%0,%1}, [%2];" : "=r"(cur[p][0]), "=r"(cur[p][1]) : "r"(xld + (i % 3) * XSLOT + p * 128));
#pragma unroll
          for (int j = 0; j < 7; j++) {
            if (j >= 1 && j + 4 < 9)
              asm volatile("ld.shared.v2.u32 {%0,%1}, [%2];" : "=r"(cur[j + 4][0]), "=r"(cur[j + 4][1]) : "r"(xld + (i % 3) * XSLOT + (j + 4) * 128));
            if (i >= 2) {
              uint32_t o[2];
#pragma unroll
              for (int e = 0; e < 2; e++) {
                uint32_t a = hfma(cur[j][e], wt[6][e], accA[j][e]);
                a = hfma(cur[j + 1][e], wt[7][e], a);
                a = hfma(cur[j + 2][e], wt[8][e], a);
                o[e] = hadd(ctr[j][e], a);
              }
              const int tok = (i - 2) * 7 + j, ps = tok >> 1;
              if (!(tok & 1)) { held[0] = o[0]; held[1] = o[1]; }
              if ((tok & 1) || tok == 48)
                asm volatile("st.shared.v4.u32 [%0], {%1,%2,%3,%4};" :: "r"(((ps & 1) ? st1 : st0) + ps * 768), "r"(held[0]), "r"(o[0]), "r"(held[1]), "r"(o[1]) : "memory");
            }
#pragma unroll
            for (int e = 0; e < 2; e++) {
              if (i >= 1 && i <= 7) {
                uint32_t a = hfma(cur[j][e], wt[3][e], accB[j][e]);
                a = hfma(cur[j + 1][e], wt[4][e], a);
                accA[j][e] = hfma(cur[j + 2][e], wt[5][e], a);
                ctr[j][e] = cur[j + 1][e];
              }
              if (i <= 6) {
                uint32_t a = hmul(cur[j][e], wt[0][e]);
                a = hfma(cur[j + 1][e], wt[1][e], a);
                accB[j][e] = hfma(cur[j + 2][e], wt[2][e], a);
              }
            }
          }
        }
        __syncwarp();
        if (lane == 0) mbar_arrive(sb + BAR_TFULL);
        TR(1);
        mbar_wait(sb + BAR_TFULL, r & 1);
        stats_pass(sb, 4 + cw, lane);
        __syncwarp();
        if (lane == 0) mbar_arrive(sb + BAR_SFULL);
      }
    }
  } else {
    asm volatile("setmaxnreg.inc.sync.aligned.u32 " CREGS ";");
    const int wg = warp >> 2, w4 = warp & 3, g = lane >> 2, q = lane & 3;
    const int row0 = w4 * 16 + g, row1 = row0 + 8;
    const int ps = min(w4 * 8 + g, 24);
    const int tok0 = 2 * ps, tok1 = min(2 * ps + 1, 48);
    const uint32_t kv = sb + OFF_KV + wg * KV_BYTES;
    const int srow = w4 * 16 + (lane & 15);
    const uint32_t vst = kv + (lane >> 4) * KV_PITCH + (srow < 56 ? srow : min(srow - 7, 55)) * 16;
    uint32_t misc = ((uint32_t)((tok1 / 7) * IMG + tok1 % 7) << 20) | ((uint32_t)((tok0 / 7) * IMG + tok0 % 7) << 8) | (ps * 4 + q);
    const uint32_t vmask = (row0 < 49 ? 0xffffu : 0u) | (row1 < 49 ? 0xffff0000u : 0u);

    const uint32_t tx = sb + OFF_TILE + wg * TILE_BYTES + ps * 768 + q * 32 + (ps & 1) * 16;
    const int myrounds = window_of(nrounds - 1, nfull, cta, ncta, wg) < 0 ? nrounds - 1 : nrounds;

    if (never == 2) return;
    uint32_t X[48];
    float acc[72];
    mbar_wait(sb + BAR_TFULL, 0);
    load_x<0, 12>(X, tx);
    mbar_wait(sb + BAR_WFULL, 0);
    mma144<0, 12>(acc, X, ds.q[0]);
    uint32_t rK;
    mbar_wait(sb + BAR_SFULL, 0);
    asm volatile("ld.shared.u32 %0, [%1];" : "=r"(rK) : "r"(sb + OFF_RSTD + wg * 100 + (misc & 0xfc)) : "memory");
    __syncwarp();
    if (lane == 0) mbar_arrive(sb + BAR_TEMPTY);

    for (int r = 0;; r++) {
      const uint32_t par = r & 1;
      if (r == myrounds) {
        wg_wait<0>(); keep(acc);
        if (r < nrounds)
        {
          mbar_wait(sb + BAR_WFULL, par);      release_end<0>(sb, ds, release_begin<0>(sb), false);
          mbar_wait(sb + BAR_WFULL + 8, par);  release_end<1>(sb, ds, release_begin<1>(sb), false);
          mbar_wait(sb + BAR_WFULL + 16, par); release_end<2>(sb, ds, release_begin<2>(sb), false);
        }
        break;
      }
      TR(0);
      const bool next_round = r + 1 < nrounds;
      const uint32_t rV = rK & vmask;
      uint32_t rel;
      uint32_t Of[48], Q[12], T[16], inv = 0;
      float S[28];
      const uint64_t* dkv = ds.kv[wg];

#define PRE(H, ACC)                                                                     \
      packn<0, 12>(T, ACC); scalen<0, 12>(T, rK); stsm12(T, vst + KV_KOFF);                       \
      packn<0, 12>(T, ACC + 24); hold<0, 12>(T);                                        \
      PIN();                                                                            \
      if (H > 0) { wg_wait<0>(); keep(S); }                                             \
      proxy_fence();                                                                    \
      _Pragma("unroll") for (int i = 0; i < 12; i++) Q[i] = T[i];                       \
      scalen<0, 12>(Q, rK); hold<0, 12>(Q);
#define PRE2(H)                                                                         \
      if (H > 0) { inv = inv_sum(S); packn<0, 12>(Of + 12 * (H > 0 ? H - 1 : 0), S);    \
                   hold<0, 12>(Of + 12 * (H > 0 ? H - 1 : 0)); hold<0, 1>(&inv); }
#define MID(VACC, FIRST2)                                                               \
      PIN();                                                                            \
      packn<0, 12>(T, VACC); scalen<0, 12>(T, rV); stsm12(T, vst);                      \
      PIN();                                                                            \
      FIRST2;                                                                           \
      wg_wait<1>(); keep(S);

      wg_wait<0>(); keep(acc);
      TR(2);
      rel = release_begin<0>(sb);
      PRE(0, acc) PRE2(0)
      release_end<0>(sb, ds, rel, next_round);
      mbar_wait(sb + BAR_WFULL + 8, par);
      bar_sync(1 + wg);
      TR(3);
      issue_s(S, Q, dkv);
      MID(acc + 48, (mma144<0, 2>(acc, X, ds.q[1])))
      TR(4);
      softmax_pv<12, false>(S, dkv + 4, Of, inv, wg, [&](auto a, auto b) { mma144<a.v, b.v>(acc, X, ds.q[1]); });
      TR(5);
      wg_wait<1>(); keep(acc);
      TR(6);
      rel = release_begin<1>(sb);
      PRE(1, acc) PRE2(1)
      release_end<1>(sb, ds, rel, next_round);
      mbar_wait(sb + BAR_WFULL + 16, par);
      bar_sync(1 + wg);
      TR(7);
      issue_s(S, Q, dkv);
      MID(acc + 48, (mma144<0, 2>(acc, X, ds.q[2])))
      TR(8);
      softmax_pv<12, true>(S, dkv + 4, Of, inv, wg, [&](auto a, auto b) { mma144<a.v, b.v>(acc, X, ds.q[2]); });
      TR(9);
      float kq[48], va[24], pa[32], pb[32];
      wg_wait<1>(); keep(acc);
      TR(10);
      rel = release_begin<2>(sb);
      PRE(2, acc) PRE2(2)
      release_end<2>(sb, ds, rel, next_round);
      mbar_wait(sb + BAR_WFULL + 24, par);
      bar_sync(1 + wg);
      TR(11);
      issue_s(S, Q, dkv);
      MID(acc + 48, (mma96<0, 2>(kq, X, ds.q[3])))
      TR(12);
      softmax_pv<12, true>(S, dkv + 4, Of + 12, inv, wg, [&](auto a, auto b) { mma96<a.v, b.v>(kq, X, ds.q[3]); });
      TR(13);
      wg_wait<1>(); keep(kq);
      TR(14);
      packn<0, 12>(T, kq); scalen<0, 12>(T, rK); stsm12(T, vst + KV_KOFF); PIN();
      wg_wait<0>(); keep(S);
      mma48<0, 4>(va, X, ds.v3);
      packn<0, 6>(Q, kq + 24); scalen<0, 6>(Q, rK); hold<0, 6>(Q); PIN();
      mma48<4, 8>(va, X, ds.v3);
      packn<6, 12>(Q, kq + 24); scalen<6, 12>(Q, rK); hold<6, 12>(Q); PIN();
      mma48<8, 12>(va, X, ds.v3);
      PIN();
      proxy_fence();
      PRE2(3)
      mbar_wait(sb + BAR_WFULL + 32, par);
      bar_sync(1 + wg);
      TR(15);
      issue_s(S, Q, dkv);
      wg_wait<1>(); keep(va);
      rel = release_begin<3>(sb);
      MID(va, (mma64<0, 2>(pa, Of, ds.p)))
      release_end<3>(sb, ds, rel, next_round);
      TR(16);
      softmax_pv<9, true>(S, dkv + 4, Of + 24, inv, wg, [&](auto a, auto b) { mma64<a.v, b.v>(pa, Of, ds.p); });
      TR(17);
#undef PRE
#undef PRE2
#undef MID
      const bool more = r + 1 < myrounds;
      const int w = window_of(r, nfull, cta, ncta, wg);
      const int wy = w / NWX, wx = w - wy * NWX;
      asm volatile("" : "+r"(misc));
      const uint32_t wb = (uint32_t)(wy * 7 * IMG + wx * 7) * 384u + (misc & 3) * 16;
      uint8_t* o0 = reinterpret_cast<uint8_t*>(out) + (wb + ((misc >> 8) & 0xfff) * 384u);
      uint8_t* o1 = reinterpret_cast<uint8_t*>(out) + (wb + (misc >> 20) * 384u);
      mbar_wait(sb + BAR_WFULL + 40, par);
      wg_wait<0>(); keep(S); keep(pa);
      TR(18);
      inv = inv_sum(S); packn<0, 12>(Of + 36, S); hold<36, 48>(Of); PIN();
      mma64<0, 5>(pb, Of, ds.p + 12);
      scalen<36, 48>(Of, inv); hold<36, 48>(Of); PIN();
      mma64<9, 12>(pa, Of, ds.p);
      mma64<5, 12>(pb, Of, ds.p + 12);
      bar_sync(1 + wg);
      if (more) mbar_wait(sb + BAR_TFULL, par ^ 1);
      TR(19);
      wg_wait<1>(); keep(pa);
      TR(20);
      packn<0, 16>(T, pa); add_res<0, 0, 12>(T, X); hold<0, 16>(T); PIN();
      mma64<0, 3, 2>(pa, Of, ds.p + 24);
      add_res<0, 12, 16>(T, X); hold<12, 16>(T); PIN();
      load_x<0, 4>(X, tx); store_out<0>(T, o0, o1); PIN();
      mma64<3, 12>(pa, Of, ds.p + 24);
      PIN();
      TR(21);
      wg_wait<2>(); keep(pb);
      rel = release_begin<4>(sb);
      packn<0, 16>(T, pb); add_res<1, 0, 16>(T, X); hold<0, 16>(T); PIN();
      load_x<4, 8>(X, tx); store_out<1>(T, o0, o1);
      release_end<4>(sb, ds, rel, next_round);
      if (more) mbar_wait(sb + BAR_WFULL, par ^ 1);
      TR(22);
      wg_wait<0>(); keep(pa);
      TR(23);
      rel = release_begin<5>(sb);
      mma144<0, 1>(acc, X, ds.q[0]);
      packn<0, 6>(T, pa); add_res<2, 0, 4>(T, X); hold<0, 6>(T); PIN();
      mma144<1, 2>(acc, X, ds.q[0]);
      packn<6, 11>(T, pa); add_res<2, 4, 9>(T, X); hold<4, 11>(T); PIN();
      mma144<2, 3>(acc, X, ds.q[0]);
      packn<11, 16>(T, pa); add_res<2, 9, 16>(T, X); hold<9, 16>(T); PIN();
      mma144<3, 4>(acc, X, ds.q[0]);
      load_x<8, 12>(X, tx); store_out<2>(T, o0, o1); PIN();
      mma144<4, 8>(acc, X, ds.q[0]);
      release_end<5>(sb, ds, rel, next_round);
      if (more) mbar_wait(sb + BAR_SFULL, par ^ 1);
      asm volatile("ld.shared.u32 %0, [%1];" : "=r"(rK) : "r"(sb + OFF_RSTD + wg * 100 + (misc & 0xfc)) : "memory");
      mma144<8, 12>(acc, X, ds.q[0]);
      __syncwarp();
      if (lane == 0) mbar_arrive(sb + BAR_TEMPTY);
      TR(1);
    }
  }
}

typedef CUresult (*EncodeFn)(CUtensorMap*, CUtensorMapDataType, cuuint32_t, void*, const cuuint64_t*, const cuuint64_t*,
                             const cuuint32_t*, const cuuint32_t*, CUtensorMapInterleave, CUtensorMapSwizzle,
                             CUtensorMapL2promotion, CUtensorMapFloatOOBfill);

}

extern "C" void kernel_launch(void* const* d_in, const int* in_sizes, int n_in, void* d_out, int out_size) {
  const __nv_bfloat16* x = (const __nv_bfloat16*)d_in[0];
  const __nv_bfloat16* dw = (const __nv_bfloat16*)d_in[1];
  const __nv_bfloat16* wqkv = (const __nv_bfloat16*)d_in[2];
  const __nv_bfloat16* wo = (const __nv_bfloat16*)d_in[3];
  static EncodeFn encode = nullptr;
  static int nsm = 0;
  static void* wpack = nullptr;
  if (!encode) {
    void* fn = nullptr;
    cudaDriverEntryPointQueryResult qr;
    cudaGetDriverEntryPoint("cuTensorMapEncodeTiled", &fn, cudaEnableDefault, &qr);
    encode = (EncodeFn)fn;
    int dev = 0;
    cudaGetDevice(&dev);
    cudaDeviceGetAttribute(&nsm, cudaDevAttrMultiProcessorCount, dev);
    cudaGetSymbolAddress(&wpack, g_wpack);
    cudaFuncSetAttribute(fused_kernel, cudaFuncAttributeMaxDynamicSharedMemorySize, SMEM_BYTES);
  }
  CUtensorMap tmx;
  cuuint64_t gdim[3] = {CH, IMG, IMG};
  cuuint64_t gstr[2] = {CH * 2, (cuuint64_t)CH * 2 * IMG};
  cuuint32_t box[3] = {64, 9, 1};
  cuuint32_t estr[3] = {1, 1, 1};
  encode(&tmx, CU_TENSOR_MAP_DATA_TYPE_BFLOAT16, 3, (void*)x, gdim, gstr, box, estr, CU_TENSOR_MAP_INTERLEAVE_NONE,
         CU_TENSOR_MAP_SWIZZLE_NONE, CU_TENSOR_MAP_L2_PROMOTION_L2_128B, CU_TENSOR_MAP_FLOAT_OOB_FILL_NONE);
  Descs ds;
  for (int i = 0; i < 12; i++) {
    for (int h = 0; h < 4; h++) ds.q[h][i] = mkdesc(SMEM_BASE + OFF_W + qkv_off(h, i), 128, 256);
    ds.v3[i] = mkdesc(SMEM_BASE + OFF_W + qkv_off(3, i) + 3072, 128, 256);
    for (int c = 0; c < 3; c++) ds.p[c * 12 + i] = mkdesc(SMEM_BASE + OFF_W + wo_off(c, i), 128, 256);
  }
  for (int i = 0; i < 16; i++) ds.src[i] = (const uint8_t*)wpack + i * SLICE;
  for (int g = 0; g < 2; g++)
    for (int i = 0; i < 4; i++) {
      ds.kv[g][i] = mkdesc(SMEM_BASE + OFF_KV + g * KV_BYTES + KV_KOFF + 2 * i * KV_PITCH, KV_PITCH, 128);
      ds.kv[g][4 + i] = mkdesc(SMEM_BASE + OFF_KV + g * KV_BYTES + 256 * i, 128, KV_PITCH);
    }
  prepack_kernel<<<96, 192>>>(wqkv, wo);
  fused_kernel<<<nsm, 384, SMEM_BYTES>>>(tmx, ds, dw, (__nv_bfloat16*)d_out, 0);
}
```

```cpp
#include <cuda_runtime.h>
#include <cuda_bf16.h>
#include <cuda.h>
#include <stdint.h>

#define CREGS "208"
#define PREGS "88"
namespace {

constexpr int IMG = 511;
constexpr int CH = 192;
constexpr int NWX = 73;
constexpr int NWIN = NWX * NWX;
constexpr int SLICE = 18432;
constexpr int OFF_W = 0;
constexpr int KV_PITCH = 1792, KV_KOFF = 896, KV_BYTES = 6 * KV_PITCH + 1024;
constexpr int OFF_KV = 8 * SLICE;
constexpr int TILE_BYTES = 25 * 768;
constexpr int OFF_TILE = OFF_KV + 2 * KV_BYTES;
constexpr int XSLOT = 2304;
constexpr int OFF_X = OFF_TILE + 2 * TILE_BYTES;
constexpr int OFF_BAR = OFF_X + 9 * XSLOT;
constexpr int BAR_WFULL = OFF_BAR;
constexpr int BAR_XFULL = OFF_BAR + 72;
constexpr int BAR_TFULL = OFF_BAR + 144;
constexpr int BAR_TEMPTY = OFF_BAR + 152;
constexpr int BAR_TPART = OFF_BAR + 160;
constexpr int BAR_SFULL = OFF_BAR + 176;
constexpr int OFF_RSTD = OFF_BAR + 192;
constexpr int CNT_WREL = OFF_RSTD + 208;
constexpr int OFF_TRACE = CNT_WREL + 768;
constexpr int SMEM_BYTES = OFF_TRACE;

constexpr int SMEM_BASE = 1024;
struct Descs { uint64_t q[4][12]; uint64_t v3[12]; uint64_t p[36]; uint64_t kv[2][8]; const uint8_t* src[16]; };

__device__ uint4 g_wpack[16 * SLICE / 16];
#define TR(id)
template <int ID> __device__ __forceinline__ void sched_fence(uint32_t v) {
  asm volatile("{\n.reg .pred p;\nsetp.ne.u32 p, %0, %1;\n@p bra.uni SF_%=;\ntrap;\nSF_%=:\n}\n" :: "r"(v), "n"(ID) : "memory");
}
__device__ __forceinline__ void anchor(uint32_t v) { sched_fence<0x7fc1ffc1>(v); }

template <int V> struct IC { static constexpr int v = V; };
typedef __nv_bfloat162 bf2;
__device__ __forceinline__ bf2 u2b(uint32_t u) { return *reinterpret_cast<bf2*>(&u); }
__device__ __forceinline__ uint32_t b2u(bf2 b) { return *reinterpret_cast<uint32_t*>(&b); }
__device__ __forceinline__ uint32_t pack2(float lo, float hi) {
  uint32_t r; asm("cvt.rn.bf16x2.f32 %0, %1, %2;" : "=r"(r) : "f"(hi), "f"(lo)); return r;
}
__device__ __forceinline__ uint32_t hadd(uint32_t a, uint32_t b) { return b2u(__hadd2_rn(u2b(a), u2b(b))); }
__device__ __forceinline__ uint32_t hmul(uint32_t a, uint32_t b) { return b2u(__hmul2_rn(u2b(a), u2b(b))); }
__device__ __forceinline__ uint32_t hfma(uint32_t a, uint32_t b, uint32_t c) { return b2u(__hfma2(u2b(a), u2b(b), u2b(c))); }
__device__ __forceinline__ uint32_t hmax(uint32_t a, uint32_t b) { return b2u(__hmax2(u2b(a), u2b(b))); }
template <int HI> __device__ __forceinline__ bf2 bcast(uint32_t a) { return HI ? __high2bfloat162(u2b(a)) : __low2bfloat162(u2b(a)); }
template <int HI> __device__ __forceinline__ uint32_t hmul_b(uint32_t a, uint32_t s) { return b2u(__hmul2_rn(u2b(a), bcast<HI>(s))); }
template <int HI> __device__ __forceinline__ uint32_t hsub_b(uint32_t a, uint32_t s) { return b2u(__hsub2_rn(u2b(a), bcast<HI>(s))); }
__device__ __forceinline__ uint32_t hex2(uint32_t a) { uint32_t r; asm("ex2.approx.ftz.bf16x2 %0, %1;" : "=r"(r) : "r"(a)); return r; }
__device__ __forceinline__ uint32_t hex1(uint32_t a) {
  uint32_t r; asm("{\n.reg .b16 l, h, e;\nmov.b32 {l, h}, %1;\nex2.approx.ftz.bf16 e, l;\ncvt.u32.u16 %0, e;\n}\n" : "=r"(r) : "r"(a)); return r;
}
__device__ __forceinline__ float lo2f(uint32_t a) { return __uint_as_float(a << 16); }
__device__ __forceinline__ float hi2f(uint32_t a) { return __uint_as_float(a & 0xffff0000u); }

__device__ __forceinline__ void mbar_init(uint32_t bar, uint32_t cnt) { asm volatile("mbarrier.init.shared::cta.b64 [%0], %1;" :: "r"(bar), "r"(cnt) : "memory"); }
__device__ __forceinline__ void mbar_arrive(uint32_t bar) { asm volatile("mbarrier.arrive.shared::cta.b64 _, [%0];" :: "r"(bar) : "memory"); }
__device__ __forceinline__ void mbar_expect(uint32_t bar, uint32_t bytes) { asm volatile("mbarrier.arrive.expect_tx.shared::cta.b64 _, [%0], %1;" :: "r"(bar), "r"(bytes) : "memory"); }
template <int HINT>
__device__ __forceinline__ bool mbar_try(uint32_t bar, uint32_t parity) {
  uint32_t ok;
  if (HINT) asm volatile("{\n.reg .pred p;\nmbarrier.try_wait.parity.shared::cta.b64 p, [%1], %2, %3;\nselp.u32 %0, 1, 0, p;\n}\n" : "=r"(ok) : "r"(bar), "r"(parity), "n"(HINT) : "memory");
  else asm volatile("{\n.reg .pred p;\nmbarrier.try_wait.parity.shared::cta.b64 p, [%1], %2;\nselp.u32 %0, 1, 0, p;\n}\n" : "=r"(ok) : "r"(bar), "r"(parity) : "memory");
  return ok != 0;
}
__device__ __forceinline__ void mbar_wait(uint32_t bar, uint32_t parity) {
  if (__builtin_expect(!mbar_try<0>(bar, parity), 0)) {
    uint32_t n = 0;
    while (!mbar_try<4000>(bar, parity)) { if (++n > (1u << 20)) __trap(); }
  }
}
__device__ __forceinline__ void wg_fence() { asm volatile("wgmma.fence.sync.aligned;" ::: "memory"); }
__device__ __forceinline__ void wg_commit() { asm volatile("wgmma.commit_group.sync.aligned;" ::: "memory"); }
template <int N> __device__ __forceinline__ void wg_wait() { asm volatile("wgmma.wait_group.sync.aligned %0;" :: "n"(N) : "memory"); }
__device__ __forceinline__ void bar_sync(int id) { asm volatile("bar.sync %0, 128;" :: "r"(id) : "memory"); }
__device__ __forceinline__ void stsm4(uint32_t addr, uint32_t a, uint32_t b, uint32_t c, uint32_t d) {
  asm volatile("stmatrix.sync.aligned.m8n8.x4.shared.b16 [%0], {%1,%2,%3,%4};" :: "r"(addr), "r"(a), "r"(b), "r"(c), "r"(d) : "memory");
}
template <int N> __device__ __forceinline__ void keep(float (&d)[N]) {
#pragma unroll
  for (int i = 0; i < N; i++) asm volatile("" : "+f"(d[i]) :: "memory");
}
__host__ __device__ __forceinline__ uint64_t mkdesc(uint32_t addr, uint32_t lbo, uint32_t sbo) {
  return ((uint64_t)(sbo >> 4) << 32) | (uint64_t)(((lbo >> 4) << 16) | ((addr & 0x3FFFF) >> 4));
}

template <int SCALE_D>
__device__ __forceinline__ void wgmma_n144(float (&d)[72], uint32_t a0, uint32_t a1, uint32_t a2, uint32_t a3, uint64_t descB) {
  if (SCALE_D == 0)
  asm volatile("wgmma.mma_async.sync.aligned.m64n144k16.f32.bf16.bf16 "
    "{%0, %1, %2, %3, %4, %5, %6, %7, %8, %9, %10, %11, %12, %13, %14, %15, "
    "%16, %17, %18, %19, %20, %21, %22, %23, %24, %25, %26, %27, %28, %29, %30, %31, "
    "%32, %33, %34, %35, %36, %37, %38, %39, %40, %41, %42, %43, %44, %45, %46, %47, "
    "%48, %49, %50, %51, %52, %53, %54, %55, %56, %57, %58, %59, %60, %61, %62, %63, "
    "%64, %65, %66, %67, %68, %69, %70, %71}, "
    "{%72, %73, %74, %75}, %76, 0, 1, 1, 0;\n"
    : "=f"(d[0]), "=f"(d[1]), "=f"(d[2]), "=f"(d[3]), "=f"(d[4]), "=f"(d[5]), "=f"(d[6]), "=f"(d[7]),
      "=f"(d[8]), "=f"(d[9]), "=f"(d[10]), "=f"(d[11]), "=f"(d[12]), "=f"(d[13]), "=f"(d[14]), "=f"(d[15]),
      "=f"(d[16]), "=f"(d[17]), "=f"(d[18]), "=f"(d[19]), "=f"(d[20]), "=f"(d[21]), "=f"(d[22]), "=f"(d[23]),
      "=f"(d[24]), "=f"(d[25]), "=f"(d[26]), "=f"(d[27]), "=f"(d[28]), "=f"(d[29]), "=f"(d[30]), "=f"(d[31]),
      "=f"(d[32]), "=f"(d[33]), "=f"(d[34]), "=f"(d[35]), "=f"(d[36]), "=f"(d[37]), "=f"(d[38]), "=f"(d[39]),
      "=f"(d[40]), "=f"(d[41]), "=f"(d[42]), "=f"(d[43]), "=f"(d[44]), "=f"(d[45]), "=f"(d[46]), "=f"(d[47]),
      "=f"(d[48]), "=f"(d[49]), "=f"(d[50]), "=f"(d[51]), "=f"(d[52]), "=f"(d[53]), "=f"(d[54]), "=f"(d[55]),
      "=f"(d[56]), "=f"(d[57]), "=f"(d[58]), "=f"(d[59]), "=f"(d[60]), "=f"(d[61]), "=f"(d[62]), "=f"(d[63]),
      "=f"(d[64]), "=f"(d[65]), "=f"(d[66]), "=f"(d[67]), "=f"(d[68]), "=f"(d[69]), "=f"(d[70]), "=f"(d[71])
    : "r"(a0), "r"(a1), "r"(a2), "r"(a3), "l"(descB));
  else
  asm volatile("wgmma.mma_async.sync.aligned.m64n144k16.f32.bf16.bf16 "
    "{%0, %1, %2, %3, %4, %5, %6, %7, %8, %9, %10, %11, %12, %13, %14, %15, "
    "%16, %17, %18, %19, %20, %21, %22, %23, %24, %25, %26, %27, %28, %29, %30, %31, "
    "%32, %33, %34, %35, %36, %37, %38, %39, %40, %41, %42, %43, %44, %45, %46, %47, "
    "%48, %49, %50, %51, %52, %53, %54, %55, %56, %57, %58, %59, %60, %61, %62, %63, "
    "%64, %65, %66, %67, %68, %69, %70, %71}, "
    "{%72, %73, %74, %75}, %76, 1, 1, 1, 0;\n"
    : "+f"(d[0]), "+f"(d[1]), "+f"(d[2]), "+f"(d[3]), "+f"(d[4]), "+f"(d[5]), "+f"(d[6]), "+f"(d[7]),
      "+f"(d[8]), "+f"(d[9]), "+f"(d[10]), "+f"(d[11]), "+f"(d[12]), "+f"(d[13]), "+f"(d[14]), "+f"(d[15]),
      "+f"(d[16]), "+f"(d[17]), "+f"(d[18]), "+f"(d[19]), "+f"(d[20]), "+f"(d[21]), "+f"(d[22]), "+f"(d[23]),
      "+f"(d[24]), "+f"(d[25]), "+f"(d[26]), "+f"(d[27]), "+f"(d[28]), "+f"(d[29]), "+f"(d[30]), "+f"(d[31]),
      "+f"(d[32]), "+f"(d[33]), "+f"(d[34]), "+f"(d[35]), "+f"(d[36]), "+f"(d[37]), "+f"(d[38]), "+f"(d[39]),
      "+f"(d[40]), "+f"(d[41]), "+f"(d[42]), "+f"(d[43]), "+f"(d[44]), "+f"(d[45]), "+f"(d[46]), "+f"(d[47]),
      "+f"(d[48]), "+f"(d[49]), "+f"(d[50]), "+f"(d[51]), "+f"(d[52]), "+f"(d[53]), "+f"(d[54]), "+f"(d[55]),
      "+f"(d[56]), "+f"(d[57]), "+f"(d[58]), "+f"(d[59]), "+f"(d[60]), "+f"(d[61]), "+f"(d[62]), "+f"(d[63]),
      "+f"(d[64]), "+f"(d[65]), "+f"(d[66]), "+f"(d[67]), "+f"(d[68]), "+f"(d[69]), "+f"(d[70]), "+f"(d[71])
    : "r"(a0), "r"(a1), "r"(a2), "r"(a3), "l"(descB));
}

template <int SCALE_D>
__device__ __forceinline__ void wgmma_n96(float (&d)[48], uint32_t a0, uint32_t a1, uint32_t a2, uint32_t a3, uint64_t descB) {
  if (SCALE_D == 0)
  asm volatile("wgmma.mma_async.sync.aligned.m64n96k16.f32.bf16.bf16 "
    "{%0, %1, %2, %3, %4, %5, %6, %7, %8, %9, %10, %11, %12, %13, %14, %15, "
    "%16, %17, %18, %19, %20, %21, %22, %23, %24, %25, %26, %27, %28, %29, %30, %31, "
    "%32, %33, %34, %35, %36, %37, %38, %39, %40, %41, %42, %43, %44, %45, %46, %47}, "
    "{%48, %49, %50, %51}, %52, 0, 1, 1, 0;\n"
    : "=f"(d[0]), "=f"(d[1]), "=f"(d[2]), "=f"(d[3]), "=f"(d[4]), "=f"(d[5]), "=f"(d[6]), "=f"(d[7]),
      "=f"(d[8]), "=f"(d[9]), "=f"(d[10]), "=f"(d[11]), "=f"(d[12]), "=f"(d[13]), "=f"(d[14]), "=f"(d[15]),
      "=f"(d[16]), "=f"(d[17]), "=f"(d[18]), "=f"(d[19]), "=f"(d[20]), "=f"(d[21]), "=f"(d[22]), "=f"(d[23]),
      "=f"(d[24]), "=f"(d[25]), "=f"(d[26]), "=f"(d[27]), "=f"(d[28]), "=f"(d[29]), "=f"(d[30]), "=f"(d[31]),
      "=f"(d[32]), "=f"(d[33]), "=f"(d[34]), "=f"(d[35]), "=f"(d[36]), "=f"(d[37]), "=f"(d[38]), "=f"(d[39]),
      "=f"(d[40]), "=f"(d[41]), "=f"(d[42]), "=f"(d[43]), "=f"(d[44]), "=f"(d[45]), "=f"(d[46]), "=f"(d[47])
    : "r"(a0), "r"(a1), "r"(a2), "r"(a3), "l"(descB));
  else
  asm volatile("wgmma.mma_async.sync.aligned.m64n96k16.f32.bf16.bf16 "
    "{%0, %1, %2, %3, %4, %5, %6, %7, %8, %9, %10, %11, %12, %13, %14, %15, "
    "%16, %17, %18, %19, %20, %21, %22, %23, %24, %25, %26, %27, %28, %29, %30, %31, "
    "%32, %33, %34, %35, %36, %37, %38, %39, %40, %41, %42, %43, %44, %45, %46, %47}, "
    "{%48, %49, %50, %51}, %52, 1, 1, 1, 0;\n"
    : "+f"(d[0]), "+f"(d[1]), "+f"(d[2]), "+f"(d[3]), "+f"(d[4]), "+f"(d[5]), "+f"(d[6]), "+f"(d[7]),
      "+f"(d[8]), "+f"(d[9]), "+f"(d[10]), "+f"(d[11]), "+f"(d[12]), "+f"(d[13]), "+f"(d[14]), "+f"(d[15]),
      "+f"(d[16]), "+f"(d[17]), "+f"(d[18]), "+f"(d[19]), "+f"(d[20]), "+f"(d[21]), "+f"(d[22]), "+f"(d[23]),
      "+f"(d[24]), "+f"(d[25]), "+f"(d[26]), "+f"(d[27]), "+f"(d[28]), "+f"(d[29]), "+f"(d[30]), "+f"(d[31]),
      "+f"(d[32]), "+f"(d[33]), "+f"(d[34]), "+f"(d[35]), "+f"(d[36]), "+f"(d[37]), "+f"(d[38]), "+f"(d[39]),
      "+f"(d[40]), "+f"(d[41]), "+f"(d[42]), "+f"(d[43]), "+f"(d[44]), "+f"(d[45]), "+f"(d[46]), "+f"(d[47])
    : "r"(a0), "r"(a1), "r"(a2), "r"(a3), "l"(descB));
}

template <int SCALE_D>
__device__ __forceinline__ void wgmma_n48(float (&d)[24], uint32_t a0, uint32_t a1, uint32_t a2, uint32_t a3, uint64_t descB) {
  if (SCALE_D == 0)
  asm volatile("wgmma.mma_async.sync.aligned.m64n48k16.f32.bf16.bf16 "
    "{%0, %1, %2, %3, %4, %5, %6, %7, %8, %9, %10, %11, %12, %13, %14, %15, "
    "%16, %17, %18, %19, %20, %21, %22, %23}, "
    "{%24, %25, %26, %27}, %28, 0, 1, 1, 0;\n"
    : "=f"(d[0]), "=f"(d[1]), "=f"(d[2]), "=f"(d[3]), "=f"(d[4]), "=f"(d[5]), "=f"(d[6]), "=f"(d[7]),
      "=f"(d[8]), "=f"(d[9]), "=f"(d[10]), "=f"(d[11]), "=f"(d[12]), "=f"(d[13]), "=f"(d[14]), "=f"(d[15]),
      "=f"(d[16]), "=f"(d[17]), "=f"(d[18]), "=f"(d[19]), "=f"(d[20]), "=f"(d[21]), "=f"(d[22]), "=f"(d[23])
    : "r"(a0), "r"(a1), "r"(a2), "r"(a3), "l"(descB));
  else
  asm volatile("wgmma.mma_async.sync.aligned.m64n48k16.f32.bf16.bf16 "
    "{%0, %1, %2, %3, %4, %5, %6, %7, %8, %9, %10, %11, %12, %13, %14, %15, "
    "%16, %17, %18, %19, %20, %21, %22, %23}, "
    "{%24, %25, %26, %27}, %28, 1, 1, 1, 0;\n"
    : "+f"(d[0]), "+f"(d[1]), "+f"(d[2]), "+f"(d[3]), "+f"(d[4]), "+f"(d[5]), "+f"(d[6]), "+f"(d[7]),
      "+f"(d[8]), "+f"(d[9]), "+f"(d[10]), "+f"(d[11]), "+f"(d[12]), "+f"(d[13]), "+f"(d[14]), "+f"(d[15]),
      "+f"(d[16]), "+f"(d[17]), "+f"(d[18]), "+f"(d[19]), "+f"(d[20]), "+f"(d[21]), "+f"(d[22]), "+f"(d[23])
    : "r"(a0), "r"(a1), "r"(a2), "r"(a3), "l"(descB));
}

template <int SCALE_D>
__device__ __forceinline__ void wgmma_n64(float (&d)[32], uint32_t a0, uint32_t a1, uint32_t a2, uint32_t a3, uint64_t descB) {
  if (SCALE_D == 0)
  asm volatile("wgmma.mma_async.sync.aligned.m64n64k16.f32.bf16.bf16 "
    "{%0, %1, %2, %3, %4, %5, %6, %7, %8, %9, %10, %11, %12, %13, %14, %15, "
    "%16, %17, %18, %19, %20, %21, %22, %23, %24, %25, %26, %27, %28, %29, %30, %31}, "
    "{%32, %33, %34, %35}, %36, 0, 1, 1, 0;\n"
    : "=f"(d[0]), "=f"(d[1]), "=f"(d[2]), "=f"(d[3]), "=f"(d[4]), "=f"(d[5]), "=f"(d[6]), "=f"(d[7]),
      "=f"(d[8]), "=f"(d[9]), "=f"(d[10]), "=f"(d[11]), "=f"(d[12]), "=f"(d[13]), "=f"(d[14]), "=f"(d[15]),
      "=f"(d[16]), "=f"(d[17]), "=f"(d[18]), "=f"(d[19]), "=f"(d[20]), "=f"(d[21]), "=f"(d[22]), "=f"(d[23]),
      "=f"(d[24]), "=f"(d[25]), "=f"(d[26]), "=f"(d[27]), "=f"(d[28]), "=f"(d[29]), "=f"(d[30]), "=f"(d[31])
    : "r"(a0), "r"(a1), "r"(a2), "r"(a3), "l"(descB));
  else if (SCALE_D == 2)
  asm volatile("wgmma.mma_async.sync.aligned.m64n64k16.f32.bf16.bf16 "
    "{%0, %1, %2, %3, %4, %5, %6, %7, %8, %9, %10, %11, %12, %13, %14, %15, "
    "%16, %17, %18, %19, %20, %21, %22, %23, %24, %25, %26, %27, %28, %29, %30, %31}, "
    "{%32, %33, %34, %35}, %36, 0, 1, 1, 0;\n"
    : "+f"(d[0]), "+f"(d[1]), "+f"(d[2]), "+f"(d[3]), "+f"(d[4]), "+f"(d[5]), "+f"(d[6]), "+f"(d[7]),
      "+f"(d[8]), "+f"(d[9]), "+f"(d[10]), "+f"(d[11]), "+f"(d[12]), "+f"(d[13]), "+f"(d[14]), "+f"(d[15]),
      "+f"(d[16]), "+f"(d[17]), "+f"(d[18]), "+f"(d[19]), "+f"(d[20]), "+f"(d[21]), "+f"(d[22]), "+f"(d[23]),
      "+f"(d[24]), "+f"(d[25]), "+f"(d[26]), "+f"(d[27]), "+f"(d[28]), "+f"(d[29]), "+f"(d[30]), "+f"(d[31])
    : "r"(a0), "r"(a1), "r"(a2), "r"(a3), "l"(descB));
  else
  asm volatile("wgmma.mma_async.sync.aligned.m64n64k16.f32.bf16.bf16 "
    "{%0, %1, %2, %3, %4, %5, %6, %7, %8, %9, %10, %11, %12, %13, %14, %15, "
    "%16, %17, %18, %19, %20, %21, %22, %23, %24, %25, %26, %27, %28, %29, %30, %31}, "
    "{%32, %33, %34, %35}, %36, 1, 1, 1, 0;\n"
    : "+f"(d[0]), "+f"(d[1]), "+f"(d[2]), "+f"(d[3]), "+f"(d[4]), "+f"(d[5]), "+f"(d[6]), "+f"(d[7]),
      "+f"(d[8]), "+f"(d[9]), "+f"(d[10]), "+f"(d[11]), "+f"(d[12]), "+f"(d[13]), "+f"(d[14]), "+f"(d[15]),
      "+f"(d[16]), "+f"(d[17]), "+f"(d[18]), "+f"(d[19]), "+f"(d[20]), "+f"(d[21]), "+f"(d[22]), "+f"(d[23]),
      "+f"(d[24]), "+f"(d[25]), "+f"(d[26]), "+f"(d[27]), "+f"(d[28]), "+f"(d[29]), "+f"(d[30]), "+f"(d[31])
    : "r"(a0), "r"(a1), "r"(a2), "r"(a3), "l"(descB));
}

template <int SCALE_D>
__device__ __forceinline__ void wgmma_n56(float (&d)[28], uint32_t a0, uint32_t a1, uint32_t a2, uint32_t a3, uint64_t descB) {
  if (SCALE_D == 0)
  asm volatile("wgmma.mma_async.sync.aligned.m64n56k16.f32.bf16.bf16 "
    "{%0, %1, %2, %3, %4, %5, %6, %7, %8, %9, %10, %11, %12, %13, %14, %15, "
    "%16, %17, %18, %19, %20, %21, %22, %23, %24, %25, %26, %27}, "
    "{%28, %29, %30, %31}, %32, 0, 1, 1, 0;\n"
    : "=f"(d[0]), "=f"(d[1]), "=f"(d[2]), "=f"(d[3]), "=f"(d[4]), "=f"(d[5]), "=f"(d[6]), "=f"(d[7]),
      "=f"(d[8]), "=f"(d[9]), "=f"(d[10]), "=f"(d[11]), "=f"(d[12]), "=f"(d[13]), "=f"(d[14]), "=f"(d[15]),
      "=f"(d[16]), "=f"(d[17]), "=f"(d[18]), "=f"(d[19]), "=f"(d[20]), "=f"(d[21]), "=f"(d[22]), "=f"(d[23]),
      "=f"(d[24]), "=f"(d[25]), "=f"(d[26]), "=f"(d[27])
    : "r"(a0), "r"(a1), "r"(a2), "r"(a3), "l"(descB));
  else
  asm volatile("wgmma.mma_async.sync.aligned.m64n56k16.f32.bf16.bf16 "
    "{%0, %1, %2, %3, %4, %5, %6, %7, %8, %9, %10, %11, %12, %13, %14, %15, "
    "%16, %17, %18, %19, %20, %21, %22, %23, %24, %25, %26, %27}, "
    "{%28, %29, %30, %31}, %32, 1, 1, 1, 0;\n"
    : "+f"(d[0]), "+f"(d[1]), "+f"(d[2]), "+f"(d[3]), "+f"(d[4]), "+f"(d[5]), "+f"(d[6]), "+f"(d[7]),
      "+f"(d[8]), "+f"(d[9]), "+f"(d[10]), "+f"(d[11]), "+f"(d[12]), "+f"(d[13]), "+f"(d[14]), "+f"(d[15]),
      "+f"(d[16]), "+f"(d[17]), "+f"(d[18]), "+f"(d[19]), "+f"(d[20]), "+f"(d[21]), "+f"(d[22]), "+f"(d[23]),
      "+f"(d[24]), "+f"(d[25]), "+f"(d[26]), "+f"(d[27])
    : "r"(a0), "r"(a1), "r"(a2), "r"(a3), "l"(descB));
}

template <int SCALE_D>
__device__ __forceinline__ void wgmma_n56t(float (&d)[28], uint32_t a0, uint32_t a1, uint32_t a2, uint32_t a3, uint64_t descB) {
  if (SCALE_D == 0)
  asm volatile("wgmma.mma_async.sync.aligned.m64n56k16.f32.bf16.bf16 "
    "{%0, %1, %2, %3, %4, %5, %6, %7, %8, %9, %10, %11, %12, %13, %14, %15, "
    "%16, %17, %18, %19, %20, %21, %22, %23, %24, %25, %26, %27}, "
    "{%28, %29, %30, %31}, %32, 0, 1, 1, 1;\n"
    : "=f"(d[0]), "=f"(d[1]), "=f"(d[2]), "=f"(d[3]), "=f"(d[4]), "=f"(d[5]), "=f"(d[6]), "=f"(d[7]),
      "=f"(d[8]), "=f"(d[9]), "=f"(d[10]), "=f"(d[11]), "=f"(d[12]), "=f"(d[13]), "=f"(d[14]), "=f"(d[15]),
      "=f"(d[16]), "=f"(d[17]), "=f"(d[18]), "=f"(d[19]), "=f"(d[20]), "=f"(d[21]), "=f"(d[22]), "=f"(d[23]),
      "=f"(d[24]), "=f"(d[25]), "=f"(d[26]), "=f"(d[27])
    : "r"(a0), "r"(a1), "r"(a2), "r"(a3), "l"(descB));
  else
  asm volatile("wgmma.mma_async.sync.aligned.m64n56k16.f32.bf16.bf16 "
    "{%0, %1, %2, %3, %4, %5, %6, %7, %8, %9, %10, %11, %12, %13, %14, %15, "
    "%16, %17, %18, %19, %20, %21, %22, %23, %24, %25, %26, %27}, "
    "{%28, %29, %30, %31}, %32, 1, 1, 1, 1;\n"
    : "+f"(d[0]), "+f"(d[1]), "+f"(d[2]), "+f"(d[3]), "+f"(d[4]), "+f"(d[5]), "+f"(d[6]), "+f"(d[7]),
      "+f"(d[8]), "+f"(d[9]), "+f"(d[10]), "+f"(d[11]), "+f"(d[12]), "+f"(d[13]), "+f"(d[14]), "+f"(d[15]),
      "+f"(d[16]), "+f"(d[17]), "+f"(d[18]), "+f"(d[19]), "+f"(d[20]), "+f"(d[21]), "+f"(d[22]), "+f"(d[23]),
      "+f"(d[24]), "+f"(d[25]), "+f"(d[26]), "+f"(d[27])
    : "r"(a0), "r"(a1), "r"(a2), "r"(a3), "l"(descB));
}

__global__ void __launch_bounds__(384) prepack_kernel(const __nv_bfloat16* __restrict__ wqkv, const __nv_bfloat16* __restrict__ wo) {
  asm volatile("griddepcontrol.launch_dependents;");
  __nv_bfloat16* dst = reinterpret_cast<__nv_bfloat16*>(g_wpack);
  const int c = threadIdx.x, nb = blockIdx.x * 2 + threadIdx.y;
  if (nb < 72) {
    __shared__ float red2[2][6][8];
    float (*red)[8] = red2[threadIdx.y];
    const int h = nb / 18, j = nb % 18, part = j / 6;
    const int col = (part == 0 ? 192 : part == 1 ? 0 : 384) + h * 48 + (j % 6) * 8;
    uint4 raw = *reinterpret_cast<const uint4*>(wqkv + c * 576 + col);
    uint32_t u[4] = {raw.x, raw.y, raw.z, raw.w};
    float v[8];
#pragma unroll
    for (int i = 0; i < 4; i++) { v[2 * i] = lo2f(u[i]); v[2 * i + 1] = hi2f(u[i]); }
#pragma unroll
    for (int i = 0; i < 8; i++) {
      float s = v[i];
#pragma unroll
      for (int o = 16; o; o >>= 1) s += __shfl_xor_sync(~0u, s, o);
      if ((c & 31) == 0) red[c >> 5][i] = s;
    }
    __syncthreads();
    const int cc = c >> 5, q = (c >> 3) & 3, s1 = (c >> 2) & 1, hh = (c >> 1) & 1, e = c & 1;
    const int base = h * 27648 + (2 * cc + s1) * 2304 + j * 128 + hh * 64 + 2 * q + e;
#pragma unroll
    for (int n = 0; n < 8; n++) {
      float m = (red[0][n] + red[1][n] + red[2][n] + red[3][n] + red[4][n] + red[5][n]) * (1.0f / 192.0f);
      dst[base + n * 8] = __float2bfloat16((v[n] - m) * (part == 1 ? 0.14433756729740643f * 1.4426950408889634f : 1.0f));
    }
  } else {
    const int jb = nb - 72, chunk = jb / 8, j = jb % 8;
    const int s = c >> 4, hh = (c >> 3) & 1, kk = c & 7;
    const int base = 110592 + (chunk * 12 + s) * 1024 + j * 128 + hh * 64 + kk;
#pragma unroll
    for (int n = 0; n < 8; n++) {
      const int ch = 32 * (jb >> 2) + 8 * (n >> 1) + 2 * (jb & 3) + (n & 1);
      dst[base + n * 8] = wo[c * 192 + ch];
    }
  }
}

__device__ __forceinline__ int window_of(int round, int nfull, int cta, int ncta, int wg) {
  if (round < nfull) return round * 2 * ncta + 2 * cta + wg;
  const int rem = NWIN - nfull * 2 * ncta;
  const int i = cta + wg * ncta;
  return i < rem ? nfull * 2 * ncta + i : -1;
}

__host__ __device__ constexpr int qkv_off(int h, int s) { return ((3 * h + s / 4) % 8) * SLICE + (s % 4) * 4608; }
__host__ __device__ constexpr int wo_off(int chunk, int s) { return 4 * SLICE + (chunk * 12 + s) * 2048; }

#define DEF_ISSUE(NAME, NREG, FN, FIRST)                                                                          \
  template <int S0, int S1, int INIT = FIRST>                                                                     \
  __device__ __forceinline__ void NAME(float (&acc)[NREG], const uint32_t (&A)[48], const uint64_t* d) {          \
    wg_fence();                                                                                                   \
    _Pragma("unroll") for (int s = S0; s < S1; s++) {                                                             \
      if (s == 0) FN<INIT>(acc, A[4 * s], A[4 * s + 1], A[4 * s + 2], A[4 * s + 3], d[s]);                        \
      else        FN<1>(acc, A[4 * s], A[4 * s + 1], A[4 * s + 2], A[4 * s + 3], d[s]);                           \
    }                                                                                                             \
    wg_commit();                                                                                                  \
  }
DEF_ISSUE(mma144, 72, wgmma_n144, 0)
DEF_ISSUE(mma96, 48, wgmma_n96, 0)
DEF_ISSUE(mma64, 32, wgmma_n64, 0)
DEF_ISSUE(mma48, 24, wgmma_n48, 0)
#undef DEF_ISSUE

#define PIN() asm volatile("pmevent 0;" ::: "memory")
template <int A, int B> __device__ __forceinline__ void hold(uint32_t* v) {
#pragma unroll
  for (int i = A; i < B; i++) asm volatile("" : "+r"(v[i]));
}
template <int A, int B> __device__ __forceinline__ void packn(uint32_t* d, const float* a) {
#pragma unroll
  for (int i = A; i < B; i++) d[i] = pack2(a[2 * i], a[2 * i + 1]);
}
template <int A, int B> __device__ __forceinline__ void scalen(uint32_t* d, uint32_t r) {
#pragma unroll
  for (int i = A; i < B; i++) d[i] = (i & 1) ? hmul_b<1>(d[i], r) : hmul_b<0>(d[i], r);
}
__device__ __forceinline__ void stsm12(const uint32_t* v, uint32_t addr) {
#pragma unroll
  for (int j = 0; j < 3; j++) stsm4(addr + 2 * j * KV_PITCH, v[4 * j], v[4 * j + 1], v[4 * j + 2], v[4 * j + 3]);
}
__device__ __forceinline__ uint32_t inv_sum(const float (&o)[28]) {
  float i0, i1;
  asm("rcp.approx.ftz.f32 %0, %1;" : "=f"(i0) : "f"(o[24]));
  asm("rcp.approx.ftz.f32 %0, %1;" : "=f"(i1) : "f"(o[26]));
  return pack2(i0, i1);
}
__device__ __forceinline__ void proxy_fence() { asm volatile("fence.proxy.async.shared::cta;" ::: "memory"); }
__device__ __forceinline__ void issue_s(float (&S)[28], const uint32_t (&Q)[12], const uint64_t* d) {
  wg_fence();
  wgmma_n56<0>(S, Q[0], Q[1], Q[2], Q[3], d[0]);
  wgmma_n56<1>(S, Q[4], Q[5], Q[6], Q[7], d[1]);
  wgmma_n56<1>(S, Q[8], Q[9], Q[10], Q[11], d[2]);
  wg_commit();
}
struct H2 { uint16_t l, h; };
__device__ __forceinline__ H2 exp_halves(uint32_t a) {
  H2 r;
  asm("{\n.reg .b16 l, h;\nmov.b32 {l, h}, %2;\nex2.approx.ftz.bf16 %0, l;\nex2.approx.ftz.bf16 %1, h;\n}\n" : "=h"(r.l), "=h"(r.h) : "r"(a));
  return r;
}
__device__ __forceinline__ uint32_t join(H2 v) { uint32_t r; asm("mov.b32 %0, {%1, %2};" : "=r"(r) : "h"(v.l), "h"(v.h)); return r; }
__device__ __forceinline__ void hold(H2& v) { asm volatile("" : "+h"(v.l), "+h"(v.h)); }

template <int NK, bool PREV, class G>
__device__ __forceinline__ void softmax_pv(float (&S)[28], const uint64_t* dV, uint32_t* Op, uint32_t inv, int wg, G g) {
#define GK(k) if ((k) < NK) g(IC<((k) < NK ? (k) : 0)>{}, IC<((k) < NK ? (k) + 1 : 0)>{});
  uint32_t P[16];
  GK(2) packn<0, 4>(P, S);  if (PREV) { scalen<0, 4>(Op, inv); hold<0, 4>(Op); }   hold<0, 4>(P); PIN();
  GK(3) packn<4, 9>(P, S);  if (PREV) { scalen<4, 8>(Op, inv); hold<4, 8>(Op); }   hold<4, 9>(P); PIN();
  GK(4) packn<9, 14>(P, S); if (PREV) { scalen<8, 12>(Op, inv); hold<8, 12>(Op); } hold<9, 14>(P); PIN();
  GK(5)
  uint32_t m0 = hmax(hmax(hmax(hmax(P[0], P[2]), P[4]), hmax(hmax(P[6], P[8]), P[10])), P[12]);
  uint32_t m1 = hmax(hmax(hmax(hmax(P[1], P[3]), P[5]), hmax(hmax(P[7], P[9]), P[11])), P[13]);
  uint32_t mx = hmax(__byte_perm(m0, m1, 0x5410), __byte_perm(m0, m1, 0x7632));
  uint32_t sh = __shfl_xor_sync(~0u, mx, 1);
  PIN();
  GK(6)
  PIN();
  mx = hmax(mx, sh);
  sh = __shfl_xor_sync(~0u, mx, 2);
  PIN();
  GK(7)
  PIN();
  mx = hmax(mx, sh);
#pragma unroll
  for (int j = 0; j < 14; j++) P[j] = (j & 1) ? hsub_b<1>(P[j], mx) : hsub_b<0>(P[j], mx);
  H2 e0 = exp_halves(P[0]), e1 = exp_halves(P[1]);
  GK(8)
  hold<2, 14>(P); hold(e0); hold(e1); PIN();
  GK(9)
  H2 e2 = exp_halves(P[2]), e3 = exp_halves(P[3]);
  P[0] = join(e0); P[1] = join(e1);
  hold<0, 2>(P); hold(e2); hold(e3); PIN();
  GK(10)
  e0 = exp_halves(P[4]); e1 = exp_halves(P[5]);
  P[2] = join(e2); P[3] = join(e3);
  hold<2, 4>(P); hold(e0); hold(e1); PIN();
  GK(11)
  PIN();
  proxy_fence();
  P[12] = hex1(P[12]); P[13] = hex1(P[13]); P[14] = 0; P[15] = 0;
  P[4] = join(e0); P[5] = join(e1);
#pragma unroll
  for (int j = 6; j < 12; j++) P[j] = hex2(P[j]);
  bar_sync(1 + wg);
  wg_fence();
  wgmma_n56t<0>(S, P[0], P[1], P[2], P[3], dV[0]);
  wgmma_n56t<1>(S, P[4], P[5], P[6], P[7], dV[1]);
  wgmma_n56t<1>(S, P[12], P[13], P[14], P[15], dV[3]);
  wgmma_n56t<1>(S, P[8], P[9], P[10], P[11], dV[2]);
  wg_commit();
#undef GK
}
template <int S0, int S1>
__device__ __forceinline__ void load_x(uint32_t (&X)[48], uint32_t t0) {
#pragma unroll
  for (int s = S0; s < S1; s++)
    asm volatile("ld.shared.v4.u32 {%0,%1,%2,%3}, [%4];" : "=r"(X[4 * s]), "=r"(X[4 * s + 1]), "=r"(X[4 * s + 2]), "=r"(X[4 * s + 3])
                 : "r"(((s & 1) ? (t0 ^ 16) : t0) + (s >> 1) * 128) : "memory");
}

template <int C, int A, int B> __device__ __forceinline__ void add_res(uint32_t* T, const uint32_t (&X)[48]) {
#pragma unroll
  for (int i = A; i < B; i++) T[i] = hadd(X[16 * C + i], T[i]);
}
template <int C>
__device__ __forceinline__ void store_out(const uint32_t* T, uint8_t* o0, uint8_t* o1) {
#pragma unroll
  for (int c = 0; c < 2; c++) {
    asm volatile("st.global.v4.u32 [%0], {%1,%2,%3,%4};" :: "l"(o0 + C * 128 + c * 64), "r"(T[8 * c]), "r"(T[8 * c + 2]), "r"(T[8 * c + 4]), "r"(T[8 * c + 6]) : "memory");
    asm volatile("st.global.v4.u32 [%0], {%1,%2,%3,%4};" :: "l"(o1 + C * 128 + c * 64), "r"(T[8 * c + 1]), "r"(T[8 * c + 3]), "r"(T[8 * c + 5]), "r"(T[8 * c + 7]) : "memory");
  }
}

template <int K, int CNT> __device__ __forceinline__ void load_slices(uint32_t sb, const Descs& ds) {
  constexpr int st = K < 12 ? K / 3 : 4 + (K - 12) / 2;
  constexpr bool first = K < 12 ? (K % 3 == 0) : (K % 2 == 0);
  if (first)
    asm volatile("{\n.reg .pred p;\nelect.sync _|p, 0xffffffff;\n@p mbarrier.arrive.expect_tx.shared::cta.b64 _, [%0], %1;\n}\n"
                 :: "r"(sb + BAR_WFULL + 8 * st), "n"((K < 12 ? 3 : 2) * SLICE) : "memory");
  asm volatile("{\n.reg .pred p;\nelect.sync _|p, 0xffffffff;\n"
               "@p cp.async.bulk.shared::cluster.global.mbarrier::complete_tx::bytes [%0], [%1], %2, [%3];\n}\n"
               :: "r"(sb + OFF_W + (K & 7) * SLICE), "l"(ds.src[K]), "n"(CNT * SLICE), "r"(sb + BAR_WFULL + 8 * st) : "memory");
}
template <int STAGE> __device__ __forceinline__ uint32_t release_begin(uint32_t sb) {
  uint32_t old;
  asm volatile("{\n.reg .b32 a;\nmov.u32 a, %%laneid;\nmad.lo.u32 a, a, 4, %1;\natom.shared.inc.u32 %0, [a + %2], 7;\n}\n"
               : "=r"(old) : "r"(sb), "n"(CNT_WREL + 128 * STAGE) : "memory");
  return old;
}
template <int STAGE> __device__ __forceinline__ void release_end(uint32_t sb, const Descs& ds, uint32_t old, bool next_round) {
  if (__ballot_sync(0xffffffffu, old == 7) & 1) {
    if (STAGE == 0) { load_slices<8, 1>(sb, ds); load_slices<9, 2>(sb, ds); }
    if (STAGE == 1) { load_slices<11, 1>(sb, ds); load_slices<12, 2>(sb, ds); }
    if (STAGE == 2) { load_slices<14, 2>(sb, ds); if (next_round) load_slices<0, 1>(sb, ds); }
    if (STAGE == 3 && next_round) { load_slices<1, 2>(sb, ds); load_slices<3, 1>(sb, ds); }
    if (STAGE == 4 && next_round) load_slices<4, 2>(sb, ds);
    if (STAGE == 5 && next_round) load_slices<6, 2>(sb, ds);
  }
}

__device__ __forceinline__ uint32_t ln_rstd(const uint32_t (&X)[48]) {
  uint32_t sm[2];
#pragma unroll
  for (int a = 0; a < 2; a++) {
    uint32_t t[12];
#pragma unroll
    for (int i = 0; i < 12; i++) t[i] = hadd(X[4 * i + a], X[4 * i + 2 + a]);
#pragma unroll
    for (int i = 0; i < 6; i++) t[i] = hadd(t[i], t[i + 6]);
#pragma unroll
    for (int i = 0; i < 3; i++) t[i] = hadd(t[i], t[i + 3]);
    sm[a] = hadd(hadd(t[0], t[1]), t[2]);
  }
  uint32_t m = hadd(__byte_perm(sm[0], sm[1], 0x5410), __byte_perm(sm[0], sm[1], 0x7632));
  m = hadd(m, __shfl_xor_sync(~0u, m, 1));
  m = hadd(m, __shfl_xor_sync(~0u, m, 2));
  m = hmul(m, 0x3bab3babu);
  float var[2];
#pragma unroll
  for (int a = 0; a < 2; a++) {
    uint32_t t[4];
#pragma unroll
    for (int i = 0; i < 24; i++) {
      const uint32_t d = a ? hsub_b<1>(X[2 * i + 1], m) : hsub_b<0>(X[2 * i], m);
      t[i & 3] = i < 4 ? hmul(d, d) : hfma(d, d, t[i & 3]);
    }
    const uint32_t s = hadd(hadd(t[0], t[1]), hadd(t[2], t[3]));
    float v = lo2f(s) + hi2f(s);
    v += __shfl_xor_sync(~0u, v, 1);
    v += __shfl_xor_sync(~0u, v, 2);
    asm("rsqrt.approx.ftz.f32 %0, %1;" : "=f"(var[a]) : "f"(fmaf(v, 1.0f / 192.0f, 1e-5f)));
  }
  return pack2(var[0], var[1]);
}

__device__ __forceinline__ void stats_pass(uint32_t sb, int pass, int lane) {
  const int g = lane >> 2, q = lane & 3;
  const int tile = pass < 6 ? (pass & 1) : (g & 1);
  const int ps = pass < 6 ? (pass >> 1) * 8 + g : 24;
  uint32_t X[48];
  load_x<0, 12>(X, sb + OFF_TILE + tile * TILE_BYTES + ps * 768 + q * 32 + (ps & 1) * 16);
  const uint32_t rs = ln_rstd(X);
  asm volatile("st.shared.u32 [%0], %1;" :: "r"(sb + OFF_RSTD + tile * 100 + ps * 4), "r"(rs) : "memory");
}

__global__ void __launch_bounds__(384, 1)
fused_kernel(const __grid_constant__ CUtensorMap tmx, const __grid_constant__ CUtensorMap tmp, const __grid_constant__ Descs ds, const __nv_bfloat16* __restrict__ dw, __nv_bfloat16* __restrict__ out, const int never) {
  extern __shared__ __align__(1024) uint8_t smem[];
  const uint32_t sb = (uint32_t)__cvta_generic_to_shared(smem);
  const int tid = threadIdx.x, lane = tid & 31;
  const int warp = __shfl_sync(0xffffffffu, tid >> 5, 0);
  const int cta = blockIdx.x, ncta = gridDim.x;
  const int nfull = NWIN / (2 * ncta);
  const int nrounds = nfull + ((NWIN - nfull * 2 * ncta) > cta ? 1 : 0);

  auto prefetch_round = [&](int r) {
#pragma unroll
    for (int k = 0; k < 2; k++) {
      const int w = window_of(r, nfull, cta, ncta, k);
      if (w >= 0) {
        const int a = w / NWX;
        asm volatile("{\n.reg .pred p;\nelect.sync _|p, 0xffffffff;\n@p cp.async.bulk.prefetch.tensor.3d.L2.global [%0, {0, %1, %2}];\n}\n"
                     :: "l"(reinterpret_cast<uint64_t>(&tmp)), "r"((w - a * NWX) * 7 - 1), "r"(a * 7 - 1) : "memory");
      }
    }
  };
  if (warp == 11) prefetch_round(0);
  if (warp == 10 && lane == 0) asm volatile("prefetch.tensormap [%0];" :: "l"(reinterpret_cast<uint64_t>(&tmx)) : "memory");
  if (tid == 0) {
    if ((sb & 0x3FFFF) != SMEM_BASE) __trap();
    for (int i = 0; i < 6; i++) { mbar_init(sb + BAR_WFULL + 8 * i, 1); }
    for (int i = 0; i < 9; i++) mbar_init(sb + BAR_XFULL + 8 * i, 1);
    mbar_init(sb + BAR_TFULL, 3);
    mbar_init(sb + BAR_TEMPTY, 8);
    mbar_init(sb + BAR_TPART, 3);
    mbar_init(sb + BAR_TPART + 8, 3);
    mbar_init(sb + BAR_SFULL, 4);
    asm volatile("fence.mbarrier_init.release.cluster;" ::: "memory");
  }
  if (tid >= 128 && tid < 320) *reinterpret_cast<uint32_t*>(smem + CNT_WREL + (tid - 128) * 4) = 0;
  if (tid < 128) {
    const uint32_t v = (tid & 63) < 49 ? 0x3f803f80u : 0u;
    *reinterpret_cast<uint4*>(smem + OFF_KV + (tid >> 6) * KV_BYTES + 6 * KV_PITCH + (tid & 63) * 16) = make_uint4(v, v, v, v);
    asm volatile("fence.proxy.async.shared::cta;" ::: "memory");
  }
  __syncthreads();

  if (warp >= 8) {
    asm volatile("setmaxnreg.dec.sync.aligned.u32 " PREGS ";");
    if (warp == 11) {
      asm volatile("griddepcontrol.wait;" ::: "memory");
      load_slices<0, 3>(sb, ds); load_slices<3, 3>(sb, ds); load_slices<6, 2>(sb, ds);
      for (int r = 0; r < nrounds; r++) {
        if (r + 1 < nrounds) prefetch_round(r + 1);
#pragma unroll 1
        for (int pass = 0; pass < 4; pass++) {
          if (!(pass & 1)) mbar_wait(sb + BAR_TPART + 4 * pass, r & 1);
          stats_pass(sb, pass, lane);
        }
        __syncwarp();
        if (lane == 0) mbar_arrive(sb + BAR_SFULL);
        TR(2);
      }
    } else {
      const int cw = warp - 8;
      const int win = lane >> 4;
      const int ch0 = cw * 64 + (lane & 15) * 4;
      uint32_t wt[9][2];
#pragma unroll
      for (int t = 0; t < 9; t++) {
        uint2 v = *reinterpret_cast<const uint2*>(dw + t * CH + ch0);
        wt[t][0] = v.x; wt[t][1] = v.y;
      }
      const uint32_t xs = sb + OFF_X + cw * 3 * XSLOT;
      const uint32_t xld = xs + (lane >> 4) * 1152 + (lane & 15) * 8;
      const uint32_t xbar = sb + BAR_XFULL + cw * 24;
      const uint32_t st0 = sb + OFF_TILE + win * TILE_BYTES + ch0 * 4;
      const uint32_t st1 = sb + OFF_TILE + win * TILE_BYTES + ((ch0 * 4) ^ 16);
      const uint64_t tm = reinterpret_cast<uint64_t>(&tmx);
      int cx0, cy0, cx1, cy1;
      auto coords = [&](int r) {
        const int w0 = window_of(r, nfull, cta, ncta, 0);
        int w1 = window_of(r, nfull, cta, ncta, 1);
        if (w1 < 0) w1 = w0;
        const int a = w0 / NWX, b = w1 / NWX;
        cx0 = (w0 - a * NWX) * 7 - 1; cy0 = a * 7 - 1;
        cx1 = (w1 - b * NWX) * 7 - 1; cy1 = b * 7 - 1;
      };
      auto issue = [&](int slot, int dy) {
        asm volatile("{\n.reg .pred p;\nelect.sync _|p, 0xffffffff;\n"
                     "@p mbarrier.arrive.expect_tx.shared::cta.b64 _, [%2], %8;\n"
                     "@p cp.async.bulk.tensor.3d.shared::cluster.global.mbarrier::complete_tx::bytes [%0], [%1, {%3, %4, %5}], [%2];\n"
                     "@p cp.async.bulk.tensor.3d.shared::cluster.global.mbarrier::complete_tx::bytes [%0 + 1152], [%1, {%3, %6, %7}], [%2];\n}\n"
                     :: "r"(xs + slot * XSLOT), "l"(tm), "r"(xbar + slot * 8), "r"(cw * 64), "r"(cx0), "r"(cy0 + dy), "r"(cx1), "r"(cy1 + dy), "n"(XSLOT) : "memory");
      };
      coords(0);
      issue(0, 0); issue(1, 1); issue(2, 2);
      for (int r = 0; r < nrounds; r++) {
        const bool more = r + 1 < nrounds;
        uint32_t accA[7][2], accB[7][2], ctr[7][2], held[2];
#pragma unroll
        for (int i = 0; i < 9; i++) {
          mbar_wait(xbar + (i % 3) * 8, (r + i / 3) & 1);
          if (i == 5 || i == 7) { __syncwarp(); if (lane == 0) mbar_arrive(sb + BAR_TPART + (i == 5 ? 0 : 8)); }
          if (i == 7 && more) coords(r + 1);
          if (i == 0) { if (r > 0) issue(2, 2); }
          else if (i < 7) issue((i + 2) % 3, i + 2);
          else if (more) issue((i + 2) % 3, i - 7);
          if (i == 2 && r > 0) mbar_wait(sb + BAR_TEMPTY, (r - 1) & 1);
          if (i == 2) { TR(0); }
          uint32_t cur[9][2];
#pragma unroll
          for (int p = 0; p < 5; p++)
            asm volatile("ld.shared.v2.u32 {%0,%1}, [%2];" : "=r"(cur[p][0]), "=r"(cur[p][1]) : "r"(xld + (i % 3) * XSLOT + p * 128));
#pragma unroll
          for (int j = 0; j < 7; j++) {
            if (j >= 1 && j + 4 < 9)
              asm volatile("ld.shared.v2.u32 {%0,%1}, [%2];" : "=r"(cur[j + 4][0]), "=r"(cur[j + 4][1]) : "r"(xld + (i % 3) * XSLOT + (j + 4) * 128));
            if (i >= 2) {
              uint32_t o[2];
#pragma unroll
              for (int e = 0; e < 2; e++) {
                uint32_t a = hfma(cur[j][e], wt[6][e], accA[j][e]);
                a = hfma(cur[j + 1][e], wt[7][e], a);
                a = hfma(cur[j + 2][e], wt[8][e], a);
                o[e] = hadd(ctr[j][e], a);
              }
              const int tok = (i - 2) * 7 + j, ps = tok >> 1;
              if (!(tok & 1)) { held[0] = o[0]; held[1] = o[1]; }
              if ((tok & 1) || tok == 48)
                asm volatile("st.shared.v4.u32 [%0], {%1,%2,%3,%4};" :: "r"(((ps & 1) ? st1 : st0) + ps * 768), "r"(held[0]), "r"(o[0]), "r"(held[1]), "r"(o[1]) : "memory");
            }
#pragma unroll
            for (int e = 0; e < 2; e++) {
              if (i >= 1 && i <= 7) {
                uint32_t a = hfma(cur[j][e], wt[3][e], accB[j][e]);
                a = hfma(cur[j + 1][e], wt[4][e], a);
                accA[j][e] = hfma(cur[j + 2][e], wt[5][e], a);
                ctr[j][e] = cur[j + 1][e];
              }
              if (i <= 6) {
                uint32_t a = hmul(cur[j][e], wt[0][e]);
                a = hfma(cur[j + 1][e], wt[1][e], a);
                accB[j][e] = hfma(cur[j + 2][e], wt[2][e], a);
              }
            }
          }
        }
        __syncwarp();
        if (lane == 0) mbar_arrive(sb + BAR_TFULL);
        TR(1);
        mbar_wait(sb + BAR_TFULL, r & 1);
        stats_pass(sb, 4 + cw, lane);
        __syncwarp();
        if (lane == 0) mbar_arrive(sb + BAR_SFULL);
      }
    }
  } else {
    asm volatile("setmaxnreg.inc.sync.aligned.u32 " CREGS ";");
    const int wg = warp >> 2, w4 = warp & 3, g = lane >> 2, q = lane & 3;
    const int row0 = w4 * 16 + g, row1 = row0 + 8;
    const int ps = min(w4 * 8 + g, 24);
    const int tok0 = 2 * ps, tok1 = min(2 * ps + 1, 48);
    const uint32_t kv = sb + OFF_KV + wg * KV_BYTES;
    const int srow = w4 * 16 + (lane & 15);
    const uint32_t vst = kv + (lane >> 4) * KV_PITCH + (srow < 56 ? srow : min(srow - 7, 55)) * 16;
    uint32_t misc = ((uint32_t)((tok1 / 7) * IMG + tok1 % 7) << 20) | ((uint32_t)((tok0 / 7) * IMG + tok0 % 7) << 8) | (ps * 4 + q);
    const uint32_t vmask = (row0 < 49 ? 0xffffu : 0u) | (row1 < 49 ? 0xffff0000u : 0u);

    const uint32_t tx = sb + OFF_TILE + wg * TILE_BYTES + ps * 768 + q * 32 + (ps & 1) * 16;
    const int myrounds = window_of(nrounds - 1, nfull, cta, ncta, wg) < 0 ? nrounds - 1 : nrounds;

    if (never == 2) return;
    uint32_t X[48];
    float acc[72];
    mbar_wait(sb + BAR_TFULL, 0);
    load_x<0, 12>(X, tx);
    mbar_wait(sb + BAR_WFULL, 0);
    mma144<0, 12>(acc, X, ds.q[0]);
    uint32_t rK;
    mbar_wait(sb + BAR_SFULL, 0);
    asm volatile("ld.shared.u32 %0, [%1];" : "=r"(rK) : "r"(sb + OFF_RSTD + wg * 100 + (misc & 0xfc)) : "memory");
    __syncwarp();
    if (lane == 0) mbar_arrive(sb + BAR_TEMPTY);

    for (int r = 0;; r++) {
      const uint32_t par = r & 1;
      if (r == myrounds) {
        wg_wait<0>(); keep(acc);
        if (r < nrounds)
        {
          mbar_wait(sb + BAR_WFULL, par);      release_end<0>(sb, ds, release_begin<0>(sb), false);
          mbar_wait(sb + BAR_WFULL + 8, par);  release_end<1>(sb, ds, release_begin<1>(sb), false);
          mbar_wait(sb + BAR_WFULL + 16, par); release_end<2>(sb, ds, release_begin<2>(sb), false);
        }
        break;
      }
      TR(0);
      const bool next_round = r + 1 < nrounds;
      const uint32_t rV = rK & vmask;
      uint32_t rel;
      uint32_t Of[48], Q[12], T[16], inv = 0;
      float S[28];
      const uint64_t* dkv = ds.kv[wg];

#define PRE(H, ACC)                                                                     \
      packn<0, 12>(T, ACC); scalen<0, 12>(T, rK); stsm12(T, vst + KV_KOFF);                       \
      packn<0, 12>(T, ACC + 24); hold<0, 12>(T);                                        \
      PIN();                                                                            \
      if (H > 0) { wg_wait<0>(); keep(S); }                                             \
      proxy_fence();                                                                    \
      _Pragma("unroll") for (int i = 0; i < 12; i++) Q[i] = T[i];                       \
      scalen<0, 12>(Q, rK); hold<0, 12>(Q);
#define PRE2(H)                                                                         \
      if (H > 0) { inv = inv_sum(S); packn<0, 12>(Of + 12 * (H > 0 ? H - 1 : 0), S);    \
                   hold<0, 12>(Of + 12 * (H > 0 ? H - 1 : 0)); hold<0, 1>(&inv); }
#define MID(VACC, FIRST2)                                                               \
      PIN();                                                                            \
      packn<0, 12>(T, VACC); scalen<0, 12>(T, rV); stsm12(T, vst);                      \
      PIN();                                                                            \
      FIRST2;                                                                           \
      wg_wait<1>(); keep(S);

      wg_wait<0>(); keep(acc);
      TR(2);
      rel = release_begin<0>(sb);
      PRE(0, acc) PRE2(0)
      release_end<0>(sb, ds, rel, next_round);
      mbar_wait(sb + BAR_WFULL + 8, par);
      bar_sync(1 + wg);
      TR(3);
      issue_s(S, Q, dkv);
      MID(acc + 48, (mma144<0, 2>(acc, X, ds.q[1])))
      TR(4);
      softmax_pv<12, false>(S, dkv + 4, Of, inv, wg, [&](auto a, auto b) { mma144<a.v, b.v>(acc, X, ds.q[1]); });
      TR(5);
      wg_wait<1>(); keep(acc);
      TR(6);
      rel = release_begin<1>(sb);
      PRE(1, acc) PRE2(1)
      release_end<1>(sb, ds, rel, next_round);
      mbar_wait(sb + BAR_WFULL + 16, par);
      bar_sync(1 + wg);
      TR(7);
      issue_s(S, Q, dkv);
      MID(acc + 48, (mma144<0, 2>(acc, X, ds.q[2])))
      TR(8);
      softmax_pv<12, true>(S, dkv + 4, Of, inv, wg, [&](auto a, auto b) { mma144<a.v, b.v>(acc, X, ds.q[2]); });
      TR(9);
      float kq[48], va[24], pa[32], pb[32];
      wg_wait<1>(); keep(acc);
      TR(10);
      rel = release_begin<2>(sb);
      PRE(2, acc) PRE2(2)
      release_end<2>(sb, ds, rel, next_round);
      mbar_wait(sb + BAR_WFULL + 24, par);
      bar_sync(1 + wg);
      TR(11);
      issue_s(S, Q, dkv);
      MID(acc + 48, (mma96<0, 2>(kq, X, ds.q[3])))
      TR(12);
      softmax_pv<12, true>(S, dkv + 4, Of + 12, inv, wg, [&](auto a, auto b) { mma96<a.v, b.v>(kq, X, ds.q[3]); });
      TR(13);
      wg_wait<1>(); keep(kq);
      TR(14);
      packn<0, 12>(T, kq); scalen<0, 12>(T, rK); stsm12(T, vst + KV_KOFF); PIN();
      wg_wait<0>(); keep(S);
      mma48<0, 4>(va, X, ds.v3);
      packn<0, 6>(Q, kq + 24); scalen<0, 6>(Q, rK); hold<0, 6>(Q); PIN();
      mma48<4, 8>(va, X, ds.v3);
      packn<6, 12>(Q, kq + 24); scalen<6, 12>(Q, rK); hold<6, 12>(Q); PIN();
      mma48<8, 12>(va, X, ds.v3);
      PIN();
      proxy_fence();
      PRE2(3)
      mbar_wait(sb + BAR_WFULL + 32, par);
      bar_sync(1 + wg);
      TR(15);
      issue_s(S, Q, dkv);
      wg_wait<1>(); keep(va);
      rel = release_begin<3>(sb);
      MID(va, (mma64<0, 2>(pa, Of, ds.p)))
      release_end<3>(sb, ds, rel, next_round);
      TR(16);
      softmax_pv<9, true>(S, dkv + 4, Of + 24, inv, wg, [&](auto a, auto b) { mma64<a.v, b.v>(pa, Of, ds.p); });
      TR(17);
#undef PRE
#undef PRE2
#undef MID
      const bool more = r + 1 < myrounds;
      const int w = window_of(r, nfull, cta, ncta, wg);
      const int wy = w / NWX, wx = w - wy * NWX;
      asm volatile("" : "+r"(misc));
      const uint32_t wb = (uint32_t)(wy * 7 * IMG + wx * 7) * 384u + (misc & 3) * 16;
      uint8_t* o0 = reinterpret_cast<uint8_t*>(out) + (wb + ((misc >> 8) & 0xfff) * 384u);
      uint8_t* o1 = reinterpret_cast<uint8_t*>(out) + (wb + (misc >> 20) * 384u);
      mbar_wait(sb + BAR_WFULL + 40, par);
      wg_wait<0>(); keep(S); keep(pa);
      TR(18);
      inv = inv_sum(S); packn<0, 12>(Of + 36, S); hold<36, 48>(Of); PIN();
      mma64<0, 5>(pb, Of, ds.p + 12);
      scalen<36, 48>(Of, inv); hold<36, 48>(Of); PIN();
      mma64<9, 12>(pa, Of, ds.p);
      mma64<5, 12>(pb, Of, ds.p + 12);
      bar_sync(1 + wg);
      if (more) mbar_wait(sb + BAR_TFULL, par ^ 1);
      TR(19);
      wg_wait<1>(); keep(pa);
      TR(20);
      packn<0, 16>(T, pa); add_res<0, 0, 12>(T, X); hold<0, 16>(T); PIN();
      mma64<0, 3, 2>(pa, Of, ds.p + 24);
      add_res<0, 12, 16>(T, X); hold<12, 16>(T); PIN();
      load_x<0, 4>(X, tx); store_out<0>(T, o0, o1); PIN();
      mma64<3, 12>(pa, Of, ds.p + 24);
      PIN();
      TR(21);
      wg_wait<2>(); keep(pb);
      rel = release_begin<4>(sb);
      packn<0, 16>(T, pb); add_res<1, 0, 16>(T, X); hold<0, 16>(T); PIN();
      load_x<4, 8>(X, tx); store_out<1>(T, o0, o1);
      release_end<4>(sb, ds, rel, next_round);
      if (more) mbar_wait(sb + BAR_WFULL, par ^ 1);
      TR(22);
      wg_wait<0>(); keep(pa);
      TR(23);
      rel = release_begin<5>(sb);
      mma144<0, 1>(acc, X, ds.q[0]);
      packn<0, 6>(T, pa); add_res<2, 0, 4>(T, X); hold<0, 6>(T); PIN();
      mma144<1, 2>(acc, X, ds.q[0]);
      packn<6, 11>(T, pa); add_res<2, 4, 9>(T, X); hold<4, 11>(T); PIN();
      mma144<2, 3>(acc, X, ds.q[0]);
      packn<11, 16>(T, pa); add_res<2, 9, 16>(T, X); hold<9, 16>(T); PIN();
      mma144<3, 4>(acc, X, ds.q[0]);
      load_x<8, 12>(X, tx); store_out<2>(T, o0, o1); PIN();
      mma144<4, 8>(acc, X, ds.q[0]);
      release_end<5>(sb, ds, rel, next_round);
      if (more) mbar_wait(sb + BAR_SFULL, par ^ 1);
      asm volatile("ld.shared.u32 %0, [%1];" : "=r"(rK) : "r"(sb + OFF_RSTD + wg * 100 + (misc & 0xfc)) : "memory");
      mma144<8, 12>(acc, X, ds.q[0]);
      __syncwarp();
      if (lane == 0) mbar_arrive(sb + BAR_TEMPTY);
      TR(1);
    }
  }
}

typedef CUresult (*EncodeFn)(CUtensorMap*, CUtensorMapDataType, cuuint32_t, void*, const cuuint64_t*, const cuuint64_t*,
                             const cuuint32_t*, const cuuint32_t*, CUtensorMapInterleave, CUtensorMapSwizzle,
                             CUtensorMapL2promotion, CUtensorMapFloatOOBfill);

}

extern "C" void kernel_launch(void* const* d_in, const int* in_sizes, int n_in, void* d_out, int out_size) {
  const __nv_bfloat16* x = (const __nv_bfloat16*)d_in[0];
  const __nv_bfloat16* dw = (const __nv_bfloat16*)d_in[1];
  const __nv_bfloat16* wqkv = (const __nv_bfloat16*)d_in[2];
  const __nv_bfloat16* wo = (const __nv_bfloat16*)d_in[3];
  static EncodeFn encode = nullptr;
  static int nsm = 0;
  static void* wpack = nullptr;
  if (!encode) {
    void* fn = nullptr;
    cudaDriverEntryPointQueryResult qr;
    cudaGetDriverEntryPoint("cuTensorMapEncodeTiled", &fn, cudaEnableDefault, &qr);
    encode = (EncodeFn)fn;
    int dev = 0;
    cudaGetDevice(&dev);
    cudaDeviceGetAttribute(&nsm, cudaDevAttrMultiProcessorCount, dev);
    cudaGetSymbolAddress(&wpack, g_wpack);
    cudaFuncSetAttribute(fused_kernel, cudaFuncAttributeMaxDynamicSharedMemorySize, SMEM_BYTES);
  }
  CUtensorMap tmx;
  cuuint64_t gdim[3] = {CH, IMG, IMG};
  cuuint64_t gstr[2] = {CH * 2, (cuuint64_t)CH * 2 * IMG};
  cuuint32_t box[3] = {64, 9, 1};
  cuuint32_t estr[3] = {1, 1, 1};
  encode(&tmx, CU_TENSOR_MAP_DATA_TYPE_BFLOAT16, 3, (void*)x, gdim, gstr, box, estr, CU_TENSOR_MAP_INTERLEAVE_NONE,
         CU_TENSOR_MAP_SWIZZLE_NONE, CU_TENSOR_MAP_L2_PROMOTION_L2_128B, CU_TENSOR_MAP_FLOAT_OOB_FILL_NONE);
  Descs ds;
  for (int i = 0; i < 12; i++) {
    for (int h = 0; h < 4; h++) ds.q[h][i] = mkdesc(SMEM_BASE + OFF_W + qkv_off(h, i), 128, 256);
    ds.v3[i] = mkdesc(SMEM_BASE + OFF_W + qkv_off(3, i) + 3072, 128, 256);
    for (int c = 0; c < 3; c++) ds.p[c * 12 + i] = mkdesc(SMEM_BASE + OFF_W + wo_off(c, i), 128, 256);
  }
  for (int i = 0; i < 16; i++) ds.src[i] = (const uint8_t*)wpack + i * SLICE;
  for (int g = 0; g < 2; g++)
    for (int i = 0; i < 4; i++) {
      ds.kv[g][i] = mkdesc(SMEM_BASE + OFF_KV + g * KV_BYTES + KV_KOFF + 2 * i * KV_PITCH, KV_PITCH, 128);
      ds.kv[g][4 + i] = mkdesc(SMEM_BASE + OFF_KV + g * KV_BYTES + 256 * i, 128, KV_PITCH);
    }
  CUtensorMap tmp;
  cuuint32_t boxp[3] = {CH, 9, 9};
  encode(&tmp, CU_TENSOR_MAP_DATA_TYPE_BFLOAT16, 3, (void*)x, gdim, gstr, boxp, estr, CU_TENSOR_MAP_INTERLEAVE_NONE,
         CU_TENSOR_MAP_SWIZZLE_NONE, CU_TENSOR_MAP_L2_PROMOTION_L2_128B, CU_TENSOR_MAP_FLOAT_OOB_FILL_NONE);
  prepack_kernel<<<48, dim3(192, 2), 0, cudaStreamPerThread>>>(wqkv, wo);
  cudaLaunchConfig_t cfg = {};
  cfg.gridDim = dim3(nsm); cfg.blockDim = dim3(384); cfg.dynamicSmemBytes = SMEM_BYTES; cfg.stream = cudaStreamPerThread;
  cudaLaunchAttribute at[1];
  at[0].id = cudaLaunchAttributeProgrammaticStreamSerialization;
  at[0].val.programmaticStreamSerializationAllowed = 1;
  cfg.attrs = at; cfg.numAttrs = 1;
  cudaLaunchKernelEx(&cfg, fused_kernel, tmx, tmp, ds, dw, (__nv_bfloat16*)d_out, 0);
}
```

```cpp
#include <cuda_runtime.h>
#include <cuda_bf16.h>
#include <cuda.h>
#include <stdint.h>

#define CREGS "208"
#define PREGS "88"
namespace {

constexpr int IMG = 511;
constexpr int CH = 192;
constexpr int NWX = 73;
constexpr int NWIN = NWX * NWX;
constexpr int SLICE = 18432;
constexpr int OFF_W = 0;
constexpr int KV_PITCH = 1792, KV_KOFF = 896, KV_BYTES = 6 * KV_PITCH + 1024;
constexpr int OFF_KV = 8 * SLICE;
constexpr int TILE_BYTES = 25 * 768;
constexpr int OFF_TILE = OFF_KV + 2 * KV_BYTES;
constexpr int XSLOT = 2304;
constexpr int OFF_X = OFF_TILE + 2 * TILE_BYTES;
constexpr int OFF_BAR = OFF_X + 9 * XSLOT;
constexpr int BAR_WFULL = OFF_BAR;
constexpr int BAR_XFULL = OFF_BAR + 72;
constexpr int BAR_TFULL = OFF_BAR + 144;
constexpr int BAR_TEMPTY = OFF_BAR + 152;
constexpr int BAR_TPART = OFF_BAR + 160;
constexpr int BAR_SFULL = OFF_BAR + 176;
constexpr int OFF_RSTD = OFF_BAR + 192;
constexpr int CNT_WREL = OFF_RSTD + 208;
constexpr int OFF_TRACE = CNT_WREL + 768;
constexpr int SMEM_BYTES = OFF_TRACE;

constexpr int SMEM_BASE = 1024;
struct Descs { uint64_t q[4][12]; uint64_t v3[12]; uint64_t p[36]; uint64_t kv[2][8]; const uint8_t* src[16]; };

__device__ uint4 g_wpack[16 * SLICE / 16];
#define TR(id)
#define GTS(i)
template <int ID> __device__ __forceinline__ void sched_fence(uint32_t v) {
  asm volatile("{\n.reg .pred p;\nsetp.ne.u32 p, %0, %1;\n@p bra.uni SF_%=;\ntrap;\nSF_%=:\n}\n" :: "r"(v), "n"(ID) : "memory");
}
__device__ __forceinline__ void anchor(uint32_t v) { sched_fence<0x7fc1ffc1>(v); }

template <int V> struct IC { static constexpr int v = V; };
typedef __nv_bfloat162 bf2;
__device__ __forceinline__ bf2 u2b(uint32_t u) { return *reinterpret_cast<bf2*>(&u); }
__device__ __forceinline__ uint32_t b2u(bf2 b) { return *reinterpret_cast<uint32_t*>(&b); }
__device__ __forceinline__ uint32_t pack2(float lo, float hi) {
  uint32_t r; asm("cvt.rn.bf16x2.f32 %0, %1, %2;" : "=r"(r) : "f"(hi), "f"(lo)); return r;
}
__device__ __forceinline__ uint32_t hadd(uint32_t a, uint32_t b) { return b2u(__hadd2_rn(u2b(a), u2b(b))); }
__device__ __forceinline__ uint32_t hmul(uint32_t a, uint32_t b) { return b2u(__hmul2_rn(u2b(a), u2b(b))); }
__device__ __forceinline__ uint32_t hfma(uint32_t a, uint32_t b, uint32_t c) { return b2u(__hfma2(u2b(a), u2b(b), u2b(c))); }
__device__ __forceinline__ uint32_t hmax(uint32_t a, uint32_t b) { return b2u(__hmax2(u2b(a), u2b(b))); }
template <int HI> __device__ __forceinline__ bf2 bcast(uint32_t a) { return HI ? __high2bfloat162(u2b(a)) : __low2bfloat162(u2b(a)); }
template <int HI> __device__ __forceinline__ uint32_t hmul_b(uint32_t a, uint32_t s) { return b2u(__hmul2_rn(u2b(a), bcast<HI>(s))); }
template <int HI> __device__ __forceinline__ uint32_t hsub_b(uint32_t a, uint32_t s) { return b2u(__hsub2_rn(u2b(a), bcast<HI>(s))); }
__device__ __forceinline__ uint32_t hex2(uint32_t a) { uint32_t r; asm("ex2.approx.ftz.bf16x2 %0, %1;" : "=r"(r) : "r"(a)); return r; }
__device__ __forceinline__ float lo2f(uint32_t a) { return __uint_as_float(a << 16); }
__device__ __forceinline__ float hi2f(uint32_t a) { return __uint_as_float(a & 0xffff0000u); }

__device__ __forceinline__ void mbar_init(uint32_t bar, uint32_t cnt) { asm volatile("mbarrier.init.shared::cta.b64 [%0], %1;" :: "r"(bar), "r"(cnt) : "memory"); }
__device__ __forceinline__ void mbar_arrive(uint32_t bar) { asm volatile("mbarrier.arrive.shared::cta.b64 _, [%0];" :: "r"(bar) : "memory"); }
__device__ __forceinline__ void mbar_expect(uint32_t bar, uint32_t bytes) { asm volatile("mbarrier.arrive.expect_tx.shared::cta.b64 _, [%0], %1;" :: "r"(bar), "r"(bytes) : "memory"); }
template <int HINT>
__device__ __forceinline__ bool mbar_try(uint32_t bar, uint32_t parity) {
  uint32_t ok;
  if (HINT) asm volatile("{\n.reg .pred p;\nmbarrier.try_wait.parity.shared::cta.b64 p, [%1], %2, %3;\nselp.u32 %0, 1, 0, p;\n}\n" : "=r"(ok) : "r"(bar), "r"(parity), "n"(HINT) : "memory");
  else asm volatile("{\n.reg .pred p;\nmbarrier.try_wait.parity.shared::cta.b64 p, [%1], %2;\nselp.u32 %0, 1, 0, p;\n}\n" : "=r"(ok) : "r"(bar), "r"(parity) : "memory");
  return ok != 0;
}
__device__ __forceinline__ void mbar_wait(uint32_t bar, uint32_t parity) {
  if (__builtin_expect(!mbar_try<0>(bar, parity), 0)) {
    uint32_t n = 0;
    while (!mbar_try<4000>(bar, parity)) { if (++n > (1u << 20)) __trap(); }
  }
}
__device__ __forceinline__ void wg_fence() { asm volatile("wgmma.fence.sync.aligned;" ::: "memory"); }
__device__ __forceinline__ void wg_commit() { asm volatile("wgmma.commit_group.sync.aligned;" ::: "memory"); }
template <int N> __device__ __forceinline__ void wg_wait() { asm volatile("wgmma.wait_group.sync.aligned %0;" :: "n"(N) : "memory"); }
__device__ __forceinline__ void bar_sync(int id) { asm volatile("bar.sync %0, 128;" :: "r"(id) : "memory"); }
#define PPMASK 0x37
#define PASS_AT 11
template <int SEC> __device__ __forceinline__ void turn_wait(int wg) { if (PPMASK >> SEC & 1) asm volatile("bar.sync %0, 256;" :: "r"(3 + wg) : "memory"); }
template <int SEC> __device__ __forceinline__ void turn_pass(int wg) { if (PPMASK >> SEC & 1) asm volatile("bar.arrive %0, 256;" :: "r"(4 - wg) : "memory"); }
constexpr int PP_LAST = PPMASK >= 32 ? 5 : PPMASK >= 16 ? 4 : PPMASK >= 8 ? 3 : PPMASK >= 4 ? 2 : PPMASK >= 2 ? 1 : 0;
__device__ __forceinline__ void stsm4(uint32_t addr, uint32_t a, uint32_t b, uint32_t c, uint32_t d) {
  asm volatile("stmatrix.sync.aligned.m8n8.x4.shared.b16 [%0], {%1,%2,%3,%4};" :: "r"(addr), "r"(a), "r"(b), "r"(c), "r"(d) : "memory");
}
template <int N> __device__ __forceinline__ void keep(float (&d)[N]) {
#pragma unroll
  for (int i = 0; i < N; i++) asm volatile("" : "+f"(d[i]) :: "memory");
}
__host__ __device__ __forceinline__ uint64_t mkdesc(uint32_t addr, uint32_t lbo, uint32_t sbo) {
  return ((uint64_t)(sbo >> 4) << 32) | (uint64_t)(((lbo >> 4) << 16) | ((addr & 0x3FFFF) >> 4));
}

template <int SCALE_D>
__device__ __forceinline__ void wgmma_n144(float (&d)[72], uint32_t a0, uint32_t a1, uint32_t a2, uint32_t a3, uint64_t descB) {
  if (SCALE_D == 0)
  asm volatile("wgmma.mma_async.sync.aligned.m64n144k16.f32.bf16.bf16 "
    "{%0, %1, %2, %3, %4, %5, %6, %7, %8, %9, %10, %11, %12, %13, %14, %15, "
    "%16, %17, %18, %19, %20, %21, %22, %23, %24, %25, %26, %27, %28, %29, %30, %31, "
    "%32, %33, %34, %35, %36, %37, %38, %39, %40, %41, %42, %43, %44, %45, %46, %47, "
    "%48, %49, %50, %51, %52, %53, %54, %55, %56, %57, %58, %59, %60, %61, %62, %63, "
    "%64, %65, %66, %67, %68, %69, %70, %71}, "
    "{%72, %73, %74, %75}, %76, 0, 1, 1, 0;\n"
    : "=f"(d[0]), "=f"(d[1]), "=f"(d[2]), "=f"(d[3]), "=f"(d[4]), "=f"(d[5]), "=f"(d[6]), "=f"(d[7]),
      "=f"(d[8]), "=f"(d[9]), "=f"(d[10]), "=f"(d[11]), "=f"(d[12]), "=f"(d[13]), "=f"(d[14]), "=f"(d[15]),
      "=f"(d[16]), "=f"(d[17]), "=f"(d[18]), "=f"(d[19]), "=f"(d[20]), "=f"(d[21]), "=f"(d[22]), "=f"(d[23]),
      "=f"(d[24]), "=f"(d[25]), "=f"(d[26]), "=f"(d[27]), "=f"(d[28]), "=f"(d[29]), "=f"(d[30]), "=f"(d[31]),
      "=f"(d[32]), "=f"(d[33]), "=f"(d[34]), "=f"(d[35]), "=f"(d[36]), "=f"(d[37]), "=f"(d[38]), "=f"(d[39]),
      "=f"(d[40]), "=f"(d[41]), "=f"(d[42]), "=f"(d[43]), "=f"(d[44]), "=f"(d[45]), "=f"(d[46]), "=f"(d[47]),
      "=f"(d[48]), "=f"(d[49]), "=f"(d[50]), "=f"(d[51]), "=f"(d[52]), "=f"(d[53]), "=f"(d[54]), "=f"(d[55]),
      "=f"(d[56]), "=f"(d[57]), "=f"(d[58]), "=f"(d[59]), "=f"(d[60]), "=f"(d[61]), "=f"(d[62]), "=f"(d[63]),
      "=f"(d[64]), "=f"(d[65]), "=f"(d[66]), "=f"(d[67]), "=f"(d[68]), "=f"(d[69]), "=f"(d[70]), "=f"(d[71])
    : "r"(a0), "r"(a1), "r"(a2), "r"(a3), "l"(descB));
  else
  asm volatile("wgmma.mma_async.sync.aligned.m64n144k16.f32.bf16.bf16 "
    "{%0, %1, %2, %3, %4, %5, %6, %7, %8, %9, %10, %11, %12, %13, %14, %15, "
    "%16, %17, %18, %19, %20, %21, %22, %23, %24, %25, %26, %27, %28, %29, %30, %31, "
    "%32, %33, %34, %35, %36, %37, %38, %39, %40, %41, %42, %43, %44, %45, %46, %47, "
    "%48, %49, %50, %51, %52, %53, %54, %55, %56, %57, %58, %59, %60, %61, %62, %63, "
    "%64, %65, %66, %67, %68, %69, %70, %71}, "
    "{%72, %73, %74, %75}, %76, 1, 1, 1, 0;\n"
    : "+f"(d[0]), "+f"(d[1]), "+f"(d[2]), "+f"(d[3]), "+f"(d[4]), "+f"(d[5]), "+f"(d[6]), "+f"(d[7]),
      "+f"(d[8]), "+f"(d[9]), "+f"(d[10]), "+f"(d[11]), "+f"(d[12]), "+f"(d[13]), "+f"(d[14]), "+f"(d[15]),
      "+f"(d[16]), "+f"(d[17]), "+f"(d[18]), "+f"(d[19]), "+f"(d[20]), "+f"(d[21]), "+f"(d[22]), "+f"(d[23]),
      "+f"(d[24]), "+f"(d[25]), "+f"(d[26]), "+f"(d[27]), "+f"(d[28]), "+f"(d[29]), "+f"(d[30]), "+f"(d[31]),
      "+f"(d[32]), "+f"(d[33]), "+f"(d[34]), "+f"(d[35]), "+f"(d[36]), "+f"(d[37]), "+f"(d[38]), "+f"(d[39]),
      "+f"(d[40]), "+f"(d[41]), "+f"(d[42]), "+f"(d[43]), "+f"(d[44]), "+f"(d[45]), "+f"(d[46]), "+f"(d[47]),
      "+f"(d[48]), "+f"(d[49]), "+f"(d[50]), "+f"(d[51]), "+f"(d[52]), "+f"(d[53]), "+f"(d[54]), "+f"(d[55]),
      "+f"(d[56]), "+f"(d[57]), "+f"(d[58]), "+f"(d[59]), "+f"(d[60]), "+f"(d[61]), "+f"(d[62]), "+f"(d[63]),
      "+f"(d[64]), "+f"(d[65]), "+f"(d[66]), "+f"(d[67]), "+f"(d[68]), "+f"(d[69]), "+f"(d[70]), "+f"(d[71])
    : "r"(a0), "r"(a1), "r"(a2), "r"(a3), "l"(descB));
}

template <int SCALE_D>
__device__ __forceinline__ void wgmma_n96(float (&d)[48], uint32_t a0, uint32_t a1, uint32_t a2, uint32_t a3, uint64_t descB) {
  if (SCALE_D == 0)
  asm volatile("wgmma.mma_async.sync.aligned.m64n96k16.f32.bf16.bf16 "
    "{%0, %1, %2, %3, %4, %5, %6, %7, %8, %9, %10, %11, %12, %13, %14, %15, "
    "%16, %17, %18, %19, %20, %21, %22, %23, %24, %25, %26, %27, %28, %29, %30, %31, "
    "%32, %33, %34, %35, %36, %37, %38, %39, %40, %41, %42, %43, %44, %45, %46, %47}, "
    "{%48, %49, %50, %51}, %52, 0, 1, 1, 0;\n"
    : "=f"(d[0]), "=f"(d[1]), "=f"(d[2]), "=f"(d[3]), "=f"(d[4]), "=f"(d[5]), "=f"(d[6]), "=f"(d[7]),
      "=f"(d[8]), "=f"(d[9]), "=f"(d[10]), "=f"(d[11]), "=f"(d[12]), "=f"(d[13]), "=f"(d[14]), "=f"(d[15]),
      "=f"(d[16]), "=f"(d[17]), "=f"(d[18]), "=f"(d[19]), "=f"(d[20]), "=f"(d[21]), "=f"(d[22]), "=f"(d[23]),
      "=f"(d[24]), "=f"(d[25]), "=f"(d[26]), "=f"(d[27]), "=f"(d[28]), "=f"(d[29]), "=f"(d[30]), "=f"(d[31]),
      "=f"(d[32]), "=f"(d[33]), "=f"(d[34]), "=f"(d[35]), "=f"(d[36]), "=f"(d[37]), "=f"(d[38]), "=f"(d[39]),
      "=f"(d[40]), "=f"(d[41]), "=f"(d[42]), "=f"(d[43]), "=f"(d[44]), "=f"(d[45]), "=f"(d[46]), "=f"(d[47])
    : "r"(a0), "r"(a1), "r"(a2), "r"(a3), "l"(descB));
  else if (SCALE_D == 2)
  asm volatile("wgmma.mma_async.sync.aligned.m64n96k16.f32.bf16.bf16 "
    "{%0, %1, %2, %3, %4, %5, %6, %7, %8, %9, %10, %11, %12, %13, %14, %15, "
    "%16, %17, %18, %19, %20, %21, %22, %23, %24, %25, %26, %27, %28, %29, %30, %31, "
    "%32, %33, %34, %35, %36, %37, %38, %39, %40, %41, %42, %43, %44, %45, %46, %47}, "
    "{%48, %49, %50, %51}, %52, 0, 1, 1, 0;\n"
    : "+f"(d[0]), "+f"(d[1]), "+f"(d[2]), "+f"(d[3]), "+f"(d[4]), "+f"(d[5]), "+f"(d[6]), "+f"(d[7]),
      "+f"(d[8]), "+f"(d[9]), "+f"(d[10]), "+f"(d[11]), "+f"(d[12]), "+f"(d[13]), "+f"(d[14]), "+f"(d[15]),
      "+f"(d[16]), "+f"(d[17]), "+f"(d[18]), "+f"(d[19]), "+f"(d[20]), "+f"(d[21]), "+f"(d[22]), "+f"(d[23]),
      "+f"(d[24]), "+f"(d[25]), "+f"(d[26]), "+f"(d[27]), "+f"(d[28]), "+f"(d[29]), "+f"(d[30]), "+f"(d[31]),
      "+f"(d[32]), "+f"(d[33]), "+f"(d[34]), "+f"(d[35]), "+f"(d[36]), "+f"(d[37]), "+f"(d[38]), "+f"(d[39]),
      "+f"(d[40]), "+f"(d[41]), "+f"(d[42]), "+f"(d[43]), "+f"(d[44]), "+f"(d[45]), "+f"(d[46]), "+f"(d[47])
    : "r"(a0), "r"(a1), "r"(a2), "r"(a3), "l"(descB));
  else
  asm volatile("wgmma.mma_async.sync.aligned.m64n96k16.f32.bf16.bf16 "
    "{%0, %1, %2, %3, %4, %5, %6, %7, %8, %9, %10, %11, %12, %13, %14, %15, "
    "%16, %17, %18, %19, %20, %21, %22, %23, %24, %25, %26, %27, %28, %29, %30, %31, "
    "%32, %33, %34, %35, %36, %37, %38, %39, %40, %41, %42, %43, %44, %45, %46, %47}, "
    "{%48, %49, %50, %51}, %52, 1, 1, 1, 0;\n"
    : "+f"(d[0]), "+f"(d[1]), "+f"(d[2]), "+f"(d[3]), "+f"(d[4]), "+f"(d[5]), "+f"(d[6]), "+f"(d[7]),
      "+f"(d[8]), "+f"(d[9]), "+f"(d[10]), "+f"(d[11]), "+f"(d[12]), "+f"(d[13]), "+f"(d[14]), "+f"(d[15]),
      "+f"(d[16]), "+f"(d[17]), "+f"(d[18]), "+f"(d[19]), "+f"(d[20]), "+f"(d[21]), "+f"(d[22]), "+f"(d[23]),
      "+f"(d[24]), "+f"(d[25]), "+f"(d[26]), "+f"(d[27]), "+f"(d[28]), "+f"(d[29]), "+f"(d[30]), "+f"(d[31]),
      "+f"(d[32]), "+f"(d[33]), "+f"(d[34]), "+f"(d[35]), "+f"(d[36]), "+f"(d[37]), "+f"(d[38]), "+f"(d[39]),
      "+f"(d[40]), "+f"(d[41]), "+f"(d[42]), "+f"(d[43]), "+f"(d[44]), "+f"(d[45]), "+f"(d[46]), "+f"(d[47])
    : "r"(a0), "r"(a1), "r"(a2), "r"(a3), "l"(descB));
}

template <int SCALE_D>
__device__ __forceinline__ void wgmma_n48(float (&d)[24], uint32_t a0, uint32_t a1, uint32_t a2, uint32_t a3, uint64_t descB) {
  if (SCALE_D == 0)
  asm volatile("wgmma.mma_async.sync.aligned.m64n48k16.f32.bf16.bf16 "
    "{%0, %1, %2, %3, %4, %5, %6, %7, %8, %9, %10, %11, %12, %13, %14, %15, "
    "%16, %17, %18, %19, %20, %21, %22, %23}, "
    "{%24, %25, %26, %27}, %28, 0, 1, 1, 0;\n"
    : "=f"(d[0]), "=f"(d[1]), "=f"(d[2]), "=f"(d[3]), "=f"(d[4]), "=f"(d[5]), "=f"(d[6]), "=f"(d[7]),
      "=f"(d[8]), "=f"(d[9]), "=f"(d[10]), "=f"(d[11]), "=f"(d[12]), "=f"(d[13]), "=f"(d[14]), "=f"(d[15]),
      "=f"(d[16]), "=f"(d[17]), "=f"(d[18]), "=f"(d[19]), "=f"(d[20]), "=f"(d[21]), "=f"(d[22]), "=f"(d[23])
    : "r"(a0), "r"(a1), "r"(a2), "r"(a3), "l"(descB));
  else
  asm volatile("wgmma.mma_async.sync.aligned.m64n48k16.f32.bf16.bf16 "
    "{%0, %1, %2, %3, %4, %5, %6, %7, %8, %9, %10, %11, %12, %13, %14, %15, "
    "%16, %17, %18, %19, %20, %21, %22, %23}, "
    "{%24, %25, %26, %27}, %28, 1, 1, 1, 0;\n"
    : "+f"(d[0]), "+f"(d[1]), "+f"(d[2]), "+f"(d[3]), "+f"(d[4]), "+f"(d[5]), "+f"(d[6]), "+f"(d[7]),
      "+f"(d[8]), "+f"(d[9]), "+f"(d[10]), "+f"(d[11]), "+f"(d[12]), "+f"(d[13]), "+f"(d[14]), "+f"(d[15]),
      "+f"(d[16]), "+f"(d[17]), "+f"(d[18]), "+f"(d[19]), "+f"(d[20]), "+f"(d[21]), "+f"(d[22]), "+f"(d[23])
    : "r"(a0), "r"(a1), "r"(a2), "r"(a3), "l"(descB));
}

template <int SCALE_D>
__device__ __forceinline__ void wgmma_n64(float (&d)[32], uint32_t a0, uint32_t a1, uint32_t a2, uint32_t a3, uint64_t descB) {
  if (SCALE_D == 0)
  asm volatile("wgmma.mma_async.sync.aligned.m64n64k16.f32.bf16.bf16 "
    "{%0, %1, %2, %3, %4, %5, %6, %7, %8, %9, %10, %11, %12, %13, %14, %15, "
    "%16, %17, %18, %19, %20, %21, %22, %23, %24, %25, %26, %27, %28, %29, %30, %31}, "
    "{%32, %33, %34, %35}, %36, 0, 1, 1, 0;\n"
    : "=f"(d[0]), "=f"(d[1]), "=f"(d[2]), "=f"(d[3]), "=f"(d[4]), "=f"(d[5]), "=f"(d[6]), "=f"(d[7]),
      "=f"(d[8]), "=f"(d[9]), "=f"(d[10]), "=f"(d[11]), "=f"(d[12]), "=f"(d[13]), "=f"(d[14]), "=f"(d[15]),
      "=f"(d[16]), "=f"(d[17]), "=f"(d[18]), "=f"(d[19]), "=f"(d[20]), "=f"(d[21]), "=f"(d[22]), "=f"(d[23]),
      "=f"(d[24]), "=f"(d[25]), "=f"(d[26]), "=f"(d[27]), "=f"(d[28]), "=f"(d[29]), "=f"(d[30]), "=f"(d[31])
    : "r"(a0), "r"(a1), "r"(a2), "r"(a3), "l"(descB));
  else if (SCALE_D == 2)
  asm volatile("wgmma.mma_async.sync.aligned.m64n64k16.f32.bf16.bf16 "
    "{%0, %1, %2, %3, %4, %5, %6, %7, %8, %9, %10, %11, %12, %13, %14, %15, "
    "%16, %17, %18, %19, %20, %21, %22, %23, %24, %25, %26, %27, %28, %29, %30, %31}, "
    "{%32, %33, %34, %35}, %36, 0, 1, 1, 0;\n"
    : "+f"(d[0]), "+f"(d[1]), "+f"(d[2]), "+f"(d[3]), "+f"(d[4]), "+f"(d[5]), "+f"(d[6]), "+f"(d[7]),
      "+f"(d[8]), "+f"(d[9]), "+f"(d[10]), "+f"(d[11]), "+f"(d[12]), "+f"(d[13]), "+f"(d[14]), "+f"(d[15]),
      "+f"(d[16]), "+f"(d[17]), "+f"(d[18]), "+f"(d[19]), "+f"(d[20]), "+f"(d[21]), "+f"(d[22]), "+f"(d[23]),
      "+f"(d[24]), "+f"(d[25]), "+f"(d[26]), "+f"(d[27]), "+f"(d[28]), "+f"(d[29]), "+f"(d[30]), "+f"(d[31])
    : "r"(a0), "r"(a1), "r"(a2), "r"(a3), "l"(descB));
  else
  asm volatile("wgmma.mma_async.sync.aligned.m64n64k16.f32.bf16.bf16 "
    "{%0, %1, %2, %3, %4, %5, %6, %7, %8, %9, %10, %11, %12, %13, %14, %15, "
    "%16, %17, %18, %19, %20, %21, %22, %23, %24, %25, %26, %27, %28, %29, %30, %31}, "
    "{%32, %33, %34, %35}, %36, 1, 1, 1, 0;\n"
    : "+f"(d[0]), "+f"(d[1]), "+f"(d[2]), "+f"(d[3]), "+f"(d[4]), "+f"(d[5]), "+f"(d[6]), "+f"(d[7]),
      "+f"(d[8]), "+f"(d[9]), "+f"(d[10]), "+f"(d[11]), "+f"(d[12]), "+f"(d[13]), "+f"(d[14]), "+f"(d[15]),
      "+f"(d[16]), "+f"(d[17]), "+f"(d[18]), "+f"(d[19]), "+f"(d[20]), "+f"(d[21]), "+f"(d[22]), "+f"(d[23]),
      "+f"(d[24]), "+f"(d[25]), "+f"(d[26]), "+f"(d[27]), "+f"(d[28]), "+f"(d[29]), "+f"(d[30]), "+f"(d[31])
    : "r"(a0), "r"(a1), "r"(a2), "r"(a3), "l"(descB));
}

template <int SCALE_D>
__device__ __forceinline__ void wgmma_n56(float (&d)[28], uint32_t a0, uint32_t a1, uint32_t a2, uint32_t a3, uint64_t descB) {
  if (SCALE_D == 0)
  asm volatile("wgmma.mma_async.sync.aligned.m64n56k16.f32.bf16.bf16 "
    "{%0, %1, %2, %3, %4, %5, %6, %7, %8, %9, %10, %11, %12, %13, %14, %15, "
    "%16, %17, %18, %19, %20, %21, %22, %23, %24, %25, %26, %27}, "
    "{%28, %29, %30, %31}, %32, 0, 1, 1, 0;\n"
    : "=f"(d[0]), "=f"(d[1]), "=f"(d[2]), "=f"(d[3]), "=f"(d[4]), "=f"(d[5]), "=f"(d[6]), "=f"(d[7]),
      "=f"(d[8]), "=f"(d[9]), "=f"(d[10]), "=f"(d[11]), "=f"(d[12]), "=f"(d[13]), "=f"(d[14]), "=f"(d[15]),
      "=f"(d[16]), "=f"(d[17]), "=f"(d[18]), "=f"(d[19]), "=f"(d[20]), "=f"(d[21]), "=f"(d[22]), "=f"(d[23]),
      "=f"(d[24]), "=f"(d[25]), "=f"(d[26]), "=f"(d[27])
    : "r"(a0), "r"(a1), "r"(a2), "r"(a3), "l"(descB));
  else
  asm volatile("wgmma.mma_async.sync.aligned.m64n56k16.f32.bf16.bf16 "
    "{%0, %1, %2, %3, %4, %5, %6, %7, %8, %9, %10, %11, %12, %13, %14, %15, "
    "%16, %17, %18, %19, %20, %21, %22, %23, %24, %25, %26, %27}, "
    "{%28, %29, %30, %31}, %32, 1, 1, 1, 0;\n"
    : "+f"(d[0]), "+f"(d[1]), "+f"(d[2]), "+f"(d[3]), "+f"(d[4]), "+f"(d[5]), "+f"(d[6]), "+f"(d[7]),
      "+f"(d[8]), "+f"(d[9]), "+f"(d[10]), "+f"(d[11]), "+f"(d[12]), "+f"(d[13]), "+f"(d[14]), "+f"(d[15]),
      "+f"(d[16]), "+f"(d[17]), "+f"(d[18]), "+f"(d[19]), "+f"(d[20]), "+f"(d[21]), "+f"(d[22]), "+f"(d[23]),
      "+f"(d[24]), "+f"(d[25]), "+f"(d[26]), "+f"(d[27])
    : "r"(a0), "r"(a1), "r"(a2), "r"(a3), "l"(descB));
}

template <int SCALE_D>
__device__ __forceinline__ void wgmma_n56t(float (&d)[28], uint32_t a0, uint32_t a1, uint32_t a2, uint32_t a3, uint64_t descB) {
  if (SCALE_D == 0)
  asm volatile("wgmma.mma_async.sync.aligned.m64n56k16.f32.bf16.bf16 "
    "{%0, %1, %2, %3, %4, %5, %6, %7, %8, %9, %10, %11, %12, %13, %14, %15, "
    "%16, %17, %18, %19, %20, %21, %22, %23, %24, %25, %26, %27}, "
    "{%28, %29, %30, %31}, %32, 0, 1, 1, 1;\n"
    : "=f"(d[0]), "=f"(d[1]), "=f"(d[2]), "=f"(d[3]), "=f"(d[4]), "=f"(d[5]), "=f"(d[6]), "=f"(d[7]),
      "=f"(d[8]), "=f"(d[9]), "=f"(d[10]), "=f"(d[11]), "=f"(d[12]), "=f"(d[13]), "=f"(d[14]), "=f"(d[15]),
      "=f"(d[16]), "=f"(d[17]), "=f"(d[18]), "=f"(d[19]), "=f"(d[20]), "=f"(d[21]), "=f"(d[22]), "=f"(d[23]),
      "=f"(d[24]), "=f"(d[25]), "=f"(d[26]), "=f"(d[27])
    : "r"(a0), "r"(a1), "r"(a2), "r"(a3), "l"(descB));
  else
  asm volatile("wgmma.mma_async.sync.aligned.m64n56k16.f32.bf16.bf16 "
    "{%0, %1, %2, %3, %4, %5, %6, %7, %8, %9, %10, %11, %12, %13, %14, %15, "
    "%16, %17, %18, %19, %20, %21, %22, %23, %24, %25, %26, %27}, "
    "{%28, %29, %30, %31}, %32, 1, 1, 1, 1;\n"
    : "+f"(d[0]), "+f"(d[1]), "+f"(d[2]), "+f"(d[3]), "+f"(d[4]), "+f"(d[5]), "+f"(d[6]), "+f"(d[7]),
      "+f"(d[8]), "+f"(d[9]), "+f"(d[10]), "+f"(d[11]), "+f"(d[12]), "+f"(d[13]), "+f"(d[14]), "+f"(d[15]),
      "+f"(d[16]), "+f"(d[17]), "+f"(d[18]), "+f"(d[19]), "+f"(d[20]), "+f"(d[21]), "+f"(d[22]), "+f"(d[23]),
      "+f"(d[24]), "+f"(d[25]), "+f"(d[26]), "+f"(d[27])
    : "r"(a0), "r"(a1), "r"(a2), "r"(a3), "l"(descB));
}

__global__ void __launch_bounds__(384) prepack_kernel(const __nv_bfloat16* __restrict__ wqkv, const __nv_bfloat16* __restrict__ wo) {
  asm volatile("griddepcontrol.launch_dependents;");
  __nv_bfloat16* dst = reinterpret_cast<__nv_bfloat16*>(g_wpack);
  const int c = threadIdx.x, nb = blockIdx.x * 2 + threadIdx.y;
  if (nb < 72) {
    __shared__ float red2[2][6][8];
    float (*red)[8] = red2[threadIdx.y];
    const int h = nb / 18, j = nb % 18, part = j / 6;
    const int col = (part == 0 ? 192 : part == 1 ? 0 : 384) + h * 48 + (j % 6) * 8;
    uint4 raw = *reinterpret_cast<const uint4*>(wqkv + c * 576 + col);
    uint32_t u[4] = {raw.x, raw.y, raw.z, raw.w};
    float v[8];
#pragma unroll
    for (int i = 0; i < 4; i++) { v[2 * i] = lo2f(u[i]); v[2 * i + 1] = hi2f(u[i]); }
#pragma unroll
    for (int i = 0; i < 8; i++) {
      float s = v[i];
#pragma unroll
      for (int o = 16; o; o >>= 1) s += __shfl_xor_sync(~0u, s, o);
      if ((c & 31) == 0) red[c >> 5][i] = s;
    }
    __syncthreads();
    const int cc = c >> 5, q = (c >> 3) & 3, s1 = (c >> 2) & 1, hh = (c >> 1) & 1, e = c & 1;
    const int base = h * 27648 + (2 * cc + s1) * 2304 + j * 128 + hh * 64 + 2 * q + e;
#pragma unroll
    for (int n = 0; n < 8; n++) {
      float m = (red[0][n] + red[1][n] + red[2][n] + red[3][n] + red[4][n] + red[5][n]) * (1.0f / 192.0f);
      dst[base + n * 8] = __float2bfloat16((v[n] - m) * (part == 1 ? 0.14433756729740643f * 1.4426950408889634f : 1.0f));
    }
  } else {
    const int jb = nb - 72, chunk = jb / 8, j = jb % 8;
    const int s = c >> 4, hh = (c >> 3) & 1, kk = c & 7;
    const int base = 110592 + (chunk * 12 + s) * 1024 + j * 128 + hh * 64 + kk;
#pragma unroll
    for (int n = 0; n < 8; n++) {
      const int ch = 32 * (jb >> 2) + 8 * (n >> 1) + 2 * (jb & 3) + (n & 1);
      dst[base + n * 8] = wo[c * 192 + ch];
    }
  }
}

__device__ __forceinline__ int window_of(int round, int nfull, int cta, int ncta, int wg) {
  if (round < nfull) return round * 2 * ncta + 2 * cta + wg;
  const int rem = NWIN - nfull * 2 * ncta;
  const int i = cta + wg * ncta;
  return i < rem ? nfull * 2 * ncta + i : -1;
}

__host__ __device__ constexpr int qkv_off(int h, int s) { return ((3 * h + s / 4) % 8) * SLICE + (s % 4) * 4608; }
__host__ __device__ constexpr int wo_off(int chunk, int s) { return 4 * SLICE + (chunk * 12 + s) * 2048; }

#define DEF_ISSUE(NAME, NREG, FN, FIRST)                                                                          \
  template <int S0, int S1, int INIT = FIRST>                                                                     \
  __device__ __forceinline__ void NAME(float (&acc)[NREG], const uint32_t (&A)[48], const uint64_t* d) {          \
    wg_fence();                                                                                                   \
    _Pragma("unroll") for (int s = S0; s < S1; s++) {                                                             \
      if (s == 0) FN<INIT>(acc, A[4 * s], A[4 * s + 1], A[4 * s + 2], A[4 * s + 3], d[s]);                        \
      else        FN<1>(acc, A[4 * s], A[4 * s + 1], A[4 * s + 2], A[4 * s + 3], d[s]);                           \
    }                                                                                                             \
    wg_commit();                                                                                                  \
  }
DEF_ISSUE(mma144, 72, wgmma_n144, 0)
DEF_ISSUE(mma96, 48, wgmma_n96, 0)
DEF_ISSUE(mma48, 24, wgmma_n48, 0)
DEF_ISSUE(mma64, 32, wgmma_n64, 0)
#undef DEF_ISSUE

#define PIN() asm volatile("pmevent 0;" ::: "memory")
template <int A, int B> __device__ __forceinline__ void hold(uint32_t* v) {
#pragma unroll
  for (int i = A; i < B; i++) asm volatile("" : "+r"(v[i]));
}
template <int A, int B> __device__ __forceinline__ void packn(uint32_t* d, const float* a) {
#pragma unroll
  for (int i = A; i < B; i++) d[i] = pack2(a[2 * i], a[2 * i + 1]);
}
template <int A, int B> __device__ __forceinline__ void scalen(uint32_t* d, uint32_t r) {
#pragma unroll
  for (int i = A; i < B; i++) d[i] = (i & 1) ? hmul_b<1>(d[i], r) : hmul_b<0>(d[i], r);
}
__device__ __forceinline__ void stsm12(const uint32_t* v, uint32_t addr) {
#pragma unroll
  for (int j = 0; j < 3; j++) stsm4(addr + 2 * j * KV_PITCH, v[4 * j], v[4 * j + 1], v[4 * j + 2], v[4 * j + 3]);
}
__device__ __forceinline__ uint32_t inv_sum(const float (&o)[28]) {
  float i0, i1;
  asm("rcp.approx.ftz.f32 %0, %1;" : "=f"(i0) : "f"(o[24]));
  asm("rcp.approx.ftz.f32 %0, %1;" : "=f"(i1) : "f"(o[26]));
  return pack2(i0, i1);
}
__device__ __forceinline__ void proxy_fence() { asm volatile("fence.proxy.async.shared::cta;" ::: "memory"); }
__device__ __forceinline__ void issue_s(float (&S)[28], const uint32_t (&Q)[12], const uint64_t* d) {
  wg_fence();
  wgmma_n56<0>(S, Q[0], Q[1], Q[2], Q[3], d[0]);
  wgmma_n56<1>(S, Q[4], Q[5], Q[6], Q[7], d[1]);
  wgmma_n56<1>(S, Q[8], Q[9], Q[10], Q[11], d[2]);
  wg_commit();
}
struct H2 { uint16_t l, h; };
__device__ __forceinline__ H2 exp_halves(uint32_t a) {
  H2 r;
  asm("{\n.reg .b16 l, h;\nmov.b32 {l, h}, %2;\nex2.approx.ftz.bf16 %0, l;\nex2.approx.ftz.bf16 %1, h;\n}\n" : "=h"(r.l), "=h"(r.h) : "r"(a));
  return r;
}
__device__ __forceinline__ uint32_t join(H2 v) { uint32_t r; asm("mov.b32 %0, {%1, %2};" : "=r"(r) : "h"(v.l), "h"(v.h)); return r; }
__device__ __forceinline__ void hold(H2& v) { asm volatile("" : "+h"(v.l), "+h"(v.h)); }

template <int SEC, int NK, bool PREV, class G>
__device__ __forceinline__ void softmax_pv(float (&S)[28], const uint64_t* dV, uint32_t* Op, uint32_t inv, int wg, bool pass, G g) {
#define GK(k) if ((k) < NK) g(IC<((k) < NK ? (k) : 0)>{}, IC<((k) < NK ? (k) + 1 : 0)>{}); if ((k) == (PASS_AT < NK ? PASS_AT : NK - 1) && (SEC != PP_LAST || pass)) turn_pass<SEC>(wg);
  uint32_t P[16];
  GK(2) packn<0, 4>(P, S);  if (PREV) { scalen<0, 4>(Op, inv); hold<0, 4>(Op); }   hold<0, 4>(P); PIN();
  GK(3) packn<4, 9>(P, S);  if (PREV) { scalen<4, 8>(Op, inv); hold<4, 8>(Op); }   hold<4, 9>(P); PIN();
  GK(4) packn<9, 12>(P, S); P[12] = pack2(S[24], S[26]);
  if (PREV) { scalen<8, 12>(Op, inv); hold<8, 12>(Op); } hold<9, 13>(P); PIN();
  GK(5)
  uint32_t m0 = hmax(hmax(hmax(hmax(hmax(P[0], P[2]), P[4]), P[6]), P[8]), P[10]);
  uint32_t m1 = hmax(hmax(hmax(hmax(hmax(P[1], P[3]), P[5]), P[7]), P[9]), P[11]);
  uint32_t mx = hmax(hmax(__byte_perm(m0, m1, 0x5410), __byte_perm(m0, m1, 0x7632)), P[12]);
  uint32_t sh = __shfl_xor_sync(~0u, mx, 1);
  PIN();
  GK(6)
  PIN();
  mx = hmax(mx, sh);
  sh = __shfl_xor_sync(~0u, mx, 2);
  PIN();
  GK(7)
  PIN();
  mx = hmax(mx, sh);
#pragma unroll
  for (int j = 0; j < 12; j++) P[j] = (j & 1) ? hsub_b<1>(P[j], mx) : hsub_b<0>(P[j], mx);
  P[12] = b2u(__hsub2_rn(u2b(P[12]), u2b(mx)));
  H2 e0 = exp_halves(P[0]), e1 = exp_halves(P[1]);
  GK(8)
  hold<2, 13>(P); hold(e0); hold(e1); PIN();
  GK(9)
  H2 e2 = exp_halves(P[2]), e3 = exp_halves(P[3]);
  P[0] = join(e0); P[1] = join(e1);
  hold<0, 2>(P); hold(e2); hold(e3); PIN();
  GK(10)
  e0 = exp_halves(P[4]); e1 = exp_halves(P[5]);
  P[2] = join(e2); P[3] = join(e3);
  hold<2, 4>(P); hold(e0); hold(e1); PIN();
  GK(11)
  PIN();
  proxy_fence();
  e2 = exp_halves(P[12]);
  P[12] = e2.l; P[13] = e2.h; P[14] = 0; P[15] = 0;
  P[4] = join(e0); P[5] = join(e1);
#pragma unroll
  for (int j = 6; j < 12; j++) P[j] = hex2(P[j]);
  bar_sync(1 + wg);
  wg_fence();
  wgmma_n56t<0>(S, P[0], P[1], P[2], P[3], dV[0]);
  wgmma_n56t<1>(S, P[4], P[5], P[6], P[7], dV[1]);
  wgmma_n56t<1>(S, P[12], P[13], P[14], P[15], dV[3]);
  wgmma_n56t<1>(S, P[8], P[9], P[10], P[11], dV[2]);
  wg_commit();
#undef GK
}
template <int S0, int S1>
__device__ __forceinline__ void load_x(uint32_t (&X)[48], uint32_t t0) {
#pragma unroll
  for (int s = S0; s < S1; s++)
    asm volatile("ld.shared.v4.u32 {%0,%1,%2,%3}, [%4];" : "=r"(X[4 * s]), "=r"(X[4 * s + 1]), "=r"(X[4 * s + 2]), "=r"(X[4 * s + 3])
                 : "r"(((s & 1) ? (t0 ^ 16) : t0) + (s >> 1) * 128) : "memory");
}

template <int C, int A, int B> __device__ __forceinline__ void add_res(uint32_t* T, const uint32_t (&X)[48]) {
#pragma unroll
  for (int i = A; i < B; i++) T[i] = hadd(X[16 * C + i], T[i]);
}
template <int C>
__device__ __forceinline__ void store_out(const uint32_t* T, uint8_t* o0, uint8_t* o1) {
#pragma unroll
  for (int c = 0; c < 2; c++) {
    asm volatile("st.global.v4.u32 [%0], {%1,%2,%3,%4};" :: "l"(o0 + C * 128 + c * 64), "r"(T[8 * c]), "r"(T[8 * c + 2]), "r"(T[8 * c + 4]), "r"(T[8 * c + 6]) : "memory");
    asm volatile("st.global.v4.u32 [%0], {%1,%2,%3,%4};" :: "l"(o1 + C * 128 + c * 64), "r"(T[8 * c + 1]), "r"(T[8 * c + 3]), "r"(T[8 * c + 5]), "r"(T[8 * c + 7]) : "memory");
  }
}

#define WDIV 1
template <int K, int CNT, int DIV = WDIV> __device__ __forceinline__ void load_slices(uint32_t sb, const Descs& ds) {
  constexpr int st = K < 12 ? K / 3 : 4 + (K - 12) / 2;
  constexpr bool first = K < 12 ? (K % 3 == 0) : (K % 2 == 0);
  if (first)
    asm volatile("{\n.reg .pred p;\nelect.sync _|p, 0xffffffff;\n@p mbarrier.arrive.expect_tx.shared::cta.b64 _, [%0], %1;\n}\n"
                 :: "r"(sb + BAR_WFULL + 8 * st), "n"(DIV == 1 && K == 6 ? 2 * SLICE + SLICE / WDIV : (K < 12 ? 3 : 2) * SLICE / DIV) : "memory");
  asm volatile("{\n.reg .pred p;\nelect.sync _|p, 0xffffffff;\n"
               "@p cp.async.bulk.shared::cluster.global.mbarrier::complete_tx::bytes [%0], [%1], %2, [%3];\n}\n"
               :: "r"(sb + OFF_W + (K & 7) * SLICE), "l"(ds.src[K]), "n"(CNT * SLICE / DIV), "r"(sb + BAR_WFULL + 8 * st) : "memory");
}
template <int STAGE> __device__ __forceinline__ void release(uint32_t sb, const Descs& ds, bool next_round) {
  uint32_t old;
  asm volatile("{\n.reg .b32 a;\nmov.u32 a, %%laneid;\nmad.lo.u32 a, a, 4, %1;\natom.shared.inc.u32 %0, [a + %2], 1;\n}\n"
               : "=r"(old) : "r"(sb), "n"(CNT_WREL + 128 * STAGE) : "memory");
  if (__ballot_sync(0xffffffffu, old == 1) & 1) {
    if (STAGE == 0) { load_slices<8, 1>(sb, ds); load_slices<9, 2>(sb, ds); }
    if (STAGE == 1) { load_slices<11, 1>(sb, ds); load_slices<12, 2>(sb, ds); }
    if (STAGE == 2) { load_slices<14, 2>(sb, ds); if (next_round) load_slices<0, 1>(sb, ds); }
    if (STAGE == 3 && next_round) { load_slices<1, 2>(sb, ds); load_slices<3, 1>(sb, ds); }
    if (STAGE == 4 && next_round) load_slices<4, 2>(sb, ds);
    if (STAGE == 5 && next_round) load_slices<6, 2>(sb, ds);
  }
}

__device__ __forceinline__ uint32_t ln_rstd(const uint32_t (&X)[48]) {
  uint32_t sm[2];
#pragma unroll
  for (int a = 0; a < 2; a++) {
    uint32_t t[12];
#pragma unroll
    for (int i = 0; i < 12; i++) t[i] = hadd(X[4 * i + a], X[4 * i + 2 + a]);
#pragma unroll
    for (int i = 0; i < 6; i++) t[i] = hadd(t[i], t[i + 6]);
#pragma unroll
    for (int i = 0; i < 3; i++) t[i] = hadd(t[i], t[i + 3]);
    sm[a] = hadd(hadd(t[0], t[1]), t[2]);
  }
  uint32_t m = hadd(__byte_perm(sm[0], sm[1], 0x5410), __byte_perm(sm[0], sm[1], 0x7632));
  m = hadd(m, __shfl_xor_sync(~0u, m, 1));
  m = hadd(m, __shfl_xor_sync(~0u, m, 2));
  m = hmul(m, 0x3bab3babu);
  float var[2];
#pragma unroll
  for (int a = 0; a < 2; a++) {
    uint32_t t[4];
#pragma unroll
    for (int i = 0; i < 24; i++) {
      const uint32_t d = a ? hsub_b<1>(X[2 * i + 1], m) : hsub_b<0>(X[2 * i], m);
      t[i & 3] = i < 4 ? hmul(d, d) : hfma(d, d, t[i & 3]);
    }
    const uint32_t s = hadd(hadd(t[0], t[1]), hadd(t[2], t[3]));
    float v = lo2f(s) + hi2f(s);
    v += __shfl_xor_sync(~0u, v, 1);
    v += __shfl_xor_sync(~0u, v, 2);
    asm("rsqrt.approx.ftz.f32 %0, %1;" : "=f"(var[a]) : "f"(fmaf(v, 1.0f / 192.0f, 1e-5f)));
  }
  return pack2(var[0], var[1]);
}

#define DUMMY()
__device__ __forceinline__ void stats_pass(uint32_t sb, int pass, int lane) {
  const int g = lane >> 2, q = lane & 3;
  const int tile = pass < 6 ? (pass & 1) : (g & 1);
  const int ps = pass < 6 ? (pass >> 1) * 8 + g : 24;
  uint32_t X[48];
  load_x<0, 12>(X, sb + OFF_TILE + tile * TILE_BYTES + ps * 768 + q * 32 + (ps & 1) * 16);
  const uint32_t rs = ln_rstd(X);
  asm volatile("st.shared.u32 [%0], %1;" :: "r"(sb + OFF_RSTD + tile * 100 + ps * 4), "r"(rs) : "memory");
}

__global__ void __launch_bounds__(384, 1)
fused_kernel(const __grid_constant__ CUtensorMap tmx, const __grid_constant__ CUtensorMap tmp, const __grid_constant__ Descs ds, const __nv_bfloat16* __restrict__ dw, __nv_bfloat16* __restrict__ out, const int never) {
  extern __shared__ __align__(1024) uint8_t smem[];
  const uint32_t sb = (uint32_t)__cvta_generic_to_shared(smem);
  const int tid = threadIdx.x, lane = tid & 31;
  const int warp = __shfl_sync(0xffffffffu, tid >> 5, 0);
  const int cta = blockIdx.x, ncta = gridDim.x;
  const int nfull = NWIN / (2 * ncta);
  const int nrounds = nfull + ((NWIN - nfull * 2 * ncta) > cta ? 1 : 0);

  if (warp == 0) GTS(0);
  auto prefetch_round = [&](int r) {
#pragma unroll
    for (int k = 0; k < 2; k++) {
      const int w = window_of(r, nfull, cta, ncta, k);
      if (w >= 0) {
        const int a = w / NWX;
        asm volatile("{\n.reg .pred p;\nelect.sync _|p, 0xffffffff;\n@p cp.async.bulk.prefetch.tensor.3d.L2.global [%0, {0, %1, %2}];\n}\n"
                     :: "l"(reinterpret_cast<uint64_t>(&tmp)), "r"((w - a * NWX) * 7 - 1), "r"(a * 7 - 1) : "memory");
      }
    }
  };
  if (warp == 11) prefetch_round(0);
  if (warp == 10 && lane == 0) asm volatile("prefetch.tensormap [%0];" :: "l"(reinterpret_cast<uint64_t>(&tmx)) : "memory");
  if (tid == 0) {
    if ((sb & 0x3FFFF) != SMEM_BASE) __trap();
    for (int i = 0; i < 6; i++) { mbar_init(sb + BAR_WFULL + 8 * i, 1); }
    for (int i = 0; i < 9; i++) mbar_init(sb + BAR_XFULL + 8 * i, 1);
    mbar_init(sb + BAR_TFULL, 3);
    mbar_init(sb + BAR_TEMPTY, 8);
    mbar_init(sb + BAR_TPART, 3);
    mbar_init(sb + BAR_TPART + 8, 3);
    mbar_init(sb + BAR_SFULL, 4);
    asm volatile("fence.mbarrier_init.release.cluster;" ::: "memory");
  }
  if (tid >= 128 && tid < 320) *reinterpret_cast<uint32_t*>(smem + CNT_WREL + (tid - 128) * 4) = 0;
  if (tid < 128) {
    const uint32_t v = (tid & 63) < 49 ? 0x3f803f80u : 0u;
    *reinterpret_cast<uint4*>(smem + OFF_KV + (tid >> 6) * KV_BYTES + 6 * KV_PITCH + (tid & 63) * 16) = make_uint4(v, v, v, v);
    asm volatile("fence.proxy.async.shared::cta;" ::: "memory");
  }
  __syncthreads();

  if (warp >= 8) {
    asm volatile("setmaxnreg.dec.sync.aligned.u32 " PREGS ";");
    if (warp == 11) {
      asm volatile("griddepcontrol.wait;" ::: "memory");
      load_slices<0, 3, 1>(sb, ds); load_slices<3, 3, 1>(sb, ds); load_slices<6, 2, 1>(sb, ds);
      for (int r = 0; r < nrounds; r++) {
#pragma unroll 1
        for (int pass = 0; pass < 4; pass++) {
          if (!(pass & 1)) mbar_wait(sb + BAR_TPART + 4 * pass, r & 1);
          stats_pass(sb, pass, lane);
        }
        __syncwarp();
        if (lane == 0) mbar_arrive(sb + BAR_SFULL);
        DUMMY();
        TR(2);
      }
    } else {
      const int cw = warp - 8;
      const int win = lane >> 4;
      const int ch0 = cw * 64 + (lane & 15) * 4;
      uint32_t wt[9][2];
#pragma unroll
      for (int t = 0; t < 9; t++) {
        uint2 v = *reinterpret_cast<const uint2*>(dw + t * CH + ch0);
        wt[t][0] = v.x; wt[t][1] = v.y;
      }
      const uint32_t xs = sb + OFF_X + cw * 3 * XSLOT;
      const uint32_t xld = xs + (lane >> 4) * 1152 + (lane & 15) * 8;
      const uint32_t xbar = sb + BAR_XFULL + cw * 24;
      const uint32_t st0 = sb + OFF_TILE + win * TILE_BYTES + ch0 * 4;
      const uint32_t st1 = sb + OFF_TILE + win * TILE_BYTES + ((ch0 * 4) ^ 16);
      const uint64_t tm = reinterpret_cast<uint64_t>(&tmx);
      int cx0, cy0, cx1, cy1;
      auto coords = [&](int r) {
        const int w0 = window_of(r, nfull, cta, ncta, 0);
        int w1 = window_of(r, nfull, cta, ncta, 1);
        if (w1 < 0) w1 = w0;
        const int a = w0 / NWX, b = w1 / NWX;
        cx0 = (w0 - a * NWX) * 7 - 1; cy0 = a * 7 - 1;
        cx1 = (w1 - b * NWX) * 7 - 1; cy1 = b * 7 - 1;
      };
      auto issue = [&](int slot, int dy) {
        asm volatile("{\n.reg .pred p;\nelect.sync _|p, 0xffffffff;\n"
                     "@p mbarrier.arrive.expect_tx.shared::cta.b64 _, [%2], %8;\n"
                     "@p cp.async.bulk.tensor.3d.shared::cluster.global.mbarrier::complete_tx::bytes [%0], [%1, {%3, %4, %5}], [%2];\n"
                     "@p cp.async.bulk.tensor.3d.shared::cluster.global.mbarrier::complete_tx::bytes [%0 + 1152], [%1, {%3, %6, %7}], [%2];\n}\n"
                     :: "r"(xs + slot * XSLOT), "l"(tm), "r"(xbar + slot * 8), "r"(cw * 64), "r"(cx0), "r"(cy0 + dy), "r"(cx1), "r"(cy1 + dy), "n"(XSLOT) : "memory");
      };
      coords(0);
      issue(0, 0); issue(1, 1); issue(2, 2);
      for (int r = 0; r < nrounds; r++) {
        const bool more = r + 1 < nrounds;
        uint32_t accA[7][2], accB[7][2], ctr[7][2], held[2];
#pragma unroll
        for (int i = 0; i < 9; i++) {
          mbar_wait(xbar + (i % 3) * 8, (r + i / 3) & 1);
          if (i == 0 && r == 0 && cw == 0) GTS(7);
          if (i == 5 || i == 7) { __syncwarp(); if (lane == 0) mbar_arrive(sb + BAR_TPART + (i == 5 ? 0 : 8)); }
          if (i == 7 && more) coords(r + 1);
          if (i == 0) { if (r > 0) issue(2, 2); }
          else if (i < 7) issue((i + 2) % 3, i + 2);
          else if (more) issue((i + 2) % 3, i - 7);
          if (i == 2 && r > 0) mbar_wait(sb + BAR_TEMPTY, (r - 1) & 1);
          if (i == 2) { TR(0); }
          uint32_t cur[9][2];
#pragma unroll
          for (int p = 0; p < 5; p++)
            asm volatile("ld.shared.v2.u32 {%0,%1}, [%2];" : "=r"(cur[p][0]), "=r"(cur[p][1]) : "r"(xld + (i % 3) * XSLOT + p * 128));
#pragma unroll
          for (int j = 0; j < 7; j++) {
            if (j >= 1 && j + 4 < 9)
              asm volatile("ld.shared.v2.u32 {%0,%1}, [%2];" : "=r"(cur[j + 4][0]), "=r"(cur[j + 4][1]) : "r"(xld + (i % 3) * XSLOT + (j + 4) * 128));
            if (i >= 2) {
              uint32_t o[2];
#pragma unroll
              for (int e = 0; e < 2; e++) {
                uint32_t a = hfma(cur[j][e], wt[6][e], accA[j][e]);
                a = hfma(cur[j + 1][e], wt[7][e], a);
                a = hfma(cur[j + 2][e], wt[8][e], a);
                o[e] = hadd(ctr[j][e], a);
              }
              const int tok = (i - 2) * 7 + j, ps = tok >> 1;
              if (!(tok & 1)) { held[0] = o[0]; held[1] = o[1]; }
              if ((tok & 1) || tok == 48)
                asm volatile("st.shared.v4.u32 [%0], {%1,%2,%3,%4};" :: "r"(((ps & 1) ? st1 : st0) + ps * 768), "r"(held[0]), "r"(o[0]), "r"(held[1]), "r"(o[1]) : "memory");
            }
#pragma unroll
            for (int e = 0; e < 2; e++) {
              if (i >= 1 && i <= 7) {
                uint32_t a = hfma(cur[j][e], wt[3][e], accB[j][e]);
                a = hfma(cur[j + 1][e], wt[4][e], a);
                accA[j][e] = hfma(cur[j + 2][e], wt[5][e], a);
                ctr[j][e] = cur[j + 1][e];
              }
              if (i <= 6) {
                uint32_t a = hmul(cur[j][e], wt[0][e]);
                a = hfma(cur[j + 1][e], wt[1][e], a);
                accB[j][e] = hfma(cur[j + 2][e], wt[2][e], a);
              }
            }
          }
        }
        __syncwarp();
        if (lane == 0) mbar_arrive(sb + BAR_TFULL);
        TR(1);
        mbar_wait(sb + BAR_TFULL, r & 1);
        stats_pass(sb, 4 + cw, lane);
        __syncwarp();
        if (lane == 0) mbar_arrive(sb + BAR_SFULL);
        DUMMY();
      }
    }
  } else {
    asm volatile("setmaxnreg.inc.sync.aligned.u32 " CREGS ";");
    const int wg = warp >> 2, w4 = warp & 3, g = lane >> 2, q = lane & 3;
    const int row0 = w4 * 16 + g, row1 = row0 + 8;
    const int ps = min(w4 * 8 + g, 24);
    const int tok0 = 2 * ps, tok1 = min(2 * ps + 1, 48);
    const uint32_t kv = sb + OFF_KV + wg * KV_BYTES;
    const int srow = w4 * 16 + (lane & 15);
    const uint32_t vst = kv + (lane >> 4) * KV_PITCH + (srow < 56 ? srow : min(srow - 7, 55)) * 16;
    uint32_t misc = ((uint32_t)((tok1 / 7) * IMG + tok1 % 7) << 20) | ((uint32_t)((tok0 / 7) * IMG + tok0 % 7) << 8) | (ps * 4 + q);
    const uint32_t vmask = (row0 < 49 ? 0xffffu : 0u) | (row1 < 49 ? 0xffff0000u : 0u);

    const uint32_t tx = sb + OFF_TILE + wg * TILE_BYTES + ps * 768 + q * 32 + (ps & 1) * 16;
    const int myrounds = window_of(nrounds - 1, nfull, cta, ncta, wg) < 0 ? nrounds - 1 : nrounds;

    if (never == 2) return;
    uint32_t X[48];
    float acc[72];
    if (warp == 0) GTS(1);
    mbar_wait(sb + BAR_TFULL, 0);
    if (warp == 0) GTS(2);
    load_x<0, 12>(X, tx);
    mbar_wait(sb + BAR_WFULL, 0);
    if (warp == 0) GTS(3);
    mma144<0, 12>(acc, X, ds.q[0]);
    uint32_t rK;
    mbar_wait(sb + BAR_SFULL, 0);
    if (warp == 0) GTS(4);
    asm volatile("ld.shared.u32 %0, [%1];" : "=r"(rK) : "r"(sb + OFF_RSTD + wg * 100 + (misc & 0xfc)) : "memory");
    __syncwarp();
    if (lane == 0) mbar_arrive(sb + BAR_TEMPTY);

    if (wg == 1) turn_pass<PP_LAST>(1);
    for (int r = 0;; r++) {
      const uint32_t par = r & 1;
      if (r == myrounds) {
        wg_wait<0>(); keep(acc);
        if (w4 == 0) GTS(5 + wg);
        if (r < nrounds)
        {
          mbar_wait(sb + BAR_WFULL, par);      if (w4 == 3) release<0>(sb, ds, false);
          mbar_wait(sb + BAR_WFULL + 8, par);  if (w4 == 3) release<1>(sb, ds, false);
          turn_wait<0>(wg); if (PP_LAST != 0) turn_pass<0>(wg);
          mbar_wait(sb + BAR_WFULL + 16, par); if (w4 == 3) release<2>(sb, ds, false);
          turn_wait<1>(wg); if (PP_LAST != 1) turn_pass<1>(wg);
          turn_wait<2>(wg); if (PP_LAST != 2) turn_pass<2>(wg);
          turn_wait<3>(wg); if (PP_LAST != 3) turn_pass<3>(wg);
          turn_wait<4>(wg); if (PP_LAST != 4) turn_pass<4>(wg);
          turn_wait<5>(wg);
        }
        break;
      }
      TR(0);
      const bool next_round = r + 1 < nrounds;
      const bool pass = wg == 0 || next_round;
      const uint32_t rV = rK & vmask;
      uint32_t Of[48], Q[12], T[16], inv = 0;
      float S[28];
      const uint64_t* dkv = ds.kv[wg];

#define PRE(H, ACC)                                                                     \
      packn<0, 12>(T, ACC); scalen<0, 12>(T, rK); stsm12(T, vst + KV_KOFF);                       \
      packn<0, 12>(T, ACC + 24); hold<0, 12>(T);                                        \
      PIN();                                                                            \
      if (H > 0) { wg_wait<0>(); keep(S); }                                             \
      proxy_fence();                                                                    \
      _Pragma("unroll") for (int i = 0; i < 12; i++) Q[i] = T[i];                       \
      scalen<0, 12>(Q, rK); hold<0, 12>(Q);
#define PRE2(H)                                                                         \
      if (H > 0) { inv = inv_sum(S); packn<0, 12>(Of + 12 * (H > 0 ? H - 1 : 0), S);    \
                   hold<0, 12>(Of + 12 * (H > 0 ? H - 1 : 0)); hold<0, 1>(&inv); }
#define MID(H, VACC, FIRST2)                                                             \
      PIN();                                                                            \
      packn<0, 12>(T, VACC); scalen<0, 12>(T, rV); stsm12(T, vst);                      \
      turn_wait<H>(wg);                                                                 \
      PIN();                                                                            \
      FIRST2;                                                                           \
      if (H < 3 && w4 == 3) release<(H < 3 ? H : 0)>(sb, ds, next_round);               \
      wg_wait<1>(); keep(S);

      wg_wait<0>(); keep(acc);
      TR(2);
      PRE(0, acc) PRE2(0)
      mbar_wait(sb + BAR_WFULL + 8, par);
      bar_sync(1 + wg);
      TR(3);
      issue_s(S, Q, dkv);
      MID(0, acc + 48, (mma144<0, 2>(acc, X, ds.q[1])))
      TR(4);
      softmax_pv<0, 12, false>(S, dkv + 4, Of, inv, wg, pass, [&](auto a, auto b) { mma144<a.v, b.v>(acc, X, ds.q[1]); });
      TR(5);
      wg_wait<1>(); keep(acc);
      TR(6);
      PRE(1, acc) PRE2(1)
      mbar_wait(sb + BAR_WFULL + 16, par);
      bar_sync(1 + wg);
      TR(7);
      issue_s(S, Q, dkv);
      MID(1, acc + 48, (mma144<0, 2>(acc, X, ds.q[2])))
      TR(8);
      softmax_pv<1, 12, true>(S, dkv + 4, Of, inv, wg, pass, [&](auto a, auto b) { mma144<a.v, b.v>(acc, X, ds.q[2]); });
      TR(9);
      float kq[48], va[24], pa[32], pb[32];
      wg_wait<1>(); keep(acc);
      TR(10);
      PRE(2, acc) PRE2(2)
      mbar_wait(sb + BAR_WFULL + 24, par);
      bar_sync(1 + wg);
      TR(11);
      issue_s(S, Q, dkv);
      MID(2, acc + 48, (mma96<0, 2>(kq, X, ds.q[3])))
      TR(12);
      softmax_pv<2, 12, true>(S, dkv + 4, Of + 12, inv, wg, pass, [&](auto a, auto b) { mma96<a.v, b.v>(kq, X, ds.q[3]); });
      TR(13);
      wg_wait<1>(); keep(kq);
      TR(14);
      packn<0, 12>(T, kq); scalen<0, 12>(T, rK); stsm12(T, vst + KV_KOFF); PIN();
      wg_wait<0>(); keep(S);
      mma48<0, 4>(va, X, ds.v3);
      packn<0, 6>(Q, kq + 24); scalen<0, 6>(Q, rK); hold<0, 6>(Q); PIN();
      mma48<4, 8>(va, X, ds.v3);
      packn<6, 12>(Q, kq + 24); scalen<6, 12>(Q, rK); hold<6, 12>(Q); PIN();
      mma48<8, 12>(va, X, ds.v3);
      PIN();
      proxy_fence();
      PRE2(3)
      mbar_wait(sb + BAR_WFULL + 32, par);
      bar_sync(1 + wg);
      TR(15);
      issue_s(S, Q, dkv);
      wg_wait<1>(); keep(va);
      MID(3, va, (mma64<0, 2>(pa, Of, ds.p)))
      TR(16);
      softmax_pv<3, 9, true>(S, dkv + 4, Of + 24, inv, wg, pass, [&](auto a, auto b) { mma64<a.v, b.v>(pa, Of, ds.p); });
      if (w4 == 3) release<3>(sb, ds, next_round);
      TR(17);
#undef PRE
#undef PRE2
#undef MID
      const bool more = r + 1 < myrounds;
      const int w = window_of(r, nfull, cta, ncta, wg);
      const int wy = w / NWX, wx = w - wy * NWX;
      asm volatile("" : "+r"(misc));
      const uint32_t wb = (uint32_t)(wy * 7 * IMG + wx * 7) * 384u + (misc & 3) * 16;
      uint8_t* o0 = reinterpret_cast<uint8_t*>(out) + (wb + ((misc >> 8) & 0xfff) * 384u);
      uint8_t* o1 = reinterpret_cast<uint8_t*>(out) + (wb + (misc >> 20) * 384u);
      mbar_wait(sb + BAR_WFULL + 40, par);
      wg_wait<0>(); keep(S); keep(pa);
      TR(18);
      inv = inv_sum(S); packn<0, 12>(Of + 36, S); hold<36, 48>(Of); turn_wait<4>(wg); PIN();
      mma64<0, 5>(pb, Of, ds.p + 12);
      scalen<36, 48>(Of, inv); hold<36, 48>(Of); PIN();
      mma64<9, 12>(pa, Of, ds.p);
      mma64<5, 12>(pb, Of, ds.p + 12);
      if (more) mbar_wait(sb + BAR_TFULL, par ^ 1);
      TR(19);
      wg_wait<1>(); keep(pa);
      TR(20);
      packn<0, 16>(T, pa); add_res<0, 0, 12>(T, X); hold<0, 16>(T); PIN();
      mma64<0, 3, 2>(pa, Of, ds.p + 24);
      add_res<0, 12, 16>(T, X); hold<12, 16>(T); PIN();
      load_x<0, 4>(X, tx); store_out<0>(T, o0, o1); PIN();
      mma64<3, 12>(pa, Of, ds.p + 24);
      if (PP_LAST != 4 || pass) turn_pass<4>(wg);
      PIN();
      TR(21);
      wg_wait<2>(); keep(pb);
      bar_sync(1 + wg);
      packn<0, 16>(T, pb); add_res<1, 0, 16>(T, X); hold<0, 16>(T); PIN();
      if (w4 == 3) release<4>(sb, ds, next_round);
      load_x<4, 8>(X, tx); store_out<1>(T, o0, o1);
      if (more) mbar_wait(sb + BAR_WFULL, par ^ 1);
      TR(22);
      wg_wait<0>(); keep(pa);
      TR(23);
      if (PPMASK >> 5 & 1) turn_wait<5>(wg); else bar_sync(1 + wg);
      mma144<0, 1>(acc, X, ds.q[0]);
      packn<0, 6>(T, pa); add_res<2, 0, 4>(T, X); hold<0, 6>(T); PIN();
      mma144<1, 2>(acc, X, ds.q[0]);
      packn<6, 11>(T, pa); add_res<2, 4, 9>(T, X); hold<4, 11>(T); PIN();
      mma144<2, 3>(acc, X, ds.q[0]);
      packn<11, 16>(T, pa); add_res<2, 9, 16>(T, X); hold<9, 16>(T); PIN();
      mma144<3, 8>(acc, X, ds.q[0]);
      load_x<8, 12>(X, tx); store_out<2>(T, o0, o1);
      if (w4 == 3) release<5>(sb, ds, next_round);
      if (more) mbar_wait(sb + BAR_SFULL, par ^ 1);
      asm volatile("ld.shared.u32 %0, [%1];" : "=r"(rK) : "r"(sb + OFF_RSTD + wg * 100 + (misc & 0xfc)) : "memory");
      mma144<8, 12>(acc, X, ds.q[0]);
      if (pass) turn_pass<5>(wg);
      __syncwarp();
      if (lane == 0) mbar_arrive(sb + BAR_TEMPTY);
      TR(1);
    }
  }
}

typedef CUresult (*EncodeFn)(CUtensorMap*, CUtensorMapDataType, cuuint32_t, void*, const cuuint64_t*, const cuuint64_t*,
                             const cuuint32_t*, const cuuint32_t*, CUtensorMapInterleave, CUtensorMapSwizzle,
                             CUtensorMapL2promotion, CUtensorMapFloatOOBfill);

}

extern "C" void kernel_launch(void* const* d_in, const int* in_sizes, int n_in, void* d_out, int out_size) {
  const __nv_bfloat16* x = (const __nv_bfloat16*)d_in[0];
  const __nv_bfloat16* dw = (const __nv_bfloat16*)d_in[1];
  const __nv_bfloat16* wqkv = (const __nv_bfloat16*)d_in[2];
  const __nv_bfloat16* wo = (const __nv_bfloat16*)d_in[3];
  static EncodeFn encode = nullptr;
  static int nsm = 0;
  static void* wpack = nullptr;
  if (!encode) {
    void* fn = nullptr;
    cudaDriverEntryPointQueryResult qr;
    cudaGetDriverEntryPoint("cuTensorMapEncodeTiled", &fn, cudaEnableDefault, &qr);
    encode = (EncodeFn)fn;
    int dev = 0;
    cudaGetDevice(&dev);
    cudaDeviceGetAttribute(&nsm, cudaDevAttrMultiProcessorCount, dev);
    cudaGetSymbolAddress(&wpack, g_wpack);
    cudaFuncSetAttribute(fused_kernel, cudaFuncAttributeMaxDynamicSharedMemorySize, SMEM_BYTES);
  }
  CUtensorMap tmx;
  cuuint64_t gdim[3] = {CH, IMG, IMG};
  cuuint64_t gstr[2] = {CH * 2, (cuuint64_t)CH * 2 * IMG};
  cuuint32_t box[3] = {64, 9, 1};
  cuuint32_t estr[3] = {1, 1, 1};
  encode(&tmx, CU_TENSOR_MAP_DATA_TYPE_BFLOAT16, 3, (void*)x, gdim, gstr, box, estr, CU_TENSOR_MAP_INTERLEAVE_NONE,
         CU_TENSOR_MAP_SWIZZLE_NONE, CU_TENSOR_MAP_L2_PROMOTION_L2_128B, CU_TENSOR_MAP_FLOAT_OOB_FILL_NONE);
  Descs ds;
  for (int i = 0; i < 12; i++) {
    for (int h = 0; h < 4; h++) ds.q[h][i] = mkdesc(SMEM_BASE + OFF_W + qkv_off(h, i), 128, 256);
    ds.v3[i] = mkdesc(SMEM_BASE + OFF_W + qkv_off(3, i) + 3072, 128, 256);
    for (int c = 0; c < 3; c++) ds.p[c * 12 + i] = mkdesc(SMEM_BASE + OFF_W + wo_off(c, i), 128, 256);
  }
  for (int i = 0; i < 16; i++) ds.src[i] = (const uint8_t*)wpack + i * SLICE;
  for (int g = 0; g < 2; g++)
    for (int i = 0; i < 4; i++) {
      ds.kv[g][i] = mkdesc(SMEM_BASE + OFF_KV + g * KV_BYTES + KV_KOFF + 2 * i * KV_PITCH, KV_PITCH, 128);
      ds.kv[g][4 + i] = mkdesc(SMEM_BASE + OFF_KV + g * KV_BYTES + 256 * i, 128, KV_PITCH);
    }
  CUtensorMap tmp;
  cuuint32_t boxp[3] = {CH, 9, 9};
  encode(&tmp, CU_TENSOR_MAP_DATA_TYPE_BFLOAT16, 3, (void*)x, gdim, gstr, boxp, estr, CU_TENSOR_MAP_INTERLEAVE_NONE,
         CU_TENSOR_MAP_SWIZZLE_NONE, CU_TENSOR_MAP_L2_PROMOTION_L2_128B, CU_TENSOR_MAP_FLOAT_OOB_FILL_NONE);
  prepack_kernel<<<48, dim3(192, 2), 0, cudaStreamPerThread>>>(wqkv, wo);
  cudaLaunchConfig_t cfg = {};
  cfg.gridDim = dim3(nsm); cfg.blockDim = dim3(384); cfg.dynamicSmemBytes = SMEM_BYTES; cfg.stream = cudaStreamPerThread;
  cudaLaunchAttribute at[1];
  at[0].id = cudaLaunchAttributeProgrammaticStreamSerialization;
  at[0].val.programmaticStreamSerializationAllowed = 1;
  cfg.attrs = at; cfg.numAttrs = 1;
  cudaLaunchKernelEx(&cfg, fused_kernel, tmx, tmp, ds, dw, (__nv_bfloat16*)d_out, 0);
}
```

```cpp
#include <cuda_runtime.h>
#include <cuda_bf16.h>
#include <cuda.h>
#include <stdint.h>

#define CREGS "208"
#define PREGS "88"
namespace {

constexpr int IMG = 511;
constexpr int CH = 192;
constexpr int NWX = 73;
constexpr int NWIN = NWX * NWX;
constexpr int SLICE = 18432;
constexpr int OFF_W = 0;
constexpr int KV_PITCH = 1792, KV_KOFF = 896, KV_BYTES = 6 * KV_PITCH + 1024;
constexpr int OFF_KV = 8 * SLICE;
constexpr int TILE_BYTES = 25 * 768;
constexpr int OFF_TILE = OFF_KV + 2 * KV_BYTES;
constexpr int XSLOT = 2304;
constexpr int OFF_ZERO = OFF_TILE + 2 * TILE_BYTES;
constexpr int OFF_X = OFF_ZERO + 768;
constexpr int OFF_BAR = OFF_X + 9 * XSLOT;
constexpr int BAR_WFULL = OFF_BAR;
constexpr int BAR_XFULL = OFF_BAR + 72;
constexpr int BAR_TFULL = OFF_BAR + 144;
constexpr int BAR_TEMPTY = OFF_BAR + 152;
constexpr int BAR_TPART = OFF_BAR + 160;
constexpr int BAR_SFULL = OFF_BAR + 176;
constexpr int OFF_RSTD = OFF_BAR + 192;
constexpr int CNT_WREL = OFF_RSTD + 208;
constexpr int OFF_TRACE = CNT_WREL + 768;
constexpr int SMEM_BYTES = OFF_TRACE;

constexpr int SMEM_BASE = 1024;
struct Descs { uint64_t q[4][12]; uint64_t v3[12]; uint64_t p[36]; uint64_t kv[2][8]; const uint8_t* src[16]; };

__device__ uint4 g_wpack[16 * SLICE / 16];
#define TR(id)
#define GTS(i)
template <int ID> __device__ __forceinline__ void sched_fence(uint32_t v) {
  asm volatile("{\n.reg .pred p;\nsetp.ne.u32 p, %0, %1;\n@p bra.uni SF_%=;\ntrap;\nSF_%=:\n}\n" :: "r"(v), "n"(ID) : "memory");
}
__device__ __forceinline__ void anchor(uint32_t v) { sched_fence<0x7fc1ffc1>(v); }

template <int V> struct IC { static constexpr int v = V; };
typedef __nv_bfloat162 bf2;
__device__ __forceinline__ bf2 u2b(uint32_t u) { return *reinterpret_cast<bf2*>(&u); }
__device__ __forceinline__ uint32_t b2u(bf2 b) { return *reinterpret_cast<uint32_t*>(&b); }
__device__ __forceinline__ uint32_t pack2(float lo, float hi) {
  uint32_t r; asm("cvt.rn.bf16x2.f32 %0, %1, %2;" : "=r"(r) : "f"(hi), "f"(lo)); return r;
}
__device__ __forceinline__ uint32_t hadd(uint32_t a, uint32_t b) { return b2u(__hadd2_rn(u2b(a), u2b(b))); }
__device__ __forceinline__ uint32_t hmul(uint32_t a, uint32_t b) { return b2u(__hmul2_rn(u2b(a), u2b(b))); }
__device__ __forceinline__ uint32_t hfma(uint32_t a, uint32_t b, uint32_t c) { return b2u(__hfma2(u2b(a), u2b(b), u2b(c))); }
__device__ __forceinline__ uint32_t hmax(uint32_t a, uint32_t b) { return b2u(__hmax2(u2b(a), u2b(b))); }
template <int HI> __device__ __forceinline__ bf2 bcast(uint32_t a) { return HI ? __high2bfloat162(u2b(a)) : __low2bfloat162(u2b(a)); }
template <int HI> __device__ __forceinline__ uint32_t hmul_b(uint32_t a, uint32_t s) { return b2u(__hmul2_rn(u2b(a), bcast<HI>(s))); }
template <int HI> __device__ __forceinline__ uint32_t hsub_b(uint32_t a, uint32_t s) { return b2u(__hsub2_rn(u2b(a), bcast<HI>(s))); }
__device__ __forceinline__ uint32_t hex2(uint32_t a) { uint32_t r; asm("ex2.approx.ftz.bf16x2 %0, %1;" : "=r"(r) : "r"(a)); return r; }
__device__ __forceinline__ float lo2f(uint32_t a) { return __uint_as_float(a << 16); }
__device__ __forceinline__ float hi2f(uint32_t a) { return __uint_as_float(a & 0xffff0000u); }

__device__ __forceinline__ void mbar_init(uint32_t bar, uint32_t cnt) { asm volatile("mbarrier.init.shared::cta.b64 [%0], %1;" :: "r"(bar), "r"(cnt) : "memory"); }
__device__ __forceinline__ void mbar_arrive(uint32_t bar) { asm volatile("mbarrier.arrive.shared::cta.b64 _, [%0];" :: "r"(bar) : "memory"); }
__device__ __forceinline__ void mbar_expect(uint32_t bar, uint32_t bytes) { asm volatile("mbarrier.arrive.expect_tx.shared::cta.b64 _, [%0], %1;" :: "r"(bar), "r"(bytes) : "memory"); }
template <int HINT>
__device__ __forceinline__ bool mbar_try(uint32_t bar, uint32_t parity) {
  uint32_t ok;
  if (HINT) asm volatile("{\n.reg .pred p;\nmbarrier.try_wait.parity.shared::cta.b64 p, [%1], %2, %3;\nselp.u32 %0, 1, 0, p;\n}\n" : "=r"(ok) : "r"(bar), "r"(parity), "n"(HINT) : "memory");
  else asm volatile("{\n.reg .pred p;\nmbarrier.try_wait.parity.shared::cta.b64 p, [%1], %2;\nselp.u32 %0, 1, 0, p;\n}\n" : "=r"(ok) : "r"(bar), "r"(parity) : "memory");
  return ok != 0;
}
__device__ __forceinline__ void mbar_wait(uint32_t bar, uint32_t parity) {
  if (__builtin_expect(!mbar_try<0>(bar, parity), 0)) {
    uint32_t n = 0;
    while (!mbar_try<4000>(bar, parity)) { if (++n > (1u << 20)) __trap(); }
  }
}
__device__ __forceinline__ void wg_fence() { asm volatile("wgmma.fence.sync.aligned;" ::: "memory"); }
__device__ __forceinline__ void wg_commit() { asm volatile("wgmma.commit_group.sync.aligned;" ::: "memory"); }
template <int N> __device__ __forceinline__ void wg_wait() { asm volatile("wgmma.wait_group.sync.aligned %0;" :: "n"(N) : "memory"); }
__device__ __forceinline__ void bar_sync(int id) { asm volatile("bar.sync %0, 128;" :: "r"(id) : "memory"); }
#define PPMASK 0x3f
template <int SEC> __device__ __forceinline__ void turn_wait(int wg) { if (PPMASK >> SEC & 1) asm volatile("bar.sync %0, 256;" :: "r"(3 + wg) : "memory"); }
template <int SEC> __device__ __forceinline__ void turn_pass(int wg) { if (PPMASK >> SEC & 1) asm volatile("bar.arrive %0, 256;" :: "r"(4 - wg) : "memory"); }
constexpr int PP_LAST = PPMASK >= 32 ? 5 : PPMASK >= 16 ? 4 : PPMASK >= 8 ? 3 : PPMASK >= 4 ? 2 : PPMASK >= 2 ? 1 : 0;
__device__ __forceinline__ void stsm4(uint32_t addr, uint32_t a, uint32_t b, uint32_t c, uint32_t d) {
  asm volatile("stmatrix.sync.aligned.m8n8.x4.shared.b16 [%0], {%1,%2,%3,%4};" :: "r"(addr), "r"(a), "r"(b), "r"(c), "r"(d) : "memory");
}
template <int N> __device__ __forceinline__ void keep(float (&d)[N]) {
#pragma unroll
  for (int i = 0; i < N; i++) asm volatile("" : "+f"(d[i]) :: "memory");
}
__host__ __device__ __forceinline__ uint64_t mkdesc(uint32_t addr, uint32_t lbo, uint32_t sbo) {
  return ((uint64_t)(sbo >> 4) << 32) | (uint64_t)(((lbo >> 4) << 16) | ((addr & 0x3FFFF) >> 4));
}

template <int SCALE_D>
__device__ __forceinline__ void wgmma_n144(float (&d)[72], uint32_t a0, uint32_t a1, uint32_t a2, uint32_t a3, uint64_t descB) {
  if (SCALE_D == 0)
  asm volatile("wgmma.mma_async.sync.aligned.m64n144k16.f32.bf16.bf16 "
    "{%0, %1, %2, %3, %4, %5, %6, %7, %8, %9, %10, %11, %12, %13, %14, %15, "
    "%16, %17, %18, %19, %20, %21, %22, %23, %24, %25, %26, %27, %28, %29, %30, %31, "
    "%32, %33, %34, %35, %36, %37, %38, %39, %40, %41, %42, %43, %44, %45, %46, %47, "
    "%48, %49, %50, %51, %52, %53, %54, %55, %56, %57, %58, %59, %60, %61, %62, %63, "
    "%64, %65, %66, %67, %68, %69, %70, %71}, "
    "{%72, %73, %74, %75}, %76, 0, 1, 1, 0;\n"
    : "=f"(d[0]), "=f"(d[1]), "=f"(d[2]), "=f"(d[3]), "=f"(d[4]), "=f"(d[5]), "=f"(d[6]), "=f"(d[7]),
      "=f"(d[8]), "=f"(d[9]), "=f"(d[10]), "=f"(d[11]), "=f"(d[12]), "=f"(d[13]), "=f"(d[14]), "=f"(d[15]),
      "=f"(d[16]), "=f"(d[17]), "=f"(d[18]), "=f"(d[19]), "=f"(d[20]), "=f"(d[21]), "=f"(d[22]), "=f"(d[23]),
      "=f"(d[24]), "=f"(d[25]), "=f"(d[26]), "=f"(d[27]), "=f"(d[28]), "=f"(d[29]), "=f"(d[30]), "=f"(d[31]),
      "=f"(d[32]), "=f"(d[33]), "=f"(d[34]), "=f"(d[35]), "=f"(d[36]), "=f"(d[37]), "=f"(d[38]), "=f"(d[39]),
      "=f"(d[40]), "=f"(d[41]), "=f"(d[42]), "=f"(d[43]), "=f"(d[44]), "=f"(d[45]), "=f"(d[46]), "=f"(d[47]),
      "=f"(d[48]), "=f"(d[49]), "=f"(d[50]), "=f"(d[51]), "=f"(d[52]), "=f"(d[53]), "=f"(d[54]), "=f"(d[55]),
      "=f"(d[56]), "=f"(d[57]), "=f"(d[58]), "=f"(d[59]), "=f"(d[60]), "=f"(d[61]), "=f"(d[62]), "=f"(d[63]),
      "=f"(d[64]), "=f"(d[65]), "=f"(d[66]), "=f"(d[67]), "=f"(d[68]), "=f"(d[69]), "=f"(d[70]), "=f"(d[71])
    : "r"(a0), "r"(a1), "r"(a2), "r"(a3), "l"(descB));
  else
  asm volatile("wgmma.mma_async.sync.aligned.m64n144k16.f32.bf16.bf16 "
    "{%0, %1, %2, %3, %4, %5, %6, %7, %8, %9, %10, %11, %12, %13, %14, %15, "
    "%16, %17, %18, %19, %20, %21, %22, %23, %24, %25, %26, %27, %28, %29, %30, %31, "
    "%32, %33, %34, %35, %36, %37, %38, %39, %40, %41, %42, %43, %44, %45, %46, %47, "
    "%48, %49, %50, %51, %52, %53, %54, %55, %56, %57, %58, %59, %60, %61, %62, %63, "
    "%64, %65, %66, %67, %68, %69, %70, %71}, "
    "{%72, %73, %74, %75}, %76, 1, 1, 1, 0;\n"
    : "+f"(d[0]), "+f"(d[1]), "+f"(d[2]), "+f"(d[3]), "+f"(d[4]), "+f"(d[5]), "+f"(d[6]), "+f"(d[7]),
      "+f"(d[8]), "+f"(d[9]), "+f"(d[10]), "+f"(d[11]), "+f"(d[12]), "+f"(d[13]), "+f"(d[14]), "+f"(d[15]),
      "+f"(d[16]), "+f"(d[17]), "+f"(d[18]), "+f"(d[19]), "+f"(d[20]), "+f"(d[21]), "+f"(d[22]), "+f"(d[23]),
      "+f"(d[24]), "+f"(d[25]), "+f"(d[26]), "+f"(d[27]), "+f"(d[28]), "+f"(d[29]), "+f"(d[30]), "+f"(d[31]),
      "+f"(d[32]), "+f"(d[33]), "+f"(d[34]), "+f"(d[35]), "+f"(d[36]), "+f"(d[37]), "+f"(d[38]), "+f"(d[39]),
      "+f"(d[40]), "+f"(d[41]), "+f"(d[42]), "+f"(d[43]), "+f"(d[44]), "+f"(d[45]), "+f"(d[46]), "+f"(d[47]),
      "+f"(d[48]), "+f"(d[49]), "+f"(d[50]), "+f"(d[51]), "+f"(d[52]), "+f"(d[53]), "+f"(d[54]), "+f"(d[55]),
      "+f"(d[56]), "+f"(d[57]), "+f"(d[58]), "+f"(d[59]), "+f"(d[60]), "+f"(d[61]), "+f"(d[62]), "+f"(d[63]),
      "+f"(d[64]), "+f"(d[65]), "+f"(d[66]), "+f"(d[67]), "+f"(d[68]), "+f"(d[69]), "+f"(d[70]), "+f"(d[71])
    : "r"(a0), "r"(a1), "r"(a2), "r"(a3), "l"(descB));
}

template <int SCALE_D>
__device__ __forceinline__ void wgmma_n96(float (&d)[48], uint32_t a0, uint32_t a1, uint32_t a2, uint32_t a3, uint64_t descB) {
  if (SCALE_D == 0)
  asm volatile("wgmma.mma_async.sync.aligned.m64n96k16.f32.bf16.bf16 "
    "{%0, %1, %2, %3, %4, %5, %6, %7, %8, %9, %10, %11, %12, %13, %14, %15, "
    "%16, %17, %18, %19, %20, %21, %22, %23, %24, %25, %26, %27, %28, %29, %30, %31, "
    "%32, %33, %34, %35, %36, %37, %38, %39, %40, %41, %42, %43, %44, %45, %46, %47}, "
    "{%48, %49, %50, %51}, %52, 0, 1, 1, 0;\n"
    : "=f"(d[0]), "=f"(d[1]), "=f"(d[2]), "=f"(d[3]), "=f"(d[4]), "=f"(d[5]), "=f"(d[6]), "=f"(d[7]),
      "=f"(d[8]), "=f"(d[9]), "=f"(d[10]), "=f"(d[11]), "=f"(d[12]), "=f"(d[13]), "=f"(d[14]), "=f"(d[15]),
      "=f"(d[16]), "=f"(d[17]), "=f"(d[18]), "=f"(d[19]), "=f"(d[20]), "=f"(d[21]), "=f"(d[22]), "=f"(d[23]),
      "=f"(d[24]), "=f"(d[25]), "=f"(d[26]), "=f"(d[27]), "=f"(d[28]), "=f"(d[29]), "=f"(d[30]), "=f"(d[31]),
      "=f"(d[32]), "=f"(d[33]), "=f"(d[34]), "=f"(d[35]), "=f"(d[36]), "=f"(d[37]), "=f"(d[38]), "=f"(d[39]),
      "=f"(d[40]), "=f"(d[41]), "=f"(d[42]), "=f"(d[43]), "=f"(d[44]), "=f"(d[45]), "=f"(d[46]), "=f"(d[47])
    : "r"(a0), "r"(a1), "r"(a2), "r"(a3), "l"(descB));
  else if (SCALE_D == 2)
  asm volatile("wgmma.mma_async.sync.aligned.m64n96k16.f32.bf16.bf16 "
    "{%0, %1, %2, %3, %4, %5, %6, %7, %8, %9, %10, %11, %12, %13, %14, %15, "
    "%16, %17, %18, %19, %20, %21, %22, %23, %24, %25, %26, %27, %28, %29, %30, %31, "
    "%32, %33, %34, %35, %36, %37, %38, %39, %40, %41, %42, %43, %44, %45, %46, %47}, "
    "{%48, %49, %50, %51}, %52, 0, 1, 1, 0;\n"
    : "+f"(d[0]), "+f"(d[1]), "+f"(d[2]), "+f"(d[3]), "+f"(d[4]), "+f"(d[5]), "+f"(d[6]), "+f"(d[7]),
      "+f"(d[8]), "+f"(d[9]), "+f"(d[10]), "+f"(d[11]), "+f"(d[12]), "+f"(d[13]), "+f"(d[14]), "+f"(d[15]),
      "+f"(d[16]), "+f"(d[17]), "+f"(d[18]), "+f"(d[19]), "+f"(d[20]), "+f"(d[21]), "+f"(d[22]), "+f"(d[23]),
      "+f"(d[24]), "+f"(d[25]), "+f"(d[26]), "+f"(d[27]), "+f"(d[28]), "+f"(d[29]), "+f"(d[30]), "+f"(d[31]),
      "+f"(d[32]), "+f"(d[33]), "+f"(d[34]), "+f"(d[35]), "+f"(d[36]), "+f"(d[37]), "+f"(d[38]), "+f"(d[39]),
      "+f"(d[40]), "+f"(d[41]), "+f"(d[42]), "+f"(d[43]), "+f"(d[44]), "+f"(d[45]), "+f"(d[46]), "+f"(d[47])
    : "r"(a0), "r"(a1), "r"(a2), "r"(a3), "l"(descB));
  else
  asm volatile("wgmma.mma_async.sync.aligned.m64n96k16.f32.bf16.bf16 "
    "{%0, %1, %2, %3, %4, %5, %6, %7, %8, %9, %10, %11, %12, %13, %14, %15, "
    "%16, %17, %18, %19, %20, %21, %22, %23, %24, %25, %26, %27, %28, %29, %30, %31, "
    "%32, %33, %34, %35, %36, %37, %38, %39, %40, %41, %42, %43, %44, %45, %46, %47}, "
    "{%48, %49, %50, %51}, %52, 1, 1, 1, 0;\n"
    : "+f"(d[0]), "+f"(d[1]), "+f"(d[2]), "+f"(d[3]), "+f"(d[4]), "+f"(d[5]), "+f"(d[6]), "+f"(d[7]),
      "+f"(d[8]), "+f"(d[9]), "+f"(d[10]), "+f"(d[11]), "+f"(d[12]), "+f"(d[13]), "+f"(d[14]), "+f"(d[15]),
      "+f"(d[16]), "+f"(d[17]), "+f"(d[18]), "+f"(d[19]), "+f"(d[20]), "+f"(d[21]), "+f"(d[22]), "+f"(d[23]),
      "+f"(d[24]), "+f"(d[25]), "+f"(d[26]), "+f"(d[27]), "+f"(d[28]), "+f"(d[29]), "+f"(d[30]), "+f"(d[31]),
      "+f"(d[32]), "+f"(d[33]), "+f"(d[34]), "+f"(d[35]), "+f"(d[36]), "+f"(d[37]), "+f"(d[38]), "+f"(d[39]),
      "+f"(d[40]), "+f"(d[41]), "+f"(d[42]), "+f"(d[43]), "+f"(d[44]), "+f"(d[45]), "+f"(d[46]), "+f"(d[47])
    : "r"(a0), "r"(a1), "r"(a2), "r"(a3), "l"(descB));
}

template <int SCALE_D>
__device__ __forceinline__ void wgmma_n48(float (&d)[24], uint32_t a0, uint32_t a1, uint32_t a2, uint32_t a3, uint64_t descB) {
  if (SCALE_D == 0)
  asm volatile("wgmma.mma_async.sync.aligned.m64n48k16.f32.bf16.bf16 "
    "{%0, %1, %2, %3, %4, %5, %6, %7, %8, %9, %10, %11, %12, %13, %14, %15, "
    "%16, %17, %18, %19, %20, %21, %22, %23}, "
    "{%24, %25, %26, %27}, %28, 0, 1, 1, 0;\n"
    : "=f"(d[0]), "=f"(d[1]), "=f"(d[2]), "=f"(d[3]), "=f"(d[4]), "=f"(d[5]), "=f"(d[6]), "=f"(d[7]),
      "=f"(d[8]), "=f"(d[9]), "=f"(d[10]), "=f"(d[11]), "=f"(d[12]), "=f"(d[13]), "=f"(d[14]), "=f"(d[15]),
      "=f"(d[16]), "=f"(d[17]), "=f"(d[18]), "=f"(d[19]), "=f"(d[20]), "=f"(d[21]), "=f"(d[22]), "=f"(d[23])
    : "r"(a0), "r"(a1), "r"(a2), "r"(a3), "l"(descB));
  else
  asm volatile("wgmma.mma_async.sync.aligned.m64n48k16.f32.bf16.bf16 "
    "{%0, %1, %2, %3, %4, %5, %6, %7, %8, %9, %10, %11, %12, %13, %14, %15, "
    "%16, %17, %18, %19, %20, %21, %22, %23}, "
    "{%24, %25, %26, %27}, %28, 1, 1, 1, 0;\n"
    : "+f"(d[0]), "+f"(d[1]), "+f"(d[2]), "+f"(d[3]), "+f"(d[4]), "+f"(d[5]), "+f"(d[6]), "+f"(d[7]),
      "+f"(d[8]), "+f"(d[9]), "+f"(d[10]), "+f"(d[11]), "+f"(d[12]), "+f"(d[13]), "+f"(d[14]), "+f"(d[15]),
      "+f"(d[16]), "+f"(d[17]), "+f"(d[18]), "+f"(d[19]), "+f"(d[20]), "+f"(d[21]), "+f"(d[22]), "+f"(d[23])
    : "r"(a0), "r"(a1), "r"(a2), "r"(a3), "l"(descB));
}

template <int SCALE_D>
__device__ __forceinline__ void wgmma_n64(float (&d)[32], uint32_t a0, uint32_t a1, uint32_t a2, uint32_t a3, uint64_t descB) {
  if (SCALE_D == 0)
  asm volatile("wgmma.mma_async.sync.aligned.m64n64k16.f32.bf16.bf16 "
    "{%0, %1, %2, %3, %4, %5, %6, %7, %8, %9, %10, %11, %12, %13, %14, %15, "
    "%16, %17, %18, %19, %20, %21, %22, %23, %24, %25, %26, %27, %28, %29, %30, %31}, "
    "{%32, %33, %34, %35}, %36, 0, 1, 1, 0;\n"
    : "=f"(d[0]), "=f"(d[1]), "=f"(d[2]), "=f"(d[3]), "=f"(d[4]), "=f"(d[5]), "=f"(d[6]), "=f"(d[7]),
      "=f"(d[8]), "=f"(d[9]), "=f"(d[10]), "=f"(d[11]), "=f"(d[12]), "=f"(d[13]), "=f"(d[14]), "=f"(d[15]),
      "=f"(d[16]), "=f"(d[17]), "=f"(d[18]), "=f"(d[19]), "=f"(d[20]), "=f"(d[21]), "=f"(d[22]), "=f"(d[23]),
      "=f"(d[24]), "=f"(d[25]), "=f"(d[26]), "=f"(d[27]), "=f"(d[28]), "=f"(d[29]), "=f"(d[30]), "=f"(d[31])
    : "r"(a0), "r"(a1), "r"(a2), "r"(a3), "l"(descB));
  else if (SCALE_D == 2)
  asm volatile("wgmma.mma_async.sync.aligned.m64n64k16.f32.bf16.bf16 "
    "{%0, %1, %2, %3, %4, %5, %6, %7, %8, %9, %10, %11, %12, %13, %14, %15, "
    "%16, %17, %18, %19, %20, %21, %22, %23, %24, %25, %26, %27, %28, %29, %30, %31}, "
    "{%32, %33, %34, %35}, %36, 0, 1, 1, 0;\n"
    : "+f"(d[0]), "+f"(d[1]), "+f"(d[2]), "+f"(d[3]), "+f"(d[4]), "+f"(d[5]), "+f"(d[6]), "+f"(d[7]),
      "+f"(d[8]), "+f"(d[9]), "+f"(d[10]), "+f"(d[11]), "+f"(d[12]), "+f"(d[13]), "+f"(d[14]), "+f"(d[15]),
      "+f"(d[16]), "+f"(d[17]), "+f"(d[18]), "+f"(d[19]), "+f"(d[20]), "+f"(d[21]), "+f"(d[22]), "+f"(d[23]),
      "+f"(d[24]), "+f"(d[25]), "+f"(d[26]), "+f"(d[27]), "+f"(d[28]), "+f"(d[29]), "+f"(d[30]), "+f"(d[31])
    : "r"(a0), "r"(a1), "r"(a2), "r"(a3), "l"(descB));
  else
  asm volatile("wgmma.mma_async.sync.aligned.m64n64k16.f32.bf16.bf16 "
    "{%0, %1, %2, %3, %4, %5, %6, %7, %8, %9, %10, %11, %12, %13, %14, %15, "
    "%16, %17, %18, %19, %20, %21, %22, %23, %24, %25, %26, %27, %28, %29, %30, %31}, "
    "{%32, %33, %34, %35}, %36, 1, 1, 1, 0;\n"
    : "+f"(d[0]), "+f"(d[1]), "+f"(d[2]), "+f"(d[3]), "+f"(d[4]), "+f"(d[5]), "+f"(d[6]), "+f"(d[7]),
      "+f"(d[8]), "+f"(d[9]), "+f"(d[10]), "+f"(d[11]), "+f"(d[12]), "+f"(d[13]), "+f"(d[14]), "+f"(d[15]),
      "+f"(d[16]), "+f"(d[17]), "+f"(d[18]), "+f"(d[19]), "+f"(d[20]), "+f"(d[21]), "+f"(d[22]), "+f"(d[23]),
      "+f"(d[24]), "+f"(d[25]), "+f"(d[26]), "+f"(d[27]), "+f"(d[28]), "+f"(d[29]), "+f"(d[30]), "+f"(d[31])
    : "r"(a0), "r"(a1), "r"(a2), "r"(a3), "l"(descB));
}

template <int SCALE_D>
__device__ __forceinline__ void wgmma_n56(float (&d)[28], uint32_t a0, uint32_t a1, uint32_t a2, uint32_t a3, uint64_t descB) {
  if (SCALE_D == 0)
  asm volatile("wgmma.mma_async.sync.aligned.m64n56k16.f32.bf16.bf16 "
    "{%0, %1, %2, %3, %4, %5, %6, %7, %8, %9, %10, %11, %12, %13, %14, %15, "
    "%16, %17, %18, %19, %20, %21, %22, %23, %24, %25, %26, %27}, "
    "{%28, %29, %30, %31}, %32, 0, 1, 1, 0;\n"
    : "=f"(d[0]), "=f"(d[1]), "=f"(d[2]), "=f"(d[3]), "=f"(d[4]), "=f"(d[5]), "=f"(d[6]), "=f"(d[7]),
      "=f"(d[8]), "=f"(d[9]), "=f"(d[10]), "=f"(d[11]), "=f"(d[12]), "=f"(d[13]), "=f"(d[14]), "=f"(d[15]),
      "=f"(d[16]), "=f"(d[17]), "=f"(d[18]), "=f"(d[19]), "=f"(d[20]), "=f"(d[21]), "=f"(d[22]), "=f"(d[23]),
      "=f"(d[24]), "=f"(d[25]), "=f"(d[26]), "=f"(d[27])
    : "r"(a0), "r"(a1), "r"(a2), "r"(a3), "l"(descB));
  else
  asm volatile("wgmma.mma_async.sync.aligned.m64n56k16.f32.bf16.bf16 "
    "{%0, %1, %2, %3, %4, %5, %6, %7, %8, %9, %10, %11, %12, %13, %14, %15, "
    "%16, %17, %18, %19, %20, %21, %22, %23, %24, %25, %26, %27}, "
    "{%28, %29, %30, %31}, %32, 1, 1, 1, 0;\n"
    : "+f"(d[0]), "+f"(d[1]), "+f"(d[2]), "+f"(d[3]), "+f"(d[4]), "+f"(d[5]), "+f"(d[6]), "+f"(d[7]),
      "+f"(d[8]), "+f"(d[9]), "+f"(d[10]), "+f"(d[11]), "+f"(d[12]), "+f"(d[13]), "+f"(d[14]), "+f"(d[15]),
      "+f"(d[16]), "+f"(d[17]), "+f"(d[18]), "+f"(d[19]), "+f"(d[20]), "+f"(d[21]), "+f"(d[22]), "+f"(d[23]),
      "+f"(d[24]), "+f"(d[25]), "+f"(d[26]), "+f"(d[27])
    : "r"(a0), "r"(a1), "r"(a2), "r"(a3), "l"(descB));
}

template <int SCALE_D>
__device__ __forceinline__ void wgmma_n56t(float (&d)[28], uint32_t a0, uint32_t a1, uint32_t a2, uint32_t a3, uint64_t descB) {
  if (SCALE_D == 0)
  asm volatile("wgmma.mma_async.sync.aligned.m64n56k16.f32.bf16.bf16 "
    "{%0, %1, %2, %3, %4, %5, %6, %7, %8, %9, %10, %11, %12, %13, %14, %15, "
    "%16, %17, %18, %19, %20, %21, %22, %23, %24, %25, %26, %27}, "
    "{%28, %29, %30, %31}, %32, 0, 1, 1, 1;\n"
    : "=f"(d[0]), "=f"(d[1]), "=f"(d[2]), "=f"(d[3]), "=f"(d[4]), "=f"(d[5]), "=f"(d[6]), "=f"(d[7]),
      "=f"(d[8]), "=f"(d[9]), "=f"(d[10]), "=f"(d[11]), "=f"(d[12]), "=f"(d[13]), "=f"(d[14]), "=f"(d[15]),
      "=f"(d[16]), "=f"(d[17]), "=f"(d[18]), "=f"(d[19]), "=f"(d[20]), "=f"(d[21]), "=f"(d[22]), "=f"(d[23]),
      "=f"(d[24]), "=f"(d[25]), "=f"(d[26]), "=f"(d[27])
    : "r"(a0), "r"(a1), "r"(a2), "r"(a3), "l"(descB));
  else
  asm volatile("wgmma.mma_async.sync.aligned.m64n56k16.f32.bf16.bf16 "
    "{%0, %1, %2, %3, %4, %5, %6, %7, %8, %9, %10, %11, %12, %13, %14, %15, "
    "%16, %17, %18, %19, %20, %21, %22, %23, %24, %25, %26, %27}, "
    "{%28, %29, %30, %31}, %32, 1, 1, 1, 1;\n"
    : "+f"(d[0]), "+f"(d[1]), "+f"(d[2]), "+f"(d[3]), "+f"(d[4]), "+f"(d[5]), "+f"(d[6]), "+f"(d[7]),
      "+f"(d[8]), "+f"(d[9]), "+f"(d[10]), "+f"(d[11]), "+f"(d[12]), "+f"(d[13]), "+f"(d[14]), "+f"(d[15]),
      "+f"(d[16]), "+f"(d[17]), "+f"(d[18]), "+f"(d[19]), "+f"(d[20]), "+f"(d[21]), "+f"(d[22]), "+f"(d[23]),
      "+f"(d[24]), "+f"(d[25]), "+f"(d[26]), "+f"(d[27])
    : "r"(a0), "r"(a1), "r"(a2), "r"(a3), "l"(descB));
}

__global__ void __launch_bounds__(384) prepack_kernel(const __nv_bfloat16* __restrict__ wqkv, const __nv_bfloat16* __restrict__ wo) {
  asm volatile("griddepcontrol.launch_dependents;");
  __nv_bfloat16* dst = reinterpret_cast<__nv_bfloat16*>(g_wpack);
  const int c = threadIdx.x, nb = blockIdx.x * 2 + threadIdx.y;
  if (nb < 72) {
    __shared__ float red2[2][6][8];
    float (*red)[8] = red2[threadIdx.y];
    const int h = nb / 18, j = nb % 18, part = j / 6;
    const int col = (part == 0 ? 192 : part == 1 ? 0 : 384) + h * 48 + (j % 6) * 8;
    uint4 raw = *reinterpret_cast<const uint4*>(wqkv + c * 576 + col);
    uint32_t u[4] = {raw.x, raw.y, raw.z, raw.w};
    float v[8];
#pragma unroll
    for (int i = 0; i < 4; i++) { v[2 * i] = lo2f(u[i]); v[2 * i + 1] = hi2f(u[i]); }
#pragma unroll
    for (int i = 0; i < 8; i++) {
      float s = v[i];
#pragma unroll
      for (int o = 16; o; o >>= 1) s += __shfl_xor_sync(~0u, s, o);
      if ((c & 31) == 0) red[c >> 5][i] = s;
    }
    __syncthreads();
    const int cc = c >> 5, q = (c >> 3) & 3, s1 = (c >> 2) & 1, hh = (c >> 1) & 1, e = c & 1;
    const int base = h * 27648 + (2 * cc + s1) * 2304 + j * 128 + hh * 64 + 2 * q + e;
#pragma unroll
    for (int n = 0; n < 8; n++) {
      float m = (red[0][n] + red[1][n] + red[2][n] + red[3][n] + red[4][n] + red[5][n]) * (1.0f / 192.0f);
      dst[base + n * 8] = __float2bfloat16((v[n] - m) * (part == 1 ? 0.14433756729740643f * 1.4426950408889634f : 1.0f));
    }
  } else {
    const int jb = nb - 72, chunk = jb / 8, j = jb % 8;
    const int s = c >> 4, hh = (c >> 3) & 1, kk = c & 7;
    const int base = 110592 + (chunk * 12 + s) * 1024 + j * 128 + hh * 64 + kk;
#pragma unroll
    for (int n = 0; n < 8; n++) {
      const int ch = 32 * (jb >> 2) + 8 * (n >> 1) + 2 * (jb & 3) + (n & 1);
      dst[base + n * 8] = wo[c * 192 + ch];
    }
  }
}

__device__ __forceinline__ int window_of(int round, int nfull, int cta, int ncta, int wg) {
  if (round < nfull) return round * 2 * ncta + 2 * cta + wg;
  const int rem = NWIN - nfull * 2 * ncta;
  const int i = cta + wg * ncta;
  return i < rem ? nfull * 2 * ncta + i : -1;
}

__host__ __device__ constexpr int qkv_off(int h, int s) { return ((3 * h + s / 4) % 8) * SLICE + (s % 4) * 4608; }
__host__ __device__ constexpr int wo_off(int chunk, int s) { return 4 * SLICE + (chunk * 12 + s) * 2048; }

#define DEF_ISSUE(NAME, NREG, FN, FIRST)                                                                          \
  template <int S0, int S1, int INIT = FIRST>                                                                     \
  __device__ __forceinline__ void NAME(float (&acc)[NREG], const uint32_t (&A)[48], const uint64_t* d) {          \
    wg_fence();                                                                                                   \
    _Pragma("unroll") for (int s = S0; s < S1; s++) {                                                             \
      if (s == 0) FN<INIT>(acc, A[4 * s], A[4 * s + 1], A[4 * s + 2], A[4 * s + 3], d[s]);                        \
      else        FN<1>(acc, A[4 * s], A[4 * s + 1], A[4 * s + 2], A[4 * s + 3], d[s]);                           \
    }                                                                                                             \
    wg_commit();                                                                                                  \
  }
DEF_ISSUE(mma144, 72, wgmma_n144, 0)
DEF_ISSUE(mma96, 48, wgmma_n96, 0)
DEF_ISSUE(mma48, 24, wgmma_n48, 0)
DEF_ISSUE(mma64, 32, wgmma_n64, 0)
#undef DEF_ISSUE

#define PIN() asm volatile("pmevent 0;" ::: "memory")
template <int A, int B> __device__ __forceinline__ void hold(uint32_t* v) {
#pragma unroll
  for (int i = A; i < B; i++) asm volatile("" : "+r"(v[i]));
}
template <int A, int B> __device__ __forceinline__ void packn(uint32_t* d, const float* a) {
#pragma unroll
  for (int i = A; i < B; i++) d[i] = pack2(a[2 * i], a[2 * i + 1]);
}
template <int A, int B> __device__ __forceinline__ void scalen(uint32_t* d, uint32_t r) {
#pragma unroll
  for (int i = A; i < B; i++) d[i] = (i & 1) ? hmul_b<1>(d[i], r) : hmul_b<0>(d[i], r);
}
__device__ __forceinline__ void stsm12(const uint32_t* v, uint32_t addr) {
#pragma unroll
  for (int j = 0; j < 3; j++) stsm4(addr + 2 * j * KV_PITCH, v[4 * j], v[4 * j + 1], v[4 * j + 2], v[4 * j + 3]);
}
__device__ __forceinline__ uint32_t inv_sum(const float (&o)[28]) {
  float i0, i1;
  asm("rcp.approx.ftz.f32 %0, %1;" : "=f"(i0) : "f"(o[24]));
  asm("rcp.approx.ftz.f32 %0, %1;" : "=f"(i1) : "f"(o[26]));
  return pack2(i0, i1);
}
__device__ __forceinline__ void proxy_fence() { asm volatile("fence.proxy.async.shared::cta;" ::: "memory"); }
__device__ __forceinline__ void issue_s(float (&S)[28], const uint32_t (&Q)[12], const uint64_t* d) {
  wg_fence();
  wgmma_n56<0>(S, Q[0], Q[1], Q[2], Q[3], d[0]);
  wgmma_n56<1>(S, Q[4], Q[5], Q[6], Q[7], d[1]);
  wgmma_n56<1>(S, Q[8], Q[9], Q[10], Q[11], d[2]);
  wg_commit();
}
struct H2 { uint16_t l, h; };
__device__ __forceinline__ H2 exp_halves(uint32_t a) {
  H2 r;
  asm("{\n.reg .b16 l, h;\nmov.b32 {l, h}, %2;\nex2.approx.ftz.bf16 %0, l;\nex2.approx.ftz.bf16 %1, h;\n}\n" : "=h"(r.l), "=h"(r.h) : "r"(a));
  return r;
}
__device__ __forceinline__ uint32_t join(H2 v) { uint32_t r; asm("mov.b32 %0, {%1, %2};" : "=r"(r) : "h"(v.l), "h"(v.h)); return r; }
__device__ __forceinline__ void hold(H2& v) { asm volatile("" : "+h"(v.l), "+h"(v.h)); }

#define KSCHED 0x23456789abcull
#define PASS_SEG2 PASS_SEG
#define PASS_SEG3 7
#define PASS_SEG 10
__host__ __device__ constexpr int ksched(int seg, int nk) { return (int)(KSCHED >> (40 - 4 * seg) & 15) < nk ? (int)(KSCHED >> (40 - 4 * seg) & 15) : nk; }
template <int SEC, int NK, bool PREV, class G>
__device__ __forceinline__ void softmax_pv(float (&S)[28], const uint64_t* dV, uint32_t* Op, uint32_t inv, int wg, bool pass, uint32_t ninf, uint32_t vm, G g) {
#define GK(i) if (ksched(i, NK) > ksched(i - 1, NK)) g(IC<ksched(i - 1, NK)>{}, IC<ksched(i, NK)>{}); \
              if (i == (SEC == 3 ? PASS_SEG3 : SEC == 2 ? PASS_SEG2 : PASS_SEG) && (SEC != PP_LAST || pass)) turn_pass<SEC>(wg);
#define PINK(i) if (ksched(i - 1, NK) < NK) PIN();
  uint32_t P[16];
  GK(1) packn<0, 4>(P, S);  if (PREV) { scalen<0, 4>(Op, inv); hold<0, 4>(Op); }   hold<0, 4>(P); PINK(1)
  GK(2) packn<4, 9>(P, S);  if (PREV) { scalen<4, 8>(Op, inv); hold<4, 8>(Op); }   hold<4, 9>(P); PINK(2)
  GK(3) packn<9, 12>(P, S); P[12] = pack2(S[24], S[26]) | ninf;
  if (PREV) { scalen<8, 12>(Op, inv); hold<8, 12>(Op); } hold<9, 13>(P); PINK(3)
  GK(4)
  uint32_t m0 = hmax(hmax(hmax(P[0], P[2]), P[4]), hmax(hmax(P[6], P[8]), P[10]));
  uint32_t m1 = hmax(hmax(hmax(P[1], P[3]), P[5]), hmax(hmax(P[7], P[9]), P[11]));
  uint32_t mx = hmax(hmax(__byte_perm(m0, m1, 0x5410), __byte_perm(m0, m1, 0x7632)), P[12]);
  uint32_t sh = __shfl_xor_sync(~0u, mx, 1);
  PINK(4)
  GK(5)
  PINK(5)
  mx = hmax(mx, sh);
  sh = __shfl_xor_sync(~0u, mx, 2);
  PINK(6)
  GK(6)
  PINK(6)
  mx = hmax(mx, sh);
#pragma unroll
  for (int j = 0; j < 12; j++) P[j] = (j & 1) ? hsub_b<1>(P[j], mx) : hsub_b<0>(P[j], mx);
  P[12] = b2u(__hsub2_rn(u2b(P[12]), u2b(mx)));
  H2 e0 = exp_halves(P[0]), e1 = exp_halves(P[1]);
  GK(7)
  if (ksched(7, NK) < NK || (SEC == 3 ? PASS_SEG3 : SEC == 2 ? PASS_SEG2 : PASS_SEG) == 8) { hold<2, 13>(P); hold(e0); hold(e1); PIN(); }
  GK(8)
  H2 e2 = exp_halves(P[2]), e3 = exp_halves(P[3]);
  P[0] = join(e0); P[1] = join(e1);
  if (ksched(8, NK) < NK || (SEC == 3 ? PASS_SEG3 : SEC == 2 ? PASS_SEG2 : PASS_SEG) == 9) { hold<0, 2>(P); hold(e2); hold(e3); PIN(); }
  GK(9)
  e0 = exp_halves(P[4]); e1 = exp_halves(P[5]);
  P[2] = join(e2); P[3] = join(e3);
  if (ksched(9, NK) < NK || (SEC == 3 ? PASS_SEG3 : SEC == 2 ? PASS_SEG2 : PASS_SEG) == 10) { hold<2, 4>(P); hold(e0); hold(e1); PIN(); }
  GK(10)
  proxy_fence();
  e2 = exp_halves(P[12]);
  P[12] = e2.l; P[13] = e2.h; P[14] = 0; P[15] = 0;
  P[4] = join(e0); P[5] = join(e1);
#pragma unroll
  for (int j = 6; j < 12; j++) P[j] = hex2(P[j]);
  if ((SEC == 3 ? PASS_SEG3 : SEC == 2 ? PASS_SEG2 : PASS_SEG) == 11 && (SEC != PP_LAST || pass)) { hold<6, 10>(P); PIN(); turn_pass<SEC>(wg); }
  bar_sync(1 + wg);
  wg_fence();
  wgmma_n56t<0>(S, P[0], P[1], P[2], P[3], dV[0]);
  wgmma_n56t<1>(S, P[4], P[5], P[6], P[7], dV[1]);
  wgmma_n56t<1>(S, P[12], P[13], P[14], P[15], dV[3]);
  wgmma_n56t<1>(S, P[8], P[9], P[10], P[11], dV[2]);
  wg_commit();
#undef GK
#undef PINK
}
template <int S0, int S1>
__device__ __forceinline__ void load_x(uint32_t (&X)[48], uint32_t t0) {
#pragma unroll
  for (int s = S0; s < S1; s++)
    asm volatile("ld.shared.v4.u32 {%0,%1,%2,%3}, [%4];" : "=r"(X[4 * s]), "=r"(X[4 * s + 1]), "=r"(X[4 * s + 2]), "=r"(X[4 * s + 3])
                 : "r"(((s & 1) ? (t0 ^ 16) : t0) + (s >> 1) * 128) : "memory");
}

template <int C, int A, int B> __device__ __forceinline__ void add_res(uint32_t* T, const uint32_t (&X)[48]) {
#pragma unroll
  for (int i = A; i < B; i++) T[i] = hadd(X[16 * C + i], T[i]);
}
template <int C>
__device__ __forceinline__ void store_out(const uint32_t* T, uint8_t* o0, uint8_t* o1, uint32_t vmask) {
#pragma unroll
  for (int c = 0; c < 2; c++) {
    asm volatile("{\n.reg .pred p;\nsetp.ne.u32 p, %5, 0;\n@p st.global.v4.u32 [%0], {%1,%2,%3,%4};\n}\n"
                 :: "l"(o0 + C * 128 + c * 64), "r"(T[8 * c]), "r"(T[8 * c + 2]), "r"(T[8 * c + 4]), "r"(T[8 * c + 6]), "r"(vmask) : "memory");
    asm volatile("{\n.reg .pred p;\nsetp.lt.s32 p, %5, 0;\n@p st.global.v4.u32 [%0], {%1,%2,%3,%4};\n}\n"
                 :: "l"(o1 + C * 128 + c * 64), "r"(T[8 * c + 1]), "r"(T[8 * c + 3]), "r"(T[8 * c + 5]), "r"(T[8 * c + 7]), "r"(vmask) : "memory");
  }
}

#define WDIV 1
template <int K, int CNT, int DIV = WDIV> __device__ __forceinline__ void load_slices(uint32_t sb, const Descs& ds) {
  constexpr int st = K < 12 ? K / 3 : 4 + (K - 12) / 2;
  constexpr bool first = K < 12 ? (K % 3 == 0) : (K % 2 == 0);
  if (first)
    asm volatile("{\n.reg .pred p;\nelect.sync _|p, 0xffffffff;\n@p mbarrier.arrive.expect_tx.shared::cta.b64 _, [%0], %1;\n}\n"
                 :: "r"(sb + BAR_WFULL + 8 * st), "n"(DIV == 1 && K == 6 ? 2 * SLICE + SLICE / WDIV : (K < 12 ? 3 : 2) * SLICE / DIV) : "memory");
  asm volatile("{\n.reg .pred p;\nelect.sync _|p, 0xffffffff;\n"
               "@p cp.async.bulk.shared::cluster.global.mbarrier::complete_tx::bytes [%0], [%1], %2, [%3];\n}\n"
               :: "r"(sb + OFF_W + (K & 7) * SLICE), "l"(ds.src[K]), "n"(CNT * SLICE / DIV), "r"(sb + BAR_WFULL + 8 * st) : "memory");
}
template <int STAGE> __device__ __forceinline__ void release(uint32_t sb, const Descs& ds, bool next_round) {
  uint32_t old;
  asm volatile("{\n.reg .b32 a;\nmov.u32 a, %%laneid;\nmad.lo.u32 a, a, 4, %1;\natom.shared.inc.u32 %0, [a + %2], 1;\n}\n"
               : "=r"(old) : "r"(sb), "n"(CNT_WREL + 128 * STAGE) : "memory");
  if (__ballot_sync(0xffffffffu, old == 1) & 1) {
    if (STAGE == 0) { load_slices<8, 1>(sb, ds); load_slices<9, 2>(sb, ds); }
    if (STAGE == 1) { load_slices<11, 1>(sb, ds); load_slices<12, 2>(sb, ds); }
    if (STAGE == 2) { load_slices<14, 2>(sb, ds); if (next_round) load_slices<0, 1>(sb, ds); }
    if (STAGE == 3 && next_round) { load_slices<1, 2>(sb, ds); load_slices<3, 1>(sb, ds); }
    if (STAGE == 4 && next_round) load_slices<4, 2>(sb, ds);
    if (STAGE == 5 && next_round) load_slices<6, 2>(sb, ds);
  }
}

__device__ __forceinline__ uint32_t ln_rstd(const uint32_t (&X)[48]) {
  uint32_t sm[2];
#pragma unroll
  for (int a = 0; a < 2; a++) {
    uint32_t t[12];
#pragma unroll
    for (int i = 0; i < 12; i++) t[i] = hadd(X[4 * i + a], X[4 * i + 2 + a]);
#pragma unroll
    for (int i = 0; i < 6; i++) t[i] = hadd(t[i], t[i + 6]);
#pragma unroll
    for (int i = 0; i < 3; i++) t[i] = hadd(t[i], t[i + 3]);
    sm[a] = hadd(hadd(t[0], t[1]), t[2]);
  }
  uint32_t m = hadd(__byte_perm(sm[0], sm[1], 0x5410), __byte_perm(sm[0], sm[1], 0x7632));
  m = hadd(m, __shfl_xor_sync(~0u, m, 1));
  m = hadd(m, __shfl_xor_sync(~0u, m, 2));
  m = hmul(m, 0x3bab3babu);
  float var[2];
#pragma unroll
  for (int a = 0; a < 2; a++) {
    uint32_t t[4];
#pragma unroll
    for (int i = 0; i < 24; i++) {
      const uint32_t d = a ? hsub_b<1>(X[2 * i + 1], m) : hsub_b<0>(X[2 * i], m);
      t[i & 3] = i < 4 ? hmul(d, d) : hfma(d, d, t[i & 3]);
    }
    const uint32_t s = hadd(hadd(t[0], t[1]), hadd(t[2], t[3]));
    float v = lo2f(s) + hi2f(s);
    v += __shfl_xor_sync(~0u, v, 1);
    v += __shfl_xor_sync(~0u, v, 2);
    asm("rsqrt.approx.ftz.f32 %0, %1;" : "=f"(var[a]) : "f"(fmaf(v, 1.0f / 192.0f, 1e-5f)));
  }
  return pack2(var[0], var[1]);
}

#define DUMMY()
__device__ __forceinline__ void stats_pass(uint32_t sb, int pass, int lane) {
  const int g = lane >> 2, q = lane & 3;
  const int tile = pass < 6 ? (pass & 1) : (g & 1);
  const int ps = pass < 6 ? (pass >> 1) * 8 + g : 24;
  uint32_t X[48];
  load_x<0, 12>(X, sb + OFF_TILE + tile * TILE_BYTES + ps * 768 + q * 32 + (ps & 1) * 16);
  const uint32_t rs = ln_rstd(X);
  asm volatile("st.shared.u32 [%0], %1;" :: "r"(sb + OFF_RSTD + tile * 100 + ps * 4), "r"(rs) : "memory");
}

__global__ void __launch_bounds__(384, 1)
fused_kernel(const __grid_constant__ CUtensorMap tmx, const __grid_constant__ CUtensorMap tmp, const __grid_constant__ Descs ds, const __nv_bfloat16* __restrict__ dw, __nv_bfloat16* __restrict__ out, const int never) {
  extern __shared__ __align__(1024) uint8_t smem[];
  const uint32_t sb = (uint32_t)__cvta_generic_to_shared(smem);
  const int tid = threadIdx.x, lane = tid & 31;
  const int warp = __shfl_sync(0xffffffffu, tid >> 5, 0);
  const int cta = blockIdx.x, ncta = gridDim.x;
  const int nfull = NWIN / (2 * ncta);
  const int nrounds = nfull + ((NWIN - nfull * 2 * ncta) > cta ? 1 : 0);

  if (warp == 0) GTS(0);
  auto prefetch_round = [&](int r) {
#pragma unroll
    for (int k = 0; k < 2; k++) {
      const int w = window_of(r, nfull, cta, ncta, k);
      if (w >= 0) {
        const int a = w / NWX;
        asm volatile("{\n.reg .pred p;\nelect.sync _|p, 0xffffffff;\n@p cp.async.bulk.prefetch.tensor.3d.L2.global [%0, {0, %1, %2}];\n}\n"
                     :: "l"(reinterpret_cast<uint64_t>(&tmp)), "r"((w - a * NWX) * 7 - 1), "r"(a * 7 - 1) : "memory");
      }
    }
  };
  if (warp == 11) prefetch_round(0);
  if (warp == 10 && lane == 0) asm volatile("prefetch.tensormap [%0];" :: "l"(reinterpret_cast<uint64_t>(&tmx)) : "memory");
  if (tid == 0) {
    if ((sb & 0x3FFFF) != SMEM_BASE) __trap();
    for (int i = 0; i < 6; i++) { mbar_init(sb + BAR_WFULL + 8 * i, 1); }
    for (int i = 0; i < 9; i++) mbar_init(sb + BAR_XFULL + 8 * i, 1);
    mbar_init(sb + BAR_TFULL, 3);
    mbar_init(sb + BAR_TEMPTY, 8);
    mbar_init(sb + BAR_TPART, 3);
    mbar_init(sb + BAR_TPART + 8, 3);
    mbar_init(sb + BAR_SFULL, 4);
    asm volatile("fence.mbarrier_init.release.cluster;" ::: "memory");
  }
  if (tid >= 128 && tid < 320) {
    *reinterpret_cast<uint32_t*>(smem + CNT_WREL + (tid - 128) * 4) = 0;
    *reinterpret_cast<uint32_t*>(smem + OFF_ZERO + (tid - 128) * 4) = 0;
  }
  if (tid < 128) {
    const uint32_t v = (tid & 63) < 49 ? 0x3f803f80u : 0u;
    *reinterpret_cast<uint4*>(smem + OFF_KV + (tid >> 6) * KV_BYTES + 6 * KV_PITCH + (tid & 63) * 16) = make_uint4(v, v, v, v);
    asm volatile("fence.proxy.async.shared::cta;" ::: "memory");
  }
  __syncthreads();

  if (warp >= 8) {
    asm volatile("setmaxnreg.dec.sync.aligned.u32 " PREGS ";");
    if (warp == 11) {
      asm volatile("griddepcontrol.wait;" ::: "memory");
      load_slices<0, 3, 1>(sb, ds); load_slices<3, 3, 1>(sb, ds); load_slices<6, 2, 1>(sb, ds);
      for (int r = 0; r < nrounds; r++) {
#pragma unroll 1
        for (int pass = 0; pass < 4; pass++) {
          if (!(pass & 1)) mbar_wait(sb + BAR_TPART + 4 * pass, r & 1);
          stats_pass(sb, pass, lane);
        }
        __syncwarp();
        if (lane == 0) mbar_arrive(sb + BAR_SFULL);
        DUMMY();
        TR(2);
      }
    } else {
      const int cw = warp - 8;
      const int win = lane >> 4;
      const int ch0 = cw * 64 + (lane & 15) * 4;
      uint32_t wt[9][2];
#pragma unroll
      for (int t = 0; t < 9; t++) {
        uint2 v = *reinterpret_cast<const uint2*>(dw + t * CH + ch0);
        wt[t][0] = v.x; wt[t][1] = v.y;
      }
      const uint32_t xs = sb + OFF_X + cw * 3 * XSLOT;
      const uint32_t xld = xs + (lane >> 4) * 1152 + (lane & 15) * 8;
      const uint32_t xbar = sb + BAR_XFULL + cw * 24;
      const uint32_t st0 = sb + OFF_TILE + win * TILE_BYTES + ch0 * 4;
      const uint32_t st1 = sb + OFF_TILE + win * TILE_BYTES + ((ch0 * 4) ^ 16);
      const uint64_t tm = reinterpret_cast<uint64_t>(&tmx);
      int cx0, cy0, cx1, cy1;
      auto coords = [&](int r) {
        const int w0 = window_of(r, nfull, cta, ncta, 0);
        int w1 = window_of(r, nfull, cta, ncta, 1);
        if (w1 < 0) w1 = w0;
        const int a = w0 / NWX, b = w1 / NWX;
        cx0 = (w0 - a * NWX) * 7 - 1; cy0 = a * 7 - 1;
        cx1 = (w1 - b * NWX) * 7 - 1; cy1 = b * 7 - 1;
      };
      auto issue = [&](int slot, int dy) {
        asm volatile("{\n.reg .pred p;\nelect.sync _|p, 0xffffffff;\n"
                     "@p mbarrier.arrive.expect_tx.shared::cta.b64 _, [%2], %8;\n"
                     "@p cp.async.bulk.tensor.3d.shared::cluster.global.mbarrier::complete_tx::bytes [%0], [%1, {%3, %4, %5}], [%2];\n"
                     "@p cp.async.bulk.tensor.3d.shared::cluster.global.mbarrier::complete_tx::bytes [%0 + 1152], [%1, {%3, %6, %7}], [%2];\n}\n"
                     :: "r"(xs + slot * XSLOT), "l"(tm), "r"(xbar + slot * 8), "r"(cw * 64), "r"(cx0), "r"(cy0 + dy), "r"(cx1), "r"(cy1 + dy), "n"(XSLOT) : "memory");
      };
      coords(0);
      issue(0, 0); issue(1, 1); issue(2, 2);
      for (int r = 0; r < nrounds; r++) {
        const bool more = r + 1 < nrounds;
        uint32_t accA[7][2], accB[7][2], ctr[7][2], held[2];
#pragma unroll
        for (int i = 0; i < 9; i++) {
          mbar_wait(xbar + (i % 3) * 8, (r + i / 3) & 1);
          if (i == 0 && r == 0 && cw == 0) GTS(7);
          if (i == 5 || i == 7) { __syncwarp(); if (lane == 0) mbar_arrive(sb + BAR_TPART + (i == 5 ? 0 : 8)); }
          if (i == 7 && more) coords(r + 1);
          if (i == 0) { if (r > 0) issue(2, 2); }
          else if (i < 7) issue((i + 2) % 3, i + 2);
          else if (more) issue((i + 2) % 3, i - 7);
          if (i == 2 && r > 0) mbar_wait(sb + BAR_TEMPTY, (r - 1) & 1);
          if (i == 2) { TR(0); }
          uint32_t cur[9][2];
#pragma unroll
          for (int p = 0; p < 5; p++)
            asm volatile("ld.shared.v2.u32 {%0,%1}, [%2];" : "=r"(cur[p][0]), "=r"(cur[p][1]) : "r"(xld + (i % 3) * XSLOT + p * 128));
#pragma unroll
          for (int j = 0; j < 7; j++) {
            if (j >= 1 && j + 4 < 9)
              asm volatile("ld.shared.v2.u32 {%0,%1}, [%2];" : "=r"(cur[j + 4][0]), "=r"(cur[j + 4][1]) : "r"(xld + (i % 3) * XSLOT + (j + 4) * 128));
            if (i >= 2) {
              uint32_t o[2];
#pragma unroll
              for (int e = 0; e < 2; e++) {
                uint32_t a = hfma(cur[j][e], wt[6][e], accA[j][e]);
                a = hfma(cur[j + 1][e], wt[7][e], a);
                a = hfma(cur[j + 2][e], wt[8][e], a);
                o[e] = hadd(ctr[j][e], a);
              }
              const int tok = (i - 2) * 7 + j, ps = tok >> 1;
              if (!(tok & 1)) { held[0] = o[0]; held[1] = o[1]; }
              if (tok == 48) o[0] = o[1] = 0;
              if ((tok & 1) || tok == 48)
                asm volatile("st.shared.v4.u32 [%0], {%1,%2,%3,%4};" :: "r"(((ps & 1) ? st1 : st0) + ps * 768), "r"(held[0]), "r"(o[0]), "r"(held[1]), "r"(o[1]) : "memory");
            }
#pragma unroll
            for (int e = 0; e < 2; e++) {
              if (i >= 1 && i <= 7) {
                uint32_t a = hfma(cur[j][e], wt[3][e], accB[j][e]);
                a = hfma(cur[j + 1][e], wt[4][e], a);
                accA[j][e] = hfma(cur[j + 2][e], wt[5][e], a);
                ctr[j][e] = cur[j + 1][e];
              }
              if (i <= 6) {
                uint32_t a = hmul(cur[j][e], wt[0][e]);
                a = hfma(cur[j + 1][e], wt[1][e], a);
                accB[j][e] = hfma(cur[j + 2][e], wt[2][e], a);
              }
            }
          }
        }
        __syncwarp();
        if (lane == 0) mbar_arrive(sb + BAR_TFULL);
        TR(1);
        mbar_wait(sb + BAR_TFULL, r & 1);
        stats_pass(sb, 4 + cw, lane);
        __syncwarp();
        if (lane == 0) mbar_arrive(sb + BAR_SFULL);
        DUMMY();
      }
    }
  } else {
    asm volatile("setmaxnreg.inc.sync.aligned.u32 " CREGS ";");
    const int wg = warp >> 2, w4 = warp & 3, g = lane >> 2, q = lane & 3;
    const int row0 = w4 * 16 + g, row1 = row0 + 8;
    const int ps = min(w4 * 8 + g, 24);
    const int tok0 = 2 * ps, tok1 = min(2 * ps + 1, 48);
    const uint32_t kv = sb + OFF_KV + wg * KV_BYTES;
    const int srow = w4 * 16 + (lane & 15);
    const uint32_t vst = kv + (lane >> 4) * KV_PITCH + (srow < 56 ? srow : min(srow - 7, 55)) * 16;
    uint32_t misc = ((uint32_t)((tok1 / 7) * IMG + tok1 % 7) << 20) | ((uint32_t)((tok0 / 7) * IMG + tok0 % 7) << 8) | (ps * 4 + q);
    const uint32_t ninf = q ? 0xff80ff80u : 0u;
    const uint32_t vmask = (row0 < 49 ? 0xffffu : 0u) | (row1 < 49 ? 0xffff0000u : 0u);

    const uint32_t tx = sb + q * 32 + (row0 < 49 ? OFF_TILE + wg * TILE_BYTES + ps * 768 + (ps & 1) * 16 : OFF_ZERO + 16);
    const int myrounds = window_of(nrounds - 1, nfull, cta, ncta, wg) < 0 ? nrounds - 1 : nrounds;

    if (never == 2) return;
    uint32_t X[48];
    float acc[72];
    if (warp == 0) GTS(1);
    mbar_wait(sb + BAR_TFULL, 0);
    if (warp == 0) GTS(2);
    load_x<0, 12>(X, tx);
    mbar_wait(sb + BAR_WFULL, 0);
    if (warp == 0) GTS(3);
    mma144<0, 12>(acc, X, ds.q[0]);
    uint32_t rK;
    mbar_wait(sb + BAR_SFULL, 0);
    if (warp == 0) GTS(4);
    asm volatile("ld.shared.u32 %0, [%1];" : "=r"(rK) : "r"(sb + OFF_RSTD + wg * 100 + (misc & 0xfc)) : "memory");
    __syncwarp();
    if (lane == 0) mbar_arrive(sb + BAR_TEMPTY);

    if (wg == 1) turn_pass<PP_LAST>(1);
    for (int r = 0;; r++) {
      const uint32_t par = r & 1;
      if (r == myrounds) {
        wg_wait<0>(); keep(acc);
        if (w4 == 0) GTS(5 + wg);
        if (r < nrounds)
        {
          mbar_wait(sb + BAR_WFULL, par);      if (w4 == 3) release<0>(sb, ds, false);
          mbar_wait(sb + BAR_WFULL + 8, par);  if (w4 == 3) release<1>(sb, ds, false);
          turn_wait<0>(wg); if (PP_LAST != 0) turn_pass<0>(wg);
          mbar_wait(sb + BAR_WFULL + 16, par); if (w4 == 3) release<2>(sb, ds, false);
          turn_wait<1>(wg); if (PP_LAST != 1) turn_pass<1>(wg);
          turn_wait<2>(wg); if (PP_LAST != 2) turn_pass<2>(wg);
          turn_wait<3>(wg); if (PP_LAST != 3) turn_pass<3>(wg);
          turn_wait<4>(wg); if (PP_LAST != 4) turn_pass<4>(wg);
          turn_wait<5>(wg);
        }
        break;
      }
      TR(0);
      const bool next_round = r + 1 < nrounds;
      const bool pass = wg == 0 || next_round;
      uint32_t Of[48], Q[12], T[16], inv = 0;
      float S[28];
      const uint64_t* dkv = ds.kv[wg];

#define PRE(H, ACC)                                                                     \
      packn<0, 12>(T, ACC); scalen<0, 12>(T, rK); stsm12(T, vst + KV_KOFF);                       \
      packn<0, 12>(T, ACC + 24); hold<0, 12>(T);                                        \
      PIN();                                                                            \
      if (H > 0) { wg_wait<0>(); keep(S); }                                             \
      proxy_fence();                                                                    \
      _Pragma("unroll") for (int i = 0; i < 12; i++) Q[i] = T[i];                       \
      scalen<0, 12>(Q, rK); hold<0, 12>(Q);
#define PRE2(H)                                                                         \
      if (H > 0) { inv = inv_sum(S) & vmask; packn<0, 12>(Of + 12 * (H > 0 ? H - 1 : 0), S);    \
                   hold<0, 12>(Of + 12 * (H > 0 ? H - 1 : 0)); hold<0, 1>(&inv); }
#define MID(H, VACC, FIRST2)                                                             \
      PIN();                                                                            \
      packn<0, 12>(T, VACC); scalen<0, 12>(T, rK); stsm12(T, vst);                      \
      if (H < 3 && w4 == 3) release<(H < 3 ? H : 0)>(sb, ds, next_round);               \
      turn_wait<H>(wg);                                                                 \
      PIN();                                                                            \
      FIRST2;                                                                           \
      wg_wait<1>(); keep(S);

      wg_wait<0>(); keep(acc);
      TR(2);
      PRE(0, acc) PRE2(0)
      mbar_wait(sb + BAR_WFULL + 8, par);
      bar_sync(1 + wg);
      TR(3);
      issue_s(S, Q, dkv);
      MID(0, acc + 48, (mma144<0, ksched(0, 12)>(acc, X, ds.q[1])))
      TR(4);
      softmax_pv<0, 12, false>(S, dkv + 4, Of, inv, wg, pass, ninf, vmask, [&](auto a, auto b) { mma144<a.v, b.v>(acc, X, ds.q[1]); });
      TR(5);
      wg_wait<1>(); keep(acc);
      TR(6);
      PRE(1, acc) PRE2(1)
      mbar_wait(sb + BAR_WFULL + 16, par);
      bar_sync(1 + wg);
      TR(7);
      issue_s(S, Q, dkv);
      MID(1, acc + 48, (mma144<0, ksched(0, 12)>(acc, X, ds.q[2])))
      TR(8);
      softmax_pv<1, 12, true>(S, dkv + 4, Of, inv, wg, pass, ninf, vmask, [&](auto a, auto b) { mma144<a.v, b.v>(acc, X, ds.q[2]); });
      TR(9);
      float kq[48], va[24], pa[32], pb[32];
      wg_wait<1>(); keep(acc);
      TR(10);
      PRE(2, acc) PRE2(2)
      mbar_wait(sb + BAR_WFULL + 24, par);
      bar_sync(1 + wg);
      TR(11);
      issue_s(S, Q, dkv);
      MID(2, acc + 48, (mma96<0, ksched(0, 12)>(kq, X, ds.q[3])))
      TR(12);
      softmax_pv<2, 12, true>(S, dkv + 4, Of + 12, inv, wg, pass, ninf, vmask, [&](auto a, auto b) { mma96<a.v, b.v>(kq, X, ds.q[3]); });
      TR(13);
      wg_wait<1>(); keep(kq);
      TR(14);
      packn<0, 12>(T, kq); scalen<0, 12>(T, rK); stsm12(T, vst + KV_KOFF); PIN();
      wg_wait<0>(); keep(S);
      mma48<0, 4>(va, X, ds.v3);
      packn<0, 6>(Q, kq + 24); scalen<0, 6>(Q, rK); hold<0, 6>(Q); PIN();
      mma48<4, 8>(va, X, ds.v3);
      packn<6, 12>(Q, kq + 24); scalen<6, 12>(Q, rK); hold<6, 12>(Q); PIN();
      mma48<8, 12>(va, X, ds.v3);
      PIN();
      proxy_fence();
      PRE2(3)
      scalen<24, 36>(Of, inv); hold<24, 36>(Of);
      mbar_wait(sb + BAR_WFULL + 32, par);
      bar_sync(1 + wg);
      TR(15);
      issue_s(S, Q, dkv);
      wg_wait<1>(); keep(va);
      MID(3, va, (mma64<0, ksched(0, 9)>(pa, Of, ds.p)))
      TR(16);
      softmax_pv<3, 9, false>(S, dkv + 4, Of + 24, inv, wg, pass, ninf, vmask, [&](auto a, auto b) { mma64<a.v, b.v>(pa, Of, ds.p); });
      if (w4 == 3) release<3>(sb, ds, next_round);
      TR(17);
#undef PRE
#undef PRE2
#undef MID
      const bool more = r + 1 < myrounds;
      const int w = window_of(r, nfull, cta, ncta, wg);
      const int wy = w / NWX, wx = w - wy * NWX;
      asm volatile("" : "+r"(misc));
      const uint32_t wb = (uint32_t)(wy * 7 * IMG + wx * 7) * 384u + (misc & 3) * 16;
      uint8_t* o0 = reinterpret_cast<uint8_t*>(out) + (wb + ((misc >> 8) & 0xfff) * 384u);
      uint8_t* o1 = reinterpret_cast<uint8_t*>(out) + (wb + (misc >> 20) * 384u);
      mbar_wait(sb + BAR_WFULL + 40, par);
      wg_wait<0>(); keep(S); keep(pa);
      TR(18);
      inv = inv_sum(S) & vmask; packn<0, 12>(Of + 36, S); hold<36, 48>(Of); turn_wait<4>(wg); PIN();
      mma64<0, 5>(pb, Of, ds.p + 12);
      scalen<36, 48>(Of, inv); hold<36, 48>(Of); PIN();
      mma64<9, 12>(pa, Of, ds.p);
      mma64<5, 12>(pb, Of, ds.p + 12);
      if (more) mbar_wait(sb + BAR_TFULL, par ^ 1);
      TR(19);
      wg_wait<1>(); keep(pa);
      TR(20);
      packn<0, 16>(T, pa); add_res<0, 0, 12>(T, X); hold<0, 16>(T); PIN();
      mma64<0, 3, 2>(pa, Of, ds.p + 24);
      add_res<0, 12, 16>(T, X); hold<12, 16>(T); PIN();
      load_x<0, 4>(X, tx); store_out<0>(T, o0, o1, vmask); PIN();
      mma64<3, 12>(pa, Of, ds.p + 24);
      if (PP_LAST != 4 || pass) turn_pass<4>(wg);
      PIN();
      TR(21);
      wg_wait<2>(); keep(pb);
      bar_sync(1 + wg);
      packn<0, 16>(T, pb); add_res<1, 0, 16>(T, X); hold<0, 16>(T); PIN();
      if (w4 == 3) release<4>(sb, ds, next_round);
      load_x<4, 8>(X, tx); store_out<1>(T, o0, o1, vmask);
      if (more) mbar_wait(sb + BAR_WFULL, par ^ 1);
      TR(22);
      wg_wait<0>(); keep(pa);
      TR(23);
      if (PPMASK >> 5 & 1) turn_wait<5>(wg); else bar_sync(1 + wg);
      mma144<0, 1>(acc, X, ds.q[0]);
      packn<0, 6>(T, pa); add_res<2, 0, 4>(T, X); hold<0, 6>(T); PIN();
      mma144<1, 2>(acc, X, ds.q[0]);
      packn<6, 11>(T, pa); add_res<2, 4, 9>(T, X); hold<4, 11>(T); PIN();
      mma144<2, 3>(acc, X, ds.q[0]);
      packn<11, 16>(T, pa); add_res<2, 9, 16>(T, X); hold<9, 16>(T); PIN();
      mma144<3, 8>(acc, X, ds.q[0]);
      load_x<8, 12>(X, tx); store_out<2>(T, o0, o1, vmask);
      if (w4 == 3) release<5>(sb, ds, next_round);
      if (more) mbar_wait(sb + BAR_SFULL, par ^ 1);
      asm volatile("ld.shared.u32 %0, [%1];" : "=r"(rK) : "r"(sb + OFF_RSTD + wg * 100 + (misc & 0xfc)) : "memory");
      mma144<8, 12>(acc, X, ds.q[0]);
      if (pass) turn_pass<5>(wg);
      __syncwarp();
      if (lane == 0) mbar_arrive(sb + BAR_TEMPTY);
      TR(1);
    }
  }
}

typedef CUresult (*EncodeFn)(CUtensorMap*, CUtensorMapDataType, cuuint32_t, void*, const cuuint64_t*, const cuuint64_t*,
                             const cuuint32_t*, const cuuint32_t*, CUtensorMapInterleave, CUtensorMapSwizzle,
                             CUtensorMapL2promotion, CUtensorMapFloatOOBfill);

}

extern "C" void kernel_launch(void* const* d_in, const int* in_sizes, int n_in, void* d_out, int out_size) {
  const __nv_bfloat16* x = (const __nv_bfloat16*)d_in[0];
  const __nv_bfloat16* dw = (const __nv_bfloat16*)d_in[1];
  const __nv_bfloat16* wqkv = (const __nv_bfloat16*)d_in[2];
  const __nv_bfloat16* wo = (const __nv_bfloat16*)d_in[3];
  static EncodeFn encode = nullptr;
  static int nsm = 0;
  static void* wpack = nullptr;
  if (!encode) {
    void* fn = nullptr;
    cudaDriverEntryPointQueryResult qr;
    cudaGetDriverEntryPoint("cuTensorMapEncodeTiled", &fn, cudaEnableDefault, &qr);
    encode = (EncodeFn)fn;
    int dev = 0;
    cudaGetDevice(&dev);
    cudaDeviceGetAttribute(&nsm, cudaDevAttrMultiProcessorCount, dev);
    cudaGetSymbolAddress(&wpack, g_wpack);
    cudaFuncSetAttribute(fused_kernel, cudaFuncAttributeMaxDynamicSharedMemorySize, SMEM_BYTES);
  }
  CUtensorMap tmx;
  cuuint64_t gdim[3] = {CH, IMG, IMG};
  cuuint64_t gstr[2] = {CH * 2, (cuuint64_t)CH * 2 * IMG};
  cuuint32_t box[3] = {64, 9, 1};
  cuuint32_t estr[3] = {1, 1, 1};
  encode(&tmx, CU_TENSOR_MAP_DATA_TYPE_BFLOAT16, 3, (void*)x, gdim, gstr, box, estr, CU_TENSOR_MAP_INTERLEAVE_NONE,
         CU_TENSOR_MAP_SWIZZLE_NONE, CU_TENSOR_MAP_L2_PROMOTION_L2_128B, CU_TENSOR_MAP_FLOAT_OOB_FILL_NONE);
  Descs ds;
  for (int i = 0; i < 12; i++) {
    for (int h = 0; h < 4; h++) ds.q[h][i] = mkdesc(SMEM_BASE + OFF_W + qkv_off(h, i), 128, 256);
    ds.v3[i] = mkdesc(SMEM_BASE + OFF_W + qkv_off(3, i) + 3072, 128, 256);
    for (int c = 0; c < 3; c++) ds.p[c * 12 + i] = mkdesc(SMEM_BASE + OFF_W + wo_off(c, i), 128, 256);
  }
  for (int i = 0; i < 16; i++) ds.src[i] = (const uint8_t*)wpack + i * SLICE;
  for (int g = 0; g < 2; g++)
    for (int i = 0; i < 4; i++) {
      ds.kv[g][i] = mkdesc(SMEM_BASE + OFF_KV + g * KV_BYTES + KV_KOFF + 2 * i * KV_PITCH, KV_PITCH, 128);
      ds.kv[g][4 + i] = mkdesc(SMEM_BASE + OFF_KV + g * KV_BYTES + 256 * i, 128, KV_PITCH);
    }
  CUtensorMap tmp;
  cuuint32_t boxp[3] = {CH, 9, 9};
  encode(&tmp, CU_TENSOR_MAP_DATA_TYPE_BFLOAT16, 3, (void*)x, gdim, gstr, boxp, estr, CU_TENSOR_MAP_INTERLEAVE_NONE,
         CU_TENSOR_MAP_SWIZZLE_NONE, CU_TENSOR_MAP_L2_PROMOTION_L2_128B, CU_TENSOR_MAP_FLOAT_OOB_FILL_NONE);
  prepack_kernel<<<48, dim3(192, 2), 0, cudaStreamPerThread>>>(wqkv, wo);
  cudaLaunchConfig_t cfg = {};
  cfg.gridDim = dim3(nsm); cfg.blockDim = dim3(384); cfg.dynamicSmemBytes = SMEM_BYTES; cfg.stream = cudaStreamPerThread;
  cudaLaunchAttribute at[1];
  at[0].id = cudaLaunchAttributeProgrammaticStreamSerialization;
  at[0].val.programmaticStreamSerializationAllowed = 1;
  cfg.attrs = at; cfg.numAttrs = 1;
  cudaLaunchKernelEx(&cfg, fused_kernel, tmx, tmp, ds, dw, (__nv_bfloat16*)d_out, 0);
}
```

```cpp
#include <cuda_runtime.h>
#include <cuda_bf16.h>
#include <cuda.h>
#include <stdint.h>

#define CREGS "208"
#define PREGS "88"
namespace {

constexpr int IMG = 511;
constexpr int CH = 192;
constexpr int NWX = 73;
constexpr int NWIN = NWX * NWX;
constexpr int SLICE = 18432;
constexpr int OFF_W = 0;
constexpr int KV_PITCH = 1792, KV_KOFF = 896, KV_BYTES = 6 * KV_PITCH + 1024;
constexpr int OFF_KV = 8 * SLICE;
constexpr int TILE_BYTES = 25 * 768;
constexpr int OFF_TILE = OFF_KV + 2 * KV_BYTES;
constexpr int XSLOT = 2304;
constexpr int OFF_ZERO = OFF_TILE + 2 * TILE_BYTES;
constexpr int OFF_X = OFF_ZERO + 768;
constexpr int OFF_BAR = OFF_X + 9 * XSLOT;
constexpr int BAR_WFULL = OFF_BAR;
constexpr int BAR_XFULL = OFF_BAR + 72;
constexpr int BAR_TFULL = OFF_BAR + 144;
constexpr int BAR_TEMPTY = OFF_BAR + 152;
constexpr int BAR_TPART = OFF_BAR + 160;
constexpr int BAR_SFULL = OFF_BAR + 176;
constexpr int OFF_RSTD = OFF_BAR + 192;
constexpr int CNT_WREL = OFF_RSTD + 208;
constexpr int OFF_TRACE = CNT_WREL + 768;
constexpr int SMEM_BYTES = OFF_TRACE;

constexpr int SMEM_BASE = 1024;
struct Descs { uint64_t q[4][12]; uint64_t v3[12]; uint64_t p[36]; uint64_t kv[2][8]; const uint8_t* src[16]; };

__device__ uint4 g_wpack[16 * SLICE / 16];
#define TR(id)
#define GTS(i)
template <int ID> __device__ __forceinline__ void sched_fence(uint32_t v) {
  asm volatile("{\n.reg .pred p;\nsetp.ne.u32 p, %0, %1;\n@p bra.uni SF_%=;\ntrap;\nSF_%=:\n}\n" :: "r"(v), "n"(ID) : "memory");
}
__device__ __forceinline__ void anchor(uint32_t v) { sched_fence<0x7fc1ffc1>(v); }

template <int V> struct IC { static constexpr int v = V; };
typedef __nv_bfloat162 bf2;
__device__ __forceinline__ bf2 u2b(uint32_t u) { return *reinterpret_cast<bf2*>(&u); }
__device__ __forceinline__ uint32_t b2u(bf2 b) { return *reinterpret_cast<uint32_t*>(&b); }
__device__ __forceinline__ uint32_t pack2(float lo, float hi) {
  uint32_t r; asm("cvt.rn.bf16x2.f32 %0, %1, %2;" : "=r"(r) : "f"(hi), "f"(lo)); return r;
}
__device__ __forceinline__ uint32_t hadd(uint32_t a, uint32_t b) { return b2u(__hadd2_rn(u2b(a), u2b(b))); }
__device__ __forceinline__ uint32_t hmul(uint32_t a, uint32_t b) { return b2u(__hmul2_rn(u2b(a), u2b(b))); }
__device__ __forceinline__ uint32_t hfma(uint32_t a, uint32_t b, uint32_t c) { return b2u(__hfma2(u2b(a), u2b(b), u2b(c))); }
__device__ __forceinline__ uint32_t hmax(uint32_t a, uint32_t b) { return b2u(__hmax2(u2b(a), u2b(b))); }
template <int HI> __device__ __forceinline__ bf2 bcast(uint32_t a) { return HI ? __high2bfloat162(u2b(a)) : __low2bfloat162(u2b(a)); }
template <int HI> __device__ __forceinline__ uint32_t hmul_b(uint32_t a, uint32_t s) { return b2u(__hmul2_rn(u2b(a), bcast<HI>(s))); }
template <int HI> __device__ __forceinline__ uint32_t hsub_b(uint32_t a, uint32_t s) { return b2u(__hsub2_rn(u2b(a), bcast<HI>(s))); }
__device__ __forceinline__ uint32_t hex2(uint32_t a) { uint32_t r; asm("ex2.approx.ftz.bf16x2 %0, %1;" : "=r"(r) : "r"(a)); return r; }
__device__ __forceinline__ float lo2f(uint32_t a) { return __uint_as_float(a << 16); }
__device__ __forceinline__ float hi2f(uint32_t a) { return __uint_as_float(a & 0xffff0000u); }

__device__ __forceinline__ void mbar_init(uint32_t bar, uint32_t cnt) { asm volatile("mbarrier.init.shared::cta.b64 [%0], %1;" :: "r"(bar), "r"(cnt) : "memory"); }
__device__ __forceinline__ void mbar_arrive(uint32_t bar) { asm volatile("mbarrier.arrive.shared::cta.b64 _, [%0];" :: "r"(bar) : "memory"); }
__device__ __forceinline__ void mbar_expect(uint32_t bar, uint32_t bytes) { asm volatile("mbarrier.arrive.expect_tx.shared::cta.b64 _, [%0], %1;" :: "r"(bar), "r"(bytes) : "memory"); }
template <int HINT>
__device__ __forceinline__ bool mbar_try(uint32_t bar, uint32_t parity) {
  uint32_t ok;
  if (HINT) asm volatile("{\n.reg .pred p;\nmbarrier.try_wait.parity.shared::cta.b64 p, [%1], %2, %3;\nselp.u32 %0, 1, 0, p;\n}\n" : "=r"(ok) : "r"(bar), "r"(parity), "n"(HINT) : "memory");
  else asm volatile("{\n.reg .pred p;\nmbarrier.try_wait.parity.shared::cta.b64 p, [%1], %2;\nselp.u32 %0, 1, 0, p;\n}\n" : "=r"(ok) : "r"(bar), "r"(parity) : "memory");
  return ok != 0;
}
__device__ __forceinline__ void mbar_wait(uint32_t bar, uint32_t parity) {
  if (__builtin_expect(!mbar_try<0>(bar, parity), 0)) {
    uint32_t n = 0;
    while (!mbar_try<4000>(bar, parity)) { if (++n > (1u << 20)) __trap(); }
  }
}
__device__ __forceinline__ void wg_fence() { asm volatile("wgmma.fence.sync.aligned;" ::: "memory"); }
__device__ __forceinline__ void wg_commit() { asm volatile("wgmma.commit_group.sync.aligned;" ::: "memory"); }
template <int N> __device__ __forceinline__ void wg_wait() { asm volatile("wgmma.wait_group.sync.aligned %0;" :: "n"(N) : "memory"); }
__device__ __forceinline__ void bar_sync(int id) { asm volatile("bar.sync %0, 128;" :: "r"(id) : "memory"); }
#define PPMASK 0x3f
template <int SEC> __device__ __forceinline__ void turn_wait(int wg) { if (PPMASK >> SEC & 1) asm volatile("bar.sync %0, 256;" :: "r"(3 + wg) : "memory"); }
template <int SEC> __device__ __forceinline__ void turn_pass(int wg) { if (PPMASK >> SEC & 1) asm volatile("bar.arrive %0, 256;" :: "r"(4 - wg) : "memory"); }
constexpr int PP_LAST = PPMASK >= 32 ? 5 : PPMASK >= 16 ? 4 : PPMASK >= 8 ? 3 : PPMASK >= 4 ? 2 : PPMASK >= 2 ? 1 : 0;
__device__ __forceinline__ void stsm4(uint32_t addr, uint32_t a, uint32_t b, uint32_t c, uint32_t d) {
  asm volatile("stmatrix.sync.aligned.m8n8.x4.shared.b16 [%0], {%1,%2,%3,%4};" :: "r"(addr), "r"(a), "r"(b), "r"(c), "r"(d) : "memory");
}
template <int N> __device__ __forceinline__ void keep(float (&d)[N]) {
#pragma unroll
  for (int i = 0; i < N; i++) asm volatile("" : "+f"(d[i]) :: "memory");
}
__host__ __device__ __forceinline__ uint64_t mkdesc(uint32_t addr, uint32_t lbo, uint32_t sbo) {
  return ((uint64_t)(sbo >> 4) << 32) | (uint64_t)(((lbo >> 4) << 16) | ((addr & 0x3FFFF) >> 4));
}

template <int SCALE_D>
__device__ __forceinline__ void wgmma_n144(float (&d)[72], uint32_t a0, uint32_t a1, uint32_t a2, uint32_t a3, uint64_t descB) {
  if (SCALE_D == 0)
  asm volatile("wgmma.mma_async.sync.aligned.m64n144k16.f32.bf16.bf16 "
    "{%0, %1, %2, %3, %4, %5, %6, %7, %8, %9, %10, %11, %12, %13, %14, %15, "
    "%16, %17, %18, %19, %20, %21, %22, %23, %24, %25, %26, %27, %28, %29, %30, %31, "
    "%32, %33, %34, %35, %36, %37, %38, %39, %40, %41, %42, %43, %44, %45, %46, %47, "
    "%48, %49, %50, %51, %52, %53, %54, %55, %56, %57, %58, %59, %60, %61, %62, %63, "
    "%64, %65, %66, %67, %68, %69, %70, %71}, "
    "{%72, %73, %74, %75}, %76, 0, 1, 1, 0;\n"
    : "=f"(d[0]), "=f"(d[1]), "=f"(d[2]), "=f"(d[3]), "=f"(d[4]), "=f"(d[5]), "=f"(d[6]), "=f"(d[7]),
      "=f"(d[8]), "=f"(d[9]), "=f"(d[10]), "=f"(d[11]), "=f"(d[12]), "=f"(d[13]), "=f"(d[14]), "=f"(d[15]),
      "=f"(d[16]), "=f"(d[17]), "=f"(d[18]), "=f"(d[19]), "=f"(d[20]), "=f"(d[21]), "=f"(d[22]), "=f"(d[23]),
      "=f"(d[24]), "=f"(d[25]), "=f"(d[26]), "=f"(d[27]), "=f"(d[28]), "=f"(d[29]), "=f"(d[30]), "=f"(d[31]),
      "=f"(d[32]), "=f"(d[33]), "=f"(d[34]), "=f"(d[35]), "=f"(d[36]), "=f"(d[37]), "=f"(d[38]), "=f"(d[39]),
      "=f"(d[40]), "=f"(d[41]), "=f"(d[42]), "=f"(d[43]), "=f"(d[44]), "=f"(d[45]), "=f"(d[46]), "=f"(d[47]),
      "=f"(d[48]), "=f"(d[49]), "=f"(d[50]), "=f"(d[51]), "=f"(d[52]), "=f"(d[53]), "=f"(d[54]), "=f"(d[55]),
      "=f"(d[56]), "=f"(d[57]), "=f"(d[58]), "=f"(d[59]), "=f"(d[60]), "=f"(d[61]), "=f"(d[62]), "=f"(d[63]),
      "=f"(d[64]), "=f"(d[65]), "=f"(d[66]), "=f"(d[67]), "=f"(d[68]), "=f"(d[69]), "=f"(d[70]), "=f"(d[71])
    : "r"(a0), "r"(a1), "r"(a2), "r"(a3), "l"(descB));
  else
  asm volatile("wgmma.mma_async.sync.aligned.m64n144k16.f32.bf16.bf16 "
    "{%0, %1, %2, %3, %4, %5, %6, %7, %8, %9, %10, %11, %12, %13, %14, %15, "
    "%16, %17, %18, %19, %20, %21, %22, %23, %24, %25, %26, %27, %28, %29, %30, %31, "
    "%32, %33, %34, %35, %36, %37, %38, %39, %40, %41, %42, %43, %44, %45, %46, %47, "
    "%48, %49, %50, %51, %52, %53, %54, %55, %56, %57, %58, %59, %60, %61, %62, %63, "
    "%64, %65, %66, %67, %68, %69, %70, %71}, "
    "{%72, %73, %74, %75}, %76, 1, 1, 1, 0;\n"
    : "+f"(d[0]), "+f"(d[1]), "+f"(d[2]), "+f"(d[3]), "+f"(d[4]), "+f"(d[5]), "+f"(d[6]), "+f"(d[7]),
      "+f"(d[8]), "+f"(d[9]), "+f"(d[10]), "+f"(d[11]), "+f"(d[12]), "+f"(d[13]), "+f"(d[14]), "+f"(d[15]),
      "+f"(d[16]), "+f"(d[17]), "+f"(d[18]), "+f"(d[19]), "+f"(d[20]), "+f"(d[21]), "+f"(d[22]), "+f"(d[23]),
      "+f"(d[24]), "+f"(d[25]), "+f"(d[26]), "+f"(d[27]), "+f"(d[28]), "+f"(d[29]), "+f"(d[30]), "+f"(d[31]),
      "+f"(d[32]), "+f"(d[33]), "+f"(d[34]), "+f"(d[35]), "+f"(d[36]), "+f"(d[37]), "+f"(d[38]), "+f"(d[39]),
      "+f"(d[40]), "+f"(d[41]), "+f"(d[42]), "+f"(d[43]), "+f"(d[44]), "+f"(d[45]), "+f"(d[46]), "+f"(d[47]),
      "+f"(d[48]), "+f"(d[49]), "+f"(d[50]), "+f"(d[51]), "+f"(d[52]), "+f"(d[53]), "+f"(d[54]), "+f"(d[55]),
      "+f"(d[56]), "+f"(d[57]), "+f"(d[58]), "+f"(d[59]), "+f"(d[60]), "+f"(d[61]), "+f"(d[62]), "+f"(d[63]),
      "+f"(d[64]), "+f"(d[65]), "+f"(d[66]), "+f"(d[67]), "+f"(d[68]), "+f"(d[69]), "+f"(d[70]), "+f"(d[71])
    : "r"(a0), "r"(a1), "r"(a2), "r"(a3), "l"(descB));
}

template <int SCALE_D>
__device__ __forceinline__ void wgmma_n96(float (&d)[48], uint32_t a0, uint32_t a1, uint32_t a2, uint32_t a3, uint64_t descB) {
  if (SCALE_D == 0)
  asm volatile("wgmma.mma_async.sync.aligned.m64n96k16.f32.bf16.bf16 "
    "{%0, %1, %2, %3, %4, %5, %6, %7, %8, %9, %10, %11, %12, %13, %14, %15, "
    "%16, %17, %18, %19, %20, %21, %22, %23, %24, %25, %26, %27, %28, %29, %30, %31, "
    "%32, %33, %34, %35, %36, %37, %38, %39, %40, %41, %42, %43, %44, %45, %46, %47}, "
    "{%48, %49, %50, %51}, %52, 0, 1, 1, 0;\n"
    : "=f"(d[0]), "=f"(d[1]), "=f"(d[2]), "=f"(d[3]), "=f"(d[4]), "=f"(d[5]), "=f"(d[6]), "=f"(d[7]),
      "=f"(d[8]), "=f"(d[9]), "=f"(d[10]), "=f"(d[11]), "=f"(d[12]), "=f"(d[13]), "=f"(d[14]), "=f"(d[15]),
      "=f"(d[16]), "=f"(d[17]), "=f"(d[18]), "=f"(d[19]), "=f"(d[20]), "=f"(d[21]), "=f"(d[22]), "=f"(d[23]),
      "=f"(d[24]), "=f"(d[25]), "=f"(d[26]), "=f"(d[27]), "=f"(d[28]), "=f"(d[29]), "=f"(d[30]), "=f"(d[31]),
      "=f"(d[32]), "=f"(d[33]), "=f"(d[34]), "=f"(d[35]), "=f"(d[36]), "=f"(d[37]), "=f"(d[38]), "=f"(d[39]),
      "=f"(d[40]), "=f"(d[41]), "=f"(d[42]), "=f"(d[43]), "=f"(d[44]), "=f"(d[45]), "=f"(d[46]), "=f"(d[47])
    : "r"(a0), "r"(a1), "r"(a2), "r"(a3), "l"(descB));
  else if (SCALE_D == 2)
  asm volatile("wgmma.mma_async.sync.aligned.m64n96k16.f32.bf16.bf16 "
    "{%0, %1, %2, %3, %4, %5, %6, %7, %8, %9, %10, %11, %12, %13, %14, %15, "
    "%16, %17, %18, %19, %20, %21, %22, %23, %24, %25, %26, %27, %28, %29, %30, %31, "
    "%32, %33, %34, %35, %36, %37, %38, %39, %40, %41, %42, %43, %44, %45, %46, %47}, "
    "{%48, %49, %50, %51}, %52, 0, 1, 1, 0;\n"
    : "+f"(d[0]), "+f"(d[1]), "+f"(d[2]), "+f"(d[3]), "+f"(d[4]), "+f"(d[5]), "+f"(d[6]), "+f"(d[7]),
      "+f"(d[8]), "+f"(d[9]), "+f"(d[10]), "+f"(d[11]), "+f"(d[12]), "+f"(d[13]), "+f"(d[14]), "+f"(d[15]),
      "+f"(d[16]), "+f"(d[17]), "+f"(d[18]), "+f"(d[19]), "+f"(d[20]), "+f"(d[21]), "+f"(d[22]), "+f"(d[23]),
      "+f"(d[24]), "+f"(d[25]), "+f"(d[26]), "+f"(d[27]), "+f"(d[28]), "+f"(d[29]), "+f"(d[30]), "+f"(d[31]),
      "+f"(d[32]), "+f"(d[33]), "+f"(d[34]), "+f"(d[35]), "+f"(d[36]), "+f"(d[37]), "+f"(d[38]), "+f"(d[39]),
      "+f"(d[40]), "+f"(d[41]), "+f"(d[42]), "+f"(d[43]), "+f"(d[44]), "+f"(d[45]), "+f"(d[46]), "+f"(d[47])
    : "r"(a0), "r"(a1), "r"(a2), "r"(a3), "l"(descB));
  else
  asm volatile("wgmma.mma_async.sync.aligned.m64n96k16.f32.bf16.bf16 "
    "{%0, %1, %2, %3, %4, %5, %6, %7, %8, %9, %10, %11, %12, %13, %14, %15, "
    "%16, %17, %18, %19, %20, %21, %22, %23, %24, %25, %26, %27, %28, %29, %30, %31, "
    "%32, %33, %34, %35, %36, %37, %38, %39, %40, %41, %42, %43, %44, %45, %46, %47}, "
    "{%48, %49, %50, %51}, %52, 1, 1, 1, 0;\n"
    : "+f"(d[0]), "+f"(d[1]), "+f"(d[2]), "+f"(d[3]), "+f"(d[4]), "+f"(d[5]), "+f"(d[6]), "+f"(d[7]),
      "+f"(d[8]), "+f"(d[9]), "+f"(d[10]), "+f"(d[11]), "+f"(d[12]), "+f"(d[13]), "+f"(d[14]), "+f"(d[15]),
      "+f"(d[16]), "+f"(d[17]), "+f"(d[18]), "+f"(d[19]), "+f"(d[20]), "+f"(d[21]), "+f"(d[22]), "+f"(d[23]),
      "+f"(d[24]), "+f"(d[25]), "+f"(d[26]), "+f"(d[27]), "+f"(d[28]), "+f"(d[29]), "+f"(d[30]), "+f"(d[31]),
      "+f"(d[32]), "+f"(d[33]), "+f"(d[34]), "+f"(d[35]), "+f"(d[36]), "+f"(d[37]), "+f"(d[38]), "+f"(d[39]),
      "+f"(d[40]), "+f"(d[41]), "+f"(d[42]), "+f"(d[43]), "+f"(d[44]), "+f"(d[45]), "+f"(d[46]), "+f"(d[47])
    : "r"(a0), "r"(a1), "r"(a2), "r"(a3), "l"(descB));
}

template <int SCALE_D>
__device__ __forceinline__ void wgmma_n48(float (&d)[24], uint32_t a0, uint32_t a1, uint32_t a2, uint32_t a3, uint64_t descB) {
  if (SCALE_D == 0)
  asm volatile("wgmma.mma_async.sync.aligned.m64n48k16.f32.bf16.bf16 "
    "{%0, %1, %2, %3, %4, %5, %6, %7, %8, %9, %10, %11, %12, %13, %14, %15, "
    "%16, %17, %18, %19, %20, %21, %22, %23}, "
    "{%24, %25, %26, %27}, %28, 0, 1, 1, 0;\n"
    : "=f"(d[0]), "=f"(d[1]), "=f"(d[2]), "=f"(d[3]), "=f"(d[4]), "=f"(d[5]), "=f"(d[6]), "=f"(d[7]),
      "=f"(d[8]), "=f"(d[9]), "=f"(d[10]), "=f"(d[11]), "=f"(d[12]), "=f"(d[13]), "=f"(d[14]), "=f"(d[15]),
      "=f"(d[16]), "=f"(d[17]), "=f"(d[18]), "=f"(d[19]), "=f"(d[20]), "=f"(d[21]), "=f"(d[22]), "=f"(d[23])
    : "r"(a0), "r"(a1), "r"(a2), "r"(a3), "l"(descB));
  else
  asm volatile("wgmma.mma_async.sync.aligned.m64n48k16.f32.bf16.bf16 "
    "{%0, %1, %2, %3, %4, %5, %6, %7, %8, %9, %10, %11, %12, %13, %14, %15, "
    "%16, %17, %18, %19, %20, %21, %22, %23}, "
    "{%24, %25, %26, %27}, %28, 1, 1, 1, 0;\n"
    : "+f"(d[0]), "+f"(d[1]), "+f"(d[2]), "+f"(d[3]), "+f"(d[4]), "+f"(d[5]), "+f"(d[6]), "+f"(d[7]),
      "+f"(d[8]), "+f"(d[9]), "+f"(d[10]), "+f"(d[11]), "+f"(d[12]), "+f"(d[13]), "+f"(d[14]), "+f"(d[15]),
      "+f"(d[16]), "+f"(d[17]), "+f"(d[18]), "+f"(d[19]), "+f"(d[20]), "+f"(d[21]), "+f"(d[22]), "+f"(d[23])
    : "r"(a0), "r"(a1), "r"(a2), "r"(a3), "l"(descB));
}

template <int SCALE_D>
__device__ __forceinline__ void wgmma_n64(float (&d)[32], uint32_t a0, uint32_t a1, uint32_t a2, uint32_t a3, uint64_t descB) {
  if (SCALE_D == 0)
  asm volatile("wgmma.mma_async.sync.aligned.m64n64k16.f32.bf16.bf16 "
    "{%0, %1, %2, %3, %4, %5, %6, %7, %8, %9, %10, %11, %12, %13, %14, %15, "
    "%16, %17, %18, %19, %20, %21, %22, %23, %24, %25, %26, %27, %28, %29, %30, %31}, "
    "{%32, %33, %34, %35}, %36, 0, 1, 1, 0;\n"
    : "=f"(d[0]), "=f"(d[1]), "=f"(d[2]), "=f"(d[3]), "=f"(d[4]), "=f"(d[5]), "=f"(d[6]), "=f"(d[7]),
      "=f"(d[8]), "=f"(d[9]), "=f"(d[10]), "=f"(d[11]), "=f"(d[12]), "=f"(d[13]), "=f"(d[14]), "=f"(d[15]),
      "=f"(d[16]), "=f"(d[17]), "=f"(d[18]), "=f"(d[19]), "=f"(d[20]), "=f"(d[21]), "=f"(d[22]), "=f"(d[23]),
      "=f"(d[24]), "=f"(d[25]), "=f"(d[26]), "=f"(d[27]), "=f"(d[28]), "=f"(d[29]), "=f"(d[30]), "=f"(d[31])
    : "r"(a0), "r"(a1), "r"(a2), "r"(a3), "l"(descB));
  else if (SCALE_D == 2)
  asm volatile("wgmma.mma_async.sync.aligned.m64n64k16.f32.bf16.bf16 "
    "{%0, %1, %2, %3, %4, %5, %6, %7, %8, %9, %10, %11, %12, %13, %14, %15, "
    "%16, %17, %18, %19, %20, %21, %22, %23, %24, %25, %26, %27, %28, %29, %30, %31}, "
    "{%32, %33, %34, %35}, %36, 0, 1, 1, 0;\n"
    : "+f"(d[0]), "+f"(d[1]), "+f"(d[2]), "+f"(d[3]), "+f"(d[4]), "+f"(d[5]), "+f"(d[6]), "+f"(d[7]),
      "+f"(d[8]), "+f"(d[9]), "+f"(d[10]), "+f"(d[11]), "+f"(d[12]), "+f"(d[13]), "+f"(d[14]), "+f"(d[15]),
      "+f"(d[16]), "+f"(d[17]), "+f"(d[18]), "+f"(d[19]), "+f"(d[20]), "+f"(d[21]), "+f"(d[22]), "+f"(d[23]),
      "+f"(d[24]), "+f"(d[25]), "+f"(d[26]), "+f"(d[27]), "+f"(d[28]), "+f"(d[29]), "+f"(d[30]), "+f"(d[31])
    : "r"(a0), "r"(a1), "r"(a2), "r"(a3), "l"(descB));
  else
  asm volatile("wgmma.mma_async.sync.aligned.m64n64k16.f32.bf16.bf16 "
    "{%0, %1, %2, %3, %4, %5, %6, %7, %8, %9, %10, %11, %12, %13, %14, %15, "
    "%16, %17, %18, %19, %20, %21, %22, %23, %24, %25, %26, %27, %28, %29, %30, %31}, "
    "{%32, %33, %34, %35}, %36, 1, 1, 1, 0;\n"
    : "+f"(d[0]), "+f"(d[1]), "+f"(d[2]), "+f"(d[3]), "+f"(d[4]), "+f"(d[5]), "+f"(d[6]), "+f"(d[7]),
      "+f"(d[8]), "+f"(d[9]), "+f"(d[10]), "+f"(d[11]), "+f"(d[12]), "+f"(d[13]), "+f"(d[14]), "+f"(d[15]),
      "+f"(d[16]), "+f"(d[17]), "+f"(d[18]), "+f"(d[19]), "+f"(d[20]), "+f"(d[21]), "+f"(d[22]), "+f"(d[23]),
      "+f"(d[24]), "+f"(d[25]), "+f"(d[26]), "+f"(d[27]), "+f"(d[28]), "+f"(d[29]), "+f"(d[30]), "+f"(d[31])
    : "r"(a0), "r"(a1), "r"(a2), "r"(a3), "l"(descB));
}

template <int SCALE_D>
__device__ __forceinline__ void wgmma_n56(float (&d)[28], uint32_t a0, uint32_t a1, uint32_t a2, uint32_t a3, uint64_t descB) {
  if (SCALE_D == 0)
  asm volatile("wgmma.mma_async.sync.aligned.m64n56k16.f32.bf16.bf16 "
    "{%0, %1, %2, %3, %4, %5, %6, %7, %8, %9, %10, %11, %12, %13, %14, %15, "
    "%16, %17, %18, %19, %20, %21, %22, %23, %24, %25, %26, %27}, "
    "{%28, %29, %30, %31}, %32, 0, 1, 1, 0;\n"
    : "=f"(d[0]), "=f"(d[1]), "=f"(d[2]), "=f"(d[3]), "=f"(d[4]), "=f"(d[5]), "=f"(d[6]), "=f"(d[7]),
      "=f"(d[8]), "=f"(d[9]), "=f"(d[10]), "=f"(d[11]), "=f"(d[12]), "=f"(d[13]), "=f"(d[14]), "=f"(d[15]),
      "=f"(d[16]), "=f"(d[17]), "=f"(d[18]), "=f"(d[19]), "=f"(d[20]), "=f"(d[21]), "=f"(d[22]), "=f"(d[23]),
      "=f"(d[24]), "=f"(d[25]), "=f"(d[26]), "=f"(d[27])
    : "r"(a0), "r"(a1), "r"(a2), "r"(a3), "l"(descB));
  else
  asm volatile("wgmma.mma_async.sync.aligned.m64n56k16.f32.bf16.bf16 "
    "{%0, %1, %2, %3, %4, %5, %6, %7, %8, %9, %10, %11, %12, %13, %14, %15, "
    "%16, %17, %18, %19, %20, %21, %22, %23, %24, %25, %26, %27}, "
    "{%28, %29, %30, %31}, %32, 1, 1, 1, 0;\n"
    : "+f"(d[0]), "+f"(d[1]), "+f"(d[2]), "+f"(d[3]), "+f"(d[4]), "+f"(d[5]), "+f"(d[6]), "+f"(d[7]),
      "+f"(d[8]), "+f"(d[9]), "+f"(d[10]), "+f"(d[11]), "+f"(d[12]), "+f"(d[13]), "+f"(d[14]), "+f"(d[15]),
      "+f"(d[16]), "+f"(d[17]), "+f"(d[18]), "+f"(d[19]), "+f"(d[20]), "+f"(d[21]), "+f"(d[22]), "+f"(d[23]),
      "+f"(d[24]), "+f"(d[25]), "+f"(d[26]), "+f"(d[27])
    : "r"(a0), "r"(a1), "r"(a2), "r"(a3), "l"(descB));
}

template <int SCALE_D>
__device__ __forceinline__ void wgmma_n56t(float (&d)[28], uint32_t a0, uint32_t a1, uint32_t a2, uint32_t a3, uint64_t descB) {
  if (SCALE_D == 0)
  asm volatile("wgmma.mma_async.sync.aligned.m64n56k16.f32.bf16.bf16 "
    "{%0, %1, %2, %3, %4, %5, %6, %7, %8, %9, %10, %11, %12, %13, %14, %15, "
    "%16, %17, %18, %19, %20, %21, %22, %23, %24, %25, %26, %27}, "
    "{%28, %29, %30, %31}, %32, 0, 1, 1, 1;\n"
    : "=f"(d[0]), "=f"(d[1]), "=f"(d[2]), "=f"(d[3]), "=f"(d[4]), "=f"(d[5]), "=f"(d[6]), "=f"(d[7]),
      "=f"(d[8]), "=f"(d[9]), "=f"(d[10]), "=f"(d[11]), "=f"(d[12]), "=f"(d[13]), "=f"(d[14]), "=f"(d[15]),
      "=f"(d[16]), "=f"(d[17]), "=f"(d[18]), "=f"(d[19]), "=f"(d[20]), "=f"(d[21]), "=f"(d[22]), "=f"(d[23]),
      "=f"(d[24]), "=f"(d[25]), "=f"(d[26]), "=f"(d[27])
    : "r"(a0), "r"(a1), "r"(a2), "r"(a3), "l"(descB));
  else
  asm volatile("wgmma.mma_async.sync.aligned.m64n56k16.f32.bf16.bf16 "
    "{%0, %1, %2, %3, %4, %5, %6, %7, %8, %9, %10, %11, %12, %13, %14, %15, "
    "%16, %17, %18, %19, %20, %21, %22, %23, %24, %25, %26, %27}, "
    "{%28, %29, %30, %31}, %32, 1, 1, 1, 1;\n"
    : "+f"(d[0]), "+f"(d[1]), "+f"(d[2]), "+f"(d[3]), "+f"(d[4]), "+f"(d[5]), "+f"(d[6]), "+f"(d[7]),
      "+f"(d[8]), "+f"(d[9]), "+f"(d[10]), "+f"(d[11]), "+f"(d[12]), "+f"(d[13]), "+f"(d[14]), "+f"(d[15]),
      "+f"(d[16]), "+f"(d[17]), "+f"(d[18]), "+f"(d[19]), "+f"(d[20]), "+f"(d[21]), "+f"(d[22]), "+f"(d[23]),
      "+f"(d[24]), "+f"(d[25]), "+f"(d[26]), "+f"(d[27])
    : "r"(a0), "r"(a1), "r"(a2), "r"(a3), "l"(descB));
}

__global__ void __launch_bounds__(384) prepack_kernel(const __nv_bfloat16* __restrict__ wqkv, const __nv_bfloat16* __restrict__ wo) {
  asm volatile("griddepcontrol.launch_dependents;");
  __nv_bfloat16* dst = reinterpret_cast<__nv_bfloat16*>(g_wpack);
  const int c = threadIdx.x, nb = blockIdx.x * 2 + threadIdx.y;
  if (nb < 72) {
    __shared__ float red2[2][6][8];
    float (*red)[8] = red2[threadIdx.y];
    const int h = nb / 18, j = nb % 18, part = j / 6;
    const int col = (part == 0 ? 192 : part == 1 ? 0 : 384) + h * 48 + (j % 6) * 8;
    uint4 raw = *reinterpret_cast<const uint4*>(wqkv + c * 576 + col);
    uint32_t u[4] = {raw.x, raw.y, raw.z, raw.w};
    float v[8];
#pragma unroll
    for (int i = 0; i < 4; i++) { v[2 * i] = lo2f(u[i]); v[2 * i + 1] = hi2f(u[i]); }
#pragma unroll
    for (int i = 0; i < 8; i++) {
      float s = v[i];
#pragma unroll
      for (int o = 16; o; o >>= 1) s += __shfl_xor_sync(~0u, s, o);
      if ((c & 31) == 0) red[c >> 5][i] = s;
    }
    __syncthreads();
    const int cc = c >> 5, q = (c >> 3) & 3, s1 = (c >> 2) & 1, hh = (c >> 1) & 1, e = c & 1;
    const int base = h * 27648 + (2 * cc + s1) * 2304 + j * 128 + hh * 64 + 2 * q + e;
#pragma unroll
    for (int n = 0; n < 8; n++) {
      float m = (red[0][n] + red[1][n] + red[2][n] + red[3][n] + red[4][n] + red[5][n]) * (1.0f / 192.0f);
      dst[base + n * 8] = __float2bfloat16((v[n] - m) * (part == 1 ? 0.14433756729740643f * 1.4426950408889634f : 1.0f));
    }
  } else {
    const int jb = nb - 72, chunk = jb / 8, j = jb % 8;
    const int s = c >> 4, hh = (c >> 3) & 1, kk = c & 7;
    const int base = 110592 + (chunk * 12 + s) * 1024 + j * 128 + hh * 64 + kk;
#pragma unroll
    for (int n = 0; n < 8; n++) {
      const int ch = 32 * (jb >> 2) + 8 * (n >> 1) + 2 * (jb & 3) + (n & 1);
      dst[base + n * 8] = wo[c * 192 + ch];
    }
  }
}

__device__ __forceinline__ int window_of(int round, int nfull, int cta, int ncta, int wg) {
  if (round < nfull) return round * 2 * ncta + 2 * cta + wg;
  const int rem = NWIN - nfull * 2 * ncta;
  const int i = cta + wg * ncta;
  return i < rem ? nfull * 2 * ncta + i : -1;
}

__host__ __device__ constexpr int qkv_off(int h, int s) { return ((3 * h + s / 4) % 8) * SLICE + (s % 4) * 4608; }
__host__ __device__ constexpr int wo_off(int chunk, int s) { return 4 * SLICE + (chunk * 12 + s) * 2048; }

#define DEF_ISSUE(NAME, NREG, FN, FIRST)                                                                          \
  template <int S0, int S1, int INIT = FIRST>                                                                     \
  __device__ __forceinline__ void NAME(float (&acc)[NREG], const uint32_t (&A)[48], const uint64_t* d) {          \
    wg_fence();                                                                                                   \
    _Pragma("unroll") for (int s = S0; s < S1; s++) {                                                             \
      if (s == 0) FN<INIT>(acc, A[4 * s], A[4 * s + 1], A[4 * s + 2], A[4 * s + 3], d[s]);                        \
      else        FN<1>(acc, A[4 * s], A[4 * s + 1], A[4 * s + 2], A[4 * s + 3], d[s]);                           \
    }                                                                                                             \
    wg_commit();                                                                                                  \
  }
DEF_ISSUE(mma144, 72, wgmma_n144, 0)
DEF_ISSUE(mma96, 48, wgmma_n96, 0)
DEF_ISSUE(mma48, 24, wgmma_n48, 0)
DEF_ISSUE(mma64, 32, wgmma_n64, 0)
#undef DEF_ISSUE

#define PIN() asm volatile("pmevent 0;" ::: "memory")
template <int A, int B> __device__ __forceinline__ void hold(uint32_t* v) {
#pragma unroll
  for (int i = A; i < B; i++) asm volatile("" : "+r"(v[i]));
}
template <int A, int B> __device__ __forceinline__ void packn(uint32_t* d, const float* a) {
#pragma unroll
  for (int i = A; i < B; i++) d[i] = pack2(a[2 * i], a[2 * i + 1]);
}
template <int A, int B> __device__ __forceinline__ void scalen(uint32_t* d, uint32_t r) {
#pragma unroll
  for (int i = A; i < B; i++) d[i] = (i & 1) ? hmul_b<1>(d[i], r) : hmul_b<0>(d[i], r);
}
__device__ __forceinline__ void stsm12(const uint32_t* v, uint32_t addr) {
#pragma unroll
  for (int j = 0; j < 3; j++) stsm4(addr + 2 * j * KV_PITCH, v[4 * j], v[4 * j + 1], v[4 * j + 2], v[4 * j + 3]);
}
__device__ __forceinline__ uint32_t inv_sum(const float (&o)[28]) {
  float i0, i1;
  asm("rcp.approx.ftz.f32 %0, %1;" : "=f"(i0) : "f"(o[24]));
  asm("rcp.approx.ftz.f32 %0, %1;" : "=f"(i1) : "f"(o[26]));
  return pack2(i0, i1);
}
__device__ __forceinline__ void proxy_fence() { asm volatile("fence.proxy.async.shared::cta;" ::: "memory"); }
__device__ __forceinline__ void issue_s(float (&S)[28], const uint32_t (&Q)[12], const uint64_t* d) {
  wg_fence();
  wgmma_n56<0>(S, Q[0], Q[1], Q[2], Q[3], d[0]);
  wgmma_n56<1>(S, Q[4], Q[5], Q[6], Q[7], d[1]);
  wgmma_n56<1>(S, Q[8], Q[9], Q[10], Q[11], d[2]);
  wg_commit();
}
struct H2 { uint16_t l, h; };
__device__ __forceinline__ H2 exp_halves(uint32_t a) {
  H2 r;
  asm("{\n.reg .b16 l, h;\nmov.b32 {l, h}, %2;\nex2.approx.ftz.bf16 %0, l;\nex2.approx.ftz.bf16 %1, h;\n}\n" : "=h"(r.l), "=h"(r.h) : "r"(a));
  return r;
}
__device__ __forceinline__ uint32_t join(H2 v) { uint32_t r; asm("mov.b32 %0, {%1, %2};" : "=r"(r) : "h"(v.l), "h"(v.h)); return r; }
__device__ __forceinline__ void hold(H2& v) { asm volatile("" : "+h"(v.l), "+h"(v.h)); }

#define KSCHED 0x23456789abcull
#define PASS_SEG2 PASS_SEG
#define PASS_SEG3 7
#define PASS_SEG 10
__host__ __device__ constexpr int ksched(int seg, int nk) { return (int)(KSCHED >> (40 - 4 * seg) & 15) < nk ? (int)(KSCHED >> (40 - 4 * seg) & 15) : nk; }
template <int SEC, int NK, bool PREV, class G>
__device__ __forceinline__ void softmax_pv(float (&S)[28], const uint64_t* dV, uint32_t* Op, uint32_t inv, int wg, bool pass, uint32_t ninf, G g) {
#define GK(i) if (ksched(i, NK) > ksched(i - 1, NK)) g(IC<ksched(i - 1, NK)>{}, IC<ksched(i, NK)>{}); \
              if (i == (SEC == 3 ? PASS_SEG3 : SEC == 2 ? PASS_SEG2 : PASS_SEG) && (SEC != PP_LAST || pass)) turn_pass<SEC>(wg);
#define PINK(i) if (ksched(i - 1, NK) < NK) PIN();
  uint32_t P[16];
  GK(1) packn<0, 4>(P, S);  if (PREV) { scalen<0, 4>(Op, inv); hold<0, 4>(Op); }   hold<0, 4>(P); PINK(1)
  GK(2) packn<4, 9>(P, S);  if (PREV) { scalen<4, 8>(Op, inv); hold<4, 8>(Op); }   hold<4, 9>(P); PINK(2)
  GK(3) packn<9, 12>(P, S); P[12] = pack2(S[24], S[26]) | ninf;
  if (PREV) { scalen<8, 12>(Op, inv); hold<8, 12>(Op); } hold<9, 13>(P); PINK(3)
  GK(4)
  uint32_t m0 = hmax(hmax(hmax(P[0], P[2]), P[4]), hmax(hmax(P[6], P[8]), P[10]));
  uint32_t m1 = hmax(hmax(hmax(P[1], P[3]), P[5]), hmax(hmax(P[7], P[9]), P[11]));
  uint32_t mx = hmax(hmax(__byte_perm(m0, m1, 0x5410), __byte_perm(m0, m1, 0x7632)), P[12]);
  uint32_t sh = __shfl_xor_sync(~0u, mx, 1);
  PINK(4)
  GK(5)
  PINK(5)
  mx = hmax(mx, sh);
  sh = __shfl_xor_sync(~0u, mx, 2);
  PINK(6)
  GK(6)
  PINK(6)
  mx = hmax(mx, sh);
#pragma unroll
  for (int j = 0; j < 12; j++) P[j] = (j & 1) ? hsub_b<1>(P[j], mx) : hsub_b<0>(P[j], mx);
  P[12] = b2u(__hsub2_rn(u2b(P[12]), u2b(mx)));
  H2 e0 = exp_halves(P[0]), e1 = exp_halves(P[1]);
  GK(7)
  if (ksched(7, NK) < NK || (SEC == 3 ? PASS_SEG3 : SEC == 2 ? PASS_SEG2 : PASS_SEG) == 8) { hold<2, 13>(P); hold(e0); hold(e1); PIN(); }
  GK(8)
  H2 e2 = exp_halves(P[2]), e3 = exp_halves(P[3]);
  P[0] = join(e0); P[1] = join(e1);
  if (ksched(8, NK) < NK || (SEC == 3 ? PASS_SEG3 : SEC == 2 ? PASS_SEG2 : PASS_SEG) == 9) { hold<0, 2>(P); hold(e2); hold(e3); PIN(); }
  GK(9)
  e0 = exp_halves(P[4]); e1 = exp_halves(P[5]);
  P[2] = join(e2); P[3] = join(e3);
  if (ksched(9, NK) < NK || (SEC == 3 ? PASS_SEG3 : SEC == 2 ? PASS_SEG2 : PASS_SEG) == 10) { hold<2, 4>(P); hold(e0); hold(e1); PIN(); }
  GK(10)
  proxy_fence();
  e2 = exp_halves(P[12]);
  P[12] = e2.l; P[13] = e2.h; P[14] = 0; P[15] = 0;
  P[4] = join(e0); P[5] = join(e1);
#pragma unroll
  for (int j = 6; j < 12; j++) P[j] = hex2(P[j]);
  if ((SEC == 3 ? PASS_SEG3 : SEC == 2 ? PASS_SEG2 : PASS_SEG) == 11 && (SEC != PP_LAST || pass)) { hold<6, 10>(P); PIN(); turn_pass<SEC>(wg); }
  bar_sync(1 + wg);
  wg_fence();
  wgmma_n56t<0>(S, P[0], P[1], P[2], P[3], dV[0]);
  wgmma_n56t<1>(S, P[4], P[5], P[6], P[7], dV[1]);
  wgmma_n56t<1>(S, P[12], P[13], P[14], P[15], dV[3]);
  wgmma_n56t<1>(S, P[8], P[9], P[10], P[11], dV[2]);
  wg_commit();
#undef GK
#undef PINK
}
template <int S0, int S1>
__device__ __forceinline__ void load_x(uint32_t (&X)[48], uint32_t t0) {
#pragma unroll
  for (int s = S0; s < S1; s++)
    asm volatile("ld.shared.v4.u32 {%0,%1,%2,%3}, [%4];" : "=r"(X[4 * s]), "=r"(X[4 * s + 1]), "=r"(X[4 * s + 2]), "=r"(X[4 * s + 3])
                 : "r"(((s & 1) ? (t0 ^ 16) : t0) + (s >> 1) * 128) : "memory");
}

template <int C, int A, int B> __device__ __forceinline__ void add_res(uint32_t* T, const uint32_t (&X)[48]) {
#pragma unroll
  for (int i = A; i < B; i++) T[i] = hadd(X[16 * C + i], T[i]);
}
template <int C>
__device__ __forceinline__ void store_out(const uint32_t* T, uint8_t* o0, uint8_t* o1, uint32_t vmask) {
#pragma unroll
  for (int c = 0; c < 2; c++) {
    asm volatile("{\n.reg .pred p;\nsetp.ne.u32 p, %5, 0;\n@p st.global.v4.u32 [%0], {%1,%2,%3,%4};\n}\n"
                 :: "l"(o0 + C * 128 + c * 64), "r"(T[8 * c]), "r"(T[8 * c + 2]), "r"(T[8 * c + 4]), "r"(T[8 * c + 6]), "r"(vmask) : "memory");
    asm volatile("{\n.reg .pred p;\nsetp.lt.s32 p, %5, 0;\n@p st.global.v4.u32 [%0], {%1,%2,%3,%4};\n}\n"
                 :: "l"(o1 + C * 128 + c * 64), "r"(T[8 * c + 1]), "r"(T[8 * c + 3]), "r"(T[8 * c + 5]), "r"(T[8 * c + 7]), "r"(vmask) : "memory");
  }
}

#define WDIV 1
template <int K, int CNT, int DIV = WDIV> __device__ __forceinline__ void load_slices(uint32_t sb, const Descs& ds) {
  constexpr int st = K < 12 ? K / 3 : 4 + (K - 12) / 2;
  constexpr bool first = K < 12 ? (K % 3 == 0) : (K % 2 == 0);
  if (first)
    asm volatile("{\n.reg .pred p;\nelect.sync _|p, 0xffffffff;\n@p mbarrier.arrive.expect_tx.shared::cta.b64 _, [%0], %1;\n}\n"
                 :: "r"(sb + BAR_WFULL + 8 * st), "n"(DIV == 1 && K == 6 ? 2 * SLICE + SLICE / WDIV : (K < 12 ? 3 : 2) * SLICE / DIV) : "memory");
  asm volatile("{\n.reg .pred p;\nelect.sync _|p, 0xffffffff;\n"
               "@p cp.async.bulk.shared::cluster.global.mbarrier::complete_tx::bytes [%0], [%1], %2, [%3];\n}\n"
               :: "r"(sb + OFF_W + (K & 7) * SLICE), "l"(ds.src[K]), "n"(CNT * SLICE / DIV), "r"(sb + BAR_WFULL + 8 * st) : "memory");
}
template <int STAGE> __device__ __forceinline__ void release(uint32_t sb, const Descs& ds, bool next_round) {
  uint32_t old;
  asm volatile("{\n.reg .b32 a;\nmov.u32 a, %%laneid;\nmad.lo.u32 a, a, 4, %1;\natom.shared.inc.u32 %0, [a + %2], 1;\n}\n"
               : "=r"(old) : "r"(sb), "n"(CNT_WREL + 128 * STAGE) : "memory");
  if (__ballot_sync(0xffffffffu, old == 1) & 1) {
    if (STAGE == 0) { load_slices<8, 1>(sb, ds); load_slices<9, 2>(sb, ds); }
    if (STAGE == 1) { load_slices<11, 1>(sb, ds); load_slices<12, 2>(sb, ds); }
    if (STAGE == 2) { load_slices<14, 2>(sb, ds); if (next_round) load_slices<0, 1>(sb, ds); }
    if (STAGE == 3 && next_round) { load_slices<1, 2>(sb, ds); load_slices<3, 1>(sb, ds); }
    if (STAGE == 4 && next_round) load_slices<4, 2>(sb, ds);
    if (STAGE == 5 && next_round) load_slices<6, 2>(sb, ds);
  }
}

__device__ __forceinline__ uint32_t ln_rstd(const uint32_t (&X)[48]) {
  uint32_t sm[2];
#pragma unroll
  for (int a = 0; a < 2; a++) {
    uint32_t t[12];
#pragma unroll
    for (int i = 0; i < 12; i++) t[i] = hadd(X[4 * i + a], X[4 * i + 2 + a]);
#pragma unroll
    for (int i = 0; i < 6; i++) t[i] = hadd(t[i], t[i + 6]);
#pragma unroll
    for (int i = 0; i < 3; i++) t[i] = hadd(t[i], t[i + 3]);
    sm[a] = hadd(hadd(t[0], t[1]), t[2]);
  }
  uint32_t m = hadd(__byte_perm(sm[0], sm[1], 0x5410), __byte_perm(sm[0], sm[1], 0x7632));
  m = hadd(m, __shfl_xor_sync(~0u, m, 1));
  m = hadd(m, __shfl_xor_sync(~0u, m, 2));
  m = hmul(m, 0x3bab3babu);
  float var[2];
#pragma unroll
  for (int a = 0; a < 2; a++) {
    uint32_t t[4];
#pragma unroll
    for (int i = 0; i < 24; i++) {
      const uint32_t d = a ? hsub_b<1>(X[2 * i + 1], m) : hsub_b<0>(X[2 * i], m);
      t[i & 3] = i < 4 ? hmul(d, d) : hfma(d, d, t[i & 3]);
    }
    const uint32_t s = hadd(hadd(t[0], t[1]), hadd(t[2], t[3]));
    float v = lo2f(s) + hi2f(s);
    v += __shfl_xor_sync(~0u, v, 1);
    v += __shfl_xor_sync(~0u, v, 2);
    asm("rsqrt.approx.ftz.f32 %0, %1;" : "=f"(var[a]) : "f"(fmaf(v, 1.0f / 192.0f, 1e-5f)));
  }
  return pack2(var[0], var[1]);
}

#define DUMMY()
__device__ __forceinline__ void stats_pass(uint32_t sb, int pass, int lane) {
  const int g = lane >> 2, q = lane & 3;
  const int tile = pass < 6 ? (pass & 1) : (g & 1);
  const int ps = pass < 6 ? (pass >> 1) * 8 + g : 24;
  uint32_t X[48];
  load_x<0, 12>(X, sb + OFF_TILE + tile * TILE_BYTES + ps * 768 + q * 32 + (ps & 1) * 16);
  const uint32_t rs = ln_rstd(X);
  asm volatile("st.shared.u32 [%0], %1;" :: "r"(sb + OFF_RSTD + tile * 100 + ps * 4), "r"(rs) : "memory");
}

__global__ void __launch_bounds__(384, 1)
fused_kernel(const __grid_constant__ CUtensorMap tmx, const __grid_constant__ CUtensorMap tmp, const __grid_constant__ Descs ds, const __nv_bfloat16* __restrict__ dw, __nv_bfloat16* __restrict__ out, const int never) {
  extern __shared__ __align__(1024) uint8_t smem[];
  const uint32_t sb = (uint32_t)__cvta_generic_to_shared(smem);
  const int tid = threadIdx.x, lane = tid & 31;
  const int warp = __shfl_sync(0xffffffffu, tid >> 5, 0);
  const int cta = blockIdx.x, ncta = gridDim.x;
  const int nfull = NWIN / (2 * ncta);
  const int nrounds = nfull + ((NWIN - nfull * 2 * ncta) > cta ? 1 : 0);

  if (warp == 0) GTS(0);
  auto prefetch_round = [&](int r) {
#pragma unroll
    for (int k = 0; k < 2; k++) {
      const int w = window_of(r, nfull, cta, ncta, k);
      if (w >= 0) {
        const int a = w / NWX;
        asm volatile("{\n.reg .pred p;\nelect.sync _|p, 0xffffffff;\n@p cp.async.bulk.prefetch.tensor.3d.L2.global [%0, {0, %1, %2}];\n}\n"
                     :: "l"(reinterpret_cast<uint64_t>(&tmp)), "r"((w - a * NWX) * 7 - 1), "r"(a * 7 - 1) : "memory");
      }
    }
  };
  if (warp == 11) prefetch_round(0);
  if (warp == 10 && lane == 0) asm volatile("prefetch.tensormap [%0];" :: "l"(reinterpret_cast<uint64_t>(&tmx)) : "memory");
  if (tid == 0) {
    if ((sb & 0x3FFFF) != SMEM_BASE) __trap();
    for (int i = 0; i < 6; i++) { mbar_init(sb + BAR_WFULL + 8 * i, 1); }
    for (int i = 0; i < 9; i++) mbar_init(sb + BAR_XFULL + 8 * i, 1);
    mbar_init(sb + BAR_TFULL, 3);
    mbar_init(sb + BAR_TEMPTY, 8);
    mbar_init(sb + BAR_TPART, 3);
    mbar_init(sb + BAR_TPART + 8, 3);
    mbar_init(sb + BAR_SFULL, 4);
    asm volatile("fence.mbarrier_init.release.cluster;" ::: "memory");
  }
  if (tid >= 128 && tid < 320) {
    *reinterpret_cast<uint32_t*>(smem + CNT_WREL + (tid - 128) * 4) = 0;
    *reinterpret_cast<uint32_t*>(smem + OFF_ZERO + (tid - 128) * 4) = 0;
  }
  if (tid < 128) {
    const uint32_t v = (tid & 63) < 49 ? 0x3f803f80u : 0u;
    *reinterpret_cast<uint4*>(smem + OFF_KV + (tid >> 6) * KV_BYTES + 6 * KV_PITCH + (tid & 63) * 16) = make_uint4(v, v, v, v);
    asm volatile("fence.proxy.async.shared::cta;" ::: "memory");
  }
  __syncthreads();

  if (warp >= 8) {
    asm volatile("setmaxnreg.dec.sync.aligned.u32 " PREGS ";");
    if (warp == 11) {
      asm volatile("griddepcontrol.wait;" ::: "memory");
      load_slices<0, 3, 1>(sb, ds); load_slices<3, 3, 1>(sb, ds); load_slices<6, 2, 1>(sb, ds);
      for (int r = 0; r < nrounds; r++) {
#pragma unroll 1
        for (int pass = 0; pass < 4; pass++) {
          if (!(pass & 1)) mbar_wait(sb + BAR_TPART + 4 * pass, r & 1);
          stats_pass(sb, pass, lane);
        }
        __syncwarp();
        if (lane == 0) mbar_arrive(sb + BAR_SFULL);
        DUMMY();
        TR(2);
      }
    } else {
      const int cw = warp - 8;
      const int win = lane >> 4;
      const int ch0 = cw * 64 + (lane & 15) * 4;
      uint32_t wt[9][2];
#pragma unroll
      for (int t = 0; t < 9; t++) {
        uint2 v = *reinterpret_cast<const uint2*>(dw + t * CH + ch0);
        wt[t][0] = v.x; wt[t][1] = v.y;
      }
      const uint32_t xs = sb + OFF_X + cw * 3 * XSLOT;
      const uint32_t xld = xs + (lane >> 4) * 1152 + (lane & 15) * 8;
      const uint32_t xbar = sb + BAR_XFULL + cw * 24;
      const uint32_t st0 = sb + OFF_TILE + win * TILE_BYTES + ch0 * 4;
      const uint32_t st1 = sb + OFF_TILE + win * TILE_BYTES + ((ch0 * 4) ^ 16);
      const uint64_t tm = reinterpret_cast<uint64_t>(&tmx);
      int cx0, cy0, cx1, cy1;
      auto coords = [&](int r) {
        const int w0 = window_of(r, nfull, cta, ncta, 0);
        int w1 = window_of(r, nfull, cta, ncta, 1);
        if (w1 < 0) w1 = w0;
        const int a = w0 / NWX, b = w1 / NWX;
        cx0 = (w0 - a * NWX) * 7 - 1; cy0 = a * 7 - 1;
        cx1 = (w1 - b * NWX) * 7 - 1; cy1 = b * 7 - 1;
      };
      auto issue = [&](int slot, int dy) {
        asm volatile("{\n.reg .pred p;\nelect.sync _|p, 0xffffffff;\n"
                     "@p mbarrier.arrive.expect_tx.shared::cta.b64 _, [%2], %8;\n"
                     "@p cp.async.bulk.tensor.3d.shared::cluster.global.mbarrier::complete_tx::bytes [%0], [%1, {%3, %4, %5}], [%2];\n"
                     "@p cp.async.bulk.tensor.3d.shared::cluster.global.mbarrier::complete_tx::bytes [%0 + 1152], [%1, {%3, %6, %7}], [%2];\n}\n"
                     :: "r"(xs + slot * XSLOT), "l"(tm), "r"(xbar + slot * 8), "r"(cw * 64), "r"(cx0), "r"(cy0 + dy), "r"(cx1), "r"(cy1 + dy), "n"(XSLOT) : "memory");
      };
      coords(0);
      issue(0, 0); issue(1, 1); issue(2, 2);
      for (int r = 0; r < nrounds; r++) {
        const bool more = r + 1 < nrounds;
        uint32_t accA[7][2], accB[7][2], ctr[7][2], held[2];
#pragma unroll
        for (int i = 0; i < 9; i++) {
          mbar_wait(xbar + (i % 3) * 8, (r + i / 3) & 1);
          if (i == 0 && r == 0 && cw == 0) GTS(7);
          if (i == 5 || i == 7) { __syncwarp(); if (lane == 0) mbar_arrive(sb + BAR_TPART + (i == 5 ? 0 : 8)); }
          if (i == 7 && more) coords(r + 1);
          if (i == 0) { if (r > 0) issue(2, 2); }
          else if (i < 7) issue((i + 2) % 3, i + 2);
          else if (more) issue((i + 2) % 3, i - 7);
          if (i == 2 && r > 0) mbar_wait(sb + BAR_TEMPTY, (r - 1) & 1);
          if (i == 2 && cw == 0 && r == 2) GTS(1);
          if (i == 2 && cw == 0 && r == 3) GTS(3);
          if (i == 2) { TR(0); }
          uint32_t cur[9][2];
#pragma unroll
          for (int p = 0; p < 5; p++)
            asm volatile("ld.shared.v2.u32 {%0,%1}, [%2];" : "=r"(cur[p][0]), "=r"(cur[p][1]) : "r"(xld + (i % 3) * XSLOT + p * 128));
#pragma unroll
          for (int j = 0; j < 7; j++) {
            if (j >= 1 && j + 4 < 9)
              asm volatile("ld.shared.v2.u32 {%0,%1}, [%2];" : "=r"(cur[j + 4][0]), "=r"(cur[j + 4][1]) : "r"(xld + (i % 3) * XSLOT + (j + 4) * 128));
            if (i >= 2) {
              uint32_t o[2];
#pragma unroll
              for (int e = 0; e < 2; e++) {
                uint32_t a = hfma(cur[j][e], wt[6][e], accA[j][e]);
                a = hfma(cur[j + 1][e], wt[7][e], a);
                a = hfma(cur[j + 2][e], wt[8][e], a);
                o[e] = hadd(ctr[j][e], a);
              }
              const int tok = (i - 2) * 7 + j, ps = tok >> 1;
              if (!(tok & 1)) { held[0] = o[0]; held[1] = o[1]; }
              if (tok == 48) o[0] = o[1] = 0;
              if ((tok & 1) || tok == 48)
                asm volatile("st.shared.v4.u32 [%0], {%1,%2,%3,%4};" :: "r"(((ps & 1) ? st1 : st0) + ps * 768), "r"(held[0]), "r"(o[0]), "r"(held[1]), "r"(o[1]) : "memory");
            }
#pragma unroll
            for (int e = 0; e < 2; e++) {
              if (i >= 1 && i <= 7) {
                uint32_t a = hfma(cur[j][e], wt[3][e], accB[j][e]);
                a = hfma(cur[j + 1][e], wt[4][e], a);
                accA[j][e] = hfma(cur[j + 2][e], wt[5][e], a);
                ctr[j][e] = cur[j + 1][e];
              }
              if (i <= 6) {
                uint32_t a = hmul(cur[j][e], wt[0][e]);
                a = hfma(cur[j + 1][e], wt[1][e], a);
                accB[j][e] = hfma(cur[j + 2][e], wt[2][e], a);
              }
            }
          }
        }
        __syncwarp();
        if (lane == 0) mbar_arrive(sb + BAR_TFULL);
        TR(1);
        mbar_wait(sb + BAR_TFULL, r & 1);
        stats_pass(sb, 4 + cw, lane);
        __syncwarp();
        if (lane == 0) mbar_arrive(sb + BAR_SFULL);
        DUMMY();
      }
    }
  } else {
    asm volatile("setmaxnreg.inc.sync.aligned.u32 " CREGS ";");
    const int wg = warp >> 2, w4 = warp & 3, g = lane >> 2, q = lane & 3;
    const int row0 = w4 * 16 + g, row1 = row0 + 8;
    const int ps = min(w4 * 8 + g, 24);
    const int tok0 = 2 * ps, tok1 = min(2 * ps + 1, 48);
    const uint32_t kv = sb + OFF_KV + wg * KV_BYTES;
    const int srow = w4 * 16 + (lane & 15);
    const uint32_t vst = kv + (lane >> 4) * KV_PITCH + (srow < 56 ? srow : min(srow - 7, 55)) * 16;
    uint32_t misc = ((uint32_t)((tok1 / 7) * IMG + tok1 % 7) << 20) | ((uint32_t)((tok0 / 7) * IMG + tok0 % 7) << 8) | (ps * 4 + q);
    const uint32_t ninf = q ? 0xff80ff80u : 0u;
    const uint32_t vmask = (row0 < 49 ? 0xffffu : 0u) | (row1 < 49 ? 0xffff0000u : 0u);

    const uint32_t tx = sb + q * 32 + (row0 < 49 ? OFF_TILE + wg * TILE_BYTES + ps * 768 + (ps & 1) * 16 : OFF_ZERO + 16);
    const int myrounds = window_of(nrounds - 1, nfull, cta, ncta, wg) < 0 ? nrounds - 1 : nrounds;

    if (never == 2) return;
    uint32_t X[48];
    float acc[72];
    mbar_wait(sb + BAR_TFULL, 0);
    if (warp == 0) GTS(2);
    load_x<0, 12>(X, tx);
    mbar_wait(sb + BAR_WFULL, 0);
    mma144<0, 12>(acc, X, ds.q[0]);
    uint32_t rK;
    mbar_wait(sb + BAR_SFULL, 0);
    if (warp == 0) GTS(4);
    asm volatile("ld.shared.u32 %0, [%1];" : "=r"(rK) : "r"(sb + OFF_RSTD + wg * 100 + (misc & 0xfc)) : "memory");
    __syncwarp();
    if (lane == 0) mbar_arrive(sb + BAR_TEMPTY);

    if (wg == 1) turn_pass<PP_LAST>(1);
    for (int r = 0;; r++) {
      const uint32_t par = r & 1;
      if (r == myrounds) {
        wg_wait<0>(); keep(acc);
        if (w4 == 0) GTS(5 + wg);
        if (r < nrounds)
        {
          mbar_wait(sb + BAR_WFULL, par);      if (w4 == 3) release<0>(sb, ds, false);
          mbar_wait(sb + BAR_WFULL + 8, par);  if (w4 == 3) release<1>(sb, ds, false);
          turn_wait<0>(wg); if (PP_LAST != 0) turn_pass<0>(wg);
          mbar_wait(sb + BAR_WFULL + 16, par); if (w4 == 3) release<2>(sb, ds, false);
          turn_wait<1>(wg); if (PP_LAST != 1) turn_pass<1>(wg);
          turn_wait<2>(wg); if (PP_LAST != 2) turn_pass<2>(wg);
          turn_wait<3>(wg); if (PP_LAST != 3) turn_pass<3>(wg);
          turn_wait<4>(wg); if (PP_LAST != 4) turn_pass<4>(wg);
          turn_wait<5>(wg);
        }
        break;
      }
      TR(0);
      const bool next_round = r + 1 < nrounds;
      const bool pass = wg == 0 || next_round;
      uint32_t Of[48], Q[12], T[16], inv = 0;
      float S[28];
      const uint64_t* dkv = ds.kv[wg];

#define PRE(H, ACC)                                                                     \
      packn<0, 12>(T, ACC); scalen<0, 12>(T, rK); stsm12(T, vst + KV_KOFF);                       \
      packn<0, 12>(T, ACC + 24); hold<0, 12>(T);                                        \
      PIN();                                                                            \
      if (H > 0) { wg_wait<0>(); keep(S); }                                             \
      proxy_fence();                                                                    \
      _Pragma("unroll") for (int i = 0; i < 12; i++) Q[i] = T[i];                       \
      scalen<0, 12>(Q, rK); hold<0, 12>(Q);
#define PRE2(H)                                                                         \
      if (H > 0) { inv = inv_sum(S) & vmask; packn<0, 12>(Of + 12 * (H > 0 ? H - 1 : 0), S);    \
                   hold<0, 12>(Of + 12 * (H > 0 ? H - 1 : 0)); hold<0, 1>(&inv); }
#define MID(H, VACC, FIRST2)                                                             \
      PIN();                                                                            \
      packn<0, 12>(T, VACC); scalen<0, 12>(T, rK); stsm12(T, vst);                      \
      if (H < 3 && w4 == 3) release<(H < 3 ? H : 0)>(sb, ds, next_round);               \
      turn_wait<H>(wg);                                                                 \
      PIN();                                                                            \
      FIRST2;                                                                           \
      wg_wait<1>(); keep(S);

      wg_wait<0>(); keep(acc);
      TR(2);
      PRE(0, acc) PRE2(0)
      mbar_wait(sb + BAR_WFULL + 8, par);
      bar_sync(1 + wg);
      TR(3);
      issue_s(S, Q, dkv);
      MID(0, acc + 48, (mma144<0, ksched(0, 12)>(acc, X, ds.q[1])))
      TR(4);
      softmax_pv<0, 12, false>(S, dkv + 4, Of, inv, wg, pass, ninf, [&](auto a, auto b) { mma144<a.v, b.v>(acc, X, ds.q[1]); });
      TR(5);
      wg_wait<1>(); keep(acc);
      TR(6);
      PRE(1, acc) PRE2(1)
      mbar_wait(sb + BAR_WFULL + 16, par);
      bar_sync(1 + wg);
      TR(7);
      issue_s(S, Q, dkv);
      MID(1, acc + 48, (mma144<0, ksched(0, 12)>(acc, X, ds.q[2])))
      TR(8);
      softmax_pv<1, 12, true>(S, dkv + 4, Of, inv, wg, pass, ninf, [&](auto a, auto b) { mma144<a.v, b.v>(acc, X, ds.q[2]); });
      TR(9);
      float kq[48], va[24], pa[32], pb[32];
      wg_wait<1>(); keep(acc);
      TR(10);
      PRE(2, acc) PRE2(2)
      mbar_wait(sb + BAR_WFULL + 24, par);
      bar_sync(1 + wg);
      TR(11);
      issue_s(S, Q, dkv);
      MID(2, acc + 48, (mma96<0, ksched(0, 12)>(kq, X, ds.q[3])))
      TR(12);
      softmax_pv<2, 12, true>(S, dkv + 4, Of + 12, inv, wg, pass, ninf, [&](auto a, auto b) { mma96<a.v, b.v>(kq, X, ds.q[3]); });
      TR(13);
      wg_wait<1>(); keep(kq);
      TR(14);
      packn<0, 12>(T, kq); scalen<0, 12>(T, rK); stsm12(T, vst + KV_KOFF); PIN();
      wg_wait<0>(); keep(S);
      mma48<0, 4>(va, X, ds.v3);
      packn<0, 6>(Q, kq + 24); scalen<0, 6>(Q, rK); hold<0, 6>(Q); PIN();
      mma48<4, 8>(va, X, ds.v3);
      packn<6, 12>(Q, kq + 24); scalen<6, 12>(Q, rK); hold<6, 12>(Q); PIN();
      mma48<8, 12>(va, X, ds.v3);
      PIN();
      proxy_fence();
      PRE2(3)
      scalen<24, 36>(Of, inv); hold<24, 36>(Of);
      mbar_wait(sb + BAR_WFULL + 32, par);
      bar_sync(1 + wg);
      TR(15);
      issue_s(S, Q, dkv);
      wg_wait<1>(); keep(va);
      MID(3, va, (mma64<0, ksched(0, 9)>(pa, Of, ds.p)))
      TR(16);
      softmax_pv<3, 9, false>(S, dkv + 4, Of + 24, inv, wg, pass, ninf, [&](auto a, auto b) { mma64<a.v, b.v>(pa, Of, ds.p); });
      if (w4 == 3) release<3>(sb, ds, next_round);
      TR(17);
#undef PRE
#undef PRE2
#undef MID
      const bool more = r + 1 < myrounds;
      const int w = window_of(r, nfull, cta, ncta, wg);
      const int wy = w / NWX, wx = w - wy * NWX;
      asm volatile("" : "+r"(misc));
      const uint32_t wb = (uint32_t)(wy * 7 * IMG + wx * 7) * 384u + (misc & 3) * 16;
      uint8_t* o0 = reinterpret_cast<uint8_t*>(out) + (wb + ((misc >> 8) & 0xfff) * 384u);
      uint8_t* o1 = reinterpret_cast<uint8_t*>(out) + (wb + (misc >> 20) * 384u);
      mbar_wait(sb + BAR_WFULL + 40, par);
      wg_wait<0>(); keep(S); keep(pa);
      TR(18);
      inv = inv_sum(S) & vmask; packn<0, 12>(Of + 36, S); hold<36, 48>(Of); turn_wait<4>(wg); PIN();
      mma64<0, 5>(pb, Of, ds.p + 12);
      scalen<36, 48>(Of, inv); hold<36, 48>(Of); PIN();
      mma64<9, 12>(pa, Of, ds.p);
      mma64<5, 12>(pb, Of, ds.p + 12);
      if (more) mbar_wait(sb + BAR_TFULL, par ^ 1);
      TR(19);
      wg_wait<1>(); keep(pa);
      TR(20);
      packn<0, 16>(T, pa); add_res<0, 0, 12>(T, X); hold<0, 16>(T); PIN();
      mma64<0, 3, 2>(pa, Of, ds.p + 24);
      add_res<0, 12, 16>(T, X); hold<12, 16>(T); PIN();
      load_x<0, 4>(X, tx); store_out<0>(T, o0, o1, vmask); PIN();
      mma64<3, 12>(pa, Of, ds.p + 24);
      if (PP_LAST != 4 || pass) turn_pass<4>(wg);
      PIN();
      TR(21);
      wg_wait<2>(); keep(pb);
      bar_sync(1 + wg);
      packn<0, 16>(T, pb); add_res<1, 0, 16>(T, X); hold<0, 16>(T); PIN();
      if (w4 == 3) release<4>(sb, ds, next_round);
      load_x<4, 8>(X, tx); store_out<1>(T, o0, o1, vmask);
      if (more) mbar_wait(sb + BAR_WFULL, par ^ 1);
      TR(22);
      wg_wait<0>(); keep(pa);
      TR(23);
      if (PPMASK >> 5 & 1) turn_wait<5>(wg); else bar_sync(1 + wg);
      mma144<0, 1>(acc, X, ds.q[0]);
      packn<0, 6>(T, pa); add_res<2, 0, 4>(T, X); hold<0, 6>(T); PIN();
      mma144<1, 2>(acc, X, ds.q[0]);
      packn<6, 11>(T, pa); add_res<2, 4, 9>(T, X); hold<4, 11>(T); PIN();
      mma144<2, 3>(acc, X, ds.q[0]);
      packn<11, 16>(T, pa); add_res<2, 9, 16>(T, X); hold<9, 16>(T); PIN();
      mma144<3, 8>(acc, X, ds.q[0]);
      load_x<8, 12>(X, tx); store_out<2>(T, o0, o1, vmask);
      if (w4 == 3) release<5>(sb, ds, next_round);
      if (more) mbar_wait(sb + BAR_SFULL, par ^ 1);
      asm volatile("ld.shared.u32 %0, [%1];" : "=r"(rK) : "r"(sb + OFF_RSTD + wg * 100 + (misc & 0xfc)) : "memory");
      mma144<8, 12>(acc, X, ds.q[0]);
      if (pass) turn_pass<5>(wg);
      __syncwarp();
      if (lane == 0) mbar_arrive(sb + BAR_TEMPTY);
      TR(1);
    }
  }
}

typedef CUresult (*EncodeFn)(CUtensorMap*, CUtensorMapDataType, cuuint32_t, void*, const cuuint64_t*, const cuuint64_t*,
                             const cuuint32_t*, const cuuint32_t*, CUtensorMapInterleave, CUtensorMapSwizzle,
                             CUtensorMapL2promotion, CUtensorMapFloatOOBfill);

}

extern "C" void kernel_launch(void* const* d_in, const int* in_sizes, int n_in, void* d_out, int out_size) {
  const __nv_bfloat16* x = (const __nv_bfloat16*)d_in[0];
  const __nv_bfloat16* dw = (const __nv_bfloat16*)d_in[1];
  const __nv_bfloat16* wqkv = (const __nv_bfloat16*)d_in[2];
  const __nv_bfloat16* wo = (const __nv_bfloat16*)d_in[3];
  static EncodeFn encode = nullptr;
  static int nsm = 0;
  static void* wpack = nullptr;
  if (!encode) {
    void* fn = nullptr;
    cudaDriverEntryPointQueryResult qr;
    cudaGetDriverEntryPoint("cuTensorMapEncodeTiled", &fn, cudaEnableDefault, &qr);
    encode = (EncodeFn)fn;
    int dev = 0;
    cudaGetDevice(&dev);
    cudaDeviceGetAttribute(&nsm, cudaDevAttrMultiProcessorCount, dev);
    cudaGetSymbolAddress(&wpack, g_wpack);
    cudaFuncSetAttribute(fused_kernel, cudaFuncAttributeMaxDynamicSharedMemorySize, SMEM_BYTES);
  }
  CUtensorMap tmx;
  cuuint64_t gdim[3] = {CH, IMG, IMG};
  cuuint64_t gstr[2] = {CH * 2, (cuuint64_t)CH * 2 * IMG};
  cuuint32_t box[3] = {64, 9, 1};
  cuuint32_t estr[3] = {1, 1, 1};
  encode(&tmx, CU_TENSOR_MAP_DATA_TYPE_BFLOAT16, 3, (void*)x, gdim, gstr, box, estr, CU_TENSOR_MAP_INTERLEAVE_NONE,
         CU_TENSOR_MAP_SWIZZLE_NONE, CU_TENSOR_MAP_L2_PROMOTION_L2_128B, CU_TENSOR_MAP_FLOAT_OOB_FILL_NONE);
  Descs ds;
  for (int i = 0; i < 12; i++) {
    for (int h = 0; h < 4; h++) ds.q[h][i] = mkdesc(SMEM_BASE + OFF_W + qkv_off(h, i), 128, 256);
    ds.v3[i] = mkdesc(SMEM_BASE + OFF_W + qkv_off(3, i) + 3072, 128, 256);
    for (int c = 0; c < 3; c++) ds.p[c * 12 + i] = mkdesc(SMEM_BASE + OFF_W + wo_off(c, i), 128, 256);
  }
  for (int i = 0; i < 16; i++) ds.src[i] = (const uint8_t*)wpack + i * SLICE;
  for (int g = 0; g < 2; g++)
    for (int i = 0; i < 4; i++) {
      ds.kv[g][i] = mkdesc(SMEM_BASE + OFF_KV + g * KV_BYTES + KV_KOFF + 2 * i * KV_PITCH, KV_PITCH, 128);
      ds.kv[g][4 + i] = mkdesc(SMEM_BASE + OFF_KV + g * KV_BYTES + 256 * i, 128, KV_PITCH);
    }
  CUtensorMap tmp;
  cuuint32_t boxp[3] = {CH, 9, 9};
  encode(&tmp, CU_TENSOR_MAP_DATA_TYPE_BFLOAT16, 3, (void*)x, gdim, gstr, boxp, estr, CU_TENSOR_MAP_INTERLEAVE_NONE,
         CU_TENSOR_MAP_SWIZZLE_NONE, CU_TENSOR_MAP_L2_PROMOTION_L2_128B, CU_TENSOR_MAP_FLOAT_OOB_FILL_NONE);
  prepack_kernel<<<48, dim3(192, 2), 0, cudaStreamPerThread>>>(wqkv, wo);
  cudaLaunchConfig_t cfg = {};
  cfg.gridDim = dim3(nsm); cfg.blockDim = dim3(384); cfg.dynamicSmemBytes = SMEM_BYTES; cfg.stream = cudaStreamPerThread;
  cudaLaunchAttribute at[1];
  at[0].id = cudaLaunchAttributeProgrammaticStreamSerialization;
  at[0].val.programmaticStreamSerializationAllowed = 1;
  cfg.attrs = at; cfg.numAttrs = 1;
  cudaLaunchKernelEx(&cfg, fused_kernel, tmx, tmp, ds, dw, (__nv_bfloat16*)d_out, 0);
}
```

```cpp
#include <cuda_runtime.h>
#include <cuda_bf16.h>
#include <cuda_fp16.h>
#include <cuda.h>
#include <stdint.h>

#define WHINT 0
#define CREGS "208"
#define PREGS "88"
#define ZK1 6
#define ZK2 9
#define ZPASS 3
namespace {

constexpr int IMG = 511;
constexpr int CH = 192;
constexpr int NWX = 73;
constexpr int NWIN = NWX * NWX;
constexpr int SLICE = 18432;
constexpr int OFF_W = 0;
constexpr int KV_PITCH = 1792, KV_KOFF = 896, KV_BYTES = 6 * KV_PITCH + 1024;
constexpr int OFF_KV = 8 * SLICE;
constexpr int TILE_BYTES = 25 * 768;
constexpr int OFF_TILE = OFF_KV + 2 * KV_BYTES;
constexpr int XSLOT = 2304;
constexpr int OFF_ZERO = OFF_TILE + 2 * TILE_BYTES;
constexpr int OFF_X = OFF_ZERO + 768;
constexpr int OFF_BAR = OFF_X + 9 * XSLOT;
constexpr int BAR_WFULL = OFF_BAR;
constexpr int BAR_XFULL = OFF_BAR + 72;
constexpr int BAR_TFULL = OFF_BAR + 144;
constexpr int BAR_TEMPTY = OFF_BAR + 152;
constexpr int BAR_TPART = OFF_BAR + 160;
constexpr int BAR_SFULL = OFF_BAR + 48;
constexpr int OFF_STAT = OFF_BAR + 192;
constexpr int CNT_WREL = OFF_STAT + 800;
constexpr int OFF_TRACE = CNT_WREL + 32;
constexpr int SMEM_BYTES = OFF_TRACE;

constexpr int SMEM_BASE = 1024;
struct Descs { uint64_t q[4][12]; uint64_t p[12]; uint64_t kv[2][8]; const uint8_t* src[16]; };

__device__ uint4 g_wpack[16 * SLICE / 16];
#define TR(id)
#define GTS(i)
template <int V> struct IC { static constexpr int v = V; };
typedef __nv_bfloat162 bf2;
__device__ __forceinline__ bf2 u2b(uint32_t u) { return *reinterpret_cast<bf2*>(&u); }
__device__ __forceinline__ uint32_t b2u(bf2 b) { return *reinterpret_cast<uint32_t*>(&b); }
__device__ __forceinline__ uint32_t pack2(float lo, float hi) {
  uint32_t r; asm("cvt.rn.bf16x2.f32 %0, %1, %2;" : "=r"(r) : "f"(hi), "f"(lo)); return r;
}
__device__ __forceinline__ uint32_t hadd(uint32_t a, uint32_t b) { return b2u(__hadd2_rn(u2b(a), u2b(b))); }
__device__ __forceinline__ uint32_t hmul(uint32_t a, uint32_t b) { return b2u(__hmul2_rn(u2b(a), u2b(b))); }
__device__ __forceinline__ uint32_t hfma(uint32_t a, uint32_t b, uint32_t c) { return b2u(__hfma2(u2b(a), u2b(b), u2b(c))); }
template <int HI> __device__ __forceinline__ bf2 bcast(uint32_t a) { return HI ? __high2bfloat162(u2b(a)) : __low2bfloat162(u2b(a)); }
template <int HI> __device__ __forceinline__ uint32_t hsub_b(uint32_t a, uint32_t s) { return b2u(__hsub2_rn(u2b(a), bcast<HI>(s))); }
__device__ __forceinline__ __half2 u2h(uint32_t u) { return *reinterpret_cast<__half2*>(&u); }
__device__ __forceinline__ uint32_t h2u(__half2 b) { return *reinterpret_cast<uint32_t*>(&b); }
__device__ __forceinline__ uint32_t packh(float lo, float hi) {
  uint32_t r; asm("cvt.rn.f16x2.f32 %0, %1, %2;" : "=r"(r) : "f"(hi), "f"(lo)); return r;
}
__device__ __forceinline__ uint32_t fmax2(uint32_t a, uint32_t b) { return h2u(__hmax2(u2h(a), u2h(b))); }
template <int HI> __device__ __forceinline__ __half2 hcast(uint32_t a) { return HI ? __high2half2(u2h(a)) : __low2half2(u2h(a)); }
template <int HI> __device__ __forceinline__ uint32_t fmul_b(uint32_t a, uint32_t s) { return h2u(__hmul2_rn(u2h(a), hcast<HI>(s))); }
template <int HI> __device__ __forceinline__ uint32_t fsub_b(uint32_t a, uint32_t s) { return h2u(__hsub2_rn(u2h(a), hcast<HI>(s))); }
__device__ __forceinline__ uint32_t fex2(uint32_t a) { uint32_t r; asm("ex2.approx.f16x2 %0, %1;" : "=r"(r) : "r"(a)); return r; }
__device__ __forceinline__ float lo2f(uint32_t a) { return __uint_as_float(a << 16); }
__device__ __forceinline__ float hi2f(uint32_t a) { return __uint_as_float(a & 0xffff0000u); }

__device__ __forceinline__ void mbar_init(uint32_t bar, uint32_t cnt) { asm volatile("mbarrier.init.shared::cta.b64 [%0], %1;" :: "r"(bar), "r"(cnt) : "memory"); }
__device__ __forceinline__ void mbar_arrive(uint32_t bar) { asm volatile("mbarrier.arrive.shared::cta.b64 _, [%0];" :: "r"(bar) : "memory"); }
__device__ __forceinline__ void mbar_expect(uint32_t bar, uint32_t bytes) { asm volatile("mbarrier.arrive.expect_tx.shared::cta.b64 _, [%0], %1;" :: "r"(bar), "r"(bytes) : "memory"); }
template <int HINT>
__device__ __forceinline__ bool mbar_try(uint32_t bar, uint32_t parity) {
  uint32_t ok;
  if (HINT) asm volatile("{\n.reg .pred p;\nmbarrier.try_wait.parity.shared::cta.b64 p, [%1], %2, %3;\nselp.u32 %0, 1, 0, p;\n}\n" : "=r"(ok) : "r"(bar), "r"(parity), "n"(HINT) : "memory");
  else asm volatile("{\n.reg .pred p;\nmbarrier.try_wait.parity.shared::cta.b64 p, [%1], %2;\nselp.u32 %0, 1, 0, p;\n}\n" : "=r"(ok) : "r"(bar), "r"(parity) : "memory");
  return ok != 0;
}
__device__ __forceinline__ void mbar_wait(uint32_t bar, uint32_t parity) {
  if (__builtin_expect(!mbar_try<0>(bar, parity), 0)) {
    uint32_t n = 0;
    while (!mbar_try<WHINT>(bar, parity)) { if (++n > (1u << 24)) __trap(); }
  }
}
__device__ __forceinline__ void wg_fence() { asm volatile("wgmma.fence.sync.aligned;" ::: "memory"); }
__device__ __forceinline__ void wg_commit() { asm volatile("wgmma.commit_group.sync.aligned;" ::: "memory"); }
template <int N> __device__ __forceinline__ void wg_wait() { asm volatile("wgmma.wait_group.sync.aligned %0;" :: "n"(N) : "memory"); }
__device__ __forceinline__ void bar_sync(int id) { asm volatile("bar.sync %0, 128;" :: "r"(id) : "memory"); }
#define PPMASK 0x2f
template <int SEC> __device__ __forceinline__ void turn_wait(int wg) { if (PPMASK >> SEC & 1) asm volatile("bar.sync %0, 256;" :: "r"(3 + wg) : "memory"); }
template <int SEC> __device__ __forceinline__ void turn_pass(int wg) { if (PPMASK >> SEC & 1) asm volatile("bar.arrive %0, 256;" :: "r"(4 - wg) : "memory"); }
static_assert(PPMASK == 0 || (PPMASK & 32), "section 5 starts the hand-over chain");
__device__ __forceinline__ void stsm4(uint32_t addr, uint32_t a, uint32_t b, uint32_t c, uint32_t d) {
  asm volatile("stmatrix.sync.aligned.m8n8.x4.shared.b16 [%0], {%1,%2,%3,%4};" :: "r"(addr), "r"(a), "r"(b), "r"(c), "r"(d) : "memory");
}
template <int N> __device__ __forceinline__ void keep(float (&d)[N]) {
#pragma unroll
  for (int i = 0; i < N; i++) asm volatile("" : "+f"(d[i]) :: "memory");
}
template <int N> __device__ __forceinline__ void keep(uint32_t (&d)[N]) {
#pragma unroll
  for (int i = 0; i < N; i++) asm volatile("" : "+r"(d[i]) :: "memory");
}
__host__ __device__ __forceinline__ uint64_t mkdesc(uint32_t addr, uint32_t lbo, uint32_t sbo) {
  return ((uint64_t)(sbo >> 4) << 32) | (uint64_t)(((lbo >> 4) << 16) | ((addr & 0x3FFFF) >> 4));
}

template <int SCALE_D>
__device__ __forceinline__ void wgmma_n144(uint32_t (&d)[36], uint32_t a0, uint32_t a1, uint32_t a2, uint32_t a3, uint64_t descB) {
  if (SCALE_D == 0)
  asm volatile("wgmma.mma_async.sync.aligned.m64n144k16.f16.f16.f16 "
    "{%0, %1, %2, %3, %4, %5, %6, %7, %8, %9, %10, %11, %12, %13, %14, %15, "
    "%16, %17, %18, %19, %20, %21, %22, %23, %24, %25, %26, %27, %28, %29, %30, %31, "
    "%32, %33, %34, %35}, "
    "{%36, %37, %38, %39}, %40, 0, 1, 1, 0;\n"
    : "=r"(d[0]), "=r"(d[1]), "=r"(d[2]), "=r"(d[3]), "=r"(d[4]), "=r"(d[5]), "=r"(d[6]), "=r"(d[7]),
      "=r"(d[8]), "=r"(d[9]), "=r"(d[10]), "=r"(d[11]), "=r"(d[12]), "=r"(d[13]), "=r"(d[14]), "=r"(d[15]),
      "=r"(d[16]), "=r"(d[17]), "=r"(d[18]), "=r"(d[19]), "=r"(d[20]), "=r"(d[21]), "=r"(d[22]), "=r"(d[23]),
      "=r"(d[24]), "=r"(d[25]), "=r"(d[26]), "=r"(d[27]), "=r"(d[28]), "=r"(d[29]), "=r"(d[30]), "=r"(d[31]),
      "=r"(d[32]), "=r"(d[33]), "=r"(d[34]), "=r"(d[35])
    : "r"(a0), "r"(a1), "r"(a2), "r"(a3), "l"(descB));
  else
  asm volatile("wgmma.mma_async.sync.aligned.m64n144k16.f16.f16.f16 "
    "{%0, %1, %2, %3, %4, %5, %6, %7, %8, %9, %10, %11, %12, %13, %14, %15, "
    "%16, %17, %18, %19, %20, %21, %22, %23, %24, %25, %26, %27, %28, %29, %30, %31, "
    "%32, %33, %34, %35}, "
    "{%36, %37, %38, %39}, %40, 1, 1, 1, 0;\n"
    : "+r"(d[0]), "+r"(d[1]), "+r"(d[2]), "+r"(d[3]), "+r"(d[4]), "+r"(d[5]), "+r"(d[6]), "+r"(d[7]),
      "+r"(d[8]), "+r"(d[9]), "+r"(d[10]), "+r"(d[11]), "+r"(d[12]), "+r"(d[13]), "+r"(d[14]), "+r"(d[15]),
      "+r"(d[16]), "+r"(d[17]), "+r"(d[18]), "+r"(d[19]), "+r"(d[20]), "+r"(d[21]), "+r"(d[22]), "+r"(d[23]),
      "+r"(d[24]), "+r"(d[25]), "+r"(d[26]), "+r"(d[27]), "+r"(d[28]), "+r"(d[29]), "+r"(d[30]), "+r"(d[31]),
      "+r"(d[32]), "+r"(d[33]), "+r"(d[34]), "+r"(d[35])
    : "r"(a0), "r"(a1), "r"(a2), "r"(a3), "l"(descB));
}

template <int SCALE_D>
__device__ __forceinline__ void wgmma_n192(uint32_t (&d)[48], uint32_t a0, uint32_t a1, uint32_t a2, uint32_t a3, uint64_t descB) {
  if (SCALE_D == 0)
  asm volatile("wgmma.mma_async.sync.aligned.m64n192k16.f16.f16.f16 "
    "{%0, %1, %2, %3, %4, %5, %6, %7, %8, %9, %10, %11, %12, %13, %14, %15, "
    "%16, %17, %18, %19, %20, %21, %22, %23, %24, %25, %26, %27, %28, %29, %30, %31, "
    "%32, %33, %34, %35, %36, %37, %38, %39, %40, %41, %42, %43, %44, %45, %46, %47}, "
    "{%48, %49, %50, %51}, %52, 0, 1, 1, 0;\n"
    : "=r"(d[0]), "=r"(d[1]), "=r"(d[2]), "=r"(d[3]), "=r"(d[4]), "=r"(d[5]), "=r"(d[6]), "=r"(d[7]),
      "=r"(d[8]), "=r"(d[9]), "=r"(d[10]), "=r"(d[11]), "=r"(d[12]), "=r"(d[13]), "=r"(d[14]), "=r"(d[15]),
      "=r"(d[16]), "=r"(d[17]), "=r"(d[18]), "=r"(d[19]), "=r"(d[20]), "=r"(d[21]), "=r"(d[22]), "=r"(d[23]),
      "=r"(d[24]), "=r"(d[25]), "=r"(d[26]), "=r"(d[27]), "=r"(d[28]), "=r"(d[29]), "=r"(d[30]), "=r"(d[31]),
      "=r"(d[32]), "=r"(d[33]), "=r"(d[34]), "=r"(d[35]), "=r"(d[36]), "=r"(d[37]), "=r"(d[38]), "=r"(d[39]),
      "=r"(d[40]), "=r"(d[41]), "=r"(d[42]), "=r"(d[43]), "=r"(d[44]), "=r"(d[45]), "=r"(d[46]), "=r"(d[47])
    : "r"(a0), "r"(a1), "r"(a2), "r"(a3), "l"(descB));
  else
  asm volatile("wgmma.mma_async.sync.aligned.m64n192k16.f16.f16.f16 "
    "{%0, %1, %2, %3, %4, %5, %6, %7, %8, %9, %10, %11, %12, %13, %14, %15, "
    "%16, %17, %18, %19, %20, %21, %22, %23, %24, %25, %26, %27, %28, %29, %30, %31, "
    "%32, %33, %34, %35, %36, %37, %38, %39, %40, %41, %42, %43, %44, %45, %46, %47}, "
    "{%48, %49, %50, %51}, %52, 1, 1, 1, 0;\n"
    : "+r"(d[0]), "+r"(d[1]), "+r"(d[2]), "+r"(d[3]), "+r"(d[4]), "+r"(d[5]), "+r"(d[6]), "+r"(d[7]),
      "+r"(d[8]), "+r"(d[9]), "+r"(d[10]), "+r"(d[11]), "+r"(d[12]), "+r"(d[13]), "+r"(d[14]), "+r"(d[15]),
      "+r"(d[16]), "+r"(d[17]), "+r"(d[18]), "+r"(d[19]), "+r"(d[20]), "+r"(d[21]), "+r"(d[22]), "+r"(d[23]),
      "+r"(d[24]), "+r"(d[25]), "+r"(d[26]), "+r"(d[27]), "+r"(d[28]), "+r"(d[29]), "+r"(d[30]), "+r"(d[31]),
      "+r"(d[32]), "+r"(d[33]), "+r"(d[34]), "+r"(d[35]), "+r"(d[36]), "+r"(d[37]), "+r"(d[38]), "+r"(d[39]),
      "+r"(d[40]), "+r"(d[41]), "+r"(d[42]), "+r"(d[43]), "+r"(d[44]), "+r"(d[45]), "+r"(d[46]), "+r"(d[47])
    : "r"(a0), "r"(a1), "r"(a2), "r"(a3), "l"(descB));
}

template <int SCALE_D>
__device__ __forceinline__ void wgmma_n56(uint32_t (&d)[14], uint32_t a0, uint32_t a1, uint32_t a2, uint32_t a3, uint64_t descB) {
  if (SCALE_D == 0)
  asm volatile("wgmma.mma_async.sync.aligned.m64n56k16.f16.f16.f16 "
    "{%0, %1, %2, %3, %4, %5, %6, %7, %8, %9, %10, %11, %12, %13}, "
    "{%14, %15, %16, %17}, %18, 0, 1, 1, 0;\n"
    : "=r"(d[0]), "=r"(d[1]), "=r"(d[2]), "=r"(d[3]), "=r"(d[4]), "=r"(d[5]), "=r"(d[6]), "=r"(d[7]),
      "=r"(d[8]), "=r"(d[9]), "=r"(d[10]), "=r"(d[11]), "=r"(d[12]), "=r"(d[13])
    : "r"(a0), "r"(a1), "r"(a2), "r"(a3), "l"(descB));
  else
  asm volatile("wgmma.mma_async.sync.aligned.m64n56k16.f16.f16.f16 "
    "{%0, %1, %2, %3, %4, %5, %6, %7, %8, %9, %10, %11, %12, %13}, "
    "{%14, %15, %16, %17}, %18, 1, 1, 1, 0;\n"
    : "+r"(d[0]), "+r"(d[1]), "+r"(d[2]), "+r"(d[3]), "+r"(d[4]), "+r"(d[5]), "+r"(d[6]), "+r"(d[7]),
      "+r"(d[8]), "+r"(d[9]), "+r"(d[10]), "+r"(d[11]), "+r"(d[12]), "+r"(d[13])
    : "r"(a0), "r"(a1), "r"(a2), "r"(a3), "l"(descB));
}

template <int SCALE_D>
__device__ __forceinline__ void wgmma_n56t(uint32_t (&d)[14], uint32_t a0, uint32_t a1, uint32_t a2, uint32_t a3, uint64_t descB) {
  if (SCALE_D == 0)
  asm volatile("wgmma.mma_async.sync.aligned.m64n56k16.f16.f16.f16 "
    "{%0, %1, %2, %3, %4, %5, %6, %7, %8, %9, %10, %11, %12, %13}, "
    "{%14, %15, %16, %17}, %18, 0, 1, 1, 1;\n"
    : "=r"(d[0]), "=r"(d[1]), "=r"(d[2]), "=r"(d[3]), "=r"(d[4]), "=r"(d[5]), "=r"(d[6]), "=r"(d[7]),
      "=r"(d[8]), "=r"(d[9]), "=r"(d[10]), "=r"(d[11]), "=r"(d[12]), "=r"(d[13])
    : "r"(a0), "r"(a1), "r"(a2), "r"(a3), "l"(descB));
  else
  asm volatile("wgmma.mma_async.sync.aligned.m64n56k16.f16.f16.f16 "
    "{%0, %1, %2, %3, %4, %5, %6, %7, %8, %9, %10, %11, %12, %13}, "
    "{%14, %15, %16, %17}, %18, 1, 1, 1, 1;\n"
    : "+r"(d[0]), "+r"(d[1]), "+r"(d[2]), "+r"(d[3]), "+r"(d[4]), "+r"(d[5]), "+r"(d[6]), "+r"(d[7]),
      "+r"(d[8]), "+r"(d[9]), "+r"(d[10]), "+r"(d[11]), "+r"(d[12]), "+r"(d[13])
    : "r"(a0), "r"(a1), "r"(a2), "r"(a3), "l"(descB));
}

__global__ void __launch_bounds__(384) prepack_kernel(const __nv_bfloat16* __restrict__ wqkv, const __nv_bfloat16* __restrict__ wo) {
  asm volatile("griddepcontrol.launch_dependents;");
  __half* dst = reinterpret_cast<__half*>(g_wpack);
  const int c = threadIdx.x, nb = blockIdx.x * 2 + threadIdx.y;
  if (nb < 72) {
    __shared__ float red2[2][6][8];
    float (*red)[8] = red2[threadIdx.y];
    const int h = nb / 18, j = nb % 18, part = j / 6;
    const int col = (part == 0 ? 192 : part == 1 ? 0 : 384) + h * 48 + (j % 6) * 8;
    uint4 raw = *reinterpret_cast<const uint4*>(wqkv + c * 576 + col);
    uint32_t u[4] = {raw.x, raw.y, raw.z, raw.w};
    float v[8];
#pragma unroll
    for (int i = 0; i < 4; i++) { v[2 * i] = lo2f(u[i]); v[2 * i + 1] = hi2f(u[i]); }
#pragma unroll
    for (int i = 0; i < 8; i++) {
      float s = v[i];
#pragma unroll
      for (int o = 16; o; o >>= 1) s += __shfl_xor_sync(~0u, s, o);
      if ((c & 31) == 0) red[c >> 5][i] = s;
    }
    __syncthreads();
    const int cc = c >> 5, q = (c >> 3) & 3, s1 = (c >> 2) & 1, hh = (c >> 1) & 1, e = c & 1;
    const int base = h * 27648 + (2 * cc + s1) * 2304 + j * 128 + hh * 64 + 2 * q + e;
#pragma unroll
    for (int n = 0; n < 8; n++) {
      float m = (red[0][n] + red[1][n] + red[2][n] + red[3][n] + red[4][n] + red[5][n]) * (1.0f / 192.0f);
      dst[base + n * 8] = __float2half_rn((v[n] - m) * (part == 1 ? 0.14433756729740643f * 1.4426950408889634f : 1.0f));
    }
  } else {
    const int jb = nb - 72;
    const int s = c >> 4, hh = (c >> 3) & 1, kk = c & 7;
    const int base = 110592 + s * 3072 + jb * 128 + hh * 64 + kk;
#pragma unroll
    for (int n = 0; n < 8; n++) {
      const int ch = 32 * (jb >> 2) + 8 * (n >> 1) + 2 * (jb & 3) + (n & 1);
      dst[base + n * 8] = __float2half_rn(__bfloat162float(wo[c * 192 + ch]));
    }
  }
}

__device__ __forceinline__ int window_of(int round, int nfull, int cta, int ncta, int wg) {
  if (round < nfull) return round * 2 * ncta + 2 * cta + wg;
  const int rem = NWIN - nfull * 2 * ncta;
  const int i = cta + wg * ncta;
  return i < rem ? nfull * 2 * ncta + i : -1;
}

__host__ __device__ constexpr int qkv_off(int h, int s) { return ((3 * h + s / 4) % 8) * SLICE + (s % 4) * 4608; }
__host__ __device__ constexpr int wo_off(int s) { return 4 * SLICE + s * 6144; }

template <int S0, int S1>
__device__ __forceinline__ void mma_qkv(uint32_t (&acc)[36], const uint32_t (&A)[48], const uint64_t* d) {
  wg_fence();
#pragma unroll
  for (int s = S0; s < S1; s++) {
    if (s == 0) wgmma_n144<0>(acc, A[4 * s], A[4 * s + 1], A[4 * s + 2], A[4 * s + 3], d[s]);
    else        wgmma_n144<1>(acc, A[4 * s], A[4 * s + 1], A[4 * s + 2], A[4 * s + 3], d[s]);
  }
  wg_commit();
}
template <int S0, int S1>
__device__ __forceinline__ void mma_proj(uint32_t (&acc)[48], const uint32_t (&A)[48], const uint64_t* d) {
  wg_fence();
#pragma unroll
  for (int s = S0; s < S1; s++) wgmma_n192<1>(acc, A[4 * s], A[4 * s + 1], A[4 * s + 2], A[4 * s + 3], d[s]);
  wg_commit();
}

#define PIN() asm volatile("pmevent 0;" ::: "memory")
template <int A, int B> __device__ __forceinline__ void hold(uint32_t* v) {
#pragma unroll
  for (int i = A; i < B; i++) asm volatile("" : "+r"(v[i]));
}
__device__ __forceinline__ void stsm12(const uint32_t* v, uint32_t addr) {
#pragma unroll
  for (int j = 0; j < 3; j++) stsm4(addr + 2 * j * KV_PITCH, v[4 * j], v[4 * j + 1], v[4 * j + 2], v[4 * j + 3]);
}
__device__ __forceinline__ void copy_q(uint32_t (&Q)[12], const uint32_t* a, uint32_t z) {
#pragma unroll
  for (int i = 0; i < 12; i++) Q[i] = a[i] ^ z;
  hold<0, 12>(Q);
}
__device__ __forceinline__ void finish_o(const uint32_t (&O)[14], uint32_t* Of, float rs0, float rs1) {
  float i0, i1;
  asm("rcp.approx.ftz.f32 %0, %1;" : "=f"(i0) : "f"(__low2float(u2h(O[12]))));
  asm("rcp.approx.ftz.f32 %0, %1;" : "=f"(i1) : "f"(__low2float(u2h(O[13]))));
  const uint32_t inv = packh(i0 * rs0, i1 * rs1);
#pragma unroll
  for (int i = 0; i < 12; i++) Of[i] = (i & 1) ? fmul_b<1>(O[i], inv) : fmul_b<0>(O[i], inv);
}
template <int A, int B, int CHUNK = 48> __device__ __forceinline__ void normalise(uint32_t (&X)[48], const float (&rs)[2], const float (&sh)[2]) {
#pragma unroll
  for (int i = A; i < B; i++) {
    if ((i - A) % CHUNK == 0 && CHUNK < 48) PIN();
    asm volatile("" : "+r"(X[i]));
    X[i] = packh(fmaf(lo2f(X[i]), rs[i & 1], sh[i & 1]), fmaf(hi2f(X[i]), rs[i & 1], sh[i & 1]));
    asm volatile("" : "+r"(X[i]));
  }
}
template <int CC>
__device__ __forceinline__ void store_out(const uint32_t (&Y)[48], const float (&sd)[2], const float (&mu)[2], uint8_t* o0, uint8_t* o1, uint32_t vmask) {
  uint32_t T[8];
#pragma unroll
  for (int i = 0; i < 8; i++) {
    const float2 f = __half22float2(u2h(Y[8 * CC + i]));
    T[i] = pack2(fmaf(f.x, sd[i & 1], mu[i & 1]), fmaf(f.y, sd[i & 1], mu[i & 1]));
  }
  asm volatile("{\n.reg .pred p;\nsetp.ne.u32 p, %5, 0;\n@p st.global.v4.u32 [%0], {%1,%2,%3,%4};\n}\n"
               :: "l"(o0 + CC * 64), "r"(T[0]), "r"(T[2]), "r"(T[4]), "r"(T[6]), "r"(vmask) : "memory");
  asm volatile("{\n.reg .pred p;\nsetp.lt.s32 p, %5, 0;\n@p st.global.v4.u32 [%0], {%1,%2,%3,%4};\n}\n"
               :: "l"(o1 + CC * 64), "r"(T[1]), "r"(T[3]), "r"(T[5]), "r"(T[7]), "r"(vmask) : "memory");
}
__device__ __forceinline__ void proxy_fence() { asm volatile("fence.proxy.async.shared::cta;" ::: "memory"); }
__device__ __forceinline__ void issue_s(uint32_t (&S)[14], const uint32_t (&Q)[12], const uint64_t* d) {
  wg_fence();
  wgmma_n56<0>(S, Q[0], Q[1], Q[2], Q[3], d[0]);
  wgmma_n56<1>(S, Q[4], Q[5], Q[6], Q[7], d[1]);
  wgmma_n56<1>(S, Q[8], Q[9], Q[10], Q[11], d[2]);
  wg_commit();
}
struct H2 { uint16_t l, h; };
__device__ __forceinline__ H2 exp_halves(uint32_t a) {
  H2 r;
  asm("{\n.reg .b16 l, h;\nmov.b32 {l, h}, %2;\nex2.approx.f16 %0, l;\nex2.approx.f16 %1, h;\n}\n" : "=h"(r.l), "=h"(r.h) : "r"(a));
  return r;
}
__device__ __forceinline__ uint32_t join(H2 v) { uint32_t r; asm("mov.b32 %0, {%1, %2};" : "=r"(r) : "h"(v.l), "h"(v.h)); return r; }
__device__ __forceinline__ void hold(H2& v) { asm volatile("" : "+h"(v.l), "+h"(v.h)); }

#define KSCHED 0x2468abccull
#define PASS_SEG 7
#define PASS_SEG3 7
__host__ __device__ constexpr int ksched(int seg, int nk) { return (int)(KSCHED >> (28 - 4 * seg) & 15) < nk ? (int)(KSCHED >> (28 - 4 * seg) & 15) : nk; }
template <int SEC, int NK, class G, class F>
__device__ __forceinline__ void softmax_pv(const uint32_t (&S)[14], uint32_t (&O)[14], const uint64_t* dV, int wg, uint32_t ninf, G g, F f) {
  constexpr int PS = SEC == 3 ? PASS_SEG3 : PASS_SEG;
#define GK(i) if (ksched(i, NK) > ksched(i - 1, NK)) g(IC<ksched(i - 1, NK)>{}, IC<ksched(i, NK)>{}); \
              if (i == PS) turn_pass<SEC>(wg);
#define NEED(i) (ksched(i, NK) < NK || PS > (i))
  uint32_t P[16];
  GK(1)
  const uint32_t k48 = __byte_perm(S[12], S[13], 0x5410) | ninf;
  uint32_t m0 = fmax2(fmax2(fmax2(S[0], S[2]), S[4]), fmax2(fmax2(S[6], S[8]), S[10]));
  uint32_t m1 = fmax2(fmax2(fmax2(S[1], S[3]), S[5]), fmax2(fmax2(S[7], S[9]), S[11]));
  uint32_t mx = fmax2(fmax2(__byte_perm(m0, m1, 0x5410), __byte_perm(m0, m1, 0x7632)), k48);
  uint32_t sh = __shfl_xor_sync(~0u, mx, 1);
  if (NEED(1)) PIN();
  GK(2)
  if (NEED(1)) PIN();
  mx = fmax2(mx, sh);
  sh = __shfl_xor_sync(~0u, mx, 2);
  if (NEED(2)) PIN();
  GK(3)
  if (NEED(2)) PIN();
  mx = fmax2(mx, sh);
#pragma unroll
  for (int j = 0; j < 12; j++) P[j] = (j & 1) ? fsub_b<1>(S[j], mx) : fsub_b<0>(S[j], mx);
  P[12] = h2u(__hsub2_rn(u2h(k48), u2h(mx)));
  H2 e0 = exp_halves(P[0]), e1 = exp_halves(P[1]);
  GK(4)
  if (NEED(4)) { hold<2, 13>(P); hold(e0); hold(e1); PIN(); }
  GK(5)
  H2 e2 = exp_halves(P[2]), e3 = exp_halves(P[3]);
  P[0] = join(e0); P[1] = join(e1);
  f(IC<0>{});
  if (NEED(5)) { hold<0, 2>(P); hold(e2); hold(e3); PIN(); }
  GK(6)
  e0 = exp_halves(P[4]); e1 = exp_halves(P[5]);
  P[2] = join(e2); P[3] = join(e3);
  f(IC<1>{});
  if (NEED(6)) { hold<2, 4>(P); hold(e0); hold(e1); PIN(); }
  GK(7)
  proxy_fence();
  e2 = exp_halves(P[12]);
  P[12] = e2.l; P[13] = e2.h; P[14] = 0; P[15] = 0;
  P[4] = join(e0); P[5] = join(e1);
#pragma unroll
  for (int j = 6; j < 12; j++) P[j] = fex2(P[j]);
  f(IC<2>{});
  bar_sync(1 + wg);
  wg_fence();
  wgmma_n56t<0>(O, P[0], P[1], P[2], P[3], dV[0]);
  wgmma_n56t<1>(O, P[4], P[5], P[6], P[7], dV[1]);
  wgmma_n56t<1>(O, P[12], P[13], P[14], P[15], dV[3]);
  wgmma_n56t<1>(O, P[8], P[9], P[10], P[11], dV[2]);
  wg_commit();
#undef GK
#undef NEED
}
template <int S0, int S1>
__device__ __forceinline__ void load_x(uint32_t (&X)[48], uint32_t t0) {
#pragma unroll
  for (int s = S0; s < S1; s++)
    asm volatile("ld.shared.v4.u32 {%0,%1,%2,%3}, [%4];" : "=r"(X[4 * s]), "=r"(X[4 * s + 1]), "=r"(X[4 * s + 2]), "=r"(X[4 * s + 3])
                 : "r"(((s & 1) ? (t0 ^ 16) : t0) + (s >> 1) * 128) : "memory");
}

#define WDIV 1
template <int K, int CNT, int DIV = WDIV> __device__ __forceinline__ void load_slices(uint32_t sb, const Descs& ds) {
  constexpr int st = K < 12 ? K / 3 : 4;
  constexpr bool first = K <= 12 && K % 3 == 0;
  if (first)
    asm volatile("{\n.reg .pred p;\nelect.sync _|p, 0xffffffff;\n@p mbarrier.arrive.expect_tx.shared::cta.b64 _, [%0], %1;\n}\n"
                 :: "r"(sb + BAR_WFULL + 8 * st), "n"(DIV == 1 && K == 6 ? 2 * SLICE + SLICE / WDIV : (K < 12 ? 3 : 4) * SLICE / DIV) : "memory");
  asm volatile("{\n.reg .pred p;\nelect.sync _|p, 0xffffffff;\n"
               "@p cp.async.bulk.shared::cluster.global.mbarrier::complete_tx::bytes [%0], [%1], %2, [%3];\n}\n"
               :: "r"(sb + OFF_W + (K & 7) * SLICE), "l"(ds.src[K]), "n"(CNT * SLICE / DIV), "r"(sb + BAR_WFULL + 8 * st) : "memory");
}
template <int STAGE> __device__ __forceinline__ void release(uint32_t sb, const Descs& ds, bool next_round) {
  uint32_t old = 0;
  asm volatile("{\n.reg .pred p;\nelect.sync _|p, 0xffffffff;\n@p atom.shared.inc.u32 %0, [%1], 1;\n}\n" : "+r"(old) : "r"(sb + CNT_WREL + 4 * STAGE) : "memory");
  if (__any_sync(0xffffffffu, old == 1)) {
    if (STAGE == 0) { load_slices<8, 1>(sb, ds); load_slices<9, 2>(sb, ds); }
    if (STAGE == 1) { load_slices<11, 1>(sb, ds); load_slices<12, 2>(sb, ds); }
    if (STAGE == 2) { load_slices<14, 2>(sb, ds); if (next_round) load_slices<0, 1>(sb, ds); }
    if (STAGE == 3 && next_round) { load_slices<1, 2>(sb, ds); load_slices<3, 1>(sb, ds); }
    if (STAGE == 4 && next_round) { load_slices<4, 2>(sb, ds); load_slices<6, 1>(sb, ds); }
    if (STAGE == 5 && next_round) load_slices<7, 1>(sb, ds);
  }
}

__device__ __forceinline__ float4 ln_rows(const uint32_t (&X)[48]) {
  uint32_t sm[2];
#pragma unroll
  for (int a = 0; a < 2; a++) {
    uint32_t t[12];
#pragma unroll
    for (int i = 0; i < 12; i++) t[i] = hadd(X[4 * i + a], X[4 * i + 2 + a]);
#pragma unroll
    for (int i = 0; i < 6; i++) t[i] = hadd(t[i], t[i + 6]);
#pragma unroll
    for (int i = 0; i < 3; i++) t[i] = hadd(t[i], t[i + 3]);
    sm[a] = hadd(hadd(t[0], t[1]), t[2]);
  }
  uint32_t m = hadd(__byte_perm(sm[0], sm[1], 0x5410), __byte_perm(sm[0], sm[1], 0x7632));
  m = hadd(m, __shfl_xor_sync(~0u, m, 1));
  m = hadd(m, __shfl_xor_sync(~0u, m, 2));
  m = hmul(m, 0x3bab3babu);
  float var[2];
#pragma unroll
  for (int a = 0; a < 2; a++) {
    uint32_t t[4];
#pragma unroll
    for (int i = 0; i < 24; i++) {
      const uint32_t d = a ? hsub_b<1>(X[2 * i + 1], m) : hsub_b<0>(X[2 * i], m);
      t[i & 3] = i < 4 ? hmul(d, d) : hfma(d, d, t[i & 3]);
    }
    const uint32_t s = hadd(hadd(t[0], t[1]), hadd(t[2], t[3]));
    float v = lo2f(s) + hi2f(s);
    v += __shfl_xor_sync(~0u, v, 1);
    v += __shfl_xor_sync(~0u, v, 2);
    var[a] = fmaf(v, 1.0f / 192.0f, 1e-5f);
  }
  return make_float4(var[0], lo2f(m), var[1], hi2f(m));
}

#define DUMMY()
__device__ __forceinline__ void stats_pass(uint32_t sb, int pass, int lane) {
  const int g = lane >> 2, q = lane & 3;
  const int tile = g >> 2;
  const int ps = min(pass * 4 + (g & 3), 24);
  uint32_t X[48];
  const uint32_t t0 = sb + OFF_TILE + tile * TILE_BYTES + ps * 768 + q * 32 + (ps & 1) * 16;
  load_x<0, 12>(X, t0);
  const float4 st = ln_rows(X);
  asm volatile("st.shared.v4.f32 [%0], {%1,%2,%3,%4};" :: "r"(sb + OFF_STAT + tile * 400 + ps * 16), "f"(st.x), "f"(st.y), "f"(st.z), "f"(st.w) : "memory");
}

__global__ void __launch_bounds__(384, 1)
fused_kernel(const __grid_constant__ CUtensorMap tmx, const __grid_constant__ CUtensorMap tmp, const __grid_constant__ Descs ds, const __nv_bfloat16* __restrict__ dw, __nv_bfloat16* __restrict__ out, const int never) {
  extern __shared__ __align__(1024) uint8_t smem[];
  const uint32_t sb = (uint32_t)__cvta_generic_to_shared(smem);
  const int tid = threadIdx.x, lane = tid & 31;
  const int warp = __shfl_sync(0xffffffffu, tid >> 5, 0);
  const int cta = blockIdx.x, ncta = gridDim.x;
  const int nfull = NWIN / (2 * ncta);
  const int nrounds = nfull + ((NWIN - nfull * 2 * ncta) > cta ? 1 : 0);

  if (warp == 0) GTS(0);
  auto prefetch_round = [&](int r) {
#pragma unroll
    for (int k = 0; k < 2; k++) {
      const int w = window_of(r, nfull, cta, ncta, k);
      if (w >= 0) {
        const int a = w / NWX;
        asm volatile("{\n.reg .pred p;\nelect.sync _|p, 0xffffffff;\n@p cp.async.bulk.prefetch.tensor.3d.L2.global [%0, {0, %1, %2}];\n}\n"
                     :: "l"(reinterpret_cast<uint64_t>(&tmp)), "r"((w - a * NWX) * 7 - 1), "r"(a * 7 - 1) : "memory");
      }
    }
  };
  if (warp == 11) prefetch_round(0);
  if (warp == 10 && lane == 0) asm volatile("prefetch.tensormap [%0];" :: "l"(reinterpret_cast<uint64_t>(&tmx)) : "memory");
  if (tid == 0) {
    if ((sb & 0x3FFFF) != SMEM_BASE) __trap();
    for (int i = 0; i < 6; i++) { mbar_init(sb + BAR_WFULL + 8 * i, 1); }
    for (int i = 0; i < 9; i++) mbar_init(sb + BAR_XFULL + 8 * i, 1);
    mbar_init(sb + BAR_TFULL, 3);
    mbar_init(sb + BAR_TEMPTY, 8);
    for (int i = 0; i < 4; i++) mbar_init(sb + BAR_TPART + 8 * i, 3);
    mbar_init(sb + BAR_SFULL, 4);
    asm volatile("fence.mbarrier_init.release.cluster;" ::: "memory");
  }
  if (tid >= 128 && tid < 320) {
    if (tid < 136) *reinterpret_cast<uint32_t*>(smem + CNT_WREL + (tid - 128) * 4) = 0;
    *reinterpret_cast<uint32_t*>(smem + OFF_ZERO + (tid - 128) * 4) = 0;
  }
  if (tid < 128) {
    const uint32_t v = (tid & 63) < 49 ? 0x3c003c00u : 0u;
    *reinterpret_cast<uint4*>(smem + OFF_KV + (tid >> 6) * KV_BYTES + 6 * KV_PITCH + (tid & 63) * 16) = make_uint4(v, v, v, v);
    asm volatile("fence.proxy.async.shared::cta;" ::: "memory");
  }
  __syncthreads();

  if (warp >= 8) {
    asm volatile("setmaxnreg.dec.sync.aligned.u32 " PREGS ";");
    if (warp == 11) {
      asm volatile("griddepcontrol.wait;" ::: "memory");
      load_slices<0, 3, 1>(sb, ds); load_slices<3, 3, 1>(sb, ds); load_slices<6, 2, 1>(sb, ds);
      for (int r = 0; r < nrounds; r++) {
#pragma unroll 1
        for (int pass = 0; pass < 4; pass++) {
          mbar_wait(sb + BAR_TPART + 8 * pass, r & 1);
          stats_pass(sb, pass, lane);
        }
        __syncwarp();
        if (lane == 0) mbar_arrive(sb + BAR_SFULL);
        DUMMY();
        TR(2);
      }
    } else {
      const int cw = warp - 8;
      const int win = lane >> 4;
      const int ch0 = cw * 64 + (lane & 15) * 4;
      uint32_t wt[9][2];
#pragma unroll
      for (int t = 0; t < 9; t++) {
        uint2 v = *reinterpret_cast<const uint2*>(dw + t * CH + ch0);
        wt[t][0] = v.x; wt[t][1] = v.y;
      }
      const uint32_t xs = sb + OFF_X + cw * 3 * XSLOT;
      const uint32_t xld = xs + (lane >> 4) * 1152 + (lane & 15) * 8;
      const uint32_t xbar = sb + BAR_XFULL + cw * 24;
      const uint32_t st0 = sb + OFF_TILE + win * TILE_BYTES + ch0 * 4;
      const uint32_t st1 = sb + OFF_TILE + win * TILE_BYTES + ((ch0 * 4) ^ 16);
      const uint64_t tm = reinterpret_cast<uint64_t>(&tmx);
      int cx0, cy0, cx1, cy1;
      auto coords = [&](int r) {
        const int w0 = window_of(r, nfull, cta, ncta, 0);
        int w1 = window_of(r, nfull, cta, ncta, 1);
        if (w1 < 0) w1 = w0;
        const int a = w0 / NWX, b = w1 / NWX;
        cx0 = (w0 - a * NWX) * 7 - 1; cy0 = a * 7 - 1;
        cx1 = (w1 - b * NWX) * 7 - 1; cy1 = b * 7 - 1;
      };
      auto issue = [&](int slot, int dy) {
        asm volatile("{\n.reg .pred p;\nelect.sync _|p, 0xffffffff;\n"
                     "@p mbarrier.arrive.expect_tx.shared::cta.b64 _, [%2], %8;\n"
                     "@p cp.async.bulk.tensor.3d.shared::cluster.global.mbarrier::complete_tx::bytes [%0], [%1, {%3, %4, %5}], [%2];\n"
                     "@p cp.async.bulk.tensor.3d.shared::cluster.global.mbarrier::complete_tx::bytes [%0 + 1152], [%1, {%3, %6, %7}], [%2];\n}\n"
                     :: "r"(xs + slot * XSLOT), "l"(tm), "r"(xbar + slot * 8), "r"(cw * 64), "r"(cx0), "r"(cy0 + dy), "r"(cx1), "r"(cy1 + dy), "n"(XSLOT) : "memory");
      };
      coords(0);
      issue(0, 0); issue(1, 1); issue(2, 2);
      for (int r = 0; r < nrounds; r++) {
        const bool more = r + 1 < nrounds;
        uint32_t accA[7][2], accB[7][2], ctr[7][2], held[2];
#pragma unroll
        for (int i = 0; i < 9; i++) {
          mbar_wait(xbar + (i % 3) * 8, (r + i / 3) & 1);
          if (i == 0 && r == 0 && cw == 0) GTS(7);
          if (i >= 4 && i <= 7) { __syncwarp(); if (lane == 0) mbar_arrive(sb + BAR_TPART + 8 * (i - 4)); }
          if (i == 7 && more) coords(r + 1);
          if (i == 0) { if (r > 0) issue(2, 2); }
          else if (i < 7) issue((i + 2) % 3, i + 2);
          else if (more) issue((i + 2) % 3, i - 7);
          if (i == 2 && r > 0) mbar_wait(sb + BAR_TEMPTY, (r - 1) & 1);
          if (i == 2 && cw == 0 && r == 2) GTS(1);
          if (i == 2 && cw == 0 && r == 3) GTS(3);
          if (i == 2) { TR(0); }
          uint32_t cur[9][2];
#pragma unroll
          for (int p = 0; p < 5; p++)
            asm volatile("ld.shared.v2.u32 {%0,%1}, [%2];" : "=r"(cur[p][0]), "=r"(cur[p][1]) : "r"(xld + (i % 3) * XSLOT + p * 128));
#pragma unroll
          for (int j = 0; j < 7; j++) {
            if (j >= 1 && j + 4 < 9)
              asm volatile("ld.shared.v2.u32 {%0,%1}, [%2];" : "=r"(cur[j + 4][0]), "=r"(cur[j + 4][1]) : "r"(xld + (i % 3) * XSLOT + (j + 4) * 128));
            if (i >= 2) {
              uint32_t o[2];
#pragma unroll
              for (int e = 0; e < 2; e++) {
                uint32_t a = hfma(cur[j][e], wt[6][e], accA[j][e]);
                a = hfma(cur[j + 1][e], wt[7][e], a);
                a = hfma(cur[j + 2][e], wt[8][e], a);
                o[e] = hadd(ctr[j][e], a);
              }
              const int tok = (i - 2) * 7 + j, ps = tok >> 1;
              if (!(tok & 1)) { held[0] = o[0]; held[1] = o[1]; }
              if (tok == 48) o[0] = o[1] = 0;
              if ((tok & 1) || tok == 48)
                asm volatile("st.shared.v4.u32 [%0], {%1,%2,%3,%4};" :: "r"(((ps & 1) ? st1 : st0) + ps * 768), "r"(held[0]), "r"(o[0]), "r"(held[1]), "r"(o[1]) : "memory");
            }
#pragma unroll
            for (int e = 0; e < 2; e++) {
              if (i >= 1 && i <= 7) {
                uint32_t a = hfma(cur[j][e], wt[3][e], accB[j][e]);
                a = hfma(cur[j + 1][e], wt[4][e], a);
                accA[j][e] = hfma(cur[j + 2][e], wt[5][e], a);
                ctr[j][e] = cur[j + 1][e];
              }
              if (i <= 6) {
                uint32_t a = hmul(cur[j][e], wt[0][e]);
                a = hfma(cur[j + 1][e], wt[1][e], a);
                accB[j][e] = hfma(cur[j + 2][e], wt[2][e], a);
              }
            }
          }
        }
        __syncwarp();
        if (lane == 0) mbar_arrive(sb + BAR_TFULL);
        TR(1);
        mbar_wait(sb + BAR_TFULL, r & 1);
        stats_pass(sb, 4 + cw, lane);
        TR(3);
        __syncwarp();
        if (lane == 0) mbar_arrive(sb + BAR_SFULL);
        DUMMY();
      }
    }
  } else {
    asm volatile("setmaxnreg.inc.sync.aligned.u32 " CREGS ";");
    const int wg = warp >> 2, w4 = warp & 3, g = lane >> 2, q = lane & 3;
    const int row0 = w4 * 16 + g, row1 = row0 + 8;
    const int ps = min(w4 * 8 + g, 24);
    const int tok0 = 2 * ps, tok1 = min(2 * ps + 1, 48);
    const uint32_t kv = sb + OFF_KV + wg * KV_BYTES;
    const int srow = w4 * 16 + (lane & 15);
    const uint32_t vst = kv + (lane >> 4) * KV_PITCH + (srow < 56 ? srow : min(srow - 7, 55)) * 16;
    uint32_t misc = ((uint32_t)((tok1 / 7) * IMG + tok1 % 7) << 20) | ((uint32_t)((tok0 / 7) * IMG + tok0 % 7) << 8) | (ps * 4 + q);
    const uint32_t ninf = q ? 0xfc00fc00u : 0u;
    const uint32_t vmask = (row0 < 49 ? 0xffffu : 0u) | (row1 < 49 ? 0xffff0000u : 0u);

    const uint32_t tx = sb + q * 32 + (row0 < 49 ? OFF_TILE + wg * TILE_BYTES + ps * 768 + (ps & 1) * 16 : OFF_ZERO + 16);
    const int myrounds = window_of(nrounds - 1, nfull, cta, ncta, wg) < 0 ? nrounds - 1 : nrounds;

    if (never == 2) return;
    uint32_t H[48], Y[48];
    float rs[2], sh[2], nrs[2], nsh[2];
    uint8_t *o0 = nullptr, *o1 = nullptr;
    auto load_stat = [&]() {
      float v0, v1, m0, m1;
      asm volatile("ld.shared.v4.f32 {%0,%1,%2,%3}, [%4];" : "=f"(v0), "=f"(m0), "=f"(v1), "=f"(m1)
                   : "r"(sb + OFF_STAT + wg * 400 + (misc & 0xfc) * 4) : "memory");
      asm("rsqrt.approx.ftz.f32 %0, %1;" : "=f"(nrs[0]) : "f"(v0));
      asm("rsqrt.approx.ftz.f32 %0, %1;" : "=f"(nrs[1]) : "f"(v1));
      if (!(vmask & 1)) nrs[0] = 0.f;
      if ((int)vmask >= 0) nrs[1] = 0.f;
      nsh[0] = -m0 * nrs[0]; nsh[1] = -m1 * nrs[1];
    };
    auto tile_done = [&]() {
      asm volatile("{\n.reg .pred p;\nelect.sync _|p, 0xffffffff;\n@p mbarrier.arrive.shared::cta.b64 _, [%0];\n}\n" :: "r"(sb + BAR_TEMPTY) : "memory");
    };
#pragma unroll
    for (int i = 0; i < 48; i++) Y[i] = 0;
    rs[0] = rs[1] = 1.f; sh[0] = sh[1] = 0.f;
    mbar_wait(sb + BAR_TFULL, 0);
    load_x<0, 12>(H, tx);
    mbar_wait(sb + BAR_SFULL, 0);
    if (warp == 0) GTS(4);
    load_stat();
    tile_done();
    normalise<0, 48, 8>(H, nrs, nsh);
    mbar_wait(sb + BAR_WFULL, 0);
    if (wg == 1) turn_pass<5>(1);
    turn_wait<5>(wg);

    for (int r = 0;; r++) {
      const uint32_t par = r & 1;
      uint32_t accA[36], accB[36];
      const uint32_t smask = r > 0 ? vmask : 0u;
      float sd[2], mu[2];
      asm("rcp.approx.ftz.f32 %0, %1;" : "=f"(sd[0]) : "f"(rs[0]));
      asm("rcp.approx.ftz.f32 %0, %1;" : "=f"(sd[1]) : "f"(rs[1]));
      mu[0] = -sh[0] * sd[0]; mu[1] = -sh[1] * sd[1];
      rs[0] = nrs[0]; rs[1] = nrs[1]; sh[0] = nsh[0]; sh[1] = nsh[1];
      mma_qkv<0, 2>(accA, H, ds.q[0]);
      wg_wait<1>(); keep(Y);
      mma_qkv<2, ZK1>(accA, H, ds.q[0]);
      store_out<0>(Y, sd, mu, o0, o1, smask); PIN();
      mma_qkv<ZK1, ZK2>(accA, H, ds.q[0]);
      store_out<1>(Y, sd, mu, o0, o1, smask); PIN();
      mma_qkv<ZK2, 12>(accA, H, ds.q[0]);
      store_out<2>(Y, sd, mu, o0, o1, smask); PIN();
      if (ZPASS == 4) { store_out<3>(Y, sd, mu, o0, o1, smask); PIN(); }
      if (PPMASK)
        asm volatile("{\n.reg .pred p;\nsetp.ne.s32 p, %1, 0;\n@p bar.arrive %0, 256;\n}\n" :: "r"(4 - wg), "r"((int)(wg == 0 || r < nrounds)) : "memory");
      if (ZPASS == 3) { store_out<3>(Y, sd, mu, o0, o1, smask); PIN(); }
      store_out<4>(Y, sd, mu, o0, o1, smask); PIN();
      store_out<5>(Y, sd, mu, o0, o1, smask); PIN();
      wg_wait<0>(); keep(accA);
      stsm12(accA, vst + KV_KOFF);
      if (r == myrounds) {
        if (w4 == 0) GTS(5 + wg);
        if (r < nrounds) {
          bar_sync(1 + wg);                    if (w4 == 3) release<5>(sb, ds, true);
          mbar_wait(sb + BAR_WFULL, par);      if (w4 == 3) release<0>(sb, ds, false);
          mbar_wait(sb + BAR_WFULL + 8, par);  if (w4 == 3) release<1>(sb, ds, false);
          turn_wait<0>(wg); turn_pass<0>(wg);
          mbar_wait(sb + BAR_WFULL + 16, par); if (w4 == 3) release<2>(sb, ds, false);
          turn_wait<1>(wg); turn_pass<1>(wg);
          turn_wait<2>(wg); turn_pass<2>(wg);
          turn_wait<3>(wg); turn_pass<3>(wg);
          turn_wait<5>(wg);
        }
        break;
      }
      TR(0);
      const bool next_round = r + 1 < nrounds;
      uint32_t Of[48], S[14], O[14], Q[12];
      const uint64_t* dkv = ds.kv[wg];
      auto nothing = [](auto) {};

#define HEAD_BEGIN(HD, ACC, FIRST)                                                      \
      if (HD > 0) { wg_wait<1>(); keep(ACC); }                                                                     \
      TR(2 + 4 * HD);                                                                   \
      if (HD > 0) stsm12(ACC, vst + KV_KOFF);                                           \
      copy_q(Q, ACC + 12, never); PIN();                                                \
      proxy_fence();                                                                    \
      mbar_wait(sb + BAR_WFULL + 8 * (HD + 1), par);                                    \
      bar_sync(1 + wg);                                                                 \
      TR(3 + 4 * HD);                                                                   \
      issue_s(S, Q, dkv);                                                                      \
      if (w4 == 3) { if (HD == 0 && r > 0) release<5>(sb, ds, true); release<HD>(sb, ds, next_round); } \
      if (HD > 0) { wg_wait<1>(); keep(O); }                                            \
      if (PPMASK >> HD & 1) turn_wait<HD>(wg); else bar_sync(1 + wg);                   \
      FIRST;                                                                            \
      stsm12(ACC + 24, vst);                                                            \
      if (HD > 0) { finish_o(O, Of + 12 * (HD > 0 ? HD - 1 : 0), rs[0], rs[1]); hold<0, 12>(Of + 12 * (HD > 0 ? HD - 1 : 0)); } \
      PIN();                                                                            \
      wg_wait<1>(); keep(S);                                                            \
      TR(4 + 4 * HD);

      HEAD_BEGIN(0, accA, (mma_qkv<0, ksched(0, 12)>(accB, H, ds.q[1])))
      softmax_pv<0, 12>(S, O, dkv + 4, wg, ninf, [&](auto a, auto b) { mma_qkv<a.v, b.v>(accB, H, ds.q[1]); }, nothing);
      TR(5);
      HEAD_BEGIN(1, accB, (mma_qkv<0, ksched(0, 12)>(accA, H, ds.q[2])))
      softmax_pv<1, 12>(S, O, dkv + 4, wg, ninf, [&](auto a, auto b) { mma_qkv<a.v, b.v>(accA, H, ds.q[2]); }, nothing);
      TR(9);
      HEAD_BEGIN(2, accA, (mma_qkv<0, ksched(0, 12)>(accB, H, ds.q[3])))
      softmax_pv<2, 12>(S, O, dkv + 4, wg, ninf, [&](auto a, auto b) { mma_qkv<a.v, b.v>(accB, H, ds.q[3]); }, nothing);
      TR(13);
      const bool more = r + 1 < myrounds;
      const uint32_t rho = 0x3c003c00u + never;
      wg_wait<1>(); keep(accB);
      TR(14);
      stsm12(accB, vst + KV_KOFF);
      copy_q(Q, accB + 12, never); PIN();
      proxy_fence();
      mbar_wait(sb + BAR_WFULL + 32, par);
      wg_wait<0>(); keep(O);
      bar_sync(1 + wg);
      TR(15);
      issue_s(S, Q, dkv);
      if (w4 == 3) release<3>(sb, ds, next_round);
      stsm12(accB + 24, vst);
      finish_o(O, Of + 24, rs[0], rs[1]); hold<24, 36>(Of);
      PIN();
#pragma unroll
      for (int i = 0; i < 48; i++) Y[i] = (i & 1) ? fmul_b<1>(H[i], rho) : fmul_b<0>(H[i], rho);
      hold<0, 48>(Y);
      if (more) mbar_wait(sb + BAR_SFULL, par ^ 1);
      turn_wait<3>(wg);
      mma_proj<0, ksched(0, 9)>(Y, Of, ds.p);
      PIN();
      load_x<0, 4>(H, tx); load_stat();
      wg_wait<1>(); keep(S);
      TR(16);
      softmax_pv<3, 9>(S, O, dkv + 4, wg, ninf, [&](auto a, auto b) { mma_proj<a.v, b.v>(Y, Of, ds.p); },
                       [&](auto i) {
                         if (i.v == 1) load_x<4, 8>(H, tx);
                         if (i.v == 2) { load_x<8, 12>(H, tx); tile_done(); }
                         normalise<(i.v == 0 ? 0 : i.v == 1 ? 4 : 8), (i.v == 0 ? 4 : i.v == 1 ? 8 : 16)>(H, nrs, nsh); });
      TR(17);
#undef HEAD_BEGIN
      normalise<16, 48, 8>(H, nrs, nsh);
      const int w = window_of(r, nfull, cta, ncta, wg);
      const int wy = w / NWX, wx = w - wy * NWX;
      asm volatile("" : "+r"(misc));
      const uint32_t wb = (uint32_t)(wy * 7 * IMG + wx * 7) * 384u + (misc & 3) * 16;
      o0 = reinterpret_cast<uint8_t*>(out) + (wb + ((misc >> 8) & 0xfff) * 384u);
      o1 = reinterpret_cast<uint8_t*>(out) + (wb + (misc >> 20) * 384u);
      hold<0, 48>(H); PIN();
      TR(18);
      wg_wait<0>(); keep(O); keep(Y);
      bar_sync(1 + wg);
      finish_o(O, Of + 36, rs[0], rs[1]);
      if (w4 == 3) release<4>(sb, ds, next_round);
      if (more) mbar_wait(sb + BAR_WFULL, par ^ 1);
      TR(19);
      turn_wait<5>(wg);
      TR(20);
      mma_proj<9, 12>(Y, Of, ds.p);
      TR(1);
    }
  }
}

typedef CUresult (*EncodeFn)(CUtensorMap*, CUtensorMapDataType, cuuint32_t, void*, const cuuint64_t*, const cuuint64_t*,
                             const cuuint32_t*, const cuuint32_t*, CUtensorMapInterleave, CUtensorMapSwizzle,
                             CUtensorMapL2promotion, CUtensorMapFloatOOBfill);

}

extern "C" void kernel_launch(void* const* d_in, const int* in_sizes, int n_in, void* d_out, int out_size) {
  const __nv_bfloat16* x = (const __nv_bfloat16*)d_in[0];
  const __nv_bfloat16* dw = (const __nv_bfloat16*)d_in[1];
  const __nv_bfloat16* wqkv = (const __nv_bfloat16*)d_in[2];
  const __nv_bfloat16* wo = (const __nv_bfloat16*)d_in[3];
  static EncodeFn encode = nullptr;
  static int nsm = 0;
  static void* wpack = nullptr;
  if (!encode) {
    void* fn = nullptr;
    cudaDriverEntryPointQueryResult qr;
    cudaGetDriverEntryPoint("cuTensorMapEncodeTiled", &fn, cudaEnableDefault, &qr);
    encode = (EncodeFn)fn;
    int dev = 0;
    cudaGetDevice(&dev);
    cudaDeviceGetAttribute(&nsm, cudaDevAttrMultiProcessorCount, dev);
    cudaGetSymbolAddress(&wpack, g_wpack);
    cudaFuncSetAttribute(fused_kernel, cudaFuncAttributeMaxDynamicSharedMemorySize, SMEM_BYTES);
  }
  CUtensorMap tmx;
  cuuint64_t gdim[3] = {CH, IMG, IMG};
  cuuint64_t gstr[2] = {CH * 2, (cuuint64_t)CH * 2 * IMG};
  cuuint32_t box[3] = {64, 9, 1};
  cuuint32_t estr[3] = {1, 1, 1};
  encode(&tmx, CU_TENSOR_MAP_DATA_TYPE_BFLOAT16, 3, (void*)x, gdim, gstr, box, estr, CU_TENSOR_MAP_INTERLEAVE_NONE,
         CU_TENSOR_MAP_SWIZZLE_NONE, CU_TENSOR_MAP_L2_PROMOTION_L2_128B, CU_TENSOR_MAP_FLOAT_OOB_FILL_NONE);
  Descs ds;
  for (int i = 0; i < 12; i++) {
    for (int h = 0; h < 4; h++) ds.q[h][i] = mkdesc(SMEM_BASE + OFF_W + qkv_off(h, i), 128, 256);
    ds.p[i] = mkdesc(SMEM_BASE + OFF_W + wo_off(i), 128, 256);
  }
  for (int i = 0; i < 16; i++) ds.src[i] = (const uint8_t*)wpack + i * SLICE;
  for (int g = 0; g < 2; g++)
    for (int i = 0; i < 4; i++) {
      ds.kv[g][i] = mkdesc(SMEM_BASE + OFF_KV + g * KV_BYTES + KV_KOFF + 2 * i * KV_PITCH, KV_PITCH, 128);
      ds.kv[g][4 + i] = mkdesc(SMEM_BASE + OFF_KV + g * KV_BYTES + 256 * i, 128, KV_PITCH);
    }
  CUtensorMap tmp;
  cuuint32_t boxp[3] = {CH, 9, 9};
  encode(&tmp, CU_TENSOR_MAP_DATA_TYPE_BFLOAT16, 3, (void*)x, gdim, gstr, boxp, estr, CU_TENSOR_MAP_INTERLEAVE_NONE,
         CU_TENSOR_MAP_SWIZZLE_NONE, CU_TENSOR_MAP_L2_PROMOTION_L2_128B, CU_TENSOR_MAP_FLOAT_OOB_FILL_NONE);
  prepack_kernel<<<48, dim3(192, 2), 0, cudaStreamPerThread>>>(wqkv, wo);
  cudaLaunchConfig_t cfg = {};
  cfg.gridDim = dim3(nsm); cfg.blockDim = dim3(384); cfg.dynamicSmemBytes = SMEM_BYTES; cfg.stream = cudaStreamPerThread;
  cudaLaunchAttribute at[1];
  at[0].id = cudaLaunchAttributeProgrammaticStreamSerialization;
  at[0].val.programmaticStreamSerializationAllowed = 1;
  cfg.attrs = at; cfg.numAttrs = 1;
  cudaLaunchKernelEx(&cfg, fused_kernel, tmx, tmp, ds, dw, (__nv_bfloat16*)d_out, 0);
}
```

```cpp
#include <cuda_runtime.h>
#include <cuda_bf16.h>
#include <cuda_fp16.h>
#include <cuda.h>
#include <stdint.h>

#define WHINT 0
#define CREGS "208"
#define PREGS "88"
#define NPRE 8
#define NMID 32
#define KA 4
#define KB 9
namespace {

constexpr int IMG = 511;
constexpr int CH = 192;
constexpr int NWX = 73;
constexpr int NWIN = NWX * NWX;
constexpr int SLICE = 18432;
constexpr int OFF_W = 0;
constexpr int KV_PITCH = 1792, KV_KOFF = 896, KV_BYTES = 6 * KV_PITCH;
constexpr int OFF_KV = 8 * SLICE;
constexpr int TILE_BYTES = 25 * 768;
constexpr int OFF_TILE = OFF_KV + 2 * KV_BYTES;
constexpr int XSLOT = 2304;
constexpr int OFF_ZERO = OFF_TILE + 2 * TILE_BYTES;
constexpr int OFF_X = OFF_ZERO + 768;
constexpr int OFF_BAR = OFF_X + 9 * XSLOT;
constexpr int BAR_WFULL = OFF_BAR;
constexpr int BAR_WEMPTY = OFF_BAR + 56;
constexpr int BAR_XFULL = OFF_BAR + 112;
constexpr int BAR_TFULL = OFF_BAR + 184;
constexpr int BAR_TEMPTY = OFF_BAR + 192;
constexpr int BAR_SFULL = OFF_BAR + 200;
constexpr int OFF_STAT = OFF_BAR + 208;
constexpr int OFF_TRACE = OFF_STAT + 800;
constexpr int SMEM_BYTES = OFF_TRACE;

__host__ __device__ constexpr int qkv_pos(int h, int s) { return (h == 0 ? 1 : 3 * h + 2) * SLICE + s * 4608; }
__host__ __device__ constexpr int wo_pos(int s) { return s < 6 ? 14 * SLICE + s * 6144 : s < 9 ? (s - 6) * 6144 : 4 * SLICE + (s - 9) * 6144; }
__host__ __device__ constexpr int stage_of(int p) { return p == 0 ? 5 : p < 4 ? 0 : p == 4 ? 6 : p < 8 ? 1 : p < 11 ? 2 : p < 14 ? 3 : 4; }
constexpr int SMEM_BASE = 1024;
struct Descs { uint64_t q[4][12]; uint64_t p[12]; uint64_t kv[2][8]; const uint8_t* src[16]; };

__device__ uint4 g_wpack[16 * SLICE / 16];
#define TR(id)
#define GTS(i)
template <int V> struct IC { static constexpr int v = V; };
typedef __nv_bfloat162 bf2;
__device__ __forceinline__ bf2 u2b(uint32_t u) { return *reinterpret_cast<bf2*>(&u); }
__device__ __forceinline__ uint32_t b2u(bf2 b) { return *reinterpret_cast<uint32_t*>(&b); }
__device__ __forceinline__ uint32_t pack2(float lo, float hi) {
  uint32_t r; asm("cvt.rn.bf16x2.f32 %0, %1, %2;" : "=r"(r) : "f"(hi), "f"(lo)); return r;
}
__device__ __forceinline__ uint32_t hadd(uint32_t a, uint32_t b) { return b2u(__hadd2_rn(u2b(a), u2b(b))); }
__device__ __forceinline__ uint32_t hmul(uint32_t a, uint32_t b) { return b2u(__hmul2_rn(u2b(a), u2b(b))); }
__device__ __forceinline__ uint32_t hfma(uint32_t a, uint32_t b, uint32_t c) { return b2u(__hfma2(u2b(a), u2b(b), u2b(c))); }
template <int HI> __device__ __forceinline__ bf2 bcast(uint32_t a) { return HI ? __high2bfloat162(u2b(a)) : __low2bfloat162(u2b(a)); }
template <int HI> __device__ __forceinline__ uint32_t hsub_b(uint32_t a, uint32_t s) { return b2u(__hsub2_rn(u2b(a), bcast<HI>(s))); }
__device__ __forceinline__ __half2 u2h(uint32_t u) { return *reinterpret_cast<__half2*>(&u); }
__device__ __forceinline__ uint32_t h2u(__half2 b) { return *reinterpret_cast<uint32_t*>(&b); }
__device__ __forceinline__ uint32_t packh(float lo, float hi) {
  uint32_t r; asm("cvt.rn.f16x2.f32 %0, %1, %2;" : "=r"(r) : "f"(hi), "f"(lo)); return r;
}
__device__ __forceinline__ uint32_t fmax2(uint32_t a, uint32_t b) { return h2u(__hmax2(u2h(a), u2h(b))); }
template <int HI> __device__ __forceinline__ __half2 hcast(uint32_t a) { return HI ? __high2half2(u2h(a)) : __low2half2(u2h(a)); }
template <int HI> __device__ __forceinline__ uint32_t fmul_b(uint32_t a, uint32_t s) { return h2u(__hmul2_rn(u2h(a), hcast<HI>(s))); }
template <int HI> __device__ __forceinline__ uint32_t fsub_b(uint32_t a, uint32_t s) { return h2u(__hsub2_rn(u2h(a), hcast<HI>(s))); }
__device__ __forceinline__ uint32_t fex2(uint32_t a) { uint32_t r; asm("ex2.approx.f16x2 %0, %1;" : "=r"(r) : "r"(a)); return r; }
__device__ __forceinline__ float lo2f(uint32_t a) { return __uint_as_float(a << 16); }
__device__ __forceinline__ float hi2f(uint32_t a) { return __uint_as_float(a & 0xffff0000u); }

__device__ __forceinline__ void mbar_init(uint32_t bar, uint32_t cnt) { asm volatile("mbarrier.init.shared::cta.b64 [%0], %1;" :: "r"(bar), "r"(cnt) : "memory"); }
__device__ __forceinline__ void mbar_arrive(uint32_t bar) { asm volatile("mbarrier.arrive.shared::cta.b64 _, [%0];" :: "r"(bar) : "memory"); }
__device__ __forceinline__ void mbar_expect(uint32_t bar, uint32_t bytes) { asm volatile("mbarrier.arrive.expect_tx.shared::cta.b64 _, [%0], %1;" :: "r"(bar), "r"(bytes) : "memory"); }
template <int HINT>
__device__ __forceinline__ bool mbar_try(uint32_t bar, uint32_t parity) {
  uint32_t ok;
  if (HINT) asm volatile("{\n.reg .pred p;\nmbarrier.try_wait.parity.shared::cta.b64 p, [%1], %2, %3;\nselp.u32 %0, 1, 0, p;\n}\n" : "=r"(ok) : "r"(bar), "r"(parity), "n"(HINT) : "memory");
  else asm volatile("{\n.reg .pred p;\nmbarrier.try_wait.parity.shared::cta.b64 p, [%1], %2;\nselp.u32 %0, 1, 0, p;\n}\n" : "=r"(ok) : "r"(bar), "r"(parity) : "memory");
  return ok != 0;
}
__device__ __forceinline__ void mbar_wait(uint32_t bar, uint32_t parity) {
  if (__builtin_expect(!mbar_try<0>(bar, parity), 0)) {
    uint32_t n = 0;
    while (!mbar_try<WHINT>(bar, parity)) { if (++n > (1u << 24)) __trap(); }
  }
}
__device__ __forceinline__ void wg_fence() { asm volatile("wgmma.fence.sync.aligned;" ::: "memory"); }
__device__ __forceinline__ void wg_commit() { asm volatile("wgmma.commit_group.sync.aligned;" ::: "memory"); }
template <int N> __device__ __forceinline__ void wg_wait() { asm volatile("wgmma.wait_group.sync.aligned %0;" :: "n"(N) : "memory"); }
__device__ __forceinline__ void bar_sync(int id) { asm volatile("bar.sync %0, 128;" :: "r"(id) : "memory"); }
__device__ __forceinline__ void turn_wait(int wg) { asm volatile("bar.sync %0, 256;" :: "r"(3 + wg) : "memory"); }
__device__ __forceinline__ void turn_pass(int wg) { asm volatile("bar.arrive %0, 256;" :: "r"(4 - wg) : "memory"); }
__device__ __forceinline__ void stsm4(uint32_t addr, uint32_t a, uint32_t b, uint32_t c, uint32_t d) {
  asm volatile("stmatrix.sync.aligned.m8n8.x4.shared.b16 [%0], {%1,%2,%3,%4};" :: "r"(addr), "r"(a), "r"(b), "r"(c), "r"(d) : "memory");
}
template <int N> __device__ __forceinline__ void keep(float (&d)[N]) {
#pragma unroll
  for (int i = 0; i < N; i++) asm volatile("" : "+f"(d[i]) :: "memory");
}
template <int N> __device__ __forceinline__ void keep(uint32_t (&d)[N]) {
#pragma unroll
  for (int i = 0; i < N; i++) asm volatile("" : "+r"(d[i]) :: "memory");
}
__host__ __device__ __forceinline__ uint64_t mkdesc(uint32_t addr, uint32_t lbo, uint32_t sbo) {
  return ((uint64_t)(sbo >> 4) << 32) | (uint64_t)(((lbo >> 4) << 16) | ((addr & 0x3FFFF) >> 4));
}

template <int SCALE_D>
__device__ __forceinline__ void wgmma_n144(uint32_t (&d)[36], uint32_t a0, uint32_t a1, uint32_t a2, uint32_t a3, uint64_t descB) {
  if (SCALE_D == 0)
  asm volatile("wgmma.mma_async.sync.aligned.m64n144k16.f16.f16.f16 "
    "{%0, %1, %2, %3, %4, %5, %6, %7, %8, %9, %10, %11, %12, %13, %14, %15, "
    "%16, %17, %18, %19, %20, %21, %22, %23, %24, %25, %26, %27, %28, %29, %30, %31, "
    "%32, %33, %34, %35}, "
    "{%36, %37, %38, %39}, %40, 0, 1, 1, 0;\n"
    : "=r"(d[0]), "=r"(d[1]), "=r"(d[2]), "=r"(d[3]), "=r"(d[4]), "=r"(d[5]), "=r"(d[6]), "=r"(d[7]),
      "=r"(d[8]), "=r"(d[9]), "=r"(d[10]), "=r"(d[11]), "=r"(d[12]), "=r"(d[13]), "=r"(d[14]), "=r"(d[15]),
      "=r"(d[16]), "=r"(d[17]), "=r"(d[18]), "=r"(d[19]), "=r"(d[20]), "=r"(d[21]), "=r"(d[22]), "=r"(d[23]),
      "=r"(d[24]), "=r"(d[25]), "=r"(d[26]), "=r"(d[27]), "=r"(d[28]), "=r"(d[29]), "=r"(d[30]), "=r"(d[31]),
      "=r"(d[32]), "=r"(d[33]), "=r"(d[34]), "=r"(d[35])
    : "r"(a0), "r"(a1), "r"(a2), "r"(a3), "l"(descB));
  else
  asm volatile("wgmma.mma_async.sync.aligned.m64n144k16.f16.f16.f16 "
    "{%0, %1, %2, %3, %4, %5, %6, %7, %8, %9, %10, %11, %12, %13, %14, %15, "
    "%16, %17, %18, %19, %20, %21, %22, %23, %24, %25, %26, %27, %28, %29, %30, %31, "
    "%32, %33, %34, %35}, "
    "{%36, %37, %38, %39}, %40, 1, 1, 1, 0;\n"
    : "+r"(d[0]), "+r"(d[1]), "+r"(d[2]), "+r"(d[3]), "+r"(d[4]), "+r"(d[5]), "+r"(d[6]), "+r"(d[7]),
      "+r"(d[8]), "+r"(d[9]), "+r"(d[10]), "+r"(d[11]), "+r"(d[12]), "+r"(d[13]), "+r"(d[14]), "+r"(d[15]),
      "+r"(d[16]), "+r"(d[17]), "+r"(d[18]), "+r"(d[19]), "+r"(d[20]), "+r"(d[21]), "+r"(d[22]), "+r"(d[23]),
      "+r"(d[24]), "+r"(d[25]), "+r"(d[26]), "+r"(d[27]), "+r"(d[28]), "+r"(d[29]), "+r"(d[30]), "+r"(d[31]),
      "+r"(d[32]), "+r"(d[33]), "+r"(d[34]), "+r"(d[35])
    : "r"(a0), "r"(a1), "r"(a2), "r"(a3), "l"(descB));
}

template <int SCALE_D>
__device__ __forceinline__ void wgmma_n192(uint32_t (&d)[48], uint32_t a0, uint32_t a1, uint32_t a2, uint32_t a3, uint64_t descB) {
  if (SCALE_D == 0)
  asm volatile("wgmma.mma_async.sync.aligned.m64n192k16.f16.f16.f16 "
    "{%0, %1, %2, %3, %4, %5, %6, %7, %8, %9, %10, %11, %12, %13, %14, %15, "
    "%16, %17, %18, %19, %20, %21, %22, %23, %24, %25, %26, %27, %28, %29, %30, %31, "
    "%32, %33, %34, %35, %36, %37, %38, %39, %40, %41, %42, %43, %44, %45, %46, %47}, "
    "{%48, %49, %50, %51}, %52, 0, 1, 1, 0;\n"
    : "=r"(d[0]), "=r"(d[1]), "=r"(d[2]), "=r"(d[3]), "=r"(d[4]), "=r"(d[5]), "=r"(d[6]), "=r"(d[7]),
      "=r"(d[8]), "=r"(d[9]), "=r"(d[10]), "=r"(d[11]), "=r"(d[12]), "=r"(d[13]), "=r"(d[14]), "=r"(d[15]),
      "=r"(d[16]), "=r"(d[17]), "=r"(d[18]), "=r"(d[19]), "=r"(d[20]), "=r"(d[21]), "=r"(d[22]), "=r"(d[23]),
      "=r"(d[24]), "=r"(d[25]), "=r"(d[26]), "=r"(d[27]), "=r"(d[28]), "=r"(d[29]), "=r"(d[30]), "=r"(d[31]),
      "=r"(d[32]), "=r"(d[33]), "=r"(d[34]), "=r"(d[35]), "=r"(d[36]), "=r"(d[37]), "=r"(d[38]), "=r"(d[39]),
      "=r"(d[40]), "=r"(d[41]), "=r"(d[42]), "=r"(d[43]), "=r"(d[44]), "=r"(d[45]), "=r"(d[46]), "=r"(d[47])
    : "r"(a0), "r"(a1), "r"(a2), "r"(a3), "l"(descB));
  else
  asm volatile("wgmma.mma_async.sync.aligned.m64n192k16.f16.f16.f16 "
    "{%0, %1, %2, %3, %4, %5, %6, %7, %8, %9, %10, %11, %12, %13, %14, %15, "
    "%16, %17, %18, %19, %20, %21, %22, %23, %24, %25, %26, %27, %28, %29, %30, %31, "
    "%32, %33, %34, %35, %36, %37, %38, %39, %40, %41, %42, %43, %44, %45, %46, %47}, "
    "{%48, %49, %50, %51}, %52, 1, 1, 1, 0;\n"
    : "+r"(d[0]), "+r"(d[1]), "+r"(d[2]), "+r"(d[3]), "+r"(d[4]), "+r"(d[5]), "+r"(d[6]), "+r"(d[7]),
      "+r"(d[8]), "+r"(d[9]), "+r"(d[10]), "+r"(d[11]), "+r"(d[12]), "+r"(d[13]), "+r"(d[14]), "+r"(d[15]),
      "+r"(d[16]), "+r"(d[17]), "+r"(d[18]), "+r"(d[19]), "+r"(d[20]), "+r"(d[21]), "+r"(d[22]), "+r"(d[23]),
      "+r"(d[24]), "+r"(d[25]), "+r"(d[26]), "+r"(d[27]), "+r"(d[28]), "+r"(d[29]), "+r"(d[30]), "+r"(d[31]),
      "+r"(d[32]), "+r"(d[33]), "+r"(d[34]), "+r"(d[35]), "+r"(d[36]), "+r"(d[37]), "+r"(d[38]), "+r"(d[39]),
      "+r"(d[40]), "+r"(d[41]), "+r"(d[42]), "+r"(d[43]), "+r"(d[44]), "+r"(d[45]), "+r"(d[46]), "+r"(d[47])
    : "r"(a0), "r"(a1), "r"(a2), "r"(a3), "l"(descB));
}

template <int SCALE_D>
__device__ __forceinline__ void wgmma_n56(uint32_t (&d)[14], uint32_t a0, uint32_t a1, uint32_t a2, uint32_t a3, uint64_t descB) {
  if (SCALE_D == 0)
  asm volatile("wgmma.mma_async.sync.aligned.m64n56k16.f16.f16.f16 "
    "{%0, %1, %2, %3, %4, %5, %6, %7, %8, %9, %10, %11, %12, %13}, "
    "{%14, %15, %16, %17}, %18, 0, 1, 1, 0;\n"
    : "=r"(d[0]), "=r"(d[1]), "=r"(d[2]), "=r"(d[3]), "=r"(d[4]), "=r"(d[5]), "=r"(d[6]), "=r"(d[7]),
      "=r"(d[8]), "=r"(d[9]), "=r"(d[10]), "=r"(d[11]), "=r"(d[12]), "=r"(d[13])
    : "r"(a0), "r"(a1), "r"(a2), "r"(a3), "l"(descB));
  else
  asm volatile("wgmma.mma_async.sync.aligned.m64n56k16.f16.f16.f16 "
    "{%0, %1, %2, %3, %4, %5, %6, %7, %8, %9, %10, %11, %12, %13}, "
    "{%14, %15, %16, %17}, %18, 1, 1, 1, 0;\n"
    : "+r"(d[0]), "+r"(d[1]), "+r"(d[2]), "+r"(d[3]), "+r"(d[4]), "+r"(d[5]), "+r"(d[6]), "+r"(d[7]),
      "+r"(d[8]), "+r"(d[9]), "+r"(d[10]), "+r"(d[11]), "+r"(d[12]), "+r"(d[13])
    : "r"(a0), "r"(a1), "r"(a2), "r"(a3), "l"(descB));
}

template <int SCALE_D>
__device__ __forceinline__ void wgmma_n48t(uint32_t (&d)[12], uint32_t a0, uint32_t a1, uint32_t a2, uint32_t a3, uint64_t descB) {
  if (SCALE_D == 0)
  asm volatile("wgmma.mma_async.sync.aligned.m64n48k16.f16.f16.f16 "
    "{%0, %1, %2, %3, %4, %5, %6, %7, %8, %9, %10, %11}, "
    "{%12, %13, %14, %15}, %16, 0, 1, 1, 1;\n"
    : "=r"(d[0]), "=r"(d[1]), "=r"(d[2]), "=r"(d[3]), "=r"(d[4]), "=r"(d[5]), "=r"(d[6]), "=r"(d[7]),
      "=r"(d[8]), "=r"(d[9]), "=r"(d[10]), "=r"(d[11])
    : "r"(a0), "r"(a1), "r"(a2), "r"(a3), "l"(descB));
  else
  asm volatile("wgmma.mma_async.sync.aligned.m64n48k16.f16.f16.f16 "
    "{%0, %1, %2, %3, %4, %5, %6, %7, %8, %9, %10, %11}, "
    "{%12, %13, %14, %15}, %16, 1, 1, 1, 1;\n"
    : "+r"(d[0]), "+r"(d[1]), "+r"(d[2]), "+r"(d[3]), "+r"(d[4]), "+r"(d[5]), "+r"(d[6]), "+r"(d[7]),
      "+r"(d[8]), "+r"(d[9]), "+r"(d[10]), "+r"(d[11])
    : "r"(a0), "r"(a1), "r"(a2), "r"(a3), "l"(descB));
}

__global__ void __launch_bounds__(384) prepack_kernel(const __nv_bfloat16* __restrict__ wqkv, const __nv_bfloat16* __restrict__ wo) {
  asm volatile("griddepcontrol.launch_dependents;");
  __half* dst = reinterpret_cast<__half*>(g_wpack);
  const int c = threadIdx.x, nb = blockIdx.x * 2 + threadIdx.y;
  if (nb < 72) {
    __shared__ float red2[2][6][8];
    float (*red)[8] = red2[threadIdx.y];
    const int h = nb / 18, j = nb % 18, part = j / 6;
    const int col = (part == 0 ? 192 : part == 1 ? 0 : 384) + h * 48 + (j % 6) * 8;
    uint4 raw = *reinterpret_cast<const uint4*>(wqkv + c * 576 + col);
    uint32_t u[4] = {raw.x, raw.y, raw.z, raw.w};
    float v[8];
#pragma unroll
    for (int i = 0; i < 4; i++) { v[2 * i] = lo2f(u[i]); v[2 * i + 1] = hi2f(u[i]); }
#pragma unroll
    for (int i = 0; i < 8; i++) {
      float s = v[i];
#pragma unroll
      for (int o = 16; o; o >>= 1) s += __shfl_xor_sync(~0u, s, o);
      if ((c & 31) == 0) red[c >> 5][i] = s;
    }
    __syncthreads();
    const int cc = c >> 5, q = (c >> 3) & 3, s1 = (c >> 2) & 1, hh = (c >> 1) & 1, e = c & 1;
    const int base = qkv_pos(h, 2 * cc + s1) / 2 + j * 128 + hh * 64 + 2 * q + e;
#pragma unroll
    for (int n = 0; n < 8; n++) {
      float m = (red[0][n] + red[1][n] + red[2][n] + red[3][n] + red[4][n] + red[5][n]) * (1.0f / 192.0f);
      dst[base + n * 8] = __float2half_rn((v[n] - m) * (part == 1 ? 0.14433756729740643f * 1.4426950408889634f : 1.0f));
    }
  } else {
    const int jb = nb - 72;
    const int s = c >> 4, hh = (c >> 3) & 1, kk = c & 7;
    const int base = wo_pos(s) / 2 + jb * 128 + hh * 64 + kk;
#pragma unroll
    for (int n = 0; n < 8; n++) {
      const int ch = 32 * (jb >> 2) + 8 * (n >> 1) + 2 * (jb & 3) + (n & 1);
      dst[base + n * 8] = __float2half_rn(__bfloat162float(wo[c * 192 + ch]));
    }
  }
}

__device__ __forceinline__ int window_of(int round, int nfull, int cta, int ncta, int wg) {
  if (round < nfull) return round * 2 * ncta + 2 * cta + wg;
  const int rem = NWIN - nfull * 2 * ncta;
  const int i = cta + wg * ncta;
  return i < rem ? nfull * 2 * ncta + i : -1;
}

template <int S0 = 0, int S1 = 12>
__device__ __forceinline__ void mma_qkv(uint32_t (&acc)[36], const uint32_t (&A)[48], const uint64_t* d) {
#pragma unroll
  for (int s = S0; s < S1; s++) {
    if (s == 0) wgmma_n144<0>(acc, A[4 * s], A[4 * s + 1], A[4 * s + 2], A[4 * s + 3], d[s]);
    else        wgmma_n144<1>(acc, A[4 * s], A[4 * s + 1], A[4 * s + 2], A[4 * s + 3], d[s]);
  }
  wg_commit();
}
__device__ __forceinline__ void mma_proj(uint32_t (&acc)[48], const uint32_t (&A)[12], const uint64_t* d) {
#pragma unroll
  for (int s = 0; s < 3; s++) wgmma_n192<1>(acc, A[4 * s], A[4 * s + 1], A[4 * s + 2], A[4 * s + 3], d[s]);
}
__device__ __forceinline__ void mma_s(uint32_t (&S)[14], const uint32_t (&Q)[12], const uint64_t* d) {
  wgmma_n56<0>(S, Q[0], Q[1], Q[2], Q[3], d[0]);
  wgmma_n56<1>(S, Q[4], Q[5], Q[6], Q[7], d[1]);
  wgmma_n56<1>(S, Q[8], Q[9], Q[10], Q[11], d[2]);
}
__device__ __forceinline__ void mma_pv(uint32_t (&O)[12], const uint32_t (&P)[12], const uint64_t* d) {
  wgmma_n48t<0>(O, P[0], P[1], P[2], P[3], d[0]);
  wgmma_n48t<1>(O, P[4], P[5], P[6], P[7], d[1]);
  wgmma_n48t<1>(O, P[8], P[9], P[10], P[11], d[2]);
}

#define PIN() asm volatile("pmevent 0;" ::: "memory")
template <int A, int B> __device__ __forceinline__ void hold(uint32_t* v) {
#pragma unroll
  for (int i = A; i < B; i++) asm volatile("" : "+r"(v[i]));
}
__device__ __forceinline__ void stsm12(const uint32_t* v, uint32_t addr) {
#pragma unroll
  for (int j = 0; j < 3; j++) stsm4(addr + 2 * j * KV_PITCH, v[4 * j], v[4 * j + 1], v[4 * j + 2], v[4 * j + 3]);
}
__device__ __forceinline__ void copy12(uint32_t (&Q)[12], const uint32_t* a, uint32_t z) {
#pragma unroll
  for (int i = 0; i < 12; i++) Q[i] = a[i] ^ z;
  hold<0, 12>(Q);
}
__device__ __forceinline__ void load_v48(uint32_t (&v)[6], uint32_t addr) {
  asm volatile("ldmatrix.sync.aligned.m8n8.x4.shared.b16 {%0,%1,%2,%3}, [%4];" : "=r"(v[0]), "=r"(v[1]), "=r"(v[2]), "=r"(v[3]) : "r"(addr) : "memory");
  asm volatile("ldmatrix.sync.aligned.m8n8.x2.shared.b16 {%0,%1}, [%2];" : "=r"(v[4]), "=r"(v[5]) : "r"(addr + 4 * KV_PITCH) : "memory");
}
__device__ __forceinline__ void finish_o(const uint32_t (&O)[12], const uint32_t (&v)[6], uint32_t p48, uint32_t inv, uint32_t (&Of)[12]) {
#pragma unroll
  for (int i = 0; i < 12; i++) {
    const uint32_t t = h2u(__hfma2(u2h(v[i >> 1]), (i & 1) ? hcast<1>(p48) : hcast<0>(p48), u2h(O[i])));
    Of[i] = (i & 1) ? fmul_b<1>(t, inv) : fmul_b<0>(t, inv);
  }
  hold<0, 12>(Of);
}
template <int A, int B, int CHUNK = 48>
__device__ __forceinline__ void normalise(uint32_t (&X)[48], const float (&rs)[2], const float (&sh)[2], int never) {
#pragma unroll
  for (int i = A; i < B; i++) {
    if ((i - A) % CHUNK == 0 && CHUNK < 48) PIN();
    asm volatile("" : "+r"(X[i]));
    const float lo = fmaf(lo2f(X[i]), rs[i & 1], sh[i & 1]), hi = fmaf(hi2f(X[i]), rs[i & 1], sh[i & 1]);
    asm volatile("{\n.reg .pred p;\nsetp.eq.s32 p, %3, 0;\n@p cvt.rn.f16x2.f32 %0, %1, %2;\n}\n" : "+r"(X[i]) : "f"(hi), "f"(lo), "r"(never));
  }
}
template <int CC>
__device__ __forceinline__ void store_out(const uint32_t (&Y)[48], const float (&sd)[2], const float (&mu)[2], uint8_t* o0, uint8_t* o1, uint32_t vmask) {
  uint32_t T[8];
#pragma unroll
  for (int i = 0; i < 8; i++) {
    const float2 f = __half22float2(u2h(Y[8 * CC + i]));
    T[i] = pack2(fmaf(f.x, sd[i & 1], mu[i & 1]), fmaf(f.y, sd[i & 1], mu[i & 1]));
  }
  asm volatile("{\n.reg .pred p;\nsetp.ne.u32 p, %5, 0;\n@p st.global.v4.u32 [%0], {%1,%2,%3,%4};\n}\n"
               :: "l"(o0 + CC * 64), "r"(T[0]), "r"(T[2]), "r"(T[4]), "r"(T[6]), "r"(vmask) : "memory");
  asm volatile("{\n.reg .pred p;\nsetp.lt.s32 p, %5, 0;\n@p st.global.v4.u32 [%0], {%1,%2,%3,%4};\n}\n"
               :: "l"(o1 + CC * 64), "r"(T[1]), "r"(T[3]), "r"(T[5]), "r"(T[7]), "r"(vmask) : "memory");
}
__device__ __forceinline__ void proxy_fence() { asm volatile("fence.proxy.async.shared::cta;" ::: "memory"); }
__device__ __forceinline__ uint32_t fadd2(uint32_t a, uint32_t b) { return h2u(__hadd2_rn(u2h(a), u2h(b))); }
__device__ __forceinline__ void row_max(const uint32_t (&S)[14], uint32_t& k48, uint32_t& mx) {
  k48 = __shfl_sync(~0u, __byte_perm(S[12], S[13], 0x5410), 0, 4);
  const uint32_t m0 = fmax2(fmax2(fmax2(S[0], S[2]), S[4]), fmax2(fmax2(S[6], S[8]), S[10]));
  const uint32_t m1 = fmax2(fmax2(fmax2(S[1], S[3]), S[5]), fmax2(fmax2(S[7], S[9]), S[11]));
  mx = fmax2(__byte_perm(m0, m1, 0x5410), __byte_perm(m0, m1, 0x7632));
  mx = fmax2(mx, __shfl_xor_sync(~0u, mx, 1));
  mx = fmax2(fmax2(mx, __shfl_xor_sync(~0u, mx, 2)), k48);
  hold<0, 1>(&mx);
}
__device__ __forceinline__ void row_exp(const uint32_t (&S)[14], uint32_t k48, uint32_t mx, uint32_t (&P)[12], uint32_t& p48, uint32_t& l) {
#pragma unroll
  for (int j = 0; j < 12; j++) P[j] = fex2((j & 1) ? fsub_b<1>(S[j], mx) : fsub_b<0>(S[j], mx));
  p48 = fex2(h2u(__hsub2_rn(u2h(k48), u2h(mx))));
  const uint32_t s0 = fadd2(fadd2(fadd2(P[0], P[2]), fadd2(P[4], P[6])), fadd2(P[8], P[10]));
  const uint32_t s1 = fadd2(fadd2(fadd2(P[1], P[3]), fadd2(P[5], P[7])), fadd2(P[9], P[11]));
  l = fadd2(__byte_perm(s0, s1, 0x5410), __byte_perm(s0, s1, 0x7632));
  hold<0, 12>(P); hold<0, 1>(&p48); hold<0, 1>(&l);
}
__device__ __forceinline__ uint32_t row_scale(uint32_t l, uint32_t p48, float rs0, float rs1) {
  l = fadd2(l, __shfl_xor_sync(~0u, l, 1));
  l = fadd2(fadd2(l, __shfl_xor_sync(~0u, l, 2)), p48);
  float i0, i1;
  asm("rcp.approx.ftz.f32 %0, %1;" : "=f"(i0) : "f"(__low2float(u2h(l))));
  asm("rcp.approx.ftz.f32 %0, %1;" : "=f"(i1) : "f"(__high2float(u2h(l))));
  uint32_t inv = packh(i0 * rs0, i1 * rs1);
  hold<0, 1>(&inv);
  return inv;
}
template <int S0, int S1>
__device__ __forceinline__ void load_x(uint32_t (&X)[48], uint32_t t0) {
#pragma unroll
  for (int s = S0; s < S1; s++)
    asm volatile("ld.shared.v4.u32 {%0,%1,%2,%3}, [%4];" : "=r"(X[4 * s]), "=r"(X[4 * s + 1]), "=r"(X[4 * s + 2]), "=r"(X[4 * s + 3])
                 : "r"(((s & 1) ? (t0 ^ 16) : t0) + (s >> 1) * 128) : "memory");
}

#define WDIV 1
template <int P, int CNT, int DIV = WDIV> __device__ __forceinline__ void load_slices(uint32_t sb, const Descs& ds) {
  constexpr int st = stage_of(P);
  constexpr bool first = P == 0 || stage_of(P - 1) != st;
  if (first)
    asm volatile("{\n.reg .pred p;\nelect.sync _|p, 0xffffffff;\n@p mbarrier.arrive.expect_tx.shared::cta.b64 _, [%0], %1;\n}\n"
                 :: "r"(sb + BAR_WFULL + 8 * st), "n"((st < 4 ? 3 : st == 4 ? 2 : 1) * SLICE / DIV) : "memory");
  asm volatile("{\n.reg .pred p;\nelect.sync _|p, 0xffffffff;\n"
               "@p cp.async.bulk.shared::cluster.global.mbarrier::complete_tx::bytes [%0], [%1], %2, [%3];\n}\n"
               :: "r"(sb + OFF_W + (P & 7) * SLICE), "l"(ds.src[P]), "n"(CNT * SLICE / DIV), "r"(sb + BAR_WFULL + 8 * st) : "memory");
}
__device__ __forceinline__ void warp_arrive(uint32_t bar) {
  asm volatile("{\n.reg .pred p;\nelect.sync _|p, 0xffffffff;\n@p mbarrier.arrive.shared::cta.b64 _, [%0];\n}\n" :: "r"(bar) : "memory");
}

__device__ __forceinline__ float4 ln_rows(const uint32_t (&X)[48]) {
  uint32_t sm[2];
#pragma unroll
  for (int a = 0; a < 2; a++) {
    uint32_t t[12];
#pragma unroll
    for (int i = 0; i < 12; i++) t[i] = hadd(X[4 * i + a], X[4 * i + 2 + a]);
#pragma unroll
    for (int i = 0; i < 6; i++) t[i] = hadd(t[i], t[i + 6]);
#pragma unroll
    for (int i = 0; i < 3; i++) t[i] = hadd(t[i], t[i + 3]);
    sm[a] = hadd(hadd(t[0], t[1]), t[2]);
  }
  uint32_t m = hadd(__byte_perm(sm[0], sm[1], 0x5410), __byte_perm(sm[0], sm[1], 0x7632));
  m = hadd(m, __shfl_xor_sync(~0u, m, 1));
  m = hadd(m, __shfl_xor_sync(~0u, m, 2));
  m = hmul(m, 0x3bab3babu);
  float var[2];
#pragma unroll
  for (int a = 0; a < 2; a++) {
    uint32_t t[4];
#pragma unroll
    for (int i = 0; i < 24; i++) {
      const uint32_t d = a ? hsub_b<1>(X[2 * i + 1], m) : hsub_b<0>(X[2 * i], m);
      t[i & 3] = i < 4 ? hmul(d, d) : hfma(d, d, t[i & 3]);
    }
    const uint32_t s = hadd(hadd(t[0], t[1]), hadd(t[2], t[3]));
    float v = lo2f(s) + hi2f(s);
    v += __shfl_xor_sync(~0u, v, 1);
    v += __shfl_xor_sync(~0u, v, 2);
    var[a] = fmaf(v, 1.0f / 192.0f, 1e-5f);
  }
  return make_float4(var[0], lo2f(m), var[1], hi2f(m));
}

__device__ __forceinline__ void stats_pass(uint32_t sb, int pass, int lane) {
  const int g = lane >> 2, q = lane & 3;
  const int tile = g >> 2;
  const int ps = min(pass * 4 + (g & 3), 24);
  uint32_t X[48];
  load_x<0, 12>(X, sb + OFF_TILE + tile * TILE_BYTES + ps * 768 + q * 32 + (ps & 1) * 16);
  const float4 st = ln_rows(X);
  asm volatile("st.shared.v4.f32 [%0], {%1,%2,%3,%4};" :: "r"(sb + OFF_STAT + tile * 400 + ps * 16), "f"(st.x), "f"(st.y), "f"(st.z), "f"(st.w) : "memory");
}

__global__ void __launch_bounds__(384, 1)
fused_kernel(const __grid_constant__ CUtensorMap tmx, const __grid_constant__ CUtensorMap tmp, const __grid_constant__ Descs ds, const __nv_bfloat16* __restrict__ dw, __nv_bfloat16* __restrict__ out, const int never) {
  extern __shared__ __align__(1024) uint8_t smem[];
  const uint32_t sb = (uint32_t)__cvta_generic_to_shared(smem);
  const int tid = threadIdx.x, lane = tid & 31;
  const int warp = __shfl_sync(0xffffffffu, tid >> 5, 0);
  const int cta = blockIdx.x, ncta = gridDim.x;
  const int nfull = NWIN / (2 * ncta);
  const int nrounds = nfull + ((NWIN - nfull * 2 * ncta) > cta ? 1 : 0);

  if (warp == 0) GTS(0);
  auto prefetch_round = [&](int r) {
#pragma unroll
    for (int k = 0; k < 2; k++) {
      const int w = window_of(r, nfull, cta, ncta, k);
      if (w >= 0) {
        const int a = w / NWX;
        asm volatile("{\n.reg .pred p;\nelect.sync _|p, 0xffffffff;\n@p cp.async.bulk.prefetch.tensor.3d.L2.global [%0, {0, %1, %2}];\n}\n"
                     :: "l"(reinterpret_cast<uint64_t>(&tmp)), "r"((w - a * NWX) * 7 - 1), "r"(a * 7 - 1) : "memory");
      }
    }
  };
  if (warp == 11) prefetch_round(0);
  if (warp == 10 && lane == 0) asm volatile("prefetch.tensormap [%0];" :: "l"(reinterpret_cast<uint64_t>(&tmx)) : "memory");
  if (tid == 0) {
    if ((sb & 0x3FFFF) != SMEM_BASE) __trap();
    for (int i = 0; i < 7; i++) { mbar_init(sb + BAR_WFULL + 8 * i, 1); mbar_init(sb + BAR_WEMPTY + 8 * i, 8); }
    for (int i = 0; i < 9; i++) mbar_init(sb + BAR_XFULL + 8 * i, 1);
    mbar_init(sb + BAR_TFULL, 3);
    mbar_init(sb + BAR_TEMPTY, 8);
    mbar_init(sb + BAR_SFULL, 3);
    asm volatile("fence.mbarrier_init.release.cluster;" ::: "memory");
  }
  if (tid >= 128 && tid < 320) {
    *reinterpret_cast<uint32_t*>(smem + OFF_ZERO + (tid - 128) * 4) = 0;
  }
  __syncthreads();

  if (warp >= 8) {
    asm volatile("setmaxnreg.dec.sync.aligned.u32 " PREGS ";");
    if (warp == 11) {
      asm volatile("griddepcontrol.wait;" ::: "memory");
      load_slices<1, 3, 1>(sb, ds); load_slices<0, 1, 1>(sb, ds); load_slices<4, 1, 1>(sb, ds); load_slices<5, 3, 1>(sb, ds);
      for (int r = 0; r < nrounds; r++) {
        const uint32_t par = r & 1;
        const bool next_round = r + 1 < nrounds;
        mbar_wait(sb + BAR_WEMPTY + 40, par); load_slices<8, 1>(sb, ds);
        mbar_wait(sb + BAR_WEMPTY, par);      load_slices<9, 2>(sb, ds); load_slices<11, 1>(sb, ds);
        mbar_wait(sb + BAR_WEMPTY + 48, par); load_slices<12, 1>(sb, ds);
        mbar_wait(sb + BAR_WEMPTY + 8, par);  load_slices<13, 1>(sb, ds); load_slices<14, 2>(sb, ds);
        mbar_wait(sb + BAR_WEMPTY + 16, par); load_slices<0, 1>(sb, ds); if (next_round) load_slices<1, 2>(sb, ds);
        mbar_wait(sb + BAR_WEMPTY + 24, par);
        if (next_round) load_slices<3, 1>(sb, ds);
        load_slices<4, 1>(sb, ds);
        if (next_round) {
          load_slices<5, 1>(sb, ds);
          mbar_wait(sb + BAR_WEMPTY + 32, par); load_slices<6, 2>(sb, ds);
        }
      }
    } else {
      const int cw = warp - 8;
      const int win = lane >> 4;
      const int ch0 = cw * 64 + (lane & 15) * 4;
      uint32_t wt[9][2];
#pragma unroll
      for (int t = 0; t < 9; t++) {
        uint2 v = *reinterpret_cast<const uint2*>(dw + t * CH + ch0);
        wt[t][0] = v.x; wt[t][1] = v.y;
      }
      const uint32_t xs = sb + OFF_X + cw * 3 * XSLOT;
      const uint32_t xld = xs + (lane >> 4) * 1152 + (lane & 15) * 8;
      const uint32_t xbar = sb + BAR_XFULL + cw * 24;
      const uint32_t st0 = sb + OFF_TILE + win * TILE_BYTES + ch0 * 4;
      const uint32_t st1 = sb + OFF_TILE + win * TILE_BYTES + ((ch0 * 4) ^ 16);
      const uint64_t tm = reinterpret_cast<uint64_t>(&tmx);
      int cx0, cy0, cx1, cy1;
      auto coords = [&](int r) {
        const int w0 = window_of(r, nfull, cta, ncta, 0);
        int w1 = window_of(r, nfull, cta, ncta, 1);
        if (w1 < 0) w1 = w0;
        const int a = w0 / NWX, b = w1 / NWX;
        cx0 = (w0 - a * NWX) * 7 - 1; cy0 = a * 7 - 1;
        cx1 = (w1 - b * NWX) * 7 - 1; cy1 = b * 7 - 1;
      };
      auto issue = [&](int slot, int dy) {
        asm volatile("{\n.reg .pred p;\nelect.sync _|p, 0xffffffff;\n"
                     "@p mbarrier.arrive.expect_tx.shared::cta.b64 _, [%2], %8;\n"
                     "@p cp.async.bulk.tensor.3d.shared::cluster.global.mbarrier::complete_tx::bytes [%0], [%1, {%3, %4, %5}], [%2];\n"
                     "@p cp.async.bulk.tensor.3d.shared::cluster.global.mbarrier::complete_tx::bytes [%0 + 1152], [%1, {%3, %6, %7}], [%2];\n}\n"
                     :: "r"(xs + slot * XSLOT), "l"(tm), "r"(xbar + slot * 8), "r"(cw * 64), "r"(cx0), "r"(cy0 + dy), "r"(cx1), "r"(cy1 + dy), "n"(XSLOT) : "memory");
      };
      coords(0);
      issue(0, 0); issue(1, 1); issue(2, 2);
      for (int r = 0; r < nrounds; r++) {
        const bool more = r + 1 < nrounds;
        uint32_t accA[7][2], accB[7][2], ctr[7][2], held[2];
#pragma unroll
        for (int i = 0; i < 9; i++) {
          mbar_wait(xbar + (i % 3) * 8, (r + i / 3) & 1);
          if (i == 0 && r == 0 && cw == 0) GTS(7);
          if (i == 7 && more) coords(r + 1);
          if (i == 0) { if (r > 0) issue(2, 2); }
          else if (i < 7) issue((i + 2) % 3, i + 2);
          else if (more) issue((i + 2) % 3, i - 7);
          if (i == 2 && r > 0) mbar_wait(sb + BAR_TEMPTY, (r - 1) & 1);
          if (i == 2 && cw == 0 && r == 2) GTS(1);
          if (i == 2 && cw == 0 && r == 3) GTS(3);
          if (i == 2) { TR(0); }
          uint32_t cur[9][2];
#pragma unroll
          for (int p = 0; p < 5; p++)
            asm volatile("ld.shared.v2.u32 {%0,%1}, [%2];" : "=r"(cur[p][0]), "=r"(cur[p][1]) : "r"(xld + (i % 3) * XSLOT + p * 128));
#pragma unroll
          for (int j = 0; j < 7; j++) {
            if (j >= 1 && j + 4 < 9)
              asm volatile("ld.shared.v2.u32 {%0,%1}, [%2];" : "=r"(cur[j + 4][0]), "=r"(cur[j + 4][1]) : "r"(xld + (i % 3) * XSLOT + (j + 4) * 128));
            if (i >= 2) {
              uint32_t o[2];
#pragma unroll
              for (int e = 0; e < 2; e++) {
                uint32_t a = hfma(cur[j][e], wt[6][e], accA[j][e]);
                a = hfma(cur[j + 1][e], wt[7][e], a);
                a = hfma(cur[j + 2][e], wt[8][e], a);
                o[e] = hadd(ctr[j][e], a);
              }
              const int tok = (i - 2) * 7 + j, ps = tok >> 1;
              if (!(tok & 1)) { held[0] = o[0]; held[1] = o[1]; }
              if (tok == 48) o[0] = o[1] = 0;
              if ((tok & 1) || tok == 48)
                asm volatile("st.shared.v4.u32 [%0], {%1,%2,%3,%4};" :: "r"(((ps & 1) ? st1 : st0) + ps * 768), "r"(held[0]), "r"(o[0]), "r"(held[1]), "r"(o[1]) : "memory");
            }
#pragma unroll
            for (int e = 0; e < 2; e++) {
              if (i >= 1 && i <= 7) {
                uint32_t a = hfma(cur[j][e], wt[3][e], accB[j][e]);
                a = hfma(cur[j + 1][e], wt[4][e], a);
                accA[j][e] = hfma(cur[j + 2][e], wt[5][e], a);
                ctr[j][e] = cur[j + 1][e];
              }
              if (i <= 6) {
                uint32_t a = hmul(cur[j][e], wt[0][e]);
                a = hfma(cur[j + 1][e], wt[1][e], a);
                accB[j][e] = hfma(cur[j + 2][e], wt[2][e], a);
              }
            }
          }
        }
        __syncwarp();
        if (lane == 0) mbar_arrive(sb + BAR_TFULL);
        TR(1);
        if (r > 0) {
          mbar_wait(sb + BAR_TFULL, r & 1);
#pragma unroll 1
          for (int pass = cw; pass < 7; pass += 3) stats_pass(sb, pass, lane);
        }
        __syncwarp();
        if (lane == 0) mbar_arrive(sb + BAR_SFULL);
        TR(2);
      }
    }
  } else {
    asm volatile("setmaxnreg.inc.sync.aligned.u32 " CREGS ";");
    const int wg = warp >> 2, w4 = warp & 3, g = lane >> 2, q = lane & 3;
    const int row0 = w4 * 16 + g, row1 = row0 + 8;
    const int ps = min(w4 * 8 + g, 24);
    const int tok0 = 2 * ps, tok1 = min(2 * ps + 1, 48);
    const uint32_t kv = sb + OFF_KV + wg * KV_BYTES;
    const int srow = w4 * 16 + (lane & 15);
    const uint32_t vst = kv + (lane >> 4) * KV_PITCH + (srow < 56 ? srow : min(srow - 7, 55)) * 16;
    uint32_t misc = ((uint32_t)((tok1 / 7) * IMG + tok1 % 7) << 20) | ((uint32_t)((tok0 / 7) * IMG + tok0 % 7) << 8) | (ps * 4 + q);
    const uint32_t v48 = kv + (lane >> 3) * KV_PITCH + 48 * 16;
    const uint32_t vmask = (row0 < 49 ? 0xffffu : 0u) | (row1 < 49 ? 0xffff0000u : 0u);

    const uint32_t tx = sb + q * 32 + (row0 < 49 ? OFF_TILE + wg * TILE_BYTES + ps * 768 + (ps & 1) * 16 : OFF_ZERO + 16);
    const int myrounds = window_of(nrounds - 1, nfull, cta, ncta, wg) < 0 ? nrounds - 1 : nrounds;

    if (never == 2) return;
    uint32_t H[48], Y[48];
    float rs[2], sh[2], nrs[2], nsh[2];
    auto set_stat = [&](const float4& st) {
      asm("rsqrt.approx.ftz.f32 %0, %1;" : "=f"(nrs[0]) : "f"(st.x));
      asm("rsqrt.approx.ftz.f32 %0, %1;" : "=f"(nrs[1]) : "f"(st.z));
      if (!(vmask & 1)) nrs[0] = 0.f;
      if ((int)vmask >= 0) nrs[1] = 0.f;
      nsh[0] = -st.y * nrs[0]; nsh[1] = -st.w * nrs[1];
    };
    auto load_stat = [&]() {
      float4 st;
      asm volatile("ld.shared.v4.f32 {%0,%1,%2,%3}, [%4];" : "=f"(st.x), "=f"(st.y), "=f"(st.z), "=f"(st.w)
                   : "r"(sb + OFF_STAT + wg * 400 + (misc & 0xfc) * 4) : "memory");
      set_stat(st);
    };
    const uint64_t* dkv = ds.kv[wg];
    uint32_t P[12], Ofc[12], p48 = 0x3c003c00u, lsum = 0;
#pragma unroll
    for (int i = 0; i < 48; i++) Y[i] = 0;
#pragma unroll
    for (int i = 0; i < 12; i++) P[i] = Ofc[i] = 0;
    rs[0] = rs[1] = 1.f; sh[0] = sh[1] = 0.f;
    mbar_wait(sb + BAR_TFULL, 0);
    if (warp == 0) GTS(4);
    load_x<0, 12>(H, tx);
    warp_arrive(sb + BAR_TEMPTY);
    set_stat(ln_rows(H));
    normalise<0, NPRE, 8>(H, nrs, nsh, never);
    if (wg == 1) turn_pass(1);

    uint8_t *o0, *o1;
    float sd[2], mu[2];
    uint32_t omask;
    auto out_setup = [&](int r) {
      omask = r >= 0 ? vmask : 0u;
      const int w = window_of(r, nfull, cta, ncta, wg);
      const int wy = w / NWX, wx = w - wy * NWX;
      asm volatile("" : "+r"(misc));
      const uint32_t wb = (uint32_t)(wy * 7 * IMG + wx * 7) * 384u + (misc & 3) * 16;
      o0 = reinterpret_cast<uint8_t*>(out) + (wb + ((misc >> 8) & 0xfff) * 384u);
      o1 = reinterpret_cast<uint8_t*>(out) + (wb + (misc >> 20) * 384u);
      asm("rcp.approx.ftz.f32 %0, %1;" : "=f"(sd[0]) : "f"(rs[0]));
      asm("rcp.approx.ftz.f32 %0, %1;" : "=f"(sd[1]) : "f"(rs[1]));
      mu[0] = -sh[0] * sd[0]; mu[1] = -sh[1] * sd[1];
    };
#define OUT(c) store_out<c>(Y, sd, mu, o0, o1, omask)
    auto release = [&](int stage) { warp_arrive(sb + BAR_WEMPTY + 8 * stage); };

    for (int r = 0;; r++) {
      const uint32_t par = r & 1;
      uint32_t acc[36], S[14], O[12], Q[12], V[12], Ofa[12], Ofb[12], vr[6], inv, k48, mx;
      if (r == myrounds) {
        const bool idle = r < nrounds;
        mbar_wait(sb + BAR_WFULL + 40, par);
        turn_wait(wg);
        wg_fence(); mma_pv(O, P, dkv + 4); mma_proj(Y, Ofc, ds.p + 6); wg_commit();
        turn_pass(wg);
        load_v48(vr, v48);
        inv = row_scale(lsum, p48, rs[0], rs[1]);
        wg_wait<0>(); keep(O); keep(Y);
        finish_o(O, vr, p48, inv, Ofa);
        if (idle) { release(5); release(0); release(1); release(2); release(3); }
        mbar_wait(sb + BAR_WFULL + 48, par);
        turn_wait(wg);
        wg_fence(); mma_proj(Y, Ofa, ds.p + 9); wg_commit();
        if (wg == 0 || idle) turn_pass(wg);
        wg_wait<0>(); keep(Y);
        if (idle) { release(6); turn_wait(wg); turn_pass(wg); }
        out_setup(r - 1);
        OUT(0); PIN(); OUT(1); PIN(); OUT(2); PIN(); OUT(3); PIN(); OUT(4); PIN(); OUT(5);
        if (idle) {
          turn_wait(wg); turn_pass(wg);
          turn_wait(wg); turn_pass(wg);
          turn_wait(wg); turn_pass(wg);
          turn_wait(wg);
        }
        if (w4 == 0) GTS(5 + wg);
        break;
      }
      mbar_wait(sb + BAR_WFULL + 40, par);
      mbar_wait(sb + BAR_WFULL, par);
      TR(0);
      turn_wait(wg);
      TR(1);
      wg_fence(); mma_pv(O, P, dkv + 4); mma_proj(Y, Ofc, ds.p + 6); wg_commit(); mma_qkv<0, NPRE / 4>(acc, H, ds.q[0]);
      normalise<NPRE, NMID, 8>(H, nrs, nsh, never); PIN();
      wg_fence(); mma_qkv<NPRE / 4, NMID / 4>(acc, H, ds.q[0]);
      normalise<NMID, 48, 8>(H, nrs, nsh, never); PIN();
      wg_fence(); mma_qkv<NMID / 4, 12>(acc, H, ds.q[0]);
      turn_pass(wg);
      TR(2);
      load_v48(vr, v48);
      inv = row_scale(lsum, p48, rs[0], rs[1]);
      PIN();
      wg_wait<3>(); keep(O); keep(Y);
      release(5);
      bar_sync(1 + wg);
      finish_o(O, vr, p48, inv, Ofa);
      PIN();
      TR(3);
      wg_wait<0>(); keep(acc);
      TR(4);
      release(0);
      stsm12(acc, vst + KV_KOFF); stsm12(acc + 24, vst);
      copy12(Q, acc + 12, never); PIN();
      proxy_fence();
      mbar_wait(sb + BAR_WFULL + 48, par);
      mbar_wait(sb + BAR_WFULL + 8, par);
      TR(5);
      turn_wait(wg);
      TR(6);
      wg_fence(); mma_proj(Y, Ofa, ds.p + 9); wg_commit(); mma_s(S, Q, dkv); mma_qkv<0, 2>(acc, H, ds.q[1]);
      out_setup(r - 1);
      rs[0] = nrs[0]; rs[1] = nrs[1]; sh[0] = nsh[0]; sh[1] = nsh[1];
      PIN();
      wg_wait<1>(); keep(Y);
      release(6);
      wg_fence(); mma_qkv<2, 6>(acc, H, ds.q[1]);
      PIN();
      OUT(0);
      PIN();
      wg_wait<1>(); keep(S);
      wg_fence(); mma_qkv<6, 9>(acc, H, ds.q[1]);
      PIN();
      row_max(S, k48, mx);
      OUT(1);
      PIN();
      wg_fence(); mma_qkv<9, 12>(acc, H, ds.q[1]);
      turn_pass(wg);
      PIN();
      OUT(2); PIN();
      OUT(3); PIN();
      row_exp(S, k48, mx, P, p48, lsum);
      PIN();
      TR(7);
      wg_wait<0>(); keep(acc);
      TR(8);
      release(1);
      bar_sync(1 + wg);
      stsm12(acc, vst + KV_KOFF);
      copy12(Q, acc + 12, never); copy12(V, acc + 24, never); PIN();
      proxy_fence();
#define TURN(ID, OF, G1, G2, G3, X1)                                                       \
      TR(ID + 1);                                                                       \
      turn_wait(wg);                                                                    \
      wg_fence(); mma_pv(O, P, dkv + 4); mma_s(S, Q, dkv); wg_commit(); G1;             \
      PIN();                                                                            \
      TR(ID + 2);                                                                       \
      load_v48(vr, v48);                                                                \
      inv = row_scale(lsum, p48, rs[0], rs[1]);                                         \
      X1;                                                                               \
      PIN();                                                                            \
      wg_wait<1>(); keep(S); keep(O);                                                   \
      bar_sync(1 + wg);                                    \
      wg_fence(); G2;                                                                   \
      PIN();                                                                            \
      stsm12(V, vst);                                                                   \
      finish_o(O, vr, p48, inv, OF);                                                    \
      row_max(S, k48, mx);                                                              \
      PIN();                                                                            \
      wg_fence(); G3;                                                                   \
      turn_pass(wg);                                                                    \
      PIN();                                                                            \
      TR(ID + 3);
#define NEXT_HEAD(ID, HD)                                                               \
      row_exp(S, k48, mx, P, p48, lsum);                                                \
      PIN();                                                                            \
      TR(ID + 4);                                                                       \
      wg_wait<0>(); keep(acc);                                                          \
      release(HD);                                                                      \
      stsm12(acc, vst + KV_KOFF);                                                       \
      copy12(Q, acc + 12, never); copy12(V, acc + 24, never); PIN();
      mbar_wait(sb + BAR_WFULL + 16, par);
      TURN(8, Ofa, (mma_qkv<0, KA>(acc, H, ds.q[2])), (mma_qkv<KA, KB>(acc, H, ds.q[2])), (mma_qkv<KB, 12>(acc, H, ds.q[2])), OUT(4))
      OUT(5); PIN();
      NEXT_HEAD(8, 2)
      proxy_fence();
      mbar_wait(sb + BAR_WFULL + 24, par);
      TURN(12, Ofb, (mma_qkv<0, KA>(acc, H, ds.q[3])), (mma_qkv<KA, KB>(acc, H, ds.q[3])), (mma_qkv<KB, 12>(acc, H, ds.q[3])), )
      NEXT_HEAD(12, 3)
      const uint32_t rho = 0x3c003c00u + never;
#pragma unroll
      for (int i = 0; i < 48; i++) Y[i] = (i & 1) ? fmul_b<1>(H[i], rho) : fmul_b<0>(H[i], rho);
      hold<0, 48>(Y); PIN();
      proxy_fence();
      mbar_wait(sb + BAR_WFULL + 32, par);
      TR(17);
      turn_wait(wg);
      wg_fence(); mma_pv(O, P, dkv + 4); mma_s(S, Q, dkv); wg_commit(); mma_proj(Y, Ofa, ds.p); mma_proj(Y, Ofb, ds.p + 3); wg_commit();
      turn_pass(wg);
      PIN();
      TR(18);
      load_v48(vr, v48);
      inv = row_scale(lsum, p48, rs[0], rs[1]);
      if (r + 1 < myrounds) mbar_wait(sb + BAR_SFULL, par ^ 1);
      load_stat();
      load_x<0, 4>(H, tx);
      wg_wait<1>(); keep(S); keep(O);
      bar_sync(1 + wg);
      PIN();
      TR(19);
      row_max(S, k48, mx);
      finish_o(O, vr, p48, inv, Ofc);
      stsm12(V, vst);
      PIN();
      load_x<4, 8>(H, tx);
      row_exp(S, k48, mx, P, p48, lsum);
      PIN();
      load_x<8, 12>(H, tx);
      warp_arrive(sb + BAR_TEMPTY);
      TR(20);
      wg_wait<0>(); keep(Y);
      release(4);
      proxy_fence();
      normalise<0, NPRE>(H, nrs, nsh, never);
      TR(21);
#undef TURN
#undef NEXT_HEAD
    }
  }
}

typedef CUresult (*EncodeFn)(CUtensorMap*, CUtensorMapDataType, cuuint32_t, void*, const cuuint64_t*, const cuuint64_t*,
                             const cuuint32_t*, const cuuint32_t*, CUtensorMapInterleave, CUtensorMapSwizzle,
                             CUtensorMapL2promotion, CUtensorMapFloatOOBfill);

}

extern "C" void kernel_launch(void* const* d_in, const int* in_sizes, int n_in, void* d_out, int out_size) {
  const __nv_bfloat16* x = (const __nv_bfloat16*)d_in[0];
  const __nv_bfloat16* dw = (const __nv_bfloat16*)d_in[1];
  const __nv_bfloat16* wqkv = (const __nv_bfloat16*)d_in[2];
  const __nv_bfloat16* wo = (const __nv_bfloat16*)d_in[3];
  static EncodeFn encode = nullptr;
  static int nsm = 0;
  static void* wpack = nullptr;
  if (!encode) {
    void* fn = nullptr;
    cudaDriverEntryPointQueryResult qr;
    cudaGetDriverEntryPoint("cuTensorMapEncodeTiled", &fn, cudaEnableDefault, &qr);
    encode = (EncodeFn)fn;
    int dev = 0;
    cudaGetDevice(&dev);
    cudaDeviceGetAttribute(&nsm, cudaDevAttrMultiProcessorCount, dev);
    cudaGetSymbolAddress(&wpack, g_wpack);
    cudaFuncSetAttribute(fused_kernel, cudaFuncAttributeMaxDynamicSharedMemorySize, SMEM_BYTES);
  }
  CUtensorMap tmx;
  cuuint64_t gdim[3] = {CH, IMG, IMG};
  cuuint64_t gstr[2] = {CH * 2, (cuuint64_t)CH * 2 * IMG};
  cuuint32_t box[3] = {64, 9, 1};
  cuuint32_t estr[3] = {1, 1, 1};
  encode(&tmx, CU_TENSOR_MAP_DATA_TYPE_BFLOAT16, 3, (void*)x, gdim, gstr, box, estr, CU_TENSOR_MAP_INTERLEAVE_NONE,
         CU_TENSOR_MAP_SWIZZLE_NONE, CU_TENSOR_MAP_L2_PROMOTION_L2_128B, CU_TENSOR_MAP_FLOAT_OOB_FILL_NONE);
  Descs ds;
  for (int i = 0; i < 12; i++) {
    for (int h = 0; h < 4; h++) ds.q[h][i] = mkdesc(SMEM_BASE + OFF_W + qkv_pos(h, i) % (8 * SLICE), 128, 256);
    ds.p[i] = mkdesc(SMEM_BASE + OFF_W + wo_pos(i) % (8 * SLICE), 128, 256);
  }
  for (int i = 0; i < 16; i++) ds.src[i] = (const uint8_t*)wpack + i * SLICE;
  for (int g = 0; g < 2; g++)
    for (int i = 0; i < 4; i++) {
      ds.kv[g][i] = mkdesc(SMEM_BASE + OFF_KV + g * KV_BYTES + KV_KOFF + 2 * i * KV_PITCH, KV_PITCH, 128);
      ds.kv[g][4 + i] = mkdesc(SMEM_BASE + OFF_KV + g * KV_BYTES + 256 * i, 128, KV_PITCH);
    }
  CUtensorMap tmp;
  cuuint32_t boxp[3] = {CH, 9, 9};
  encode(&tmp, CU_TENSOR_MAP_DATA_TYPE_BFLOAT16, 3, (void*)x, gdim, gstr, boxp, estr, CU_TENSOR_MAP_INTERLEAVE_NONE,
         CU_TENSOR_MAP_SWIZZLE_NONE, CU_TENSOR_MAP_L2_PROMOTION_L2_128B, CU_TENSOR_MAP_FLOAT_OOB_FILL_NONE);
  prepack_kernel<<<48, dim3(192, 2), 0, cudaStreamPerThread>>>(wqkv, wo);
  cudaLaunchConfig_t cfg = {};
  cfg.gridDim = dim3(nsm); cfg.blockDim = dim3(384); cfg.dynamicSmemBytes = SMEM_BYTES; cfg.stream = cudaStreamPerThread;
  cudaLaunchAttribute at[1];
  at[0].id = cudaLaunchAttributeProgrammaticStreamSerialization;
  at[0].val.programmaticStreamSerializationAllowed = 1;
  cfg.attrs = at; cfg.numAttrs = 1;
  cudaLaunchKernelEx(&cfg, fused_kernel, tmx, tmp, ds, dw, (__nv_bfloat16*)d_out, 0);
}
```

```cpp
#include <cuda_runtime.h>
#include <cuda_bf16.h>
#include <cuda_fp16.h>
#include <cuda.h>
#include <stdint.h>

#define WHINT 0
#define CREGS "208"
#define PREGS "88"
#define NPRE 8
#define NMID 32
#define KA 4
#define KB 9
namespace {

constexpr int IMG = 511;
constexpr int CH = 192;
constexpr int NWX = 73;
constexpr int NWIN = NWX * NWX;
constexpr int SLICE = 18432;
constexpr int OFF_W = 0;
constexpr int KV_PITCH = 1792, KV_KOFF = 896, KV_BYTES = 6 * KV_PITCH;
constexpr int OFF_KV = 8 * SLICE;
constexpr int TILE_BYTES = 25 * 768;
constexpr int OFF_TILE = OFF_KV + 2 * KV_BYTES;
constexpr int XSLOT = 2304;
constexpr int OFF_ZERO = OFF_TILE + 2 * TILE_BYTES;
constexpr int OFF_X = OFF_ZERO + 768;
constexpr int OFF_BAR = OFF_X + 9 * XSLOT;
constexpr int BAR_WFULL = OFF_BAR;
constexpr int BAR_WEMPTY = OFF_BAR + 56;
constexpr int BAR_XFULL = OFF_BAR + 112;
constexpr int BAR_TFULL = OFF_BAR + 184;
constexpr int BAR_TEMPTY = OFF_BAR + 192;
constexpr int OFF_TRACE = OFF_BAR + 208;
constexpr int SMEM_BYTES = OFF_TRACE;

__host__ __device__ constexpr int qkv_pos(int h, int s) { return (h == 0 ? 1 : 3 * h + 2) * SLICE + s * 4608; }
__host__ __device__ constexpr int wo_pos(int s) { return s < 6 ? 14 * SLICE + s * 6144 : s < 9 ? (s - 6) * 6144 : 4 * SLICE + (s - 9) * 6144; }
__host__ __device__ constexpr int stage_of(int p) { return p == 0 ? 5 : p < 4 ? 0 : p == 4 ? 6 : p < 8 ? 1 : p < 11 ? 2 : p < 14 ? 3 : 4; }
constexpr int SMEM_BASE = 1024;
struct Descs { uint64_t q[4][12]; uint64_t p[12]; uint64_t kv[2][8]; const uint8_t* src[16]; };

__device__ uint4 g_wpack[16 * SLICE / 16];
#define TR(id)
#define GTS(i)
template <int V> struct IC { static constexpr int v = V; };
typedef __nv_bfloat162 bf2;
__device__ __forceinline__ bf2 u2b(uint32_t u) { return *reinterpret_cast<bf2*>(&u); }
__device__ __forceinline__ uint32_t b2u(bf2 b) { return *reinterpret_cast<uint32_t*>(&b); }
__device__ __forceinline__ uint32_t pack2(float lo, float hi) {
  uint32_t r; asm("cvt.rn.bf16x2.f32 %0, %1, %2;" : "=r"(r) : "f"(hi), "f"(lo)); return r;
}
__device__ __forceinline__ uint32_t hadd(uint32_t a, uint32_t b) { return b2u(__hadd2_rn(u2b(a), u2b(b))); }
__device__ __forceinline__ uint32_t hmul(uint32_t a, uint32_t b) { return b2u(__hmul2_rn(u2b(a), u2b(b))); }
__device__ __forceinline__ uint32_t hfma(uint32_t a, uint32_t b, uint32_t c) { return b2u(__hfma2(u2b(a), u2b(b), u2b(c))); }
__device__ __forceinline__ __half2 u2h(uint32_t u) { return *reinterpret_cast<__half2*>(&u); }
__device__ __forceinline__ uint32_t h2u(__half2 b) { return *reinterpret_cast<uint32_t*>(&b); }
__device__ __forceinline__ uint32_t packh(float lo, float hi) {
  uint32_t r; asm("cvt.rn.f16x2.f32 %0, %1, %2;" : "=r"(r) : "f"(hi), "f"(lo)); return r;
}
__device__ __forceinline__ uint32_t fmax2(uint32_t a, uint32_t b) { return h2u(__hmax2(u2h(a), u2h(b))); }
template <int HI> __device__ __forceinline__ __half2 hcast(uint32_t a) { return HI ? __high2half2(u2h(a)) : __low2half2(u2h(a)); }
template <int HI> __device__ __forceinline__ uint32_t fmul_b(uint32_t a, uint32_t s) { return h2u(__hmul2_rn(u2h(a), hcast<HI>(s))); }
template <int HI> __device__ __forceinline__ uint32_t fsub_b(uint32_t a, uint32_t s) { return h2u(__hsub2_rn(u2h(a), hcast<HI>(s))); }
__device__ __forceinline__ uint32_t fex2(uint32_t a) { uint32_t r; asm("ex2.approx.f16x2 %0, %1;" : "=r"(r) : "r"(a)); return r; }
__device__ __forceinline__ float lo2f(uint32_t a) { return __uint_as_float(a << 16); }
__device__ __forceinline__ float hi2f(uint32_t a) { return __uint_as_float(a & 0xffff0000u); }

__device__ __forceinline__ void mbar_init(uint32_t bar, uint32_t cnt) { asm volatile("mbarrier.init.shared::cta.b64 [%0], %1;" :: "r"(bar), "r"(cnt) : "memory"); }
__device__ __forceinline__ void mbar_arrive(uint32_t bar) { asm volatile("mbarrier.arrive.shared::cta.b64 _, [%0];" :: "r"(bar) : "memory"); }
__device__ __forceinline__ void mbar_expect(uint32_t bar, uint32_t bytes) { asm volatile("mbarrier.arrive.expect_tx.shared::cta.b64 _, [%0], %1;" :: "r"(bar), "r"(bytes) : "memory"); }
template <int HINT>
__device__ __forceinline__ bool mbar_try(uint32_t bar, uint32_t parity) {
  uint32_t ok;
  if (HINT) asm volatile("{\n.reg .pred p;\nmbarrier.try_wait.parity.shared::cta.b64 p, [%1], %2, %3;\nselp.u32 %0, 1, 0, p;\n}\n" : "=r"(ok) : "r"(bar), "r"(parity), "n"(HINT) : "memory");
  else asm volatile("{\n.reg .pred p;\nmbarrier.try_wait.parity.shared::cta.b64 p, [%1], %2;\nselp.u32 %0, 1, 0, p;\n}\n" : "=r"(ok) : "r"(bar), "r"(parity) : "memory");
  return ok != 0;
}
__device__ __forceinline__ void mbar_wait(uint32_t bar, uint32_t parity) {
  if (__builtin_expect(!mbar_try<0>(bar, parity), 0)) {
    uint32_t n = 0;
    while (!mbar_try<WHINT>(bar, parity)) { if (++n > (1u << 24)) __trap(); }
  }
}
__device__ __forceinline__ void wg_fence() { asm volatile("wgmma.fence.sync.aligned;" ::: "memory"); }
__device__ __forceinline__ void wg_commit() { asm volatile("wgmma.commit_group.sync.aligned;" ::: "memory"); }
template <int N> __device__ __forceinline__ void wg_wait() { asm volatile("wgmma.wait_group.sync.aligned %0;" :: "n"(N) : "memory"); }
__device__ __forceinline__ void bar_sync(int id) { asm volatile("bar.sync %0, 128;" :: "r"(id) : "memory"); }
__device__ __forceinline__ void turn_wait(int wg) { asm volatile("bar.sync %0, 256;" :: "r"(3 + wg) : "memory"); }
__device__ __forceinline__ void turn_pass(int wg) { asm volatile("bar.arrive %0, 256;" :: "r"(4 - wg) : "memory"); }
__device__ __forceinline__ void stsm4(uint32_t addr, uint32_t a, uint32_t b, uint32_t c, uint32_t d) {
  asm volatile("stmatrix.sync.aligned.m8n8.x4.shared.b16 [%0], {%1,%2,%3,%4};" :: "r"(addr), "r"(a), "r"(b), "r"(c), "r"(d) : "memory");
}
template <int N> __device__ __forceinline__ void keep(float (&d)[N]) {
#pragma unroll
  for (int i = 0; i < N; i++) asm volatile("" : "+f"(d[i]) :: "memory");
}
template <int N> __device__ __forceinline__ void keep(uint32_t (&d)[N]) {
#pragma unroll
  for (int i = 0; i < N; i++) asm volatile("" : "+r"(d[i]) :: "memory");
}
__host__ __device__ __forceinline__ uint64_t mkdesc(uint32_t addr, uint32_t lbo, uint32_t sbo) {
  return ((uint64_t)(sbo >> 4) << 32) | (uint64_t)(((lbo >> 4) << 16) | ((addr & 0x3FFFF) >> 4));
}

template <int SCALE_D>
__device__ __forceinline__ void wgmma_n144(uint32_t (&d)[36], uint32_t a0, uint32_t a1, uint32_t a2, uint32_t a3, uint64_t descB) {
  if (SCALE_D == 0)
  asm volatile("wgmma.mma_async.sync.aligned.m64n144k16.f16.f16.f16 "
    "{%0, %1, %2, %3, %4, %5, %6, %7, %8, %9, %10, %11, %12, %13, %14, %15, "
    "%16, %17, %18, %19, %20, %21, %22, %23, %24, %25, %26, %27, %28, %29, %30, %31, "
    "%32, %33, %34, %35}, "
    "{%36, %37, %38, %39}, %40, 0, 1, 1, 0;\n"
    : "=r"(d[0]), "=r"(d[1]), "=r"(d[2]), "=r"(d[3]), "=r"(d[4]), "=r"(d[5]), "=r"(d[6]), "=r"(d[7]),
      "=r"(d[8]), "=r"(d[9]), "=r"(d[10]), "=r"(d[11]), "=r"(d[12]), "=r"(d[13]), "=r"(d[14]), "=r"(d[15]),
      "=r"(d[16]), "=r"(d[17]), "=r"(d[18]), "=r"(d[19]), "=r"(d[20]), "=r"(d[21]), "=r"(d[22]), "=r"(d[23]),
      "=r"(d[24]), "=r"(d[25]), "=r"(d[26]), "=r"(d[27]), "=r"(d[28]), "=r"(d[29]), "=r"(d[30]), "=r"(d[31]),
      "=r"(d[32]), "=r"(d[33]), "=r"(d[34]), "=r"(d[35])
    : "r"(a0), "r"(a1), "r"(a2), "r"(a3), "l"(descB));
  else
  asm volatile("wgmma.mma_async.sync.aligned.m64n144k16.f16.f16.f16 "
    "{%0, %1, %2, %3, %4, %5, %6, %7, %8, %9, %10, %11, %12, %13, %14, %15, "
    "%16, %17, %18, %19, %20, %21, %22, %23, %24, %25, %26, %27, %28, %29, %30, %31, "
    "%32, %33, %34, %35}, "
    "{%36, %37, %38, %39}, %40, 1, 1, 1, 0;\n"
    : "+r"(d[0]), "+r"(d[1]), "+r"(d[2]), "+r"(d[3]), "+r"(d[4]), "+r"(d[5]), "+r"(d[6]), "+r"(d[7]),
      "+r"(d[8]), "+r"(d[9]), "+r"(d[10]), "+r"(d[11]), "+r"(d[12]), "+r"(d[13]), "+r"(d[14]), "+r"(d[15]),
      "+r"(d[16]), "+r"(d[17]), "+r"(d[18]), "+r"(d[19]), "+r"(d[20]), "+r"(d[21]), "+r"(d[22]), "+r"(d[23]),
      "+r"(d[24]), "+r"(d[25]), "+r"(d[26]), "+r"(d[27]), "+r"(d[28]), "+r"(d[29]), "+r"(d[30]), "+r"(d[31]),
      "+r"(d[32]), "+r"(d[33]), "+r"(d[34]), "+r"(d[35])
    : "r"(a0), "r"(a1), "r"(a2), "r"(a3), "l"(descB));
}

template <int SCALE_D>
__device__ __forceinline__ void wgmma_n192(uint32_t (&d)[48], uint32_t a0, uint32_t a1, uint32_t a2, uint32_t a3, uint64_t descB) {
  if (SCALE_D == 0)
  asm volatile("wgmma.mma_async.sync.aligned.m64n192k16.f16.f16.f16 "
    "{%0, %1, %2, %3, %4, %5, %6, %7, %8, %9, %10, %11, %12, %13, %14, %15, "
    "%16, %17, %18, %19, %20, %21, %22, %23, %24, %25, %26, %27, %28, %29, %30, %31, "
    "%32, %33, %34, %35, %36, %37, %38, %39, %40, %41, %42, %43, %44, %45, %46, %47}, "
    "{%48, %49, %50, %51}, %52, 0, 1, 1, 0;\n"
    : "=r"(d[0]), "=r"(d[1]), "=r"(d[2]), "=r"(d[3]), "=r"(d[4]), "=r"(d[5]), "=r"(d[6]), "=r"(d[7]),
      "=r"(d[8]), "=r"(d[9]), "=r"(d[10]), "=r"(d[11]), "=r"(d[12]), "=r"(d[13]), "=r"(d[14]), "=r"(d[15]),
      "=r"(d[16]), "=r"(d[17]), "=r"(d[18]), "=r"(d[19]), "=r"(d[20]), "=r"(d[21]), "=r"(d[22]), "=r"(d[23]),
      "=r"(d[24]), "=r"(d[25]), "=r"(d[26]), "=r"(d[27]), "=r"(d[28]), "=r"(d[29]), "=r"(d[30]), "=r"(d[31]),
      "=r"(d[32]), "=r"(d[33]), "=r"(d[34]), "=r"(d[35]), "=r"(d[36]), "=r"(d[37]), "=r"(d[38]), "=r"(d[39]),
      "=r"(d[40]), "=r"(d[41]), "=r"(d[42]), "=r"(d[43]), "=r"(d[44]), "=r"(d[45]), "=r"(d[46]), "=r"(d[47])
    : "r"(a0), "r"(a1), "r"(a2), "r"(a3), "l"(descB));
  else
  asm volatile("wgmma.mma_async.sync.aligned.m64n192k16.f16.f16.f16 "
    "{%0, %1, %2, %3, %4, %5, %6, %7, %8, %9, %10, %11, %12, %13, %14, %15, "
    "%16, %17, %18, %19, %20, %21, %22, %23, %24, %25, %26, %27, %28, %29, %30, %31, "
    "%32, %33, %34, %35, %36, %37, %38, %39, %40, %41, %42, %43, %44, %45, %46, %47}, "
    "{%48, %49, %50, %51}, %52, 1, 1, 1, 0;\n"
    : "+r"(d[0]), "+r"(d[1]), "+r"(d[2]), "+r"(d[3]), "+r"(d[4]), "+r"(d[5]), "+r"(d[6]), "+r"(d[7]),
      "+r"(d[8]), "+r"(d[9]), "+r"(d[10]), "+r"(d[11]), "+r"(d[12]), "+r"(d[13]), "+r"(d[14]), "+r"(d[15]),
      "+r"(d[16]), "+r"(d[17]), "+r"(d[18]), "+r"(d[19]), "+r"(d[20]), "+r"(d[21]), "+r"(d[22]), "+r"(d[23]),
      "+r"(d[24]), "+r"(d[25]), "+r"(d[26]), "+r"(d[27]), "+r"(d[28]), "+r"(d[29]), "+r"(d[30]), "+r"(d[31]),
      "+r"(d[32]), "+r"(d[33]), "+r"(d[34]), "+r"(d[35]), "+r"(d[36]), "+r"(d[37]), "+r"(d[38]), "+r"(d[39]),
      "+r"(d[40]), "+r"(d[41]), "+r"(d[42]), "+r"(d[43]), "+r"(d[44]), "+r"(d[45]), "+r"(d[46]), "+r"(d[47])
    : "r"(a0), "r"(a1), "r"(a2), "r"(a3), "l"(descB));
}

template <int SCALE_D>
__device__ __forceinline__ void wgmma_n56(uint32_t (&d)[14], uint32_t a0, uint32_t a1, uint32_t a2, uint32_t a3, uint64_t descB) {
  if (SCALE_D == 0)
  asm volatile("wgmma.mma_async.sync.aligned.m64n56k16.f16.f16.f16 "
    "{%0, %1, %2, %3, %4, %5, %6, %7, %8, %9, %10, %11, %12, %13}, "
    "{%14, %15, %16, %17}, %18, 0, 1, 1, 0;\n"
    : "=r"(d[0]), "=r"(d[1]), "=r"(d[2]), "=r"(d[3]), "=r"(d[4]), "=r"(d[5]), "=r"(d[6]), "=r"(d[7]),
      "=r"(d[8]), "=r"(d[9]), "=r"(d[10]), "=r"(d[11]), "=r"(d[12]), "=r"(d[13])
    : "r"(a0), "r"(a1), "r"(a2), "r"(a3), "l"(descB));
  else
  asm volatile("wgmma.mma_async.sync.aligned.m64n56k16.f16.f16.f16 "
    "{%0, %1, %2, %3, %4, %5, %6, %7, %8, %9, %10, %11, %12, %13}, "
    "{%14, %15, %16, %17}, %18, 1, 1, 1, 0;\n"
    : "+r"(d[0]), "+r"(d[1]), "+r"(d[2]), "+r"(d[3]), "+r"(d[4]), "+r"(d[5]), "+r"(d[6]), "+r"(d[7]),
      "+r"(d[8]), "+r"(d[9]), "+r"(d[10]), "+r"(d[11]), "+r"(d[12]), "+r"(d[13])
    : "r"(a0), "r"(a1), "r"(a2), "r"(a3), "l"(descB));
}

template <int SCALE_D>
__device__ __forceinline__ void wgmma_n48t(uint32_t (&d)[12], uint32_t a0, uint32_t a1, uint32_t a2, uint32_t a3, uint64_t descB) {
  if (SCALE_D == 0)
  asm volatile("wgmma.mma_async.sync.aligned.m64n48k16.f16.f16.f16 "
    "{%0, %1, %2, %3, %4, %5, %6, %7, %8, %9, %10, %11}, "
    "{%12, %13, %14, %15}, %16, 0, 1, 1, 1;\n"
    : "=r"(d[0]), "=r"(d[1]), "=r"(d[2]), "=r"(d[3]), "=r"(d[4]), "=r"(d[5]), "=r"(d[6]), "=r"(d[7]),
      "=r"(d[8]), "=r"(d[9]), "=r"(d[10]), "=r"(d[11])
    : "r"(a0), "r"(a1), "r"(a2), "r"(a3), "l"(descB));
  else
  asm volatile("wgmma.mma_async.sync.aligned.m64n48k16.f16.f16.f16 "
    "{%0, %1, %2, %3, %4, %5, %6, %7, %8, %9, %10, %11}, "
    "{%12, %13, %14, %15}, %16, 1, 1, 1, 1;\n"
    : "+r"(d[0]), "+r"(d[1]), "+r"(d[2]), "+r"(d[3]), "+r"(d[4]), "+r"(d[5]), "+r"(d[6]), "+r"(d[7]),
      "+r"(d[8]), "+r"(d[9]), "+r"(d[10]), "+r"(d[11])
    : "r"(a0), "r"(a1), "r"(a2), "r"(a3), "l"(descB));
}

__global__ void __launch_bounds__(384) prepack_kernel(const __nv_bfloat16* __restrict__ wqkv, const __nv_bfloat16* __restrict__ wo) {
  asm volatile("griddepcontrol.launch_dependents;");
  __half* dst = reinterpret_cast<__half*>(g_wpack);
  const int c = threadIdx.x, nb = blockIdx.x * 2 + threadIdx.y;
  if (nb < 72) {
    __shared__ float red2[2][6][8];
    float (*red)[8] = red2[threadIdx.y];
    const int h = nb / 18, j = nb % 18, part = j / 6;
    const int col = (part == 0 ? 192 : part == 1 ? 0 : 384) + h * 48 + (j % 6) * 8;
    uint4 raw = *reinterpret_cast<const uint4*>(wqkv + c * 576 + col);
    uint32_t u[4] = {raw.x, raw.y, raw.z, raw.w};
    float v[8];
#pragma unroll
    for (int i = 0; i < 4; i++) { v[2 * i] = lo2f(u[i]); v[2 * i + 1] = hi2f(u[i]); }
#pragma unroll
    for (int i = 0; i < 8; i++) {
      float s = v[i];
#pragma unroll
      for (int o = 16; o; o >>= 1) s += __shfl_xor_sync(~0u, s, o);
      if ((c & 31) == 0) red[c >> 5][i] = s;
    }
    __syncthreads();
    const int cc = c >> 5, q = (c >> 3) & 3, s1 = (c >> 2) & 1, hh = (c >> 1) & 1, e = c & 1;
    const int base = qkv_pos(h, 2 * cc + s1) / 2 + j * 128 + hh * 64 + 2 * q + e;
#pragma unroll
    for (int n = 0; n < 8; n++) {
      float m = (red[0][n] + red[1][n] + red[2][n] + red[3][n] + red[4][n] + red[5][n]) * (1.0f / 192.0f);
      dst[base + n * 8] = __float2half_rn((v[n] - m) * (part == 1 ? 0.14433756729740643f * 1.4426950408889634f : 1.0f));
    }
  } else {
    const int jb = nb - 72;
    const int s = c >> 4, hh = (c >> 3) & 1, kk = c & 7;
    const int base = wo_pos(s) / 2 + jb * 128 + hh * 64 + kk;
#pragma unroll
    for (int n = 0; n < 8; n++) {
      const int ch = 32 * (jb >> 2) + 8 * (n >> 1) + 2 * (jb & 3) + (n & 1);
      dst[base + n * 8] = __float2half_rn(__bfloat162float(wo[c * 192 + ch]));
    }
  }
}

__device__ __forceinline__ int window_of(int round, int nfull, int cta, int ncta, int wg) {
  if (round < nfull) return round * 2 * ncta + 2 * cta + wg;
  const int rem = NWIN - nfull * 2 * ncta;
  const int i = cta + wg * ncta;
  return i < rem ? nfull * 2 * ncta + i : -1;
}

template <int S0 = 0, int S1 = 12>
__device__ __forceinline__ void mma_qkv(uint32_t (&acc)[36], const uint32_t (&A)[48], const uint64_t* d) {
#pragma unroll
  for (int s = S0; s < S1; s++) {
    if (s == 0) wgmma_n144<0>(acc, A[4 * s], A[4 * s + 1], A[4 * s + 2], A[4 * s + 3], d[s]);
    else        wgmma_n144<1>(acc, A[4 * s], A[4 * s + 1], A[4 * s + 2], A[4 * s + 3], d[s]);
  }
  wg_commit();
}
__device__ __forceinline__ void mma_proj(uint32_t (&acc)[48], const uint32_t (&A)[12], const uint64_t* d) {
#pragma unroll
  for (int s = 0; s < 3; s++) wgmma_n192<1>(acc, A[4 * s], A[4 * s + 1], A[4 * s + 2], A[4 * s + 3], d[s]);
}
__device__ __forceinline__ void mma_s(uint32_t (&S)[14], const uint32_t (&Q)[12], const uint64_t* d) {
  wgmma_n56<0>(S, Q[0], Q[1], Q[2], Q[3], d[0]);
  wgmma_n56<1>(S, Q[4], Q[5], Q[6], Q[7], d[1]);
  wgmma_n56<1>(S, Q[8], Q[9], Q[10], Q[11], d[2]);
}
__device__ __forceinline__ void mma_pv(uint32_t (&O)[12], const uint32_t (&P)[12], const uint64_t* d) {
  wgmma_n48t<0>(O, P[0], P[1], P[2], P[3], d[0]);
  wgmma_n48t<1>(O, P[4], P[5], P[6], P[7], d[1]);
  wgmma_n48t<1>(O, P[8], P[9], P[10], P[11], d[2]);
}

#define PIN() asm volatile("pmevent 0;" ::: "memory")
template <int A, int B> __device__ __forceinline__ void hold(uint32_t* v) {
#pragma unroll
  for (int i = A; i < B; i++) asm volatile("" : "+r"(v[i]));
}
__device__ __forceinline__ void stsm12(const uint32_t* v, uint32_t addr) {
#pragma unroll
  for (int j = 0; j < 3; j++) stsm4(addr + 2 * j * KV_PITCH, v[4 * j], v[4 * j + 1], v[4 * j + 2], v[4 * j + 3]);
}
__device__ __forceinline__ void load_v48(uint32_t (&v)[6], uint32_t addr) {
  asm volatile("ldmatrix.sync.aligned.m8n8.x4.shared.b16 {%0,%1,%2,%3}, [%4];" : "=r"(v[0]), "=r"(v[1]), "=r"(v[2]), "=r"(v[3]) : "r"(addr) : "memory");
  asm volatile("ldmatrix.sync.aligned.m8n8.x2.shared.b16 {%0,%1}, [%2];" : "=r"(v[4]), "=r"(v[5]) : "r"(addr + 4 * KV_PITCH) : "memory");
}
__device__ __forceinline__ void finish_o(const uint32_t (&O)[12], const uint32_t (&v)[6], uint32_t p48, uint32_t inv, uint32_t (&Of)[12]) {
#pragma unroll
  for (int i = 0; i < 12; i++) {
    const uint32_t t = h2u(__hfma2(u2h(v[i >> 1]), (i & 1) ? hcast<1>(p48) : hcast<0>(p48), u2h(O[i])));
    Of[i] = (i & 1) ? fmul_b<1>(t, inv) : fmul_b<0>(t, inv);
  }
  hold<0, 12>(Of);
}
template <int A, int B, int CHUNK = 48>
__device__ __forceinline__ void convert(uint32_t (&X)[48], float (&s1)[2], float (&s2)[2], int never) {
#pragma unroll
  for (int i = A; i < B; i++) {
    if ((i - A) % CHUNK == 0 && CHUNK < 48) PIN();
    asm volatile("" : "+r"(X[i]));
    const float lo = lo2f(X[i]), hi = hi2f(X[i]);
    s1[i & 1] = i < 2 ? lo + hi : s1[i & 1] + (lo + hi);
    s2[i & 1] = fmaf(lo, lo, i < 2 ? hi * hi : fmaf(hi, hi, s2[i & 1]));
    asm volatile("{\n.reg .pred p;\nsetp.eq.s32 p, %3, 0;\n@p cvt.rn.f16x2.f32 %0, %1, %2;\n}\n" : "+r"(X[i]) : "f"(hi), "f"(lo), "r"(never));
  }
  asm volatile("" : "+f"(s1[0]), "+f"(s1[1]), "+f"(s2[0]), "+f"(s2[1]));
}
__device__ __forceinline__ uint32_t ln_rstd(const float (&s1)[2], const float (&s2)[2]) {
  float r[2];
#pragma unroll
  for (int a = 0; a < 2; a++) {
    float m = s1[a], v = s2[a];
    m += __shfl_xor_sync(~0u, m, 1); v += __shfl_xor_sync(~0u, v, 1);
    m += __shfl_xor_sync(~0u, m, 2); v += __shfl_xor_sync(~0u, v, 2);
    m *= 1.0f / 192.0f;
    v = fmaxf(fmaf(v, 1.0f / 192.0f, -m * m), 0.f) + 1e-5f;
    asm("rsqrt.approx.ftz.f32 %0, %1;" : "=f"(r[a]) : "f"(v));
  }
  uint32_t rk = packh(r[0], r[1]);
  hold<0, 1>(&rk);
  return rk;
}
__device__ __forceinline__ void scale12(uint32_t (&D)[12], const uint32_t* a, uint32_t r) {
#pragma unroll
  for (int i = 0; i < 12; i++) D[i] = (i & 1) ? fmul_b<1>(a[i], r) : fmul_b<0>(a[i], r);
  hold<0, 12>(D);
}
template <int CC>
__device__ __forceinline__ void store_out(const uint32_t (&Y)[48], uint8_t* o0, uint8_t* o1, uint32_t vmask) {
  uint32_t T[8];
#pragma unroll
  for (int i = 0; i < 8; i++) {
    const float2 f = __half22float2(u2h(Y[8 * CC + i]));
    T[i] = pack2(f.x, f.y);
  }
  asm volatile("{\n.reg .pred p;\nsetp.ne.u32 p, %5, 0;\n@p st.global.v4.u32 [%0], {%1,%2,%3,%4};\n}\n"
               :: "l"(o0 + CC * 64), "r"(T[0]), "r"(T[2]), "r"(T[4]), "r"(T[6]), "r"(vmask) : "memory");
  asm volatile("{\n.reg .pred p;\nsetp.lt.s32 p, %5, 0;\n@p st.global.v4.u32 [%0], {%1,%2,%3,%4};\n}\n"
               :: "l"(o1 + CC * 64), "r"(T[1]), "r"(T[3]), "r"(T[5]), "r"(T[7]), "r"(vmask) : "memory");
}
__device__ __forceinline__ void proxy_fence() { asm volatile("fence.proxy.async.shared::cta;" ::: "memory"); }
__device__ __forceinline__ uint32_t fadd2(uint32_t a, uint32_t b) { return h2u(__hadd2_rn(u2h(a), u2h(b))); }
__device__ __forceinline__ void row_max(const uint32_t (&S)[14], uint32_t& k48, uint32_t& mx) {
  k48 = __shfl_sync(~0u, __byte_perm(S[12], S[13], 0x5410), 0, 4);
  const uint32_t m0 = fmax2(fmax2(fmax2(S[0], S[2]), S[4]), fmax2(fmax2(S[6], S[8]), S[10]));
  const uint32_t m1 = fmax2(fmax2(fmax2(S[1], S[3]), S[5]), fmax2(fmax2(S[7], S[9]), S[11]));
  mx = fmax2(__byte_perm(m0, m1, 0x5410), __byte_perm(m0, m1, 0x7632));
  mx = fmax2(mx, __shfl_xor_sync(~0u, mx, 1));
  mx = fmax2(fmax2(mx, __shfl_xor_sync(~0u, mx, 2)), k48);
  hold<0, 1>(&mx);
}
__device__ __forceinline__ void row_exp(const uint32_t (&S)[14], uint32_t k48, uint32_t mx, uint32_t (&P)[12], uint32_t& p48, uint32_t& l) {
#pragma unroll
  for (int j = 0; j < 12; j++) P[j] = fex2((j & 1) ? fsub_b<1>(S[j], mx) : fsub_b<0>(S[j], mx));
  p48 = fex2(h2u(__hsub2_rn(u2h(k48), u2h(mx))));
  const uint32_t s0 = fadd2(fadd2(fadd2(P[0], P[2]), fadd2(P[4], P[6])), fadd2(P[8], P[10]));
  const uint32_t s1 = fadd2(fadd2(fadd2(P[1], P[3]), fadd2(P[5], P[7])), fadd2(P[9], P[11]));
  l = fadd2(__byte_perm(s0, s1, 0x5410), __byte_perm(s0, s1, 0x7632));
  hold<0, 12>(P); hold<0, 1>(&p48); hold<0, 1>(&l);
}
__device__ __forceinline__ uint32_t row_scale(uint32_t l, uint32_t p48, uint32_t vmask) {
  l = fadd2(l, __shfl_xor_sync(~0u, l, 1));
  l = fadd2(fadd2(l, __shfl_xor_sync(~0u, l, 2)), p48);
  float i0, i1;
  asm("rcp.approx.ftz.f32 %0, %1;" : "=f"(i0) : "f"(__low2float(u2h(l))));
  asm("rcp.approx.ftz.f32 %0, %1;" : "=f"(i1) : "f"(__high2float(u2h(l))));
  uint32_t inv = packh(i0, i1) & vmask;
  hold<0, 1>(&inv);
  return inv;
}
template <int S0, int S1>
__device__ __forceinline__ void load_x(uint32_t (&X)[48], uint32_t t0) {
#pragma unroll
  for (int s = S0; s < S1; s++)
    asm volatile("ld.shared.v4.u32 {%0,%1,%2,%3}, [%4];" : "=r"(X[4 * s]), "=r"(X[4 * s + 1]), "=r"(X[4 * s + 2]), "=r"(X[4 * s + 3])
                 : "r"(((s & 1) ? (t0 ^ 16) : t0) + (s >> 1) * 128) : "memory");
}

#define WDIV 1
template <int P, int CNT, int DIV = WDIV> __device__ __forceinline__ void load_slices(uint32_t sb, const Descs& ds) {
  constexpr int st = stage_of(P);
  constexpr bool first = P == 0 || stage_of(P - 1) != st;
  if (first)
    asm volatile("{\n.reg .pred p;\nelect.sync _|p, 0xffffffff;\n@p mbarrier.arrive.expect_tx.shared::cta.b64 _, [%0], %1;\n}\n"
                 :: "r"(sb + BAR_WFULL + 8 * st), "n"((st < 4 ? 3 : st == 4 ? 2 : 1) * SLICE / DIV) : "memory");
  asm volatile("{\n.reg .pred p;\nelect.sync _|p, 0xffffffff;\n"
               "@p cp.async.bulk.shared::cluster.global.mbarrier::complete_tx::bytes [%0], [%1], %2, [%3];\n}\n"
               :: "r"(sb + OFF_W + (P & 7) * SLICE), "l"(ds.src[P]), "n"(CNT * SLICE / DIV), "r"(sb + BAR_WFULL + 8 * st) : "memory");
}
__device__ __forceinline__ void warp_arrive(uint32_t bar) {
  asm volatile("{\n.reg .pred p;\nelect.sync _|p, 0xffffffff;\n@p mbarrier.arrive.shared::cta.b64 _, [%0];\n}\n" :: "r"(bar) : "memory");
}

__global__ void __launch_bounds__(384, 1)
fused_kernel(const __grid_constant__ CUtensorMap tmx, const __grid_constant__ CUtensorMap tmp, const __grid_constant__ Descs ds, const __nv_bfloat16* __restrict__ dw, __nv_bfloat16* __restrict__ out, const int never) {
  extern __shared__ __align__(1024) uint8_t smem[];
  const uint32_t sb = (uint32_t)__cvta_generic_to_shared(smem);
  const int tid = threadIdx.x, lane = tid & 31;
  const int warp = __shfl_sync(0xffffffffu, tid >> 5, 0);
  const int cta = blockIdx.x, ncta = gridDim.x;
  const int nfull = NWIN / (2 * ncta);
  const int nrounds = nfull + ((NWIN - nfull * 2 * ncta) > cta ? 1 : 0);

  if (warp == 0) GTS(0);
  auto prefetch_round = [&](int r) {
#pragma unroll
    for (int k = 0; k < 2; k++) {
      const int w = window_of(r, nfull, cta, ncta, k);
      if (w >= 0) {
        const int a = w / NWX;
        asm volatile("{\n.reg .pred p;\nelect.sync _|p, 0xffffffff;\n@p cp.async.bulk.prefetch.tensor.3d.L2.global [%0, {0, %1, %2}];\n}\n"
                     :: "l"(reinterpret_cast<uint64_t>(&tmp)), "r"((w - a * NWX) * 7 - 1), "r"(a * 7 - 1) : "memory");
      }
    }
  };
  if (warp == 11) prefetch_round(0);
  if (warp == 10 && lane == 0) asm volatile("prefetch.tensormap [%0];" :: "l"(reinterpret_cast<uint64_t>(&tmx)) : "memory");
  if (tid == 0) {
    if ((sb & 0x3FFFF) != SMEM_BASE) __trap();
    for (int i = 0; i < 7; i++) { mbar_init(sb + BAR_WFULL + 8 * i, 1); mbar_init(sb + BAR_WEMPTY + 8 * i, 8); }
    for (int i = 0; i < 9; i++) mbar_init(sb + BAR_XFULL + 8 * i, 1);
    mbar_init(sb + BAR_TFULL, 3);
    mbar_init(sb + BAR_TEMPTY, 8);
    asm volatile("fence.mbarrier_init.release.cluster;" ::: "memory");
  }
  if (tid >= 128 && tid < 320) {
    *reinterpret_cast<uint32_t*>(smem + OFF_ZERO + (tid - 128) * 4) = 0;
  }
  __syncthreads();

  if (warp >= 8) {
    asm volatile("setmaxnreg.dec.sync.aligned.u32 " PREGS ";");
    if (warp == 11) {
      asm volatile("griddepcontrol.wait;" ::: "memory");
      load_slices<1, 3, 1>(sb, ds); load_slices<0, 1, 1>(sb, ds); load_slices<4, 1, 1>(sb, ds); load_slices<5, 3, 1>(sb, ds);
      for (int r = 0; r < nrounds; r++) {
        const uint32_t par = r & 1;
        const bool next_round = r + 1 < nrounds;
        mbar_wait(sb + BAR_WEMPTY + 40, par); load_slices<8, 1>(sb, ds);
        mbar_wait(sb + BAR_WEMPTY, par);      load_slices<9, 2>(sb, ds); load_slices<11, 1>(sb, ds);
        mbar_wait(sb + BAR_WEMPTY + 48, par); load_slices<12, 1>(sb, ds);
        mbar_wait(sb + BAR_WEMPTY + 8, par);  load_slices<13, 1>(sb, ds); load_slices<14, 2>(sb, ds);
        mbar_wait(sb + BAR_WEMPTY + 16, par); load_slices<0, 1>(sb, ds); if (next_round) load_slices<1, 2>(sb, ds);
        mbar_wait(sb + BAR_WEMPTY + 24, par);
        if (next_round) load_slices<3, 1>(sb, ds);
        load_slices<4, 1>(sb, ds);
        if (next_round) {
          load_slices<5, 1>(sb, ds);
          mbar_wait(sb + BAR_WEMPTY + 32, par); load_slices<6, 2>(sb, ds);
        }
      }
    } else {
      const int cw = warp - 8;
      const int win = lane >> 4;
      const int ch0 = cw * 64 + (lane & 15) * 4;
      uint32_t wt[9][2];
#pragma unroll
      for (int t = 0; t < 9; t++) {
        uint2 v = *reinterpret_cast<const uint2*>(dw + t * CH + ch0);
        wt[t][0] = v.x; wt[t][1] = v.y;
      }
      const uint32_t xs = sb + OFF_X + cw * 3 * XSLOT;
      const uint32_t xld = xs + (lane >> 4) * 1152 + (lane & 15) * 8;
      const uint32_t xbar = sb + BAR_XFULL + cw * 24;
      const uint32_t st0 = sb + OFF_TILE + win * TILE_BYTES + ch0 * 4;
      const uint32_t st1 = sb + OFF_TILE + win * TILE_BYTES + ((ch0 * 4) ^ 16);
      const uint64_t tm = reinterpret_cast<uint64_t>(&tmx);
      int cx0, cy0, cx1, cy1;
      auto coords = [&](int r) {
        const int w0 = window_of(r, nfull, cta, ncta, 0);
        int w1 = window_of(r, nfull, cta, ncta, 1);
        if (w1 < 0) w1 = w0;
        const int a = w0 / NWX, b = w1 / NWX;
        cx0 = (w0 - a * NWX) * 7 - 1; cy0 = a * 7 - 1;
        cx1 = (w1 - b * NWX) * 7 - 1; cy1 = b * 7 - 1;
      };
      auto issue = [&](int slot, int dy) {
        asm volatile("{\n.reg .pred p;\nelect.sync _|p, 0xffffffff;\n"
                     "@p mbarrier.arrive.expect_tx.shared::cta.b64 _, [%2], %8;\n"
                     "@p cp.async.bulk.tensor.3d.shared::cluster.global.mbarrier::complete_tx::bytes [%0], [%1, {%3, %4, %5}], [%2];\n"
                     "@p cp.async.bulk.tensor.3d.shared::cluster.global.mbarrier::complete_tx::bytes [%0 + 1152], [%1, {%3, %6, %7}], [%2];\n}\n"
                     :: "r"(xs + slot * XSLOT), "l"(tm), "r"(xbar + slot * 8), "r"(cw * 64), "r"(cx0), "r"(cy0 + dy), "r"(cx1), "r"(cy1 + dy), "n"(XSLOT) : "memory");
      };
      coords(0);
      issue(0, 0); issue(1, 1); issue(2, 2);
      for (int r = 0; r < nrounds; r++) {
        const bool more = r + 1 < nrounds;
        uint32_t accA[7][2], accB[7][2], ctr[7][2], held[2];
#pragma unroll
        for (int i = 0; i < 9; i++) {
          mbar_wait(xbar + (i % 3) * 8, (r + i / 3) & 1);
          if (i == 0 && r == 0 && cw == 0) GTS(7);
          if (i == 7 && more) coords(r + 1);
          if (i == 0) { if (r > 0) issue(2, 2); }
          else if (i < 7) issue((i + 2) % 3, i + 2);
          else if (more) issue((i + 2) % 3, i - 7);
          if (i == 2 && r > 0) mbar_wait(sb + BAR_TEMPTY, (r - 1) & 1);
          if (i == 2 && cw == 0 && r == 2) GTS(1);
          if (i == 2 && cw == 0 && r == 3) GTS(3);
          if (i == 2) { TR(0); }
          uint32_t cur[9][2];
#pragma unroll
          for (int p = 0; p < 5; p++)
            asm volatile("ld.shared.v2.u32 {%0,%1}, [%2];" : "=r"(cur[p][0]), "=r"(cur[p][1]) : "r"(xld + (i % 3) * XSLOT + p * 128));
#pragma unroll
          for (int j = 0; j < 7; j++) {
            if (j >= 1 && j + 4 < 9)
              asm volatile("ld.shared.v2.u32 {%0,%1}, [%2];" : "=r"(cur[j + 4][0]), "=r"(cur[j + 4][1]) : "r"(xld + (i % 3) * XSLOT + (j + 4) * 128));
            if (i >= 2) {
              uint32_t o[2];
#pragma unroll
              for (int e = 0; e < 2; e++) {
                uint32_t a = hfma(cur[j][e], wt[6][e], accA[j][e]);
                a = hfma(cur[j + 1][e], wt[7][e], a);
                a = hfma(cur[j + 2][e], wt[8][e], a);
                o[e] = hadd(ctr[j][e], a);
              }
              const int tok = (i - 2) * 7 + j, ps = tok >> 1;
              if (!(tok & 1)) { held[0] = o[0]; held[1] = o[1]; }
              if (tok == 48) o[0] = o[1] = 0;
              if ((tok & 1) || tok == 48)
                asm volatile("st.shared.v4.u32 [%0], {%1,%2,%3,%4};" :: "r"(((ps & 1) ? st1 : st0) + ps * 768), "r"(held[0]), "r"(o[0]), "r"(held[1]), "r"(o[1]) : "memory");
            }
#pragma unroll
            for (int e = 0; e < 2; e++) {
              if (i >= 1 && i <= 7) {
                uint32_t a = hfma(cur[j][e], wt[3][e], accB[j][e]);
                a = hfma(cur[j + 1][e], wt[4][e], a);
                accA[j][e] = hfma(cur[j + 2][e], wt[5][e], a);
                ctr[j][e] = cur[j + 1][e];
              }
              if (i <= 6) {
                uint32_t a = hmul(cur[j][e], wt[0][e]);
                a = hfma(cur[j + 1][e], wt[1][e], a);
                accB[j][e] = hfma(cur[j + 2][e], wt[2][e], a);
              }
            }
          }
        }
        __syncwarp();
        if (lane == 0) mbar_arrive(sb + BAR_TFULL);
        TR(1);
      }
    }
  } else {
    asm volatile("setmaxnreg.inc.sync.aligned.u32 " CREGS ";");
    const int wg = warp >> 2, w4 = warp & 3, g = lane >> 2, q = lane & 3;
    const int row0 = w4 * 16 + g, row1 = row0 + 8;
    const int ps = min(w4 * 8 + g, 24);
    const int tok0 = 2 * ps, tok1 = min(2 * ps + 1, 48);
    const uint32_t kv = sb + OFF_KV + wg * KV_BYTES;
    const int srow = w4 * 16 + (lane & 15);
    const uint32_t vst = kv + (lane >> 4) * KV_PITCH + (srow < 56 ? srow : min(srow - 7, 55)) * 16;
    uint32_t misc = ((uint32_t)((tok1 / 7) * IMG + tok1 % 7) << 20) | ((uint32_t)((tok0 / 7) * IMG + tok0 % 7) << 8) | (ps * 4 + q);
    const uint32_t v48 = kv + (lane >> 3) * KV_PITCH + 48 * 16;
    const uint32_t vmask = (row0 < 49 ? 0xffffu : 0u) | (row1 < 49 ? 0xffff0000u : 0u);

    const uint32_t tx = sb + q * 32 + (row0 < 49 ? OFF_TILE + wg * TILE_BYTES + ps * 768 + (ps & 1) * 16 : OFF_ZERO + 16);
    const int myrounds = window_of(nrounds - 1, nfull, cta, ncta, wg) < 0 ? nrounds - 1 : nrounds;

    if (never == 2) return;
    uint32_t H[48], Y[48];
    float s1[2], s2[2];
    const uint64_t* dkv = ds.kv[wg];
    uint32_t P[12], Ofc[12], p48 = 0x3c003c00u, lsum = 0;
#pragma unroll
    for (int i = 0; i < 48; i++) Y[i] = 0;
#pragma unroll
    for (int i = 0; i < 12; i++) P[i] = Ofc[i] = 0;
    mbar_wait(sb + BAR_TFULL, 0);
    if (warp == 0) GTS(4);
    load_x<0, 12>(H, tx);
    warp_arrive(sb + BAR_TEMPTY);
    convert<0, NPRE, 8>(H, s1, s2, never);
    if (wg == 1) turn_pass(1);

    uint8_t *o0, *o1;
    uint32_t omask;
    auto out_setup = [&](int r) {
      omask = r >= 0 ? vmask : 0u;
      const int w = window_of(r, nfull, cta, ncta, wg);
      const int wy = w / NWX, wx = w - wy * NWX;
      asm volatile("" : "+r"(misc));
      const uint32_t wb = (uint32_t)(wy * 7 * IMG + wx * 7) * 384u + (misc & 3) * 16;
      o0 = reinterpret_cast<uint8_t*>(out) + (wb + ((misc >> 8) & 0xfff) * 384u);
      o1 = reinterpret_cast<uint8_t*>(out) + (wb + (misc >> 20) * 384u);
    };
#define OUT(c) store_out<c>(Y, o0, o1, omask)
    auto release = [&](int stage) { warp_arrive(sb + BAR_WEMPTY + 8 * stage); };

    for (int r = 0;; r++) {
      const uint32_t par = r & 1;
      uint32_t acc[36], S[14], O[12], Q[12], V[12], Ofa[12], Ofb[12], vr[6], inv, k48, mx;
      if (r == myrounds) {
        const bool idle = r < nrounds;
        mbar_wait(sb + BAR_WFULL + 40, par);
        turn_wait(wg);
        wg_fence(); mma_pv(O, P, dkv + 4); mma_proj(Y, Ofc, ds.p + 6); wg_commit();
        turn_pass(wg);
        load_v48(vr, v48);
        inv = row_scale(lsum, p48, vmask);
        wg_wait<0>(); keep(O); keep(Y);
        finish_o(O, vr, p48, inv, Ofa);
        if (idle) { release(5); release(0); release(1); release(2); release(3); }
        mbar_wait(sb + BAR_WFULL + 48, par);
        turn_wait(wg);
        wg_fence(); mma_proj(Y, Ofa, ds.p + 9); wg_commit();
        if (wg == 0 || idle) turn_pass(wg);
        wg_wait<0>(); keep(Y);
        if (idle) { release(6); turn_wait(wg); turn_pass(wg); }
        out_setup(r - 1);
        OUT(0); PIN(); OUT(1); PIN(); OUT(2); PIN(); OUT(3); PIN(); OUT(4); PIN(); OUT(5);
        if (idle) {
          turn_wait(wg); turn_pass(wg);
          turn_wait(wg); turn_pass(wg);
          turn_wait(wg); turn_pass(wg);
          turn_wait(wg);
        }
        if (w4 == 0) GTS(5 + wg);
        break;
      }
      mbar_wait(sb + BAR_WFULL + 40, par);
      mbar_wait(sb + BAR_WFULL, par);
      TR(0);
      turn_wait(wg);
      TR(1);
      wg_fence(); mma_pv(O, P, dkv + 4); mma_proj(Y, Ofc, ds.p + 6); wg_commit(); mma_qkv<0, NPRE / 4>(acc, H, ds.q[0]);
      convert<NPRE, NMID, 8>(H, s1, s2, never); PIN();
      wg_fence(); mma_qkv<NPRE / 4, NMID / 4>(acc, H, ds.q[0]);
      convert<NMID, 48, 8>(H, s1, s2, never); PIN();
      wg_fence(); mma_qkv<NMID / 4, 12>(acc, H, ds.q[0]);
      turn_pass(wg);
      TR(2);
      load_v48(vr, v48);
      inv = row_scale(lsum, p48, vmask);
      PIN();
      wg_wait<3>(); keep(O); keep(Y);
      release(5);
      bar_sync(1 + wg);
      finish_o(O, vr, p48, inv, Ofa);
      const uint32_t rk = ln_rstd(s1, s2);
      PIN();
      TR(3);
      wg_wait<0>(); keep(acc);
      TR(4);
      release(0);
      scale12(V, acc, rk); stsm12(V, vst + KV_KOFF);
      scale12(V, acc + 24, rk); stsm12(V, vst);
      scale12(Q, acc + 12, rk); PIN();
      proxy_fence();
      mbar_wait(sb + BAR_WFULL + 48, par);
      mbar_wait(sb + BAR_WFULL + 8, par);
      TR(5);
      turn_wait(wg);
      TR(6);
      wg_fence(); mma_proj(Y, Ofa, ds.p + 9); wg_commit(); mma_s(S, Q, dkv); mma_qkv<0, 2>(acc, H, ds.q[1]);
      out_setup(r - 1);
      PIN();
      wg_wait<1>(); keep(Y);
      release(6);
      wg_fence(); mma_qkv<2, 6>(acc, H, ds.q[1]);
      PIN();
      OUT(0);
      PIN();
      wg_wait<1>(); keep(S);
      wg_fence(); mma_qkv<6, 9>(acc, H, ds.q[1]);
      PIN();
      row_max(S, k48, mx);
      OUT(1);
      PIN();
      wg_fence(); mma_qkv<9, 12>(acc, H, ds.q[1]);
      turn_pass(wg);
      PIN();
      OUT(2); PIN();
      OUT(3); PIN();
      row_exp(S, k48, mx, P, p48, lsum);
      PIN();
      TR(7);
      wg_wait<0>(); keep(acc);
      TR(8);
      release(1);
      bar_sync(1 + wg);
      scale12(V, acc, rk); stsm12(V, vst + KV_KOFF);
      scale12(Q, acc + 12, rk); scale12(V, acc + 24, rk); PIN();
      proxy_fence();
#define TURN(ID, OF, G1, G2, G3, X1)                                                       \
      TR(ID + 1);                                                                       \
      turn_wait(wg);                                                                    \
      wg_fence(); mma_pv(O, P, dkv + 4); mma_s(S, Q, dkv); wg_commit(); G1;             \
      PIN();                                                                            \
      TR(ID + 2);                                                                       \
      load_v48(vr, v48);                                                                \
      inv = row_scale(lsum, p48, vmask);                                               \
      X1;                                                                               \
      PIN();                                                                            \
      wg_wait<1>(); keep(S); keep(O);                                                   \
      bar_sync(1 + wg);                                    \
      wg_fence(); G2;                                                                   \
      PIN();                                                                            \
      stsm12(V, vst);                                                                   \
      finish_o(O, vr, p48, inv, OF);                                                    \
      row_max(S, k48, mx);                                                              \
      PIN();                                                                            \
      wg_fence(); G3;                                                                   \
      turn_pass(wg);                                                                    \
      PIN();                                                                            \
      TR(ID + 3);
#define NEXT_HEAD(ID, HD)                                                               \
      row_exp(S, k48, mx, P, p48, lsum);                                                \
      PIN();                                                                            \
      TR(ID + 4);                                                                       \
      wg_wait<0>(); keep(acc);                                                          \
      release(HD);                                                                      \
      scale12(V, acc, rk); stsm12(V, vst + KV_KOFF);                                    \
      scale12(Q, acc + 12, rk); scale12(V, acc + 24, rk); PIN();
      mbar_wait(sb + BAR_WFULL + 16, par);
      TURN(8, Ofa, (mma_qkv<0, KA>(acc, H, ds.q[2])), (mma_qkv<KA, KB>(acc, H, ds.q[2])), (mma_qkv<KB, 12>(acc, H, ds.q[2])), OUT(4))
      OUT(5); PIN();
      NEXT_HEAD(8, 2)
      proxy_fence();
      mbar_wait(sb + BAR_WFULL + 24, par);
      TURN(12, Ofb, (mma_qkv<0, KA>(acc, H, ds.q[3])), (mma_qkv<KA, KB>(acc, H, ds.q[3])), (mma_qkv<KB, 12>(acc, H, ds.q[3])), )
      NEXT_HEAD(12, 3)
#pragma unroll
      for (int i = 0; i < 48; i++) Y[i] = (i & 1) ? H[i] ^ never : H[i] + never;
      hold<0, 48>(Y); PIN();
      proxy_fence();
      mbar_wait(sb + BAR_WFULL + 32, par);
      TR(17);
      turn_wait(wg);
      wg_fence(); mma_pv(O, P, dkv + 4); mma_s(S, Q, dkv); wg_commit(); mma_proj(Y, Ofa, ds.p); mma_proj(Y, Ofb, ds.p + 3); wg_commit();
      turn_pass(wg);
      PIN();
      TR(18);
      load_v48(vr, v48);
      inv = row_scale(lsum, p48, vmask);
      if (r + 1 < myrounds) mbar_wait(sb + BAR_TFULL, par ^ 1);
      load_x<0, 4>(H, tx);
      wg_wait<1>(); keep(S); keep(O);
      bar_sync(1 + wg);
      PIN();
      TR(19);
      row_max(S, k48, mx);
      finish_o(O, vr, p48, inv, Ofc);
      stsm12(V, vst);
      PIN();
      load_x<4, 8>(H, tx);
      row_exp(S, k48, mx, P, p48, lsum);
      PIN();
      load_x<8, 12>(H, tx);
      warp_arrive(sb + BAR_TEMPTY);
      TR(20);
      wg_wait<0>(); keep(Y);
      release(4);
      proxy_fence();
      convert<0, NPRE>(H, s1, s2, never);
      TR(21);
#undef TURN
#undef NEXT_HEAD
    }
  }
}

typedef CUresult (*EncodeFn)(CUtensorMap*, CUtensorMapDataType, cuuint32_t, void*, const cuuint64_t*, const cuuint64_t*,
                             const cuuint32_t*, const cuuint32_t*, CUtensorMapInterleave, CUtensorMapSwizzle,
                             CUtensorMapL2promotion, CUtensorMapFloatOOBfill);

}

extern "C" void kernel_launch(void* const* d_in, const int* in_sizes, int n_in, void* d_out, int out_size) {
  const __nv_bfloat16* x = (const __nv_bfloat16*)d_in[0];
  const __nv_bfloat16* dw = (const __nv_bfloat16*)d_in[1];
  const __nv_bfloat16* wqkv = (const __nv_bfloat16*)d_in[2];
  const __nv_bfloat16* wo = (const __nv_bfloat16*)d_in[3];
  static EncodeFn encode = nullptr;
  static int nsm = 0;
  static void* wpack = nullptr;
  if (!encode) {
    void* fn = nullptr;
    cudaDriverEntryPointQueryResult qr;
    cudaGetDriverEntryPoint("cuTensorMapEncodeTiled", &fn, cudaEnableDefault, &qr);
    encode = (EncodeFn)fn;
    int dev = 0;
    cudaGetDevice(&dev);
    cudaDeviceGetAttribute(&nsm, cudaDevAttrMultiProcessorCount, dev);
    cudaGetSymbolAddress(&wpack, g_wpack);
    cudaFuncSetAttribute(fused_kernel, cudaFuncAttributeMaxDynamicSharedMemorySize, SMEM_BYTES);
  }
  CUtensorMap tmx;
  cuuint64_t gdim[3] = {CH, IMG, IMG};
  cuuint64_t gstr[2] = {CH * 2, (cuuint64_t)CH * 2 * IMG};
  cuuint32_t box[3] = {64, 9, 1};
  cuuint32_t estr[3] = {1, 1, 1};
  encode(&tmx, CU_TENSOR_MAP_DATA_TYPE_BFLOAT16, 3, (void*)x, gdim, gstr, box, estr, CU_TENSOR_MAP_INTERLEAVE_NONE,
         CU_TENSOR_MAP_SWIZZLE_NONE, CU_TENSOR_MAP_L2_PROMOTION_L2_128B, CU_TENSOR_MAP_FLOAT_OOB_FILL_NONE);
  Descs ds;
  for (int i = 0; i < 12; i++) {
    for (int h = 0; h < 4; h++) ds.q[h][i] = mkdesc(SMEM_BASE + OFF_W + qkv_pos(h, i) % (8 * SLICE), 128, 256);
    ds.p[i] = mkdesc(SMEM_BASE + OFF_W + wo_pos(i) % (8 * SLICE), 128, 256);
  }
  for (int i = 0; i < 16; i++) ds.src[i] = (const uint8_t*)wpack + i * SLICE;
  for (int g = 0; g < 2; g++)
    for (int i = 0; i < 4; i++) {
      ds.kv[g][i] = mkdesc(SMEM_BASE + OFF_KV + g * KV_BYTES + KV_KOFF + 2 * i * KV_PITCH, KV_PITCH, 128);
      ds.kv[g][4 + i] = mkdesc(SMEM_BASE + OFF_KV + g * KV_BYTES + 256 * i, 128, KV_PITCH);
    }
  CUtensorMap tmp;
  cuuint32_t boxp[3] = {CH, 9, 9};
  encode(&tmp, CU_TENSOR_MAP_DATA_TYPE_BFLOAT16, 3, (void*)x, gdim, gstr, boxp, estr, CU_TENSOR_MAP_INTERLEAVE_NONE,
         CU_TENSOR_MAP_SWIZZLE_NONE, CU_TENSOR_MAP_L2_PROMOTION_L2_128B, CU_TENSOR_MAP_FLOAT_OOB_FILL_NONE);
  prepack_kernel<<<48, dim3(192, 2), 0, cudaStreamPerThread>>>(wqkv, wo);
  cudaLaunchConfig_t cfg = {};
  cfg.gridDim = dim3(nsm); cfg.blockDim = dim3(384); cfg.dynamicSmemBytes = SMEM_BYTES; cfg.stream = cudaStreamPerThread;
  cudaLaunchAttribute at[1];
  at[0].id = cudaLaunchAttributeProgrammaticStreamSerialization;
  at[0].val.programmaticStreamSerializationAllowed = 1;
  cfg.attrs = at; cfg.numAttrs = 1;
  cudaLaunchKernelEx(&cfg, fused_kernel, tmx, tmp, ds, dw, (__nv_bfloat16*)d_out, 0);
}
```

```cpp
#include <cuda_runtime.h>
#include <cuda_bf16.h>
#include <cuda_fp16.h>
#include <cuda.h>
#include <stdint.h>

#define WHINT 0
#define CREGS "208"
#define PREGS "88"
#define KA 4
#define KB 9
#define SA 8
#define SB 20
#define SC 32
namespace {

constexpr int IMG = 511;
constexpr int CH = 192;
constexpr int NWX = 73;
constexpr int NWIN = NWX * NWX;
constexpr int SLICE = 18432;
constexpr int OFF_W = 0;
constexpr int KV_PITCH = 1792, KV_KOFF = 896, KV_BYTES = 6 * KV_PITCH;
constexpr int OFF_KV = 8 * SLICE;
constexpr int TILE_BYTES = 25 * 768;
constexpr int OFF_TILE = OFF_KV + 2 * KV_BYTES;
constexpr int XSLOT = 2304;
constexpr int OFF_ZERO = OFF_TILE + 2 * TILE_BYTES;
constexpr int OFF_X = OFF_ZERO + 768;
constexpr int OFF_BAR = OFF_X + 9 * XSLOT;
constexpr int BAR_WFULL = OFF_BAR;
constexpr int BAR_WEMPTY = OFF_BAR + 56;
constexpr int BAR_XFULL = OFF_BAR + 112;
constexpr int BAR_TFULL = OFF_BAR + 184;
constexpr int BAR_TEMPTY = OFF_BAR + 192;
constexpr int OFF_TRACE = OFF_BAR + 208;
constexpr int SMEM_BYTES = OFF_TRACE;

__host__ __device__ constexpr int qkv_pos(int h, int s) { return (h == 0 ? 1 : 3 * h + 2) * SLICE + s * 4608; }
__host__ __device__ constexpr int wo_pos(int s) { return s < 6 ? 14 * SLICE + s * 6144 : s < 9 ? (s - 6) * 6144 : 4 * SLICE + (s - 9) * 6144; }
__host__ __device__ constexpr int stage_of(int p) { return p == 0 ? 5 : p < 4 ? 0 : p == 4 ? 6 : p < 8 ? 1 : p < 11 ? 2 : p < 14 ? 3 : 4; }
constexpr int SMEM_BASE = 1024;
struct Descs { uint64_t q[4][12]; uint64_t p[12]; uint64_t kv[2][8]; const uint8_t* src[16]; };

__device__ uint4 g_wpack[16 * SLICE / 16];
#define TR(id)
#define GTS(i)
template <int V> struct IC { static constexpr int v = V; };
typedef __nv_bfloat162 bf2;
__device__ __forceinline__ bf2 u2b(uint32_t u) { return *reinterpret_cast<bf2*>(&u); }
__device__ __forceinline__ uint32_t b2u(bf2 b) { return *reinterpret_cast<uint32_t*>(&b); }
__device__ __forceinline__ uint32_t pack2(float lo, float hi) {
  uint32_t r; asm("cvt.rn.bf16x2.f32 %0, %1, %2;" : "=r"(r) : "f"(hi), "f"(lo)); return r;
}
__device__ __forceinline__ uint32_t hadd(uint32_t a, uint32_t b) { return b2u(__hadd2_rn(u2b(a), u2b(b))); }
__device__ __forceinline__ uint32_t hmul(uint32_t a, uint32_t b) { return b2u(__hmul2_rn(u2b(a), u2b(b))); }
__device__ __forceinline__ uint32_t hfma(uint32_t a, uint32_t b, uint32_t c) { return b2u(__hfma2(u2b(a), u2b(b), u2b(c))); }
__device__ __forceinline__ __half2 u2h(uint32_t u) { return *reinterpret_cast<__half2*>(&u); }
__device__ __forceinline__ uint32_t h2u(__half2 b) { return *reinterpret_cast<uint32_t*>(&b); }
__device__ __forceinline__ uint32_t packh(float lo, float hi) {
  uint32_t r; asm("cvt.rn.f16x2.f32 %0, %1, %2;" : "=r"(r) : "f"(hi), "f"(lo)); return r;
}
__device__ __forceinline__ uint32_t fmax2(uint32_t a, uint32_t b) { return h2u(__hmax2(u2h(a), u2h(b))); }
template <int HI> __device__ __forceinline__ __half2 hcast(uint32_t a) { return HI ? __high2half2(u2h(a)) : __low2half2(u2h(a)); }
template <int HI> __device__ __forceinline__ uint32_t fmul_b(uint32_t a, uint32_t s) { return h2u(__hmul2_rn(u2h(a), hcast<HI>(s))); }
template <int HI> __device__ __forceinline__ uint32_t fsub_b(uint32_t a, uint32_t s) { return h2u(__hsub2_rn(u2h(a), hcast<HI>(s))); }
__device__ __forceinline__ uint32_t fex2(uint32_t a) { uint32_t r; asm("ex2.approx.f16x2 %0, %1;" : "=r"(r) : "r"(a)); return r; }
__device__ __forceinline__ float lo2f(uint32_t a) { return __uint_as_float(a << 16); }
__device__ __forceinline__ float hi2f(uint32_t a) { return __uint_as_float(a & 0xffff0000u); }

__device__ __forceinline__ void mbar_init(uint32_t bar, uint32_t cnt) { asm volatile("mbarrier.init.shared::cta.b64 [%0], %1;" :: "r"(bar), "r"(cnt) : "memory"); }
__device__ __forceinline__ void mbar_arrive(uint32_t bar) { asm volatile("mbarrier.arrive.shared::cta.b64 _, [%0];" :: "r"(bar) : "memory"); }
__device__ __forceinline__ void mbar_expect(uint32_t bar, uint32_t bytes) { asm volatile("mbarrier.arrive.expect_tx.shared::cta.b64 _, [%0], %1;" :: "r"(bar), "r"(bytes) : "memory"); }
template <int HINT>
__device__ __forceinline__ bool mbar_try(uint32_t bar, uint32_t parity) {
  uint32_t ok;
  if (HINT) asm volatile("{\n.reg .pred p;\nmbarrier.try_wait.parity.shared::cta.b64 p, [%1], %2, %3;\nselp.u32 %0, 1, 0, p;\n}\n" : "=r"(ok) : "r"(bar), "r"(parity), "n"(HINT) : "memory");
  else asm volatile("{\n.reg .pred p;\nmbarrier.try_wait.parity.shared::cta.b64 p, [%1], %2;\nselp.u32 %0, 1, 0, p;\n}\n" : "=r"(ok) : "r"(bar), "r"(parity) : "memory");
  return ok != 0;
}
__device__ __forceinline__ void mbar_wait(uint32_t bar, uint32_t parity) {
  if (__builtin_expect(!mbar_try<0>(bar, parity), 0)) {
    uint32_t n = 0;
    while (!mbar_try<WHINT>(bar, parity)) { if (++n > (1u << 24)) __trap(); }
  }
}
__device__ __forceinline__ void wg_fence() { asm volatile("wgmma.fence.sync.aligned;" ::: "memory"); }
__device__ __forceinline__ void wg_commit() { asm volatile("wgmma.commit_group.sync.aligned;" ::: "memory"); }
template <int N> __device__ __forceinline__ void wg_wait() { asm volatile("wgmma.wait_group.sync.aligned %0;" :: "n"(N) : "memory"); }
__device__ __forceinline__ void bar_sync(int id) { asm volatile("bar.sync %0, 128;" :: "r"(id) : "memory"); }
__device__ __forceinline__ void turn_wait(int wg) { asm volatile("bar.sync %0, 256;" :: "r"(3 + wg) : "memory"); }
__device__ __forceinline__ void turn_pass(int wg) { asm volatile("bar.arrive %0, 256;" :: "r"(4 - wg) : "memory"); }
__device__ __forceinline__ void stsm4(uint32_t addr, uint32_t a, uint32_t b, uint32_t c, uint32_t d) {
  asm volatile("stmatrix.sync.aligned.m8n8.x4.shared.b16 [%0], {%1,%2,%3,%4};" :: "r"(addr), "r"(a), "r"(b), "r"(c), "r"(d) : "memory");
}
template <int N> __device__ __forceinline__ void keep(float (&d)[N]) {
#pragma unroll
  for (int i = 0; i < N; i++) asm volatile("" : "+f"(d[i]) :: "memory");
}
template <int N> __device__ __forceinline__ void keep(uint32_t (&d)[N]) {
#pragma unroll
  for (int i = 0; i < N; i++) asm volatile("" : "+r"(d[i]) :: "memory");
}
__host__ __device__ __forceinline__ uint64_t mkdesc(uint32_t addr, uint32_t lbo, uint32_t sbo) {
  return ((uint64_t)(sbo >> 4) << 32) | (uint64_t)(((lbo >> 4) << 16) | ((addr & 0x3FFFF) >> 4));
}

template <int SCALE_D>
__device__ __forceinline__ void wgmma_n144(uint32_t (&d)[36], uint32_t a0, uint32_t a1, uint32_t a2, uint32_t a3, uint64_t descB) {
  if (SCALE_D == 0)
  asm volatile("wgmma.mma_async.sync.aligned.m64n144k16.f16.f16.f16 "
    "{%0, %1, %2, %3, %4, %5, %6, %7, %8, %9, %10, %11, %12, %13, %14, %15, "
    "%16, %17, %18, %19, %20, %21, %22, %23, %24, %25, %26, %27, %28, %29, %30, %31, "
    "%32, %33, %34, %35}, "
    "{%36, %37, %38, %39}, %40, 0, 1, 1, 0;\n"
    : "=r"(d[0]), "=r"(d[1]), "=r"(d[2]), "=r"(d[3]), "=r"(d[4]), "=r"(d[5]), "=r"(d[6]), "=r"(d[7]),
      "=r"(d[8]), "=r"(d[9]), "=r"(d[10]), "=r"(d[11]), "=r"(d[12]), "=r"(d[13]), "=r"(d[14]), "=r"(d[15]),
      "=r"(d[16]), "=r"(d[17]), "=r"(d[18]), "=r"(d[19]), "=r"(d[20]), "=r"(d[21]), "=r"(d[22]), "=r"(d[23]),
      "=r"(d[24]), "=r"(d[25]), "=r"(d[26]), "=r"(d[27]), "=r"(d[28]), "=r"(d[29]), "=r"(d[30]), "=r"(d[31]),
      "=r"(d[32]), "=r"(d[33]), "=r"(d[34]), "=r"(d[35])
    : "r"(a0), "r"(a1), "r"(a2), "r"(a3), "l"(descB));
  else
  asm volatile("wgmma.mma_async.sync.aligned.m64n144k16.f16.f16.f16 "
    "{%0, %1, %2, %3, %4, %5, %6, %7, %8, %9, %10, %11, %12, %13, %14, %15, "
    "%16, %17, %18, %19, %20, %21, %22, %23, %24, %25, %26, %27, %28, %29, %30, %31, "
    "%32, %33, %34, %35}, "
    "{%36, %37, %38, %39}, %40, 1, 1, 1, 0;\n"
    : "+r"(d[0]), "+r"(d[1]), "+r"(d[2]), "+r"(d[3]), "+r"(d[4]), "+r"(d[5]), "+r"(d[6]), "+r"(d[7]),
      "+r"(d[8]), "+r"(d[9]), "+r"(d[10]), "+r"(d[11]), "+r"(d[12]), "+r"(d[13]), "+r"(d[14]), "+r"(d[15]),
      "+r"(d[16]), "+r"(d[17]), "+r"(d[18]), "+r"(d[19]), "+r"(d[20]), "+r"(d[21]), "+r"(d[22]), "+r"(d[23]),
      "+r"(d[24]), "+r"(d[25]), "+r"(d[26]), "+r"(d[27]), "+r"(d[28]), "+r"(d[29]), "+r"(d[30]), "+r"(d[31]),
      "+r"(d[32]), "+r"(d[33]), "+r"(d[34]), "+r"(d[35])
    : "r"(a0), "r"(a1), "r"(a2), "r"(a3), "l"(descB));
}

template <int SCALE_D>
__device__ __forceinline__ void wgmma_n192(uint32_t (&d)[48], uint32_t a0, uint32_t a1, uint32_t a2, uint32_t a3, uint64_t descB) {
  if (SCALE_D == 0)
  asm volatile("wgmma.mma_async.sync.aligned.m64n192k16.f16.f16.f16 "
    "{%0, %1, %2, %3, %4, %5, %6, %7, %8, %9, %10, %11, %12, %13, %14, %15, "
    "%16, %17, %18, %19, %20, %21, %22, %23, %24, %25, %26, %27, %28, %29, %30, %31, "
    "%32, %33, %34, %35, %36, %37, %38, %39, %40, %41, %42, %43, %44, %45, %46, %47}, "
    "{%48, %49, %50, %51}, %52, 0, 1, 1, 0;\n"
    : "=r"(d[0]), "=r"(d[1]), "=r"(d[2]), "=r"(d[3]), "=r"(d[4]), "=r"(d[5]), "=r"(d[6]), "=r"(d[7]),
      "=r"(d[8]), "=r"(d[9]), "=r"(d[10]), "=r"(d[11]), "=r"(d[12]), "=r"(d[13]), "=r"(d[14]), "=r"(d[15]),
      "=r"(d[16]), "=r"(d[17]), "=r"(d[18]), "=r"(d[19]), "=r"(d[20]), "=r"(d[21]), "=r"(d[22]), "=r"(d[23]),
      "=r"(d[24]), "=r"(d[25]), "=r"(d[26]), "=r"(d[27]), "=r"(d[28]), "=r"(d[29]), "=r"(d[30]), "=r"(d[31]),
      "=r"(d[32]), "=r"(d[33]), "=r"(d[34]), "=r"(d[35]), "=r"(d[36]), "=r"(d[37]), "=r"(d[38]), "=r"(d[39]),
      "=r"(d[40]), "=r"(d[41]), "=r"(d[42]), "=r"(d[43]), "=r"(d[44]), "=r"(d[45]), "=r"(d[46]), "=r"(d[47])
    : "r"(a0), "r"(a1), "r"(a2), "r"(a3), "l"(descB));
  else
  asm volatile("wgmma.mma_async.sync.aligned.m64n192k16.f16.f16.f16 "
    "{%0, %1, %2, %3, %4, %5, %6, %7, %8, %9, %10, %11, %12, %13, %14, %15, "
    "%16, %17, %18, %19, %20, %21, %22, %23, %24, %25, %26, %27, %28, %29, %30, %31, "
    "%32, %33, %34, %35, %36, %37, %38, %39, %40, %41, %42, %43, %44, %45, %46, %47}, "
    "{%48, %49, %50, %51}, %52, 1, 1, 1, 0;\n"
    : "+r"(d[0]), "+r"(d[1]), "+r"(d[2]), "+r"(d[3]), "+r"(d[4]), "+r"(d[5]), "+r"(d[6]), "+r"(d[7]),
      "+r"(d[8]), "+r"(d[9]), "+r"(d[10]), "+r"(d[11]), "+r"(d[12]), "+r"(d[13]), "+r"(d[14]), "+r"(d[15]),
      "+r"(d[16]), "+r"(d[17]), "+r"(d[18]), "+r"(d[19]), "+r"(d[20]), "+r"(d[21]), "+r"(d[22]), "+r"(d[23]),
      "+r"(d[24]), "+r"(d[25]), "+r"(d[26]), "+r"(d[27]), "+r"(d[28]), "+r"(d[29]), "+r"(d[30]), "+r"(d[31]),
      "+r"(d[32]), "+r"(d[33]), "+r"(d[34]), "+r"(d[35]), "+r"(d[36]), "+r"(d[37]), "+r"(d[38]), "+r"(d[39]),
      "+r"(d[40]), "+r"(d[41]), "+r"(d[42]), "+r"(d[43]), "+r"(d[44]), "+r"(d[45]), "+r"(d[46]), "+r"(d[47])
    : "r"(a0), "r"(a1), "r"(a2), "r"(a3), "l"(descB));
}

template <int SCALE_D>
__device__ __forceinline__ void wgmma_n56(uint32_t (&d)[14], uint32_t a0, uint32_t a1, uint32_t a2, uint32_t a3, uint64_t descB) {
  if (SCALE_D == 0)
  asm volatile("wgmma.mma_async.sync.aligned.m64n56k16.f16.f16.f16 "
    "{%0, %1, %2, %3, %4, %5, %6, %7, %8, %9, %10, %11, %12, %13}, "
    "{%14, %15, %16, %17}, %18, 0, 1, 1, 0;\n"
    : "=r"(d[0]), "=r"(d[1]), "=r"(d[2]), "=r"(d[3]), "=r"(d[4]), "=r"(d[5]), "=r"(d[6]), "=r"(d[7]),
      "=r"(d[8]), "=r"(d[9]), "=r"(d[10]), "=r"(d[11]), "=r"(d[12]), "=r"(d[13])
    : "r"(a0), "r"(a1), "r"(a2), "r"(a3), "l"(descB));
  else
  asm volatile("wgmma.mma_async.sync.aligned.m64n56k16.f16.f16.f16 "
    "{%0, %1, %2, %3, %4, %5, %6, %7, %8, %9, %10, %11, %12, %13}, "
    "{%14, %15, %16, %17}, %18, 1, 1, 1, 0;\n"
    : "+r"(d[0]), "+r"(d[1]), "+r"(d[2]), "+r"(d[3]), "+r"(d[4]), "+r"(d[5]), "+r"(d[6]), "+r"(d[7]),
      "+r"(d[8]), "+r"(d[9]), "+r"(d[10]), "+r"(d[11]), "+r"(d[12]), "+r"(d[13])
    : "r"(a0), "r"(a1), "r"(a2), "r"(a3), "l"(descB));
}

template <int SCALE_D>
__device__ __forceinline__ void wgmma_n48t(uint32_t (&d)[12], uint32_t a0, uint32_t a1, uint32_t a2, uint32_t a3, uint64_t descB) {
  if (SCALE_D == 0)
  asm volatile("wgmma.mma_async.sync.aligned.m64n48k16.f16.f16.f16 "
    "{%0, %1, %2, %3, %4, %5, %6, %7, %8, %9, %10, %11}, "
    "{%12, %13, %14, %15}, %16, 0, 1, 1, 1;\n"
    : "=r"(d[0]), "=r"(d[1]), "=r"(d[2]), "=r"(d[3]), "=r"(d[4]), "=r"(d[5]), "=r"(d[6]), "=r"(d[7]),
      "=r"(d[8]), "=r"(d[9]), "=r"(d[10]), "=r"(d[11])
    : "r"(a0), "r"(a1), "r"(a2), "r"(a3), "l"(descB));
  else
  asm volatile("wgmma.mma_async.sync.aligned.m64n48k16.f16.f16.f16 "
    "{%0, %1, %2, %3, %4, %5, %6, %7, %8, %9, %10, %11}, "
    "{%12, %13, %14, %15}, %16, 1, 1, 1, 1;\n"
    : "+r"(d[0]), "+r"(d[1]), "+r"(d[2]), "+r"(d[3]), "+r"(d[4]), "+r"(d[5]), "+r"(d[6]), "+r"(d[7]),
      "+r"(d[8]), "+r"(d[9]), "+r"(d[10]), "+r"(d[11])
    : "r"(a0), "r"(a1), "r"(a2), "r"(a3), "l"(descB));
}

__global__ void __launch_bounds__(384) prepack_kernel(const __nv_bfloat16* __restrict__ wqkv, const __nv_bfloat16* __restrict__ wo) {
  asm volatile("griddepcontrol.launch_dependents;");
  __half* dst = reinterpret_cast<__half*>(g_wpack);
  const int c = threadIdx.x, nb = blockIdx.x * 2 + threadIdx.y;
  if (nb < 72) {
    __shared__ float red2[2][6][8];
    float (*red)[8] = red2[threadIdx.y];
    const int h = nb / 18, j = nb % 18, part = j / 6;
    const int col = (part == 0 ? 192 : part == 1 ? 0 : 384) + h * 48 + (j % 6) * 8;
    uint4 raw = *reinterpret_cast<const uint4*>(wqkv + c * 576 + col);
    uint32_t u[4] = {raw.x, raw.y, raw.z, raw.w};
    float v[8];
#pragma unroll
    for (int i = 0; i < 4; i++) { v[2 * i] = lo2f(u[i]); v[2 * i + 1] = hi2f(u[i]); }
#pragma unroll
    for (int i = 0; i < 8; i++) {
      float s = v[i];
#pragma unroll
      for (int o = 16; o; o >>= 1) s += __shfl_xor_sync(~0u, s, o);
      if ((c & 31) == 0) red[c >> 5][i] = s;
    }
    __syncthreads();
    const int cc = c >> 5, q = (c >> 3) & 3, s1 = (c >> 2) & 1, hh = (c >> 1) & 1, e = c & 1;
    const int base = qkv_pos(h, 2 * cc + s1) / 2 + j * 128 + hh * 64 + 2 * q + e;
#pragma unroll
    for (int n = 0; n < 8; n++) {
      float m = (red[0][n] + red[1][n] + red[2][n] + red[3][n] + red[4][n] + red[5][n]) * (1.0f / 192.0f);
      dst[base + n * 8] = __float2half_rn((v[n] - m) * (part == 1 ? 0.14433756729740643f * 1.4426950408889634f : 1.0f));
    }
  } else {
    const int jb = nb - 72;
    const int s = c >> 4, hh = (c >> 3) & 1, kk = c & 7;
    const int base = wo_pos(s) / 2 + jb * 128 + hh * 64 + kk;
#pragma unroll
    for (int n = 0; n < 8; n++) {
      const int ch = 32 * (jb >> 2) + 8 * (n >> 1) + 2 * (jb & 3) + (n & 1);
      dst[base + n * 8] = __float2half_rn(__bfloat162float(wo[c * 192 + ch]));
    }
  }
}

__device__ __forceinline__ int window_of(int round, int nfull, int cta, int ncta, int wg) {
  if (round < nfull) return round * 2 * ncta + 2 * cta + wg;
  const int rem = NWIN - nfull * 2 * ncta;
  const int i = cta + wg * ncta;
  return i < rem ? nfull * 2 * ncta + i : -1;
}

template <int S0 = 0, int S1 = 12>
__device__ __forceinline__ void mma_qkv(uint32_t (&acc)[36], const uint32_t (&A)[48], const uint64_t* d) {
#pragma unroll
  for (int s = S0; s < S1; s++) {
    if (s == 0) wgmma_n144<0>(acc, A[4 * s], A[4 * s + 1], A[4 * s + 2], A[4 * s + 3], d[s]);
    else        wgmma_n144<1>(acc, A[4 * s], A[4 * s + 1], A[4 * s + 2], A[4 * s + 3], d[s]);
  }
  wg_commit();
}
__device__ __forceinline__ void mma_proj(uint32_t (&acc)[48], const uint32_t (&A)[12], const uint64_t* d) {
#pragma unroll
  for (int s = 0; s < 3; s++) wgmma_n192<1>(acc, A[4 * s], A[4 * s + 1], A[4 * s + 2], A[4 * s + 3], d[s]);
}
__device__ __forceinline__ void mma_s(uint32_t (&S)[14], const uint32_t (&Q)[12], const uint64_t* d) {
  wgmma_n56<0>(S, Q[0], Q[1], Q[2], Q[3], d[0]);
  wgmma_n56<1>(S, Q[4], Q[5], Q[6], Q[7], d[1]);
  wgmma_n56<1>(S, Q[8], Q[9], Q[10], Q[11], d[2]);
}
__device__ __forceinline__ void mma_pv(uint32_t (&O)[12], const uint32_t (&P)[12], const uint64_t* d) {
  wgmma_n48t<0>(O, P[0], P[1], P[2], P[3], d[0]);
  wgmma_n48t<1>(O, P[4], P[5], P[6], P[7], d[1]);
  wgmma_n48t<1>(O, P[8], P[9], P[10], P[11], d[2]);
}

#define PIN() asm volatile("pmevent 0;" ::: "memory")
template <int A, int B> __device__ __forceinline__ void hold(uint32_t* v) {
#pragma unroll
  for (int i = A; i < B; i++) asm volatile("" : "+r"(v[i]));
}
__device__ __forceinline__ void stsm12(const uint32_t* v, uint32_t addr) {
#pragma unroll
  for (int j = 0; j < 3; j++) stsm4(addr + 2 * j * KV_PITCH, v[4 * j], v[4 * j + 1], v[4 * j + 2], v[4 * j + 3]);
}
__device__ __forceinline__ void load_v48(uint32_t (&v)[6], uint32_t addr) {
  asm volatile("ldmatrix.sync.aligned.m8n8.x4.shared.b16 {%0,%1,%2,%3}, [%4];" : "=r"(v[0]), "=r"(v[1]), "=r"(v[2]), "=r"(v[3]) : "r"(addr) : "memory");
  asm volatile("ldmatrix.sync.aligned.m8n8.x2.shared.b16 {%0,%1}, [%2];" : "=r"(v[4]), "=r"(v[5]) : "r"(addr + 4 * KV_PITCH) : "memory");
}
__device__ __forceinline__ void finish_o(const uint32_t (&O)[12], const uint32_t (&v)[6], uint32_t p48, uint32_t inv, uint32_t (&Of)[12]) {
#pragma unroll
  for (int i = 0; i < 12; i++) {
    const uint32_t t = h2u(__hfma2(u2h(v[i >> 1]), (i & 1) ? hcast<1>(p48) : hcast<0>(p48), u2h(O[i])));
    Of[i] = (i & 1) ? fmul_b<1>(t, inv) : fmul_b<0>(t, inv);
  }
  hold<0, 12>(Of);
}
template <int A, int B>
__device__ __forceinline__ void ln_sums(const uint32_t (&X)[48], float (&s1)[2], float (&s2)[2]) {
#pragma unroll
  for (int i = A; i < B; i++) {
    const float2 f = __half22float2(u2h(X[i]));
    s1[i & 1] = i < 2 ? f.x + f.y : s1[i & 1] + (f.x + f.y);
    s2[i & 1] = fmaf(f.x, f.x, i < 2 ? f.y * f.y : fmaf(f.y, f.y, s2[i & 1]));
  }
  asm volatile("" : "+f"(s1[0]), "+f"(s1[1]), "+f"(s2[0]), "+f"(s2[1]));
}
__device__ __forceinline__ uint32_t ln_rstd(const float (&s1)[2], const float (&s2)[2]) {
  float r[2];
#pragma unroll
  for (int a = 0; a < 2; a++) {
    float m = s1[a], v = s2[a];
    m += __shfl_xor_sync(~0u, m, 1); v += __shfl_xor_sync(~0u, v, 1);
    m += __shfl_xor_sync(~0u, m, 2); v += __shfl_xor_sync(~0u, v, 2);
    m *= 1.0f / 192.0f;
    v = fmaxf(fmaf(v, 1.0f / 192.0f, -m * m), 0.f) + 1e-5f;
    asm("rsqrt.approx.ftz.f32 %0, %1;" : "=f"(r[a]) : "f"(v));
  }
  uint32_t rk = packh(r[0], r[1]);
  hold<0, 1>(&rk);
  return rk;
}
__device__ __forceinline__ void scale12(uint32_t (&D)[12], const uint32_t* a, uint32_t r) {
#pragma unroll
  for (int i = 0; i < 12; i++) D[i] = (i & 1) ? fmul_b<1>(a[i], r) : fmul_b<0>(a[i], r);
  hold<0, 12>(D);
}
template <int CC>
__device__ __forceinline__ void store_out(const uint32_t (&Y)[48], uint8_t* o0, uint8_t* o1, uint32_t vmask) {
  uint32_t T[8];
#pragma unroll
  for (int i = 0; i < 8; i++) {
    const float2 f = __half22float2(u2h(Y[8 * CC + i]));
    T[i] = pack2(f.x, f.y);
  }
  asm volatile("{\n.reg .pred p;\nsetp.ne.u32 p, %5, 0;\n@p st.global.v4.u32 [%0], {%1,%2,%3,%4};\n}\n"
               :: "l"(o0 + CC * 64), "r"(T[0]), "r"(T[2]), "r"(T[4]), "r"(T[6]), "r"(vmask) : "memory");
  asm volatile("{\n.reg .pred p;\nsetp.lt.s32 p, %5, 0;\n@p st.global.v4.u32 [%0], {%1,%2,%3,%4};\n}\n"
               :: "l"(o1 + CC * 64), "r"(T[1]), "r"(T[3]), "r"(T[5]), "r"(T[7]), "r"(vmask) : "memory");
}
__device__ __forceinline__ void proxy_fence() { asm volatile("fence.proxy.async.shared::cta;" ::: "memory"); }
__device__ __forceinline__ uint32_t fadd2(uint32_t a, uint32_t b) { return h2u(__hadd2_rn(u2h(a), u2h(b))); }
__device__ __forceinline__ void row_max(const uint32_t (&S)[14], uint32_t& k48, uint32_t& mx) {
  k48 = __shfl_sync(~0u, __byte_perm(S[12], S[13], 0x5410), 0, 4);
  const uint32_t m0 = fmax2(fmax2(fmax2(S[0], S[2]), S[4]), fmax2(fmax2(S[6], S[8]), S[10]));
  const uint32_t m1 = fmax2(fmax2(fmax2(S[1], S[3]), S[5]), fmax2(fmax2(S[7], S[9]), S[11]));
  mx = fmax2(__byte_perm(m0, m1, 0x5410), __byte_perm(m0, m1, 0x7632));
  mx = fmax2(mx, __shfl_xor_sync(~0u, mx, 1));
  mx = fmax2(fmax2(mx, __shfl_xor_sync(~0u, mx, 2)), k48);
  hold<0, 1>(&mx);
}
__device__ __forceinline__ void row_exp(const uint32_t (&S)[14], uint32_t k48, uint32_t mx, uint32_t (&P)[12], uint32_t& p48, uint32_t& l) {
#pragma unroll
  for (int j = 0; j < 12; j++) P[j] = fex2((j & 1) ? fsub_b<1>(S[j], mx) : fsub_b<0>(S[j], mx));
  p48 = fex2(h2u(__hsub2_rn(u2h(k48), u2h(mx))));
  const uint32_t s0 = fadd2(fadd2(fadd2(P[0], P[2]), fadd2(P[4], P[6])), fadd2(P[8], P[10]));
  const uint32_t s1 = fadd2(fadd2(fadd2(P[1], P[3]), fadd2(P[5], P[7])), fadd2(P[9], P[11]));
  l = fadd2(__byte_perm(s0, s1, 0x5410), __byte_perm(s0, s1, 0x7632));
  hold<0, 12>(P); hold<0, 1>(&p48); hold<0, 1>(&l);
}
__device__ __forceinline__ uint32_t row_scale(uint32_t l, uint32_t p48, uint32_t vmask) {
  l = fadd2(l, __shfl_xor_sync(~0u, l, 1));
  l = fadd2(fadd2(l, __shfl_xor_sync(~0u, l, 2)), p48);
  float i0, i1;
  asm("rcp.approx.ftz.f32 %0, %1;" : "=f"(i0) : "f"(__low2float(u2h(l))));
  asm("rcp.approx.ftz.f32 %0, %1;" : "=f"(i1) : "f"(__high2float(u2h(l))));
  uint32_t inv = packh(i0, i1) & vmask;
  hold<0, 1>(&inv);
  return inv;
}
template <int S0, int S1>
__device__ __forceinline__ void load_x(uint32_t (&X)[48], uint32_t t0) {
#pragma unroll
  for (int s = S0; s < S1; s++)
    asm volatile("ld.shared.v4.u32 {%0,%1,%2,%3}, [%4];" : "=r"(X[4 * s]), "=r"(X[4 * s + 1]), "=r"(X[4 * s + 2]), "=r"(X[4 * s + 3])
                 : "r"(((s & 1) ? (t0 ^ 16) : t0) + (s >> 1) * 128) : "memory");
}

#define WDIV 1
template <int P, int CNT, int DIV = WDIV> __device__ __forceinline__ void load_slices(uint32_t sb, const Descs& ds) {
  constexpr int st = stage_of(P);
  constexpr bool first = P == 0 || stage_of(P - 1) != st;
  if (first)
    asm volatile("{\n.reg .pred p;\nelect.sync _|p, 0xffffffff;\n@p mbarrier.arrive.expect_tx.shared::cta.b64 _, [%0], %1;\n}\n"
                 :: "r"(sb + BAR_WFULL + 8 * st), "n"((st < 4 ? 3 : st == 4 ? 2 : 1) * SLICE / DIV) : "memory");
  asm volatile("{\n.reg .pred p;\nelect.sync _|p, 0xffffffff;\n"
               "@p cp.async.bulk.shared::cluster.global.mbarrier::complete_tx::bytes [%0], [%1], %2, [%3];\n}\n"
               :: "r"(sb + OFF_W + (P & 7) * SLICE), "l"(ds.src[P]), "n"(CNT * SLICE / DIV), "r"(sb + BAR_WFULL + 8 * st) : "memory");
}
__device__ __forceinline__ void warp_arrive(uint32_t bar) {
  asm volatile("{\n.reg .pred p;\nelect.sync _|p, 0xffffffff;\n@p mbarrier.arrive.shared::cta.b64 _, [%0];\n}\n" :: "r"(bar) : "memory");
}

__global__ void __launch_bounds__(384, 1)
fused_kernel(const __grid_constant__ CUtensorMap tmx, const __grid_constant__ CUtensorMap tmp, const __grid_constant__ Descs ds, const __nv_bfloat16* __restrict__ dw, __nv_bfloat16* __restrict__ out, const int never) {
  extern __shared__ __align__(1024) uint8_t smem[];
  const uint32_t sb = (uint32_t)__cvta_generic_to_shared(smem);
  const int tid = threadIdx.x, lane = tid & 31;
  const int warp = __shfl_sync(0xffffffffu, tid >> 5, 0);
  const int cta = blockIdx.x, ncta = gridDim.x;
  const int nfull = NWIN / (2 * ncta);
  const int nrounds = nfull + ((NWIN - nfull * 2 * ncta) > cta ? 1 : 0);

  if (warp == 0) GTS(0);
  auto prefetch_round = [&](int r) {
#pragma unroll
    for (int k = 0; k < 2; k++) {
      const int w = window_of(r, nfull, cta, ncta, k);
      if (w >= 0) {
        const int a = w / NWX;
        asm volatile("{\n.reg .pred p;\nelect.sync _|p, 0xffffffff;\n@p cp.async.bulk.prefetch.tensor.3d.L2.global [%0, {0, %1, %2}];\n}\n"
                     :: "l"(reinterpret_cast<uint64_t>(&tmp)), "r"((w - a * NWX) * 7 - 1), "r"(a * 7 - 1) : "memory");
      }
    }
  };
  if (warp == 11) prefetch_round(0);
  if (warp == 10 && lane == 0) asm volatile("prefetch.tensormap [%0];" :: "l"(reinterpret_cast<uint64_t>(&tmx)) : "memory");
  if (tid == 0) {
    if ((sb & 0x3FFFF) != SMEM_BASE) __trap();
    for (int i = 0; i < 7; i++) { mbar_init(sb + BAR_WFULL + 8 * i, 1); mbar_init(sb + BAR_WEMPTY + 8 * i, 8); }
    for (int i = 0; i < 9; i++) mbar_init(sb + BAR_XFULL + 8 * i, 1);
    mbar_init(sb + BAR_TFULL, 3);
    mbar_init(sb + BAR_TEMPTY, 8);
    asm volatile("fence.mbarrier_init.release.cluster;" ::: "memory");
  }
  if (tid >= 128 && tid < 320) {
    *reinterpret_cast<uint32_t*>(smem + OFF_ZERO + (tid - 128) * 4) = 0;
  }
  __syncthreads();

  if (warp >= 8) {
    asm volatile("setmaxnreg.dec.sync.aligned.u32 " PREGS ";");
    if (warp == 11) {
      asm volatile("griddepcontrol.wait;" ::: "memory");
      load_slices<1, 3, 1>(sb, ds); load_slices<0, 1, 1>(sb, ds); load_slices<4, 1, 1>(sb, ds); load_slices<5, 3, 1>(sb, ds);
      for (int r = 0; r < nrounds; r++) {
        const uint32_t par = r & 1;
        const bool next_round = r + 1 < nrounds;
        mbar_wait(sb + BAR_WEMPTY + 40, par); load_slices<8, 1>(sb, ds);
        mbar_wait(sb + BAR_WEMPTY, par);      load_slices<9, 2>(sb, ds); load_slices<11, 1>(sb, ds);
        mbar_wait(sb + BAR_WEMPTY + 48, par); load_slices<12, 1>(sb, ds);
        mbar_wait(sb + BAR_WEMPTY + 8, par);  load_slices<13, 1>(sb, ds); load_slices<14, 2>(sb, ds);
        mbar_wait(sb + BAR_WEMPTY + 16, par); load_slices<0, 1>(sb, ds); if (next_round) load_slices<1, 2>(sb, ds);
        mbar_wait(sb + BAR_WEMPTY + 24, par);
        if (next_round) load_slices<3, 1>(sb, ds);
        load_slices<4, 1>(sb, ds);
        if (next_round) {
          load_slices<5, 1>(sb, ds);
          mbar_wait(sb + BAR_WEMPTY + 32, par); load_slices<6, 2>(sb, ds);
        }
      }
    } else {
      const int cw = warp - 8;
      const int win = lane >> 4;
      const int ch0 = cw * 64 + (lane & 15) * 4;
      uint32_t wt[9][2];
#pragma unroll
      for (int t = 0; t < 9; t++) {
        uint2 v = *reinterpret_cast<const uint2*>(dw + t * CH + ch0);
        wt[t][0] = v.x; wt[t][1] = v.y;
      }
      const uint32_t xs = sb + OFF_X + cw * 3 * XSLOT;
      const uint32_t xld = xs + (lane >> 4) * 1152 + (lane & 15) * 8;
      const uint32_t xbar = sb + BAR_XFULL + cw * 24;
      const uint32_t st0 = sb + OFF_TILE + win * TILE_BYTES + ch0 * 4;
      const uint32_t st1 = sb + OFF_TILE + win * TILE_BYTES + ((ch0 * 4) ^ 16);
      const uint64_t tm = reinterpret_cast<uint64_t>(&tmx);
      int cx0, cy0, cx1, cy1;
      auto coords = [&](int r) {
        const int w0 = window_of(r, nfull, cta, ncta, 0);
        int w1 = window_of(r, nfull, cta, ncta, 1);
        if (w1 < 0) w1 = w0;
        const int a = w0 / NWX, b = w1 / NWX;
        cx0 = (w0 - a * NWX) * 7 - 1; cy0 = a * 7 - 1;
        cx1 = (w1 - b * NWX) * 7 - 1; cy1 = b * 7 - 1;
      };
      auto issue = [&](int slot, int dy) {
        asm volatile("{\n.reg .pred p;\nelect.sync _|p, 0xffffffff;\n"
                     "@p mbarrier.arrive.expect_tx.shared::cta.b64 _, [%2], %8;\n"
                     "@p cp.async.bulk.tensor.3d.shared::cluster.global.mbarrier::complete_tx::bytes [%0], [%1, {%3, %4, %5}], [%2];\n"
                     "@p cp.async.bulk.tensor.3d.shared::cluster.global.mbarrier::complete_tx::bytes [%0 + 1152], [%1, {%3, %6, %7}], [%2];\n}\n"
                     :: "r"(xs + slot * XSLOT), "l"(tm), "r"(xbar + slot * 8), "r"(cw * 64), "r"(cx0), "r"(cy0 + dy), "r"(cx1), "r"(cy1 + dy), "n"(XSLOT) : "memory");
      };
      coords(0);
      issue(0, 0); issue(1, 1); issue(2, 2);
      for (int r = 0; r < nrounds; r++) {
        const bool more = r + 1 < nrounds;
        uint32_t accA[7][2], accB[7][2], ctr[7][2], held[2];
#pragma unroll
        for (int i = 0; i < 9; i++) {
          mbar_wait(xbar + (i % 3) * 8, (r + i / 3) & 1);
          if (i == 0 && r == 0 && cw == 0) GTS(7);
          if (i == 7 && more) coords(r + 1);
          if (i == 0) { if (r > 0) issue(2, 2); }
          else if (i < 7) issue((i + 2) % 3, i + 2);
          else if (more) issue((i + 2) % 3, i - 7);
          if (i == 2 && r > 0) mbar_wait(sb + BAR_TEMPTY, (r - 1) & 1);
          if (i == 2 && cw == 0 && r == 2) GTS(1);
          if (i == 2 && cw == 0 && r == 3) GTS(3);
          if (i == 2) { TR(0); }
          uint32_t cur[9][2];
#pragma unroll
          for (int p = 0; p < 5; p++)
            asm volatile("ld.shared.v2.u32 {%0,%1}, [%2];" : "=r"(cur[p][0]), "=r"(cur[p][1]) : "r"(xld + (i % 3) * XSLOT + p * 128));
#pragma unroll
          for (int j = 0; j < 7; j++) {
            if (j >= 1 && j + 4 < 9)
              asm volatile("ld.shared.v2.u32 {%0,%1}, [%2];" : "=r"(cur[j + 4][0]), "=r"(cur[j + 4][1]) : "r"(xld + (i % 3) * XSLOT + (j + 4) * 128));
            if (i >= 2) {
              uint32_t o[2];
#pragma unroll
              for (int e = 0; e < 2; e++) {
                uint32_t a = hfma(cur[j][e], wt[6][e], accA[j][e]);
                a = hfma(cur[j + 1][e], wt[7][e], a);
                a = hfma(cur[j + 2][e], wt[8][e], a);
                a = hadd(ctr[j][e], a);
                o[e] = packh(lo2f(a), hi2f(a));
              }
              const int tok = (i - 2) * 7 + j, ps = tok >> 1;
              if (!(tok & 1)) { held[0] = o[0]; held[1] = o[1]; }
              if (tok == 48) o[0] = o[1] = 0;
              if ((tok & 1) || tok == 48)
                asm volatile("st.shared.v4.u32 [%0], {%1,%2,%3,%4};" :: "r"(((ps & 1) ? st1 : st0) + ps * 768), "r"(held[0]), "r"(o[0]), "r"(held[1]), "r"(o[1]) : "memory");
            }
#pragma unroll
            for (int e = 0; e < 2; e++) {
              if (i >= 1 && i <= 7) {
                uint32_t a = hfma(cur[j][e], wt[3][e], accB[j][e]);
                a = hfma(cur[j + 1][e], wt[4][e], a);
                accA[j][e] = hfma(cur[j + 2][e], wt[5][e], a);
                ctr[j][e] = cur[j + 1][e];
              }
              if (i <= 6) {
                uint32_t a = hmul(cur[j][e], wt[0][e]);
                a = hfma(cur[j + 1][e], wt[1][e], a);
                accB[j][e] = hfma(cur[j + 2][e], wt[2][e], a);
              }
            }
          }
        }
        __syncwarp();
        if (lane == 0) mbar_arrive(sb + BAR_TFULL);
        TR(1);
      }
    }
  } else {
    asm volatile("setmaxnreg.inc.sync.aligned.u32 " CREGS ";");
    const int wg = warp >> 2, w4 = warp & 3, g = lane >> 2, q = lane & 3;
    const int row0 = w4 * 16 + g, row1 = row0 + 8;
    const int ps = min(w4 * 8 + g, 24);
    const int tok0 = 2 * ps, tok1 = min(2 * ps + 1, 48);
    const uint32_t kv = sb + OFF_KV + wg * KV_BYTES;
    const int srow = w4 * 16 + (lane & 15);
    const uint32_t vst = kv + (lane >> 4) * KV_PITCH + (srow < 56 ? srow : min(srow - 7, 55)) * 16;
    uint32_t misc = ((uint32_t)((tok1 / 7) * IMG + tok1 % 7) << 20) | ((uint32_t)((tok0 / 7) * IMG + tok0 % 7) << 8) | (ps * 4 + q);
    const uint32_t v48 = kv + (lane >> 3) * KV_PITCH + 48 * 16;
    const uint32_t vmask = (row0 < 49 ? 0xffffu : 0u) | (row1 < 49 ? 0xffff0000u : 0u);

    const uint32_t tx = sb + q * 32 + (row0 < 49 ? OFF_TILE + wg * TILE_BYTES + ps * 768 + (ps & 1) * 16 : OFF_ZERO + 16);
    const int myrounds = window_of(nrounds - 1, nfull, cta, ncta, wg) < 0 ? nrounds - 1 : nrounds;

    if (never == 2) return;
    uint32_t H[48], Y[48];
    const uint64_t* dkv = ds.kv[wg];
    uint32_t P[12], Ofc[12], p48 = 0x3c003c00u, lsum = 0;
#pragma unroll
    for (int i = 0; i < 48; i++) Y[i] = 0;
#pragma unroll
    for (int i = 0; i < 12; i++) P[i] = Ofc[i] = 0;
    mbar_wait(sb + BAR_TFULL, 0);
    if (warp == 0) GTS(4);
    load_x<0, 12>(H, tx);
    warp_arrive(sb + BAR_TEMPTY);
    if (wg == 1) turn_pass(1);

    uint8_t *o0, *o1;
    uint32_t omask;
    auto out_setup = [&](int r) {
      omask = r >= 0 ? vmask : 0u;
      const int w = window_of(r, nfull, cta, ncta, wg);
      const int wy = w / NWX, wx = w - wy * NWX;
      asm volatile("" : "+r"(misc));
      const uint32_t wb = (uint32_t)(wy * 7 * IMG + wx * 7) * 384u + (misc & 3) * 16;
      o0 = reinterpret_cast<uint8_t*>(out) + (wb + ((misc >> 8) & 0xfff) * 384u);
      o1 = reinterpret_cast<uint8_t*>(out) + (wb + (misc >> 20) * 384u);
    };
#define OUT(c) store_out<c>(Y, o0, o1, omask)
    auto release = [&](int stage) { warp_arrive(sb + BAR_WEMPTY + 8 * stage); };

    for (int r = 0;; r++) {
      const uint32_t par = r & 1;
      uint32_t acc[36], S[14], O[12], Q[12], V[12], Ofa[12], Ofb[12], vr[6], inv, k48, mx;
      if (r == myrounds) {
        const bool idle = r < nrounds;
        mbar_wait(sb + BAR_WFULL + 40, par);
        turn_wait(wg);
        wg_fence(); mma_pv(O, P, dkv + 4); mma_proj(Y, Ofc, ds.p + 6); wg_commit();
        turn_pass(wg);
        load_v48(vr, v48);
        inv = row_scale(lsum, p48, vmask);
        wg_wait<0>(); keep(O); keep(Y);
        finish_o(O, vr, p48, inv, Ofa);
        if (idle) { release(5); release(0); release(1); release(2); release(3); }
        mbar_wait(sb + BAR_WFULL + 48, par);
        turn_wait(wg);
        wg_fence(); mma_proj(Y, Ofa, ds.p + 9); wg_commit();
        if (wg == 0 || idle) turn_pass(wg);
        wg_wait<0>(); keep(Y);
        if (idle) { release(6); turn_wait(wg); turn_pass(wg); }
        out_setup(r - 1);
        OUT(0); PIN(); OUT(1); PIN(); OUT(2); PIN(); OUT(3); PIN(); OUT(4); PIN(); OUT(5);
        if (idle) {
          turn_wait(wg); turn_pass(wg);
          turn_wait(wg); turn_pass(wg);
          turn_wait(wg); turn_pass(wg);
          turn_wait(wg);
        }
        if (w4 == 0) GTS(5 + wg);
        break;
      }
      float s1[2], s2[2];
      if (SA > 0) ln_sums<0, SA>(H, s1, s2);
      mbar_wait(sb + BAR_WFULL + 40, par);
      mbar_wait(sb + BAR_WFULL, par);
      TR(0);
      turn_wait(wg);
      TR(1);
      wg_fence(); mma_pv(O, P, dkv + 4); mma_proj(Y, Ofc, ds.p + 6); wg_commit(); mma_qkv<0, 3>(acc, H, ds.q[0]);
      PIN();
      load_v48(vr, v48);
      inv = row_scale(lsum, p48, vmask);
      ln_sums<SA, SB>(H, s1, s2);
      PIN();
      wg_fence(); mma_qkv<3, 8>(acc, H, ds.q[0]);
      PIN();
      ln_sums<SB, SC>(H, s1, s2);
      PIN();
      wg_fence(); mma_qkv<8, 12>(acc, H, ds.q[0]);
      turn_pass(wg);
      TR(2);
      wg_wait<3>(); keep(O); keep(Y);
      release(5);
      bar_sync(1 + wg);
      PIN();
      finish_o(O, vr, p48, inv, Ofa);
      if (SC < 48) ln_sums<SC, 48>(H, s1, s2);
      const uint32_t rk = ln_rstd(s1, s2);
      PIN();
      TR(3);
      wg_wait<0>(); keep(acc);
      TR(4);
      release(0);
      scale12(V, acc, rk); stsm12(V, vst + KV_KOFF);
      scale12(V, acc + 24, rk); stsm12(V, vst);
      scale12(Q, acc + 12, rk); PIN();
      proxy_fence();
      mbar_wait(sb + BAR_WFULL + 48, par);
      mbar_wait(sb + BAR_WFULL + 8, par);
      TR(5);
      turn_wait(wg);
      TR(6);
      wg_fence(); mma_proj(Y, Ofa, ds.p + 9); wg_commit(); mma_s(S, Q, dkv); mma_qkv<0, 2>(acc, H, ds.q[1]);
      out_setup(r - 1);
      PIN();
      wg_wait<1>(); keep(Y);
      release(6);
      wg_fence(); mma_qkv<2, 6>(acc, H, ds.q[1]);
      PIN();
      OUT(0);
      PIN();
      wg_wait<1>(); keep(S);
      wg_fence(); mma_qkv<6, 9>(acc, H, ds.q[1]);
      PIN();
      row_max(S, k48, mx);
      OUT(1);
      PIN();
      wg_fence(); mma_qkv<9, 12>(acc, H, ds.q[1]);
      turn_pass(wg);
      PIN();
      OUT(2); PIN();
      OUT(3); PIN();
      row_exp(S, k48, mx, P, p48, lsum);
      PIN();
      TR(7);
      wg_wait<0>(); keep(acc);
      TR(8);
      release(1);
      bar_sync(1 + wg);
      scale12(V, acc, rk); stsm12(V, vst + KV_KOFF);
      scale12(Q, acc + 12, rk); scale12(V, acc + 24, rk); PIN();
      proxy_fence();
#define TURN(ID, OF, G1, G2, G3, X1)                                                       \
      TR(ID + 1);                                                                       \
      turn_wait(wg);                                                                    \
      wg_fence(); mma_pv(O, P, dkv + 4); mma_s(S, Q, dkv); wg_commit(); G1;             \
      PIN();                                                                            \
      TR(ID + 2);                                                                       \
      load_v48(vr, v48);                                                                \
      inv = row_scale(lsum, p48, vmask);                                               \
      X1;                                                                               \
      PIN();                                                                            \
      wg_wait<1>(); keep(S); keep(O);                                                   \
      bar_sync(1 + wg);                                    \
      wg_fence(); G2;                                                                   \
      PIN();                                                                            \
      stsm12(V, vst);                                                                   \
      finish_o(O, vr, p48, inv, OF);                                                    \
      row_max(S, k48, mx);                                                              \
      PIN();                                                                            \
      wg_fence(); G3;                                                                   \
      turn_pass(wg);                                                                    \
      PIN();                                                                            \
      TR(ID + 3);
#define NEXT_HEAD(ID, HD)                                                               \
      row_exp(S, k48, mx, P, p48, lsum);                                                \
      PIN();                                                                            \
      TR(ID + 4);                                                                       \
      wg_wait<0>(); keep(acc);                                                          \
      release(HD);                                                                      \
      scale12(V, acc, rk); stsm12(V, vst + KV_KOFF);                                    \
      scale12(Q, acc + 12, rk); scale12(V, acc + 24, rk); PIN();
      mbar_wait(sb + BAR_WFULL + 16, par);
      TURN(8, Ofa, (mma_qkv<0, KA>(acc, H, ds.q[2])), (mma_qkv<KA, KB>(acc, H, ds.q[2])), (mma_qkv<KB, 12>(acc, H, ds.q[2])), OUT(4))
      OUT(5); PIN();
      NEXT_HEAD(8, 2)
      proxy_fence();
      mbar_wait(sb + BAR_WFULL + 24, par);
      TURN(12, Ofb, (mma_qkv<0, KA>(acc, H, ds.q[3])), (mma_qkv<KA, KB>(acc, H, ds.q[3])), (mma_qkv<KB, 12>(acc, H, ds.q[3])), )
      NEXT_HEAD(12, 3)
#pragma unroll
      for (int i = 0; i < 48; i++) Y[i] = (i & 1) ? H[i] ^ never : H[i] + never;
      hold<0, 48>(Y); PIN();
      proxy_fence();
      mbar_wait(sb + BAR_WFULL + 32, par);
      TR(17);
      turn_wait(wg);
      wg_fence(); mma_pv(O, P, dkv + 4); mma_s(S, Q, dkv); wg_commit(); mma_proj(Y, Ofa, ds.p); mma_proj(Y, Ofb, ds.p + 3); wg_commit();
      turn_pass(wg);
      PIN();
      TR(18);
      load_v48(vr, v48);
      inv = row_scale(lsum, p48, vmask);
      if (r + 1 < myrounds) mbar_wait(sb + BAR_TFULL, par ^ 1);
      load_x<0, 4>(H, tx);
      wg_wait<1>(); keep(S); keep(O);
      bar_sync(1 + wg);
      PIN();
      TR(19);
      row_max(S, k48, mx);
      finish_o(O, vr, p48, inv, Ofc);
      stsm12(V, vst);
      PIN();
      load_x<4, 8>(H, tx);
      row_exp(S, k48, mx, P, p48, lsum);
      PIN();
      load_x<8, 12>(H, tx);
      warp_arrive(sb + BAR_TEMPTY);
      TR(20);
      wg_wait<0>(); keep(Y);
      release(4);
      proxy_fence();
      TR(21);
#undef TURN
#undef NEXT_HEAD
    }
  }
}

typedef CUresult (*EncodeFn)(CUtensorMap*, CUtensorMapDataType, cuuint32_t, void*, const cuuint64_t*, const cuuint64_t*,
                             const cuuint32_t*, const cuuint32_t*, CUtensorMapInterleave, CUtensorMapSwizzle,
                             CUtensorMapL2promotion, CUtensorMapFloatOOBfill);

}

extern "C" void kernel_launch(void* const* d_in, const int* in_sizes, int n_in, void* d_out, int out_size) {
  const __nv_bfloat16* x = (const __nv_bfloat16*)d_in[0];
  const __nv_bfloat16* dw = (const __nv_bfloat16*)d_in[1];
  const __nv_bfloat16* wqkv = (const __nv_bfloat16*)d_in[2];
  const __nv_bfloat16* wo = (const __nv_bfloat16*)d_in[3];
  static EncodeFn encode = nullptr;
  static int nsm = 0;
  static void* wpack = nullptr;
  if (!encode) {
    void* fn = nullptr;
    cudaDriverEntryPointQueryResult qr;
    cudaGetDriverEntryPoint("cuTensorMapEncodeTiled", &fn, cudaEnableDefault, &qr);
    encode = (EncodeFn)fn;
    int dev = 0;
    cudaGetDevice(&dev);
    cudaDeviceGetAttribute(&nsm, cudaDevAttrMultiProcessorCount, dev);
    cudaGetSymbolAddress(&wpack, g_wpack);
    cudaFuncSetAttribute(fused_kernel, cudaFuncAttributeMaxDynamicSharedMemorySize, SMEM_BYTES);
  }
  CUtensorMap tmx;
  cuuint64_t gdim[3] = {CH, IMG, IMG};
  cuuint64_t gstr[2] = {CH * 2, (cuuint64_t)CH * 2 * IMG};
  cuuint32_t box[3] = {64, 9, 1};
  cuuint32_t estr[3] = {1, 1, 1};
  encode(&tmx, CU_TENSOR_MAP_DATA_TYPE_BFLOAT16, 3, (void*)x, gdim, gstr, box, estr, CU_TENSOR_MAP_INTERLEAVE_NONE,
         CU_TENSOR_MAP_SWIZZLE_NONE, CU_TENSOR_MAP_L2_PROMOTION_L2_128B, CU_TENSOR_MAP_FLOAT_OOB_FILL_NONE);
  Descs ds;
  for (int i = 0; i < 12; i++) {
    for (int h = 0; h < 4; h++) ds.q[h][i] = mkdesc(SMEM_BASE + OFF_W + qkv_pos(h, i) % (8 * SLICE), 128, 256);
    ds.p[i] = mkdesc(SMEM_BASE + OFF_W + wo_pos(i) % (8 * SLICE), 128, 256);
  }
  for (int i = 0; i < 16; i++) ds.src[i] = (const uint8_t*)wpack + i * SLICE;
  for (int g = 0; g < 2; g++)
    for (int i = 0; i < 4; i++) {
      ds.kv[g][i] = mkdesc(SMEM_BASE + OFF_KV + g * KV_BYTES + KV_KOFF + 2 * i * KV_PITCH, KV_PITCH, 128);
      ds.kv[g][4 + i] = mkdesc(SMEM_BASE + OFF_KV + g * KV_BYTES + 256 * i, 128, KV_PITCH);
    }
  CUtensorMap tmp;
  cuuint32_t boxp[3] = {CH, 9, 9};
  encode(&tmp, CU_TENSOR_MAP_DATA_TYPE_BFLOAT16, 3, (void*)x, gdim, gstr, boxp, estr, CU_TENSOR_MAP_INTERLEAVE_NONE,
         CU_TENSOR_MAP_SWIZZLE_NONE, CU_TENSOR_MAP_L2_PROMOTION_L2_128B, CU_TENSOR_MAP_FLOAT_OOB_FILL_NONE);
  prepack_kernel<<<48, dim3(192, 2), 0, cudaStreamPerThread>>>(wqkv, wo);
  cudaLaunchConfig_t cfg = {};
  cfg.gridDim = dim3(nsm); cfg.blockDim = dim3(384); cfg.dynamicSmemBytes = SMEM_BYTES; cfg.stream = cudaStreamPerThread;
  cudaLaunchAttribute at[1];
  at[0].id = cudaLaunchAttributeProgrammaticStreamSerialization;
  at[0].val.programmaticStreamSerializationAllowed = 1;
  cfg.attrs = at; cfg.numAttrs = 1;
  cudaLaunchKernelEx(&cfg, fused_kernel, tmx, tmp, ds, dw, (__nv_bfloat16*)d_out, 0);
}
```

```cpp
#include <cuda_runtime.h>
#include <cuda_bf16.h>
#include <cuda_fp16.h>
#include <cuda.h>
#include <stdint.h>

#define CREGS "208"
#define PREGS "88"
#define KA 4
#define KB 9
#define SA 8
#define SB 20
#define SC 32
namespace {

constexpr int IMG = 511;
constexpr int CH = 192;
constexpr int NWX = 73;
constexpr int NWIN = NWX * NWX;
constexpr int SLICE = 18432;
constexpr int OFF_W = 0;
constexpr int KV_PITCH = 1792, KV_KOFF = 896, KV_BYTES = 6 * KV_PITCH;
constexpr int OFF_KV = 8 * SLICE;
constexpr int TILE_BYTES = 25 * 768;
constexpr int OFF_TILE = OFF_KV + 2 * KV_BYTES;
constexpr int XSLOT = 2304;
constexpr int OFF_ZERO = OFF_TILE + 2 * TILE_BYTES;
constexpr int OFF_X = OFF_ZERO + 768;
constexpr int OFF_BAR = OFF_X + 9 * XSLOT;
constexpr int BAR_WFULL = OFF_BAR;
constexpr int BAR_WEMPTY = OFF_BAR + 56;
constexpr int BAR_XFULL = OFF_BAR + 112;
constexpr int BAR_TFULL = OFF_BAR + 184;
constexpr int BAR_TEMPTY = OFF_BAR + 192;
constexpr int OFF_LIM = OFF_BAR + 200;
constexpr int OFF_REDO = OFF_BAR + 208;
constexpr int OFF_TRACE = OFF_BAR + 240;
constexpr int SMEM_BYTES = OFF_TRACE;

__host__ __device__ constexpr int qkv_pos(int h, int s) { return (h == 0 ? 1 : 3 * h + 2) * SLICE + s * 4608; }
__host__ __device__ constexpr int wo_pos(int s) { return s < 6 ? 14 * SLICE + s * 6144 : s < 9 ? (s - 6) * 6144 : 4 * SLICE + (s - 9) * 6144; }
__host__ __device__ constexpr int stage_of(int p) { return p == 0 ? 5 : p < 4 ? 0 : p == 4 ? 6 : p < 8 ? 1 : p < 11 ? 2 : p < 14 ? 3 : 4; }
constexpr int SMEM_BASE = 1024;
struct Descs { uint64_t q[4][12]; uint64_t p[12]; uint64_t kv[2][8]; const uint8_t* src[16]; };

__device__ uint4 g_wpack[16 * SLICE / 16];
__device__ float2 g_wnorm[96];
#define TR(id)
#define GTS(i)
template <int V> struct IC { static constexpr int v = V; };
typedef __nv_bfloat162 bf2;
__device__ __forceinline__ bf2 u2b(uint32_t u) { return *reinterpret_cast<bf2*>(&u); }
__device__ __forceinline__ uint32_t b2u(bf2 b) { return *reinterpret_cast<uint32_t*>(&b); }
__device__ __forceinline__ uint32_t pack2(float lo, float hi) {
  uint32_t r; asm("cvt.rn.bf16x2.f32 %0, %1, %2;" : "=r"(r) : "f"(hi), "f"(lo)); return r;
}
__device__ __forceinline__ uint32_t hadd(uint32_t a, uint32_t b) { return b2u(__hadd2_rn(u2b(a), u2b(b))); }
__device__ __forceinline__ uint32_t hmul(uint32_t a, uint32_t b) { return b2u(__hmul2_rn(u2b(a), u2b(b))); }
__device__ __forceinline__ uint32_t hfma(uint32_t a, uint32_t b, uint32_t c) { return b2u(__hfma2(u2b(a), u2b(b), u2b(c))); }
__device__ __forceinline__ __half2 u2h(uint32_t u) { return *reinterpret_cast<__half2*>(&u); }
__device__ __forceinline__ uint32_t h2u(__half2 b) { return *reinterpret_cast<uint32_t*>(&b); }
__device__ __forceinline__ uint32_t packh(float lo, float hi) {
  uint32_t r; asm("cvt.rn.f16x2.f32 %0, %1, %2;" : "=r"(r) : "f"(hi), "f"(lo)); return r;
}
__device__ __forceinline__ uint32_t fmax2(uint32_t a, uint32_t b) { return h2u(__hmax2(u2h(a), u2h(b))); }
template <int HI> __device__ __forceinline__ __half2 hcast(uint32_t a) { return HI ? __high2half2(u2h(a)) : __low2half2(u2h(a)); }
template <int HI> __device__ __forceinline__ uint32_t fmul_b(uint32_t a, uint32_t s) { return h2u(__hmul2_rn(u2h(a), hcast<HI>(s))); }
template <int HI> __device__ __forceinline__ uint32_t fsub_b(uint32_t a, uint32_t s) { return h2u(__hsub2_rn(u2h(a), hcast<HI>(s))); }
__device__ __forceinline__ uint32_t fex2(uint32_t a) { uint32_t r; asm("ex2.approx.f16x2 %0, %1;" : "=r"(r) : "r"(a)); return r; }
__device__ __forceinline__ float lo2f(uint32_t a) { return __uint_as_float(a << 16); }
__device__ __forceinline__ float hi2f(uint32_t a) { return __uint_as_float(a & 0xffff0000u); }

__device__ __forceinline__ void mbar_init(uint32_t bar, uint32_t cnt) { asm volatile("mbarrier.init.shared::cta.b64 [%0], %1;" :: "r"(bar), "r"(cnt) : "memory"); }
__device__ __forceinline__ void mbar_wait(uint32_t bar, uint32_t parity) {
  asm volatile("{\n.reg .pred p;\n.reg .u32 n;\n"
               "mbarrier.try_wait.parity.shared::cta.b64 p, [%0], %1;\n"
               "@p bra.uni DONE_%=;\n"
               "mov.u32 n, 0;\n"
               "AGAIN_%=:\n"
               "mbarrier.try_wait.parity.shared::cta.b64 p, [%0], %1;\n"
               "@p bra.uni DONE_%=;\n"
               "add.u32 n, n, 1;\n"
               "setp.lt.u32 p, n, 0x1000000;\n"
               "@p bra.uni AGAIN_%=;\n"
               "trap;\n"
               "DONE_%=:\n}\n" :: "r"(bar), "r"(parity) : "memory");
}
__device__ __forceinline__ void wg_fence() { asm volatile("wgmma.fence.sync.aligned;" ::: "memory"); }
__device__ __forceinline__ void wg_commit() { asm volatile("wgmma.commit_group.sync.aligned;" ::: "memory"); }
template <int N> __device__ __forceinline__ void wg_wait() { asm volatile("wgmma.wait_group.sync.aligned %0;" :: "n"(N) : "memory"); }
__device__ __forceinline__ void bar_sync(int id) { asm volatile("bar.sync %0, 128;" :: "r"(id) : "memory"); }
__device__ __forceinline__ void turn_wait(int wg) { asm volatile("bar.sync %0, 256;" :: "r"(3 + wg) : "memory"); }
__device__ __forceinline__ void turn_pass(int wg) { asm volatile("bar.arrive %0, 256;" :: "r"(4 - wg) : "memory"); }
__device__ __forceinline__ void stsm4(uint32_t addr, uint32_t a, uint32_t b, uint32_t c, uint32_t d) {
  asm volatile("stmatrix.sync.aligned.m8n8.x4.shared.b16 [%0], {%1,%2,%3,%4};" :: "r"(addr), "r"(a), "r"(b), "r"(c), "r"(d) : "memory");
}
template <int N> __device__ __forceinline__ void keep(float (&d)[N]) {
#pragma unroll
  for (int i = 0; i < N; i++) asm volatile("" : "+f"(d[i]) :: "memory");
}
template <int N> __device__ __forceinline__ void keep(uint32_t (&d)[N]) {
#pragma unroll
  for (int i = 0; i < N; i++) asm volatile("" : "+r"(d[i]) :: "memory");
}
__host__ __device__ __forceinline__ uint64_t mkdesc(uint32_t addr, uint32_t lbo, uint32_t sbo) {
  return ((uint64_t)(sbo >> 4) << 32) | (uint64_t)(((lbo >> 4) << 16) | ((addr & 0x3FFFF) >> 4));
}

template <int SCALE_D>
__device__ __forceinline__ void wgmma_n144(uint32_t (&d)[36], uint32_t a0, uint32_t a1, uint32_t a2, uint32_t a3, uint64_t descB) {
  if (SCALE_D == 0)
  asm volatile("wgmma.mma_async.sync.aligned.m64n144k16.f16.f16.f16 "
    "{%0, %1, %2, %3, %4, %5, %6, %7, %8, %9, %10, %11, %12, %13, %14, %15, "
    "%16, %17, %18, %19, %20, %21, %22, %23, %24, %25, %26, %27, %28, %29, %30, %31, "
    "%32, %33, %34, %35}, "
    "{%36, %37, %38, %39}, %40, 0, 1, 1, 0;\n"
    : "=r"(d[0]), "=r"(d[1]), "=r"(d[2]), "=r"(d[3]), "=r"(d[4]), "=r"(d[5]), "=r"(d[6]), "=r"(d[7]),
      "=r"(d[8]), "=r"(d[9]), "=r"(d[10]), "=r"(d[11]), "=r"(d[12]), "=r"(d[13]), "=r"(d[14]), "=r"(d[15]),
      "=r"(d[16]), "=r"(d[17]), "=r"(d[18]), "=r"(d[19]), "=r"(d[20]), "=r"(d[21]), "=r"(d[22]), "=r"(d[23]),
      "=r"(d[24]), "=r"(d[25]), "=r"(d[26]), "=r"(d[27]), "=r"(d[28]), "=r"(d[29]), "=r"(d[30]), "=r"(d[31]),
      "=r"(d[32]), "=r"(d[33]), "=r"(d[34]), "=r"(d[35])
    : "r"(a0), "r"(a1), "r"(a2), "r"(a3), "l"(descB));
  else
  asm volatile("wgmma.mma_async.sync.aligned.m64n144k16.f16.f16.f16 "
    "{%0, %1, %2, %3, %4, %5, %6, %7, %8, %9, %10, %11, %12, %13, %14, %15, "
    "%16, %17, %18, %19, %20, %21, %22, %23, %24, %25, %26, %27, %28, %29, %30, %31, "
    "%32, %33, %34, %35}, "
    "{%36, %37, %38, %39}, %40, 1, 1, 1, 0;\n"
    : "+r"(d[0]), "+r"(d[1]), "+r"(d[2]), "+r"(d[3]), "+r"(d[4]), "+r"(d[5]), "+r"(d[6]), "+r"(d[7]),
      "+r"(d[8]), "+r"(d[9]), "+r"(d[10]), "+r"(d[11]), "+r"(d[12]), "+r"(d[13]), "+r"(d[14]), "+r"(d[15]),
      "+r"(d[16]), "+r"(d[17]), "+r"(d[18]), "+r"(d[19]), "+r"(d[20]), "+r"(d[21]), "+r"(d[22]), "+r"(d[23]),
      "+r"(d[24]), "+r"(d[25]), "+r"(d[26]), "+r"(d[27]), "+r"(d[28]), "+r"(d[29]), "+r"(d[30]), "+r"(d[31]),
      "+r"(d[32]), "+r"(d[33]), "+r"(d[34]), "+r"(d[35])
    : "r"(a0), "r"(a1), "r"(a2), "r"(a3), "l"(descB));
}

template <int SCALE_D>
__device__ __forceinline__ void wgmma_n192(uint32_t (&d)[48], uint32_t a0, uint32_t a1, uint32_t a2, uint32_t a3, uint64_t descB) {
  if (SCALE_D == 0)
  asm volatile("wgmma.mma_async.sync.aligned.m64n192k16.f16.f16.f16 "
    "{%0, %1, %2, %3, %4, %5, %6, %7, %8, %9, %10, %11, %12, %13, %14, %15, "
    "%16, %17, %18, %19, %20, %21, %22, %23, %24, %25, %26, %27, %28, %29, %30, %31, "
    "%32, %33, %34, %35, %36, %37, %38, %39, %40, %41, %42, %43, %44, %45, %46, %47}, "
    "{%48, %49, %50, %51}, %52, 0, 1, 1, 0;\n"
    : "=r"(d[0]), "=r"(d[1]), "=r"(d[2]), "=r"(d[3]), "=r"(d[4]), "=r"(d[5]), "=r"(d[6]), "=r"(d[7]),
      "=r"(d[8]), "=r"(d[9]), "=r"(d[10]), "=r"(d[11]), "=r"(d[12]), "=r"(d[13]), "=r"(d[14]), "=r"(d[15]),
      "=r"(d[16]), "=r"(d[17]), "=r"(d[18]), "=r"(d[19]), "=r"(d[20]), "=r"(d[21]), "=r"(d[22]), "=r"(d[23]),
      "=r"(d[24]), "=r"(d[25]), "=r"(d[26]), "=r"(d[27]), "=r"(d[28]), "=r"(d[29]), "=r"(d[30]), "=r"(d[31]),
      "=r"(d[32]), "=r"(d[33]), "=r"(d[34]), "=r"(d[35]), "=r"(d[36]), "=r"(d[37]), "=r"(d[38]), "=r"(d[39]),
      "=r"(d[40]), "=r"(d[41]), "=r"(d[42]), "=r"(d[43]), "=r"(d[44]), "=r"(d[45]), "=r"(d[46]), "=r"(d[47])
    : "r"(a0), "r"(a1), "r"(a2), "r"(a3), "l"(descB));
  else
  asm volatile("wgmma.mma_async.sync.aligned.m64n192k16.f16.f16.f16 "
    "{%0, %1, %2, %3, %4, %5, %6, %7, %8, %9, %10, %11, %12, %13, %14, %15, "
    "%16, %17, %18, %19, %20, %21, %22, %23, %24, %25, %26, %27, %28, %29, %30, %31, "
    "%32, %33, %34, %35, %36, %37, %38, %39, %40, %41, %42, %43, %44, %45, %46, %47}, "
    "{%48, %49, %50, %51}, %52, 1, 1, 1, 0;\n"
    : "+r"(d[0]), "+r"(d[1]), "+r"(d[2]), "+r"(d[3]), "+r"(d[4]), "+r"(d[5]), "+r"(d[6]), "+r"(d[7]),
      "+r"(d[8]), "+r"(d[9]), "+r"(d[10]), "+r"(d[11]), "+r"(d[12]), "+r"(d[13]), "+r"(d[14]), "+r"(d[15]),
      "+r"(d[16]), "+r"(d[17]), "+r"(d[18]), "+r"(d[19]), "+r"(d[20]), "+r"(d[21]), "+r"(d[22]), "+r"(d[23]),
      "+r"(d[24]), "+r"(d[25]), "+r"(d[26]), "+r"(d[27]), "+r"(d[28]), "+r"(d[29]), "+r"(d[30]), "+r"(d[31]),
      "+r"(d[32]), "+r"(d[33]), "+r"(d[34]), "+r"(d[35]), "+r"(d[36]), "+r"(d[37]), "+r"(d[38]), "+r"(d[39]),
      "+r"(d[40]), "+r"(d[41]), "+r"(d[42]), "+r"(d[43]), "+r"(d[44]), "+r"(d[45]), "+r"(d[46]), "+r"(d[47])
    : "r"(a0), "r"(a1), "r"(a2), "r"(a3), "l"(descB));
}

template <int SCALE_D>
__device__ __forceinline__ void wgmma_n56(uint32_t (&d)[14], uint32_t a0, uint32_t a1, uint32_t a2, uint32_t a3, uint64_t descB) {
  if (SCALE_D == 0)
  asm volatile("wgmma.mma_async.sync.aligned.m64n56k16.f16.f16.f16 "
    "{%0, %1, %2, %3, %4, %5, %6, %7, %8, %9, %10, %11, %12, %13}, "
    "{%14, %15, %16, %17}, %18, 0, 1, 1, 0;\n"
    : "=r"(d[0]), "=r"(d[1]), "=r"(d[2]), "=r"(d[3]), "=r"(d[4]), "=r"(d[5]), "=r"(d[6]), "=r"(d[7]),
      "=r"(d[8]), "=r"(d[9]), "=r"(d[10]), "=r"(d[11]), "=r"(d[12]), "=r"(d[13])
    : "r"(a0), "r"(a1), "r"(a2), "r"(a3), "l"(descB));
  else
  asm volatile("wgmma.mma_async.sync.aligned.m64n56k16.f16.f16.f16 "
    "{%0, %1, %2, %3, %4, %5, %6, %7, %8, %9, %10, %11, %12, %13}, "
    "{%14, %15, %16, %17}, %18, 1, 1, 1, 0;\n"
    : "+r"(d[0]), "+r"(d[1]), "+r"(d[2]), "+r"(d[3]), "+r"(d[4]), "+r"(d[5]), "+r"(d[6]), "+r"(d[7]),
      "+r"(d[8]), "+r"(d[9]), "+r"(d[10]), "+r"(d[11]), "+r"(d[12]), "+r"(d[13])
    : "r"(a0), "r"(a1), "r"(a2), "r"(a3), "l"(descB));
}

template <int SCALE_D>
__device__ __forceinline__ void wgmma_n48t(uint32_t (&d)[12], uint32_t a0, uint32_t a1, uint32_t a2, uint32_t a3, uint64_t descB) {
  if (SCALE_D == 0)
  asm volatile("wgmma.mma_async.sync.aligned.m64n48k16.f16.f16.f16 "
    "{%0, %1, %2, %3, %4, %5, %6, %7, %8, %9, %10, %11}, "
    "{%12, %13, %14, %15}, %16, 0, 1, 1, 1;\n"
    : "=r"(d[0]), "=r"(d[1]), "=r"(d[2]), "=r"(d[3]), "=r"(d[4]), "=r"(d[5]), "=r"(d[6]), "=r"(d[7]),
      "=r"(d[8]), "=r"(d[9]), "=r"(d[10]), "=r"(d[11])
    : "r"(a0), "r"(a1), "r"(a2), "r"(a3), "l"(descB));
  else
  asm volatile("wgmma.mma_async.sync.aligned.m64n48k16.f16.f16.f16 "
    "{%0, %1, %2, %3, %4, %5, %6, %7, %8, %9, %10, %11}, "
    "{%12, %13, %14, %15}, %16, 1, 1, 1, 1;\n"
    : "+r"(d[0]), "+r"(d[1]), "+r"(d[2]), "+r"(d[3]), "+r"(d[4]), "+r"(d[5]), "+r"(d[6]), "+r"(d[7]),
      "+r"(d[8]), "+r"(d[9]), "+r"(d[10]), "+r"(d[11])
    : "r"(a0), "r"(a1), "r"(a2), "r"(a3), "l"(descB));
}

__global__ void __launch_bounds__(384) prepack_kernel(const __nv_bfloat16* __restrict__ wqkv, const __nv_bfloat16* __restrict__ wo) {
  asm volatile("griddepcontrol.launch_dependents;");
  __shared__ float red2[2][2][6][8];
  float (*red)[6][8] = red2[threadIdx.y];
  __half* dst = reinterpret_cast<__half*>(g_wpack);
  const int c = threadIdx.x, nb = blockIdx.x * 2 + threadIdx.y;
  auto colsum = [&](int k, const float (&v)[8], float (&o)[8]) {
#pragma unroll
    for (int i = 0; i < 8; i++) {
      float t = v[i];
#pragma unroll
      for (int d = 16; d; d >>= 1) t += __shfl_xor_sync(~0u, t, d);
      if ((c & 31) == 0) red[k][c >> 5][i] = t;
    }
    __syncthreads();
#pragma unroll
    for (int i = 0; i < 8; i++) o[i] = red[k][0][i] + red[k][1][i] + red[k][2][i] + red[k][3][i] + red[k][4][i] + red[k][5][i];
  };
  float v[8], t[8];
  int base;
  if (nb < 72) {
    const int h = nb / 18, j = nb % 18, part = j / 6;
    const int col = (part == 0 ? 192 : part == 1 ? 0 : 384) + h * 48 + (j % 6) * 8;
    uint4 raw = *reinterpret_cast<const uint4*>(wqkv + c * 576 + col);
    uint32_t u[4] = {raw.x, raw.y, raw.z, raw.w};
#pragma unroll
    for (int i = 0; i < 4; i++) { v[2 * i] = lo2f(u[i]); v[2 * i + 1] = hi2f(u[i]); }
    colsum(0, v, t);
#pragma unroll
    for (int n = 0; n < 8; n++)
      v[n] = __bfloat162float(__float2bfloat16((v[n] - t[n] * (1.0f / 192.0f)) * (part == 1 ? 0.14433756729740643f * 1.4426950408889634f : 1.0f)));
    const int cc = c >> 5, q = (c >> 3) & 3, s1 = (c >> 2) & 1, hh = (c >> 1) & 1, e = c & 1;
    base = qkv_pos(h, 2 * cc + s1) / 2 + j * 128 + hh * 64 + 2 * q + e;
  } else {
    const int jb = nb - 72;
#pragma unroll
    for (int n = 0; n < 8; n++) v[n] = __bfloat162float(wo[c * 192 + 32 * (jb >> 2) + 8 * (n >> 1) + 2 * (jb & 3) + (n & 1)]);
    base = wo_pos(c >> 4) / 2 + jb * 128 + ((c >> 3) & 1) * 64 + (c & 7);
  }
#pragma unroll
  for (int n = 0; n < 8; n++) { dst[base + n * 8] = __float2half_rn(v[n]); v[n] *= v[n]; }
  colsum(1, v, t);
  if (c == 0)
    g_wnorm[nb] = make_float2(fmaxf(fmaxf(fmaxf(t[0], t[1]), fmaxf(t[2], t[3])), fmaxf(fmaxf(t[4], t[5]), fmaxf(t[6], t[7]))),
                              t[0] + t[1] + t[2] + t[3] + t[4] + t[5] + t[6] + t[7]);
}

__device__ __forceinline__ int window_of(int round, int nfull, int cta, int ncta, int wg) {
  if (round < nfull) return round * 2 * ncta + 2 * cta + wg;
  const int rem = NWIN - nfull * 2 * ncta;
  const int i = cta + wg * ncta;
  return i < rem ? nfull * 2 * ncta + i : -1;
}

template <int S0 = 0, int S1 = 12>
__device__ __forceinline__ void mma_qkv(uint32_t (&acc)[36], const uint32_t (&A)[48], const uint64_t* d) {
#pragma unroll
  for (int s = S0; s < S1; s++) {
    if (s == 0) wgmma_n144<0>(acc, A[4 * s], A[4 * s + 1], A[4 * s + 2], A[4 * s + 3], d[s]);
    else        wgmma_n144<1>(acc, A[4 * s], A[4 * s + 1], A[4 * s + 2], A[4 * s + 3], d[s]);
  }
  wg_commit();
}
__device__ __forceinline__ void mma_proj(uint32_t (&acc)[48], const uint32_t (&A)[12], const uint64_t* d) {
#pragma unroll
  for (int s = 0; s < 3; s++) wgmma_n192<1>(acc, A[4 * s], A[4 * s + 1], A[4 * s + 2], A[4 * s + 3], d[s]);
}
__device__ __forceinline__ void mma_s(uint32_t (&S)[14], const uint32_t (&Q)[12], const uint64_t* d) {
  wgmma_n56<0>(S, Q[0], Q[1], Q[2], Q[3], d[0]);
  wgmma_n56<1>(S, Q[4], Q[5], Q[6], Q[7], d[1]);
  wgmma_n56<1>(S, Q[8], Q[9], Q[10], Q[11], d[2]);
}
__device__ __forceinline__ void mma_pv(uint32_t (&O)[12], const uint32_t (&P)[12], const uint64_t* d) {
  wgmma_n48t<0>(O, P[0], P[1], P[2], P[3], d[0]);
  wgmma_n48t<1>(O, P[4], P[5], P[6], P[7], d[1]);
  wgmma_n48t<1>(O, P[8], P[9], P[10], P[11], d[2]);
}

#define PIN() asm volatile("pmevent 0;" ::: "memory")
template <int A, int B> __device__ __forceinline__ void hold(uint32_t* v) {
#pragma unroll
  for (int i = A; i < B; i++) asm volatile("" : "+r"(v[i]));
}
__device__ __forceinline__ void stsm12(const uint32_t* v, uint32_t addr) {
#pragma unroll
  for (int j = 0; j < 3; j++) stsm4(addr + 2 * j * KV_PITCH, v[4 * j], v[4 * j + 1], v[4 * j + 2], v[4 * j + 3]);
}
__device__ __forceinline__ void load_v48(uint32_t (&v)[6], uint32_t addr) {
  asm volatile("ldmatrix.sync.aligned.m8n8.x4.shared.b16 {%0,%1,%2,%3}, [%4];" : "=r"(v[0]), "=r"(v[1]), "=r"(v[2]), "=r"(v[3]) : "r"(addr) : "memory");
  asm volatile("ldmatrix.sync.aligned.m8n8.x2.shared.b16 {%0,%1}, [%2];" : "=r"(v[4]), "=r"(v[5]) : "r"(addr + 4 * KV_PITCH) : "memory");
}
__device__ __forceinline__ void finish_o(const uint32_t (&O)[12], const uint32_t (&v)[6], uint32_t p48, uint32_t inv, uint32_t (&Of)[12]) {
#pragma unroll
  for (int i = 0; i < 12; i++) {
    const uint32_t t = h2u(__hfma2(u2h(v[i >> 1]), (i & 1) ? hcast<1>(p48) : hcast<0>(p48), u2h(O[i])));
    Of[i] = (i & 1) ? fmul_b<1>(t, inv) : fmul_b<0>(t, inv);
  }
  hold<0, 12>(Of);
}
template <int A, int B>
__device__ __forceinline__ void ln_sums(const uint32_t (&X)[48], float (&s1)[2], float (&s2)[2]) {
#pragma unroll
  for (int i = A; i < B; i++) {
    const float2 f = __half22float2(u2h(X[i]));
    s1[i & 1] = i < 2 ? f.x + f.y : s1[i & 1] + (f.x + f.y);
    s2[i & 1] = fmaf(f.x, f.x, i < 2 ? f.y * f.y : fmaf(f.y, f.y, s2[i & 1]));
  }
  asm volatile("" : "+f"(s1[0]), "+f"(s1[1]), "+f"(s2[0]), "+f"(s2[1]));
}
__device__ __forceinline__ uint32_t ln_rstd(const float (&s1)[2], const float (&s2)[2], float lo, float hi, bool& ok) {
  float r[2];
  ok = true;
#pragma unroll
  for (int a = 0; a < 2; a++) {
    float m = s1[a], v = s2[a];
    m += __shfl_xor_sync(~0u, m, 1); v += __shfl_xor_sync(~0u, v, 1);
    m += __shfl_xor_sync(~0u, m, 2); v += __shfl_xor_sync(~0u, v, 2);
    ok = ok && v <= hi && (v >= lo || v == 0.f);
    m *= 1.0f / 192.0f;
    m *= m;
    v = fmaxf(fmaf(v, 1.0f / 192.0f, -m), 0.f) + 1e-5f;
    ok = ok && m <= 64.f * v;
    asm("rsqrt.approx.ftz.f32 %0, %1;" : "=f"(r[a]) : "f"(v));
  }
  uint32_t rk = packh(r[0], r[1]);
  hold<0, 1>(&rk);
  return rk;
}
__device__ __forceinline__ void scale12(uint32_t (&D)[12], const uint32_t* a, uint32_t r) {
#pragma unroll
  for (int i = 0; i < 12; i++) D[i] = (i & 1) ? fmul_b<1>(a[i], r) : fmul_b<0>(a[i], r);
  hold<0, 12>(D);
}
template <int CC>
__device__ __forceinline__ void store_out(const uint32_t (&Y)[48], uint8_t* o0, uint8_t* o1, uint32_t vmask) {
  uint32_t T[8];
#pragma unroll
  for (int i = 0; i < 8; i++) {
    const float2 f = __half22float2(u2h(Y[8 * CC + i]));
    T[i] = pack2(f.x, f.y);
  }
  asm volatile("{\n.reg .pred p;\nsetp.ne.u32 p, %5, 0;\n@p st.global.v4.u32 [%0], {%1,%2,%3,%4};\n}\n"
               :: "l"(o0 + CC * 64), "r"(T[0]), "r"(T[2]), "r"(T[4]), "r"(T[6]), "r"(vmask) : "memory");
  asm volatile("{\n.reg .pred p;\nsetp.lt.s32 p, %5, 0;\n@p st.global.v4.u32 [%0], {%1,%2,%3,%4};\n}\n"
               :: "l"(o1 + CC * 64), "r"(T[1]), "r"(T[3]), "r"(T[5]), "r"(T[7]), "r"(vmask) : "memory");
}
__device__ __forceinline__ void proxy_fence() { asm volatile("fence.proxy.async.shared::cta;" ::: "memory"); }
__device__ __forceinline__ uint32_t fadd2(uint32_t a, uint32_t b) { return h2u(__hadd2_rn(u2h(a), u2h(b))); }
__device__ __forceinline__ void row_max(const uint32_t (&S)[14], uint32_t& k48, uint32_t& mx) {
  k48 = __shfl_sync(~0u, __byte_perm(S[12], S[13], 0x5410), 0, 4);
  const uint32_t m0 = fmax2(fmax2(fmax2(S[0], S[2]), S[4]), fmax2(fmax2(S[6], S[8]), S[10]));
  const uint32_t m1 = fmax2(fmax2(fmax2(S[1], S[3]), S[5]), fmax2(fmax2(S[7], S[9]), S[11]));
  mx = fmax2(__byte_perm(m0, m1, 0x5410), __byte_perm(m0, m1, 0x7632));
  mx = fmax2(mx, __shfl_xor_sync(~0u, mx, 1));
  mx = fmax2(fmax2(mx, __shfl_xor_sync(~0u, mx, 2)), k48);
  hold<0, 1>(&mx);
}
__device__ __forceinline__ void row_exp(const uint32_t (&S)[14], uint32_t k48, uint32_t mx, uint32_t (&P)[12], uint32_t& p48, uint32_t& l) {
#pragma unroll
  for (int j = 0; j < 12; j++) P[j] = fex2((j & 1) ? fsub_b<1>(S[j], mx) : fsub_b<0>(S[j], mx));
  p48 = fex2(h2u(__hsub2_rn(u2h(k48), u2h(mx))));
  const uint32_t s0 = fadd2(fadd2(fadd2(P[0], P[2]), fadd2(P[4], P[6])), fadd2(P[8], P[10]));
  const uint32_t s1 = fadd2(fadd2(fadd2(P[1], P[3]), fadd2(P[5], P[7])), fadd2(P[9], P[11]));
  l = fadd2(__byte_perm(s0, s1, 0x5410), __byte_perm(s0, s1, 0x7632));
  hold<0, 12>(P); hold<0, 1>(&p48); hold<0, 1>(&l);
}
__device__ __forceinline__ uint32_t row_scale(uint32_t l, uint32_t p48, uint32_t vmask) {
  l = fadd2(l, __shfl_xor_sync(~0u, l, 1));
  l = fadd2(fadd2(l, __shfl_xor_sync(~0u, l, 2)), p48);
  float i0, i1;
  asm("rcp.approx.ftz.f32 %0, %1;" : "=f"(i0) : "f"(__low2float(u2h(l))));
  asm("rcp.approx.ftz.f32 %0, %1;" : "=f"(i1) : "f"(__high2float(u2h(l))));
  uint32_t inv = packh(i0, i1) & vmask;
  hold<0, 1>(&inv);
  return inv;
}
template <int S0, int S1>
__device__ __forceinline__ void load_x(uint32_t (&X)[48], uint32_t t0) {
#pragma unroll
  for (int s = S0; s < S1; s++)
    asm volatile("ld.shared.v4.u32 {%0,%1,%2,%3}, [%4];" : "=r"(X[4 * s]), "=r"(X[4 * s + 1]), "=r"(X[4 * s + 2]), "=r"(X[4 * s + 3])
                 : "r"(((s & 1) ? (t0 ^ 16) : t0) + (s >> 1) * 128) : "memory");
}

#define WDIV 1
template <int P, int CNT, int DIV = WDIV> __device__ __forceinline__ void load_slices(uint32_t sb, const Descs& ds) {
  constexpr int st = stage_of(P);
  constexpr bool first = P == 0 || stage_of(P - 1) != st;
  if (first)
    asm volatile("{\n.reg .pred p;\nelect.sync _|p, 0xffffffff;\n@p mbarrier.arrive.expect_tx.shared::cta.b64 _, [%0], %1;\n}\n"
                 :: "r"(sb + BAR_WFULL + 8 * st), "n"((st < 4 ? 3 : st == 4 ? 2 : 1) * SLICE / DIV) : "memory");
  asm volatile("{\n.reg .pred p;\nelect.sync _|p, 0xffffffff;\n"
               "@p cp.async.bulk.shared::cluster.global.mbarrier::complete_tx::bytes [%0], [%1], %2, [%3];\n}\n"
               :: "r"(sb + OFF_W + (P & 7) * SLICE), "l"(ds.src[P]), "n"(CNT * SLICE / DIV), "r"(sb + BAR_WFULL + 8 * st) : "memory");
}
__device__ __forceinline__ void warp_arrive(uint32_t bar) {
  asm volatile("{\n.reg .pred p;\nelect.sync _|p, 0xffffffff;\n@p mbarrier.arrive.shared::cta.b64 _, [%0];\n}\n" :: "r"(bar) : "memory");
}

__device__ __forceinline__ float2 fp16_limits(int lane) {
  float mx[4] = {0.f, 0.f, 0.f, 0.f}, sm[4] = {0.f, 0.f, 0.f, 0.f};
#pragma unroll
  for (int i = 0; i < 3; i++) {
    const int nb = lane + 32 * i, part = nb < 72 ? (nb % 18) / 6 : 3;
    const float2 w = g_wnorm[nb];
#pragma unroll
    for (int k = 0; k < 4; k++) if (part == k) { mx[k] = fmaxf(mx[k], w.x); sm[k] += w.y; }
  }
#pragma unroll
  for (int k = 0; k < 4; k++)
#pragma unroll
    for (int d = 16; d; d >>= 1) { mx[k] = fmaxf(mx[k], __shfl_xor_sync(~0u, mx[k], d)); sm[k] += __shfl_xor_sync(~0u, sm[k], d); }
  const float big = fmaxf(fmaxf(mx[0], mx[1]), mx[2]);
  float small = 1.f;
  bool good = sm[0] + sm[1] + sm[2] + sm[3] < 1e30f;
#pragma unroll
  for (int k = 0; k < 4; k++) { good = good && (mx[k] == 0.f || mx[k] >= 2.5e-4f); if (k < 3 && mx[k] > 0.f) small = fminf(small, mx[k]); }
  good = good && 250.f * 48.f * sqrtf(mx[0] * mx[1]) <= 5e4f;
  good = good && 16.f * 49.f * sqrtf(mx[2]) <= 5e4f && big <= 1e6f;
  good = good && 16.f * sqrtf(sm[2] * mx[3]) <= 2e4f;
  return make_float2(192.f * 2.4e-7f / small, good ? fminf(2.5e8f, 9e8f / fmaxf(big, 1e-30f)) : -1.f);
}

__device__ __forceinline__ void slow_window(float* sm, int w, int t, const __nv_bfloat16* __restrict__ x, const __nv_bfloat16* __restrict__ dw,
                                            const __nv_bfloat16* __restrict__ wqkv, const __nv_bfloat16* __restrict__ wo, __nv_bfloat16* __restrict__ out) {
  float* x0 = sm; float* h = x0 + 49 * CH; float* qkv = h + 49 * CH; float* S = qkv + 49 * 576;
  const int wy = w / NWX, wx = w % NWX;
  auto sync = [] { asm volatile("bar.sync 6, 128;" ::: "memory"); };
#pragma unroll 1
  for (int i = t; i < 49 * CH; i += 128) {
    const int k = i / CH, c = i % CH, y = wy * 7 + k / 7, xx = wx * 7 + k % 7;
    float pe = 0.f;
#pragma unroll 1
    for (int a = 0; a < 9; a++) {
      const int yy = y + a / 3 - 1, xc = xx + a % 3 - 1;
      if (yy >= 0 && yy < IMG && xc >= 0 && xc < IMG) pe = fmaf(__bfloat162float(x[((size_t)yy * IMG + xc) * CH + c]), __bfloat162float(dw[a * CH + c]), pe);
    }
    x0[i] = __bfloat162float(__float2bfloat16(__bfloat162float(x[((size_t)y * IMG + xx) * CH + c]) + pe));
  }
  sync();
  if (t < 49) {
    float m = 0.f, v = 0.f;
#pragma unroll 1
    for (int c = 0; c < CH; c++) m += x0[t * CH + c];
    m *= 1.0f / CH;
#pragma unroll 1
    for (int c = 0; c < CH; c++) { const float d = x0[t * CH + c] - m; v = fmaf(d, d, v); }
    const float rs = 1.0f / sqrtf(v * (1.0f / CH) + 1e-5f);
#pragma unroll 1
    for (int c = 0; c < CH; c++) h[t * CH + c] = (x0[t * CH + c] - m) * rs;
  }
  sync();
#pragma unroll 1
  for (int i = t; i < 7 * 576; i += 128) {
    const int n = i % 576, k0 = i / 576 * 7;
    float a[7] = {0.f, 0.f, 0.f, 0.f, 0.f, 0.f, 0.f};
#pragma unroll 1
    for (int c = 0; c < CH; c++) {
      const float wv = __bfloat162float(wqkv[c * 576 + n]);
#pragma unroll
      for (int k = 0; k < 7; k++) a[k] = fmaf(h[(k0 + k) * CH + c], wv, a[k]);
    }
#pragma unroll
    for (int k = 0; k < 7; k++) qkv[(k0 + k) * 576 + n] = a[k];
  }
  sync();
#pragma unroll 1
  for (int hd = 0; hd < 4; hd++) {
#pragma unroll 1
    for (int i = t; i < 49 * 49; i += 128) {
      const int a = i / 49, b = i % 49;
      float v = 0.f;
#pragma unroll 1
      for (int d = 0; d < 48; d++) v = fmaf(qkv[a * 576 + hd * 48 + d], qkv[b * 576 + 192 + hd * 48 + d], v);
      S[i] = v * 0.14433756729740643f;
    }
    sync();
    if (t < 49) {
      float m = S[t * 49], l = 0.f;
#pragma unroll 1
      for (int b = 1; b < 49; b++) m = fmaxf(m, S[t * 49 + b]);
#pragma unroll 1
      for (int b = 0; b < 49; b++) { const float e = expf(S[t * 49 + b] - m); S[t * 49 + b] = e; l += e; }
#pragma unroll 1
      for (int b = 0; b < 49; b++) S[t * 49 + b] /= l;
    }
    sync();
#pragma unroll 1
    for (int i = t; i < 49 * 48; i += 128) {
      const int a = i / 48, d = i % 48;
      float v = 0.f;
#pragma unroll 1
      for (int b = 0; b < 49; b++) v = fmaf(S[a * 49 + b], qkv[b * 576 + 384 + hd * 48 + d], v);
      h[a * CH + hd * 48 + d] = v;
    }
    sync();
  }
#pragma unroll 1
  for (int i = t; i < 7 * CH; i += 128) {
    const int n = i % CH, k0 = i / CH * 7;
    float a[7] = {0.f, 0.f, 0.f, 0.f, 0.f, 0.f, 0.f};
#pragma unroll 1
    for (int c = 0; c < CH; c++) {
      const float wv = __bfloat162float(wo[c * CH + n]);
#pragma unroll
      for (int k = 0; k < 7; k++) a[k] = fmaf(h[(k0 + k) * CH + c], wv, a[k]);
    }
#pragma unroll
    for (int k = 0; k < 7; k++)
      out[((size_t)(wy * 7 + k0 / 7) * IMG + wx * 7 + k) * CH + n] = __float2bfloat16(x0[(k0 + k) * CH + n] + a[k]);
  }
  sync();
}

__global__ void __launch_bounds__(384, 1)
fused_kernel(const __grid_constant__ CUtensorMap tmx, const __grid_constant__ CUtensorMap tmp, const __grid_constant__ Descs ds, const __nv_bfloat16* __restrict__ dw, __nv_bfloat16* __restrict__ out, const int never,
             const __nv_bfloat16* __restrict__ x, const __nv_bfloat16* __restrict__ wqkv, const __nv_bfloat16* __restrict__ wo) {
  extern __shared__ __align__(1024) uint8_t smem[];
  const uint32_t sb = (uint32_t)__cvta_generic_to_shared(smem);
  const int tid = threadIdx.x, lane = tid & 31;
  const int warp = __shfl_sync(0xffffffffu, tid >> 5, 0);
  const int cta = blockIdx.x, ncta = gridDim.x;
  const int nfull = NWIN / (2 * ncta);
  const int nrounds = nfull + ((NWIN - nfull * 2 * ncta) > cta ? 1 : 0);

  if (warp == 0) GTS(0);
  auto prefetch_round = [&](int r) {
#pragma unroll
    for (int k = 0; k < 2; k++) {
      const int w = window_of(r, nfull, cta, ncta, k);
      if (w >= 0) {
        const int a = w / NWX;
        asm volatile("{\n.reg .pred p;\nelect.sync _|p, 0xffffffff;\n@p cp.async.bulk.prefetch.tensor.3d.L2.global [%0, {0, %1, %2}];\n}\n"
                     :: "l"(reinterpret_cast<uint64_t>(&tmp)), "r"((w - a * NWX) * 7 - 1), "r"(a * 7 - 1) : "memory");
      }
    }
  };
  if (warp == 11) prefetch_round(0);
  if (warp == 10 && lane == 0) asm volatile("prefetch.tensormap [%0];" :: "l"(reinterpret_cast<uint64_t>(&tmx)) : "memory");
  if (tid == 0) {
    if ((sb & 0x3FFFF) != SMEM_BASE || nrounds > 128) __trap();
    for (int i = 0; i < 7; i++) { mbar_init(sb + BAR_WFULL + 8 * i, 1); mbar_init(sb + BAR_WEMPTY + 8 * i, 8); }
    for (int i = 0; i < 9; i++) mbar_init(sb + BAR_XFULL + 8 * i, 1);
    mbar_init(sb + BAR_TFULL, 3);
    mbar_init(sb + BAR_TEMPTY, 8);
    asm volatile("fence.mbarrier_init.release.cluster;" ::: "memory");
  }
  if (tid >= 128 && tid < 320) {
    *reinterpret_cast<uint32_t*>(smem + OFF_ZERO + (tid - 128) * 4) = 0;
    if (tid < 136) *reinterpret_cast<uint32_t*>(smem + OFF_REDO + (tid - 128) * 4) = 0;
  }
  __syncthreads();

  if (warp >= 8) {
    asm volatile("setmaxnreg.dec.sync.aligned.u32 " PREGS ";");
    if (warp == 11) {
      asm volatile("griddepcontrol.wait;" ::: "memory");
      load_slices<1, 3, 1>(sb, ds);
      *reinterpret_cast<float2*>(smem + OFF_LIM) = fp16_limits(lane);
      load_slices<0, 1, 1>(sb, ds); load_slices<4, 1, 1>(sb, ds); load_slices<5, 3, 1>(sb, ds);
      for (int r = 0; r < nrounds; r++) {
        const uint32_t par = r & 1;
        const bool next_round = r + 1 < nrounds;
        mbar_wait(sb + BAR_WEMPTY + 40, par); load_slices<8, 1>(sb, ds);
        mbar_wait(sb + BAR_WEMPTY, par);      load_slices<9, 2>(sb, ds); load_slices<11, 1>(sb, ds);
        mbar_wait(sb + BAR_WEMPTY + 48, par); load_slices<12, 1>(sb, ds);
        mbar_wait(sb + BAR_WEMPTY + 8, par);  load_slices<13, 1>(sb, ds); load_slices<14, 2>(sb, ds);
        mbar_wait(sb + BAR_WEMPTY + 16, par); load_slices<0, 1>(sb, ds); if (next_round) load_slices<1, 2>(sb, ds);
        mbar_wait(sb + BAR_WEMPTY + 24, par);
        if (next_round) load_slices<3, 1>(sb, ds);
        load_slices<4, 1>(sb, ds);
        if (next_round) {
          load_slices<5, 1>(sb, ds);
          mbar_wait(sb + BAR_WEMPTY + 32, par); load_slices<6, 2>(sb, ds);
        }
      }
    } else {
      const int cw = warp - 8;
      const int win = lane >> 4;
      const int ch0 = cw * 64 + (lane & 15) * 4;
      uint32_t wt[9][2];
#pragma unroll
      for (int t = 0; t < 9; t++) {
        uint2 v = *reinterpret_cast<const uint2*>(dw + t * CH + ch0);
        wt[t][0] = v.x; wt[t][1] = v.y;
      }
      const uint32_t xs = sb + OFF_X + cw * 3 * XSLOT;
      const uint32_t xld = xs + (lane >> 4) * 1152 + (lane & 15) * 8;
      const uint32_t xbar = sb + BAR_XFULL + cw * 24;
      const uint32_t st0 = sb + OFF_TILE + win * TILE_BYTES + ch0 * 4;
      const uint64_t tm = reinterpret_cast<uint64_t>(&tmx);
      int cx0, cy0, cx1, cy1;
      auto coords = [&](int r) {
        const int w0 = window_of(r, nfull, cta, ncta, 0);
        int w1 = window_of(r, nfull, cta, ncta, 1);
        if (w1 < 0) w1 = w0;
        const int a = w0 / NWX, b = w1 / NWX;
        cx0 = (w0 - a * NWX) * 7 - 1; cy0 = a * 7 - 1;
        cx1 = (w1 - b * NWX) * 7 - 1; cy1 = b * 7 - 1;
      };
      auto issue = [&](int slot, int dy) {
        asm volatile("{\n.reg .pred p;\nelect.sync _|p, 0xffffffff;\n"
                     "@p mbarrier.arrive.expect_tx.shared::cta.b64 _, [%2], %8;\n"
                     "@p cp.async.bulk.tensor.3d.shared::cluster.global.mbarrier::complete_tx::bytes [%0], [%1, {%3, %4, %5}], [%2];\n"
                     "@p cp.async.bulk.tensor.3d.shared::cluster.global.mbarrier::complete_tx::bytes [%0 + 1152], [%1, {%3, %6, %7}], [%2];\n}\n"
                     :: "r"(xs + slot * XSLOT), "l"(tm), "r"(xbar + slot * 8), "r"(cw * 64), "r"(cx0), "r"(cy0 + dy), "r"(cx1), "r"(cy1 + dy), "n"(XSLOT) : "memory");
      };
      uint32_t accA[7][2], accB[7][2], ctr[7][2], held[2];
      auto row = [&](auto fin, auto mid, auto top, int slot, int y) {
        const uint32_t ld = xld + slot * XSLOT;
        const uint32_t sa = (st0 ^ ((y & 1) << 4)) + y * 2304;
        uint32_t cur[9][2], o[2][2];
#pragma unroll
        for (int p = 0; p < 5; p++)
          asm volatile("ld.shared.v2.u32 {%0,%1}, [%2];" : "=r"(cur[p][0]), "=r"(cur[p][1]) : "r"(ld + p * 128));
#pragma unroll
        for (int j = 0; j < 7; j++) {
          if (j >= 1 && j + 4 < 9)
            asm volatile("ld.shared.v2.u32 {%0,%1}, [%2];" : "=r"(cur[j + 4][0]), "=r"(cur[j + 4][1]) : "r"(ld + (j + 4) * 128));
          if (fin.v) {
#pragma unroll
            for (int e = 0; e < 2; e++) {
              uint32_t a = hfma(cur[j][e], wt[6][e], accA[j][e]);
              a = hfma(cur[j + 1][e], wt[7][e], a);
              a = hfma(cur[j + 2][e], wt[8][e], a);
              a = hadd(ctr[j][e], a);
              o[j & 1][e] = packh(lo2f(a), hi2f(a));
            }
            if (j & 1)
              asm volatile("st.shared.v4.u32 [%0], {%1,%2,%3,%4};" :: "r"((j == 3 ? sa ^ 16 : sa) + (j >> 1) * 768),
                           "r"(o[0][0]), "r"(o[1][0]), "r"(o[0][1]), "r"(o[1][1]) : "memory");
            if (j == 6) {
              const uint32_t sb6 = (st0 ^ ((~y & 2) << 3)) + (21 + (y >> 1)) * 768;
              if (fin.v == 2)
                asm volatile("st.shared.v4.u32 [%0], {%1,%2,%3,%2};" :: "r"(sb6), "r"(o[0][0]), "r"(0), "r"(o[0][1]) : "memory");
              else
                asm volatile("{\n.reg .pred p;\nsetp.ne.s32 p, %5, 0;\n@p st.shared.v4.u32 [%0], {%1,%2,%3,%4};\n}\n"
                             :: "r"(sb6), "r"(held[0]), "r"(o[0][0]), "r"(held[1]), "r"(o[0][1]), "r"(y & 1) : "memory");
              held[0] = o[0][0]; held[1] = o[0][1];
            }
          }
#pragma unroll
          for (int e = 0; e < 2; e++) {
            if (mid.v) {
              uint32_t a = hfma(cur[j][e], wt[3][e], accB[j][e]);
              a = hfma(cur[j + 1][e], wt[4][e], a);
              accA[j][e] = hfma(cur[j + 2][e], wt[5][e], a);
              ctr[j][e] = cur[j + 1][e];
            }
            if (top.v) {
              uint32_t a = hmul(cur[j][e], wt[0][e]);
              a = hfma(cur[j + 1][e], wt[1][e], a);
              accB[j][e] = hfma(cur[j + 2][e], wt[2][e], a);
            }
          }
        }
      };
      held[0] = held[1] = 0;
      coords(0);
      issue(0, 0); issue(1, 1); issue(2, 2);
      for (int r = 0; r < nrounds; r++) {
        const bool more = r + 1 < nrounds;
        mbar_wait(xbar, r & 1);
        if (r > 0) issue(2, 2);
        row(IC<0>{}, IC<0>{}, IC<1>{}, 0, 0);
        mbar_wait(xbar + 8, r & 1);
        issue(0, 3);
        row(IC<0>{}, IC<1>{}, IC<1>{}, 1, 0);
        if (r > 0) mbar_wait(sb + BAR_TEMPTY, (r - 1) & 1);
        TR(0);
#pragma unroll 1
        for (int k = 0; k < 2; k++) {
          mbar_wait(xbar + 16, (r + k) & 1);
          issue(1, 4 + 3 * k);
          row(IC<1>{}, IC<1>{}, IC<1>{}, 2, 3 * k);
          mbar_wait(xbar, (r + k + 1) & 1);
          issue(2, 5 + 3 * k);
          row(IC<1>{}, IC<1>{}, IC<1>{}, 0, 3 * k + 1);
          mbar_wait(xbar + 8, (r + k + 1) & 1);
          if (k == 1 && more) coords(r + 1);
          if (k == 0 || more) issue(0, k == 0 ? 6 : 0);
          row(IC<1>{}, IC<1>{}, IC<1>{}, 1, 3 * k + 2);
        }
        mbar_wait(xbar + 16, r & 1);
        if (more) issue(1, 1);
        row(IC<2>{}, IC<0>{}, IC<0>{}, 2, 6);
        warp_arrive(sb + BAR_TFULL);
        TR(1);
      }
    }
    asm volatile("bar.sync 5, 384;" ::: "memory");
#pragma unroll 1
    for (int i = 0; i < 8; i++) {
      uint32_t bits = *reinterpret_cast<volatile uint32_t*>(smem + OFF_REDO + 4 * i);
#pragma unroll 1
      for (; bits; bits &= bits - 1)
        slow_window(reinterpret_cast<float*>(smem), window_of((i & 3) * 32 + __ffs(bits) - 1, nfull, cta, ncta, i >> 2), tid - 256, x, dw, wqkv, wo, out);
    }
  } else {
    asm volatile("setmaxnreg.inc.sync.aligned.u32 " CREGS ";");
    const int wg = warp >> 2, w4 = warp & 3, g = lane >> 2, q = lane & 3;
    const int row0 = w4 * 16 + g, row1 = row0 + 8;
    const int ps = min(w4 * 8 + g, 24);
    const int pix0 = ps < 21 ? (ps / 3) * IMG + (ps % 3) * 2 : (ps - 21) * 2 * IMG + 6;
    const int pix1 = pix0 + (ps < 21 ? 1 : ps < 24 ? IMG : 0);
    const uint32_t kv = sb + OFF_KV + wg * KV_BYTES;
    const int srow = w4 * 16 + (lane & 15);
    const uint32_t vst = kv + (lane >> 4) * KV_PITCH + (srow < 56 ? srow : min(srow - 7, 55)) * 16;
    uint32_t misc = ((uint32_t)pix1 << 20) | ((uint32_t)pix0 << 8) | q;
    const uint32_t v48 = kv + (lane >> 3) * KV_PITCH + 48 * 16;
    const uint32_t vmask = (row0 < 49 ? 0xffffu : 0u) | (row1 < 49 ? 0xffff0000u : 0u);

    const uint32_t tx = sb + q * 32 + (row0 < 49 ? OFF_TILE + wg * TILE_BYTES + ps * 768 + (ps & 1) * 16 : OFF_ZERO + 16);
    const int myrounds = window_of(nrounds - 1, nfull, cta, ncta, wg) < 0 ? nrounds - 1 : nrounds;

    if (never == 2) return;
    uint32_t H[48], Y[48];
    const uint64_t* dkv = ds.kv[wg];
    uint32_t P[12], Ofc[12], p48 = 0x3c003c00u, lsum = 0;
#pragma unroll
    for (int i = 0; i < 48; i++) Y[i] = 0;
#pragma unroll
    for (int i = 0; i < 12; i++) P[i] = Ofc[i] = 0;
    mbar_wait(sb + BAR_TFULL, 0);
    if (warp == 0) GTS(4);
    load_x<0, 12>(H, tx);
    warp_arrive(sb + BAR_TEMPTY);
    if (wg == 1) turn_pass(1);

    uint8_t *o0, *o1;
    uint32_t omask;
    auto out_setup = [&](int r) {
      omask = r >= 0 ? vmask : 0u;
      const int w = window_of(r, nfull, cta, ncta, wg);
      const int wy = w / NWX, wx = w - wy * NWX;
      asm volatile("" : "+r"(misc));
      const uint32_t wb = (uint32_t)(wy * 7 * IMG + wx * 7) * 384u + (misc & 3) * 16;
      o0 = reinterpret_cast<uint8_t*>(out) + (wb + ((misc >> 8) & 0xfff) * 384u);
      o1 = reinterpret_cast<uint8_t*>(out) + (wb + (misc >> 20) * 384u);
    };
#define OUT(c) store_out<c>(Y, o0, o1, omask)
    auto release = [&](int stage) { warp_arrive(sb + BAR_WEMPTY + 8 * stage); };

    for (int r = 0;; r++) {
      const uint32_t par = r & 1;
      uint32_t acc[36], S[14], O[12], Q[12], V[12], Ofa[12], Ofb[12], vr[6], inv, k48, mx;
      if (r == myrounds) {
        const bool idle = r < nrounds;
        mbar_wait(sb + BAR_WFULL + 40, par);
        turn_wait(wg);
        wg_fence(); mma_pv(O, P, dkv + 4); mma_proj(Y, Ofc, ds.p + 6); wg_commit();
        turn_pass(wg);
        load_v48(vr, v48);
        inv = row_scale(lsum, p48, vmask);
        wg_wait<0>(); keep(O); keep(Y);
        finish_o(O, vr, p48, inv, Ofa);
        if (idle) { release(5); release(0); release(1); release(2); release(3); }
        mbar_wait(sb + BAR_WFULL + 48, par);
        turn_wait(wg);
        wg_fence(); mma_proj(Y, Ofa, ds.p + 9); wg_commit();
        if (wg == 0 || idle) turn_pass(wg);
        wg_wait<0>(); keep(Y);
        if (idle) { release(6); turn_wait(wg); turn_pass(wg); }
        out_setup(r - 1);
        OUT(0); PIN(); OUT(1); PIN(); OUT(2); PIN(); OUT(3); PIN(); OUT(4); PIN(); OUT(5);
        if (idle) {
          turn_wait(wg); turn_pass(wg);
          turn_wait(wg); turn_pass(wg);
          turn_wait(wg); turn_pass(wg);
          turn_wait(wg);
        }
        if (w4 == 0) GTS(5 + wg);
        asm volatile("bar.arrive 5, 384;" ::: "memory");
        break;
      }
      float s1[2], s2[2];
      if (SA > 0) ln_sums<0, SA>(H, s1, s2);
      mbar_wait(sb + BAR_WFULL + 40, par);
      mbar_wait(sb + BAR_WFULL, par);
      TR(0);
      turn_wait(wg);
      TR(1);
      wg_fence(); mma_pv(O, P, dkv + 4); mma_proj(Y, Ofc, ds.p + 6); wg_commit(); mma_qkv<0, 3>(acc, H, ds.q[0]);
      PIN();
      load_v48(vr, v48);
      inv = row_scale(lsum, p48, vmask);
      ln_sums<SA, SB>(H, s1, s2);
      PIN();
      wg_fence(); mma_qkv<3, 8>(acc, H, ds.q[0]);
      PIN();
      ln_sums<SB, SC>(H, s1, s2);
      PIN();
      wg_fence(); mma_qkv<8, 12>(acc, H, ds.q[0]);
      turn_pass(wg);
      TR(2);
      wg_wait<3>(); keep(O); keep(Y);
      release(5);
      bar_sync(1 + wg);
      PIN();
      finish_o(O, vr, p48, inv, Ofa);
      if (SC < 48) ln_sums<SC, 48>(H, s1, s2);
      float lim_lo, lim_hi;
      asm volatile("ld.shared.v2.f32 {%0,%1}, [%2];" : "=f"(lim_lo), "=f"(lim_hi) : "r"(sb + OFF_LIM) : "memory");
      bool ok;
      const uint32_t rk = ln_rstd(s1, s2, lim_lo, lim_hi, ok);
      asm volatile("{\n.reg .pred p;\nsetp.eq.s32 p, %2, 0;\n@p red.shared.or.b32 [%0], %1;\n}\n"
                   :: "r"(sb + OFF_REDO + wg * 16 + (r >> 5) * 4), "r"(1u << (r & 31)), "r"((int)ok) : "memory");
      PIN();
      TR(3);
      wg_wait<0>(); keep(acc);
      TR(4);
      release(0);
      scale12(V, acc, rk); stsm12(V, vst + KV_KOFF);
      scale12(V, acc + 24, rk); stsm12(V, vst);
      scale12(Q, acc + 12, rk); PIN();
      proxy_fence();
      mbar_wait(sb + BAR_WFULL + 48, par);
      mbar_wait(sb + BAR_WFULL + 8, par);
      TR(5);
      turn_wait(wg);
      TR(6);
      wg_fence(); mma_proj(Y, Ofa, ds.p + 9); wg_commit(); mma_s(S, Q, dkv); mma_qkv<0, 2>(acc, H, ds.q[1]);
      out_setup(r - 1);
      PIN();
      wg_wait<1>(); keep(Y);
      release(6);
      wg_fence(); mma_qkv<2, 6>(acc, H, ds.q[1]);
      PIN();
      OUT(0);
      PIN();
      wg_wait<1>(); keep(S);
      wg_fence(); mma_qkv<6, 9>(acc, H, ds.q[1]);
      PIN();
      row_max(S, k48, mx);
      OUT(1);
      PIN();
      wg_fence(); mma_qkv<9, 12>(acc, H, ds.q[1]);
      turn_pass(wg);
      PIN();
      OUT(2); PIN();
      OUT(3); PIN();
      row_exp(S, k48, mx, P, p48, lsum);
      PIN();
      TR(7);
      wg_wait<0>(); keep(acc);
      TR(8);
      release(1);
      bar_sync(1 + wg);
      scale12(V, acc, rk); stsm12(V, vst + KV_KOFF);
      scale12(Q, acc + 12, rk); scale12(V, acc + 24, rk); PIN();
      proxy_fence();
#define TURN(ID, OF, G1, G2, G3, X1)                                                       \
      TR(ID + 1);                                                                       \
      turn_wait(wg);                                                                    \
      wg_fence(); mma_pv(O, P, dkv + 4); mma_s(S, Q, dkv); wg_commit(); G1;             \
      PIN();                                                                            \
      TR(ID + 2);                                                                       \
      load_v48(vr, v48);                                                                \
      inv = row_scale(lsum, p48, vmask);                                               \
      X1;                                                                               \
      PIN();                                                                            \
      wg_wait<1>(); keep(S); keep(O);                                                   \
      bar_sync(1 + wg);                                    \
      wg_fence(); G2;                                                                   \
      PIN();                                                                            \
      stsm12(V, vst);                                                                   \
      finish_o(O, vr, p48, inv, OF);                                                    \
      row_max(S, k48, mx);                                                              \
      PIN();                                                                            \
      wg_fence(); G3;                                                                   \
      turn_pass(wg);                                                                    \
      PIN();                                                                            \
      TR(ID + 3);
#define NEXT_HEAD(ID, HD)                                                               \
      row_exp(S, k48, mx, P, p48, lsum);                                                \
      PIN();                                                                            \
      TR(ID + 4);                                                                       \
      wg_wait<0>(); keep(acc);                                                          \
      release(HD);                                                                      \
      scale12(V, acc, rk); stsm12(V, vst + KV_KOFF);                                    \
      scale12(Q, acc + 12, rk); scale12(V, acc + 24, rk); PIN();
      mbar_wait(sb + BAR_WFULL + 16, par);
      TURN(8, Ofa, (mma_qkv<0, KA>(acc, H, ds.q[2])), (mma_qkv<KA, KB>(acc, H, ds.q[2])), (mma_qkv<KB, 12>(acc, H, ds.q[2])), OUT(4))
      OUT(5); PIN();
      NEXT_HEAD(8, 2)
      proxy_fence();
      mbar_wait(sb + BAR_WFULL + 24, par);
      TURN(12, Ofb, (mma_qkv<0, KA>(acc, H, ds.q[3])), (mma_qkv<KA, KB>(acc, H, ds.q[3])), (mma_qkv<KB, 12>(acc, H, ds.q[3])), )
      NEXT_HEAD(12, 3)
#pragma unroll
      for (int i = 0; i < 48; i++) Y[i] = (i & 1) ? H[i] ^ never : H[i] + never;
      hold<0, 48>(Y); PIN();
      proxy_fence();
      mbar_wait(sb + BAR_WFULL + 32, par);
      TR(17);
      turn_wait(wg);
      wg_fence(); mma_pv(O, P, dkv + 4); mma_s(S, Q, dkv); wg_commit(); mma_proj(Y, Ofa, ds.p); mma_proj(Y, Ofb, ds.p + 3); wg_commit();
      turn_pass(wg);
      PIN();
      TR(18);
      load_v48(vr, v48);
      inv = row_scale(lsum, p48, vmask);
      if (r + 1 < myrounds) mbar_wait(sb + BAR_TFULL, par ^ 1);
      load_x<0, 4>(H, tx);
      wg_wait<1>(); keep(S); keep(O);
      bar_sync(1 + wg);
      PIN();
      TR(19);
      row_max(S, k48, mx);
      finish_o(O, vr, p48, inv, Ofc);
      stsm12(V, vst);
      PIN();
      load_x<4, 8>(H, tx);
      row_exp(S, k48, mx, P, p48, lsum);
      PIN();
      load_x<8, 12>(H, tx);
      warp_arrive(sb + BAR_TEMPTY);
      TR(20);
      wg_wait<0>(); keep(Y);
      release(4);
      proxy_fence();
      TR(21);
#undef TURN
#undef NEXT_HEAD
    }
  }
}

typedef CUresult (*EncodeFn)(CUtensorMap*, CUtensorMapDataType, cuuint32_t, void*, const cuuint64_t*, const cuuint64_t*,
                             const cuuint32_t*, const cuuint32_t*, CUtensorMapInterleave, CUtensorMapSwizzle,
                             CUtensorMapL2promotion, CUtensorMapFloatOOBfill);

}

extern "C" void kernel_launch(void* const* d_in, const int* in_sizes, int n_in, void* d_out, int out_size) {
  const __nv_bfloat16* x = (const __nv_bfloat16*)d_in[0];
  const __nv_bfloat16* dw = (const __nv_bfloat16*)d_in[1];
  const __nv_bfloat16* wqkv = (const __nv_bfloat16*)d_in[2];
  const __nv_bfloat16* wo = (const __nv_bfloat16*)d_in[3];
  static EncodeFn encode = nullptr;
  static int nsm = 0;
  static void* wpack = nullptr;
  if (!encode) {
    void* fn = nullptr;
    cudaDriverEntryPointQueryResult qr;
    cudaGetDriverEntryPoint("cuTensorMapEncodeTiled", &fn, cudaEnableDefault, &qr);
    encode = (EncodeFn)fn;
    int dev = 0;
    cudaGetDevice(&dev);
    cudaDeviceGetAttribute(&nsm, cudaDevAttrMultiProcessorCount, dev);
    cudaGetSymbolAddress(&wpack, g_wpack);
    cudaFuncSetAttribute(fused_kernel, cudaFuncAttributeMaxDynamicSharedMemorySize, SMEM_BYTES);
  }
  CUtensorMap tmx;
  cuuint64_t gdim[3] = {CH, IMG, IMG};
  cuuint64_t gstr[2] = {CH * 2, (cuuint64_t)CH * 2 * IMG};
  cuuint32_t box[3] = {64, 9, 1};
  cuuint32_t estr[3] = {1, 1, 1};
  encode(&tmx, CU_TENSOR_MAP_DATA_TYPE_BFLOAT16, 3, (void*)x, gdim, gstr, box, estr, CU_TENSOR_MAP_INTERLEAVE_NONE,
         CU_TENSOR_MAP_SWIZZLE_NONE, CU_TENSOR_MAP_L2_PROMOTION_L2_128B, CU_TENSOR_MAP_FLOAT_OOB_FILL_NONE);
  Descs ds;
  for (int i = 0; i < 12; i++) {
    for (int h = 0; h < 4; h++) ds.q[h][i] = mkdesc(SMEM_BASE + OFF_W + qkv_pos(h, i) % (8 * SLICE), 128, 256);
    ds.p[i] = mkdesc(SMEM_BASE + OFF_W + wo_pos(i) % (8 * SLICE), 128, 256);
  }
  for (int i = 0; i < 16; i++) ds.src[i] = (const uint8_t*)wpack + i * SLICE;
  for (int g = 0; g < 2; g++)
    for (int i = 0; i < 4; i++) {
      ds.kv[g][i] = mkdesc(SMEM_BASE + OFF_KV + g * KV_BYTES + KV_KOFF + 2 * i * KV_PITCH, KV_PITCH, 128);
      ds.kv[g][4 + i] = mkdesc(SMEM_BASE + OFF_KV + g * KV_BYTES + 256 * i, 128, KV_PITCH);
    }
  CUtensorMap tmp;
  cuuint32_t boxp[3] = {CH, 9, 9};
  encode(&tmp, CU_TENSOR_MAP_DATA_TYPE_BFLOAT16, 3, (void*)x, gdim, gstr, boxp, estr, CU_TENSOR_MAP_INTERLEAVE_NONE,
         CU_TENSOR_MAP_SWIZZLE_NONE, CU_TENSOR_MAP_L2_PROMOTION_L2_128B, CU_TENSOR_MAP_FLOAT_OOB_FILL_NONE);
  prepack_kernel<<<48, dim3(192, 2), 0, cudaStreamPerThread>>>(wqkv, wo);
  cudaLaunchConfig_t cfg = {};
  cfg.gridDim = dim3(nsm); cfg.blockDim = dim3(384); cfg.dynamicSmemBytes = SMEM_BYTES; cfg.stream = cudaStreamPerThread;
  cudaLaunchAttribute at[1];
  at[0].id = cudaLaunchAttributeProgrammaticStreamSerialization;
  at[0].val.programmaticStreamSerializationAllowed = 1;
  cfg.attrs = at; cfg.numAttrs = 1;
  cudaLaunchKernelEx(&cfg, fused_kernel, tmx, tmp, ds, dw, (__nv_bfloat16*)d_out, 0, x, wqkv, wo);
}
```

```cpp
#include <cuda_runtime.h>
#include <cuda_bf16.h>
#include <cuda_fp16.h>
#include <cuda.h>
#include <stdint.h>

#define CREGS "208"
#define PREGS "88"
#define KA 3
#define KB 9
#define SA 0
#define SB 24
#define SC 48
namespace {

constexpr int IMG = 511;
constexpr int CH = 192;
constexpr int NWX = 73;
constexpr int NWIN = NWX * NWX;
constexpr int SLICE = 18432;
constexpr int OFF_W = 0;
constexpr int KV_PITCH = 1792, KV_KOFF = 896, KV_BYTES = 6 * KV_PITCH + 768;
constexpr int OFF_KV = 8 * SLICE;
constexpr int TILE_BYTES = 25 * 768;
constexpr int OFF_TILE = OFF_KV + 2 * KV_BYTES;
constexpr int XSLOT = 2304;
constexpr int OFF_ZERO = OFF_TILE + 2 * TILE_BYTES;
constexpr int OFF_X = OFF_ZERO + 768;
constexpr int OFF_BAR = OFF_X + 9 * XSLOT;
constexpr int BAR_WFULL = OFF_BAR;
constexpr int BAR_WEMPTY = OFF_BAR + 56;
constexpr int BAR_XFULL = OFF_BAR + 112;
constexpr int BAR_TFULL = OFF_BAR + 184;
constexpr int BAR_TEMPTY = OFF_BAR + 192;
constexpr int OFF_LIM = OFF_BAR + 200;
constexpr int OFF_REDO = OFF_BAR + 208;
constexpr int OFF_TRACE = OFF_BAR + 240;
constexpr int SMEM_BYTES = OFF_TRACE;

__host__ __device__ constexpr int qkv_pos(int h, int s) { return (h == 0 ? 1 : 3 * h + 2) * SLICE + s * 4608; }
__host__ __device__ constexpr int wo_pos(int s) { return s < 6 ? 14 * SLICE + s * 6144 : s < 9 ? (s - 6) * 6144 : 4 * SLICE + (s - 9) * 6144; }
__host__ __device__ constexpr int stage_of(int p) { return p == 0 ? 5 : p < 4 ? 0 : p == 4 ? 6 : p < 8 ? 1 : p < 11 ? 2 : p < 14 ? 3 : 4; }
constexpr int SMEM_BASE = 1024;
struct Descs { uint64_t q[4][12]; uint64_t p[12]; uint64_t kv[2][8]; const uint8_t* src[16]; };

__device__ uint4 g_wpack[16 * SLICE / 16];
__device__ float2 g_wnorm[96];
#define TR(id)
#define GTS(i)
template <int V> struct IC { static constexpr int v = V; };
typedef __nv_bfloat162 bf2;
__device__ __forceinline__ bf2 u2b(uint32_t u) { return *reinterpret_cast<bf2*>(&u); }
__device__ __forceinline__ uint32_t b2u(bf2 b) { return *reinterpret_cast<uint32_t*>(&b); }
__device__ __forceinline__ uint32_t pack2(float lo, float hi) {
  uint32_t r; asm("cvt.rn.bf16x2.f32 %0, %1, %2;" : "=r"(r) : "f"(hi), "f"(lo)); return r;
}
__device__ __forceinline__ uint32_t hadd(uint32_t a, uint32_t b) { return b2u(__hadd2_rn(u2b(a), u2b(b))); }
__device__ __forceinline__ uint32_t hmul(uint32_t a, uint32_t b) { return b2u(__hmul2_rn(u2b(a), u2b(b))); }
__device__ __forceinline__ uint32_t hfma(uint32_t a, uint32_t b, uint32_t c) { return b2u(__hfma2(u2b(a), u2b(b), u2b(c))); }
__device__ __forceinline__ __half2 u2h(uint32_t u) { return *reinterpret_cast<__half2*>(&u); }
__device__ __forceinline__ uint32_t h2u(__half2 b) { return *reinterpret_cast<uint32_t*>(&b); }
__device__ __forceinline__ uint32_t packh(float lo, float hi) {
  uint32_t r; asm("cvt.rn.f16x2.f32 %0, %1, %2;" : "=r"(r) : "f"(hi), "f"(lo)); return r;
}
__device__ __forceinline__ uint32_t fmax2(uint32_t a, uint32_t b) { return h2u(__hmax2(u2h(a), u2h(b))); }
template <int HI> __device__ __forceinline__ __half2 hcast(uint32_t a) { return HI ? __high2half2(u2h(a)) : __low2half2(u2h(a)); }
template <int HI> __device__ __forceinline__ uint32_t fmul_b(uint32_t a, uint32_t s) { return h2u(__hmul2_rn(u2h(a), hcast<HI>(s))); }
template <int HI> __device__ __forceinline__ uint32_t fsub_b(uint32_t a, uint32_t s) { return h2u(__hsub2_rn(u2h(a), hcast<HI>(s))); }
__device__ __forceinline__ uint32_t fex2(uint32_t a) { uint32_t r; asm("ex2.approx.f16x2 %0, %1;" : "=r"(r) : "r"(a)); return r; }
__device__ __forceinline__ float lo2f(uint32_t a) { return __uint_as_float(a << 16); }
__device__ __forceinline__ float hi2f(uint32_t a) { return __uint_as_float(a & 0xffff0000u); }

__device__ __forceinline__ void mbar_init(uint32_t bar, uint32_t cnt) { asm volatile("mbarrier.init.shared::cta.b64 [%0], %1;" :: "r"(bar), "r"(cnt) : "memory"); }
__device__ __forceinline__ void mbar_wait(uint32_t bar, uint32_t parity) {
  asm volatile("{\n.reg .pred p;\n.reg .u32 n;\n"
               "mbarrier.try_wait.parity.shared::cta.b64 p, [%0], %1;\n"
               "@p bra.uni DONE_%=;\n"
               "mov.u32 n, 0;\n"
               "AGAIN_%=:\n"
               "mbarrier.try_wait.parity.shared::cta.b64 p, [%0], %1;\n"
               "@p bra.uni DONE_%=;\n"
               "add.u32 n, n, 1;\n"
               "setp.lt.u32 p, n, 0x1000000;\n"
               "@p bra.uni AGAIN_%=;\n"
               "trap;\n"
               "DONE_%=:\n}\n" :: "r"(bar), "r"(parity) : "memory");
}
__device__ __forceinline__ void mbar_wait_idle(uint32_t bar, uint32_t parity) {
  asm volatile("{\n.reg .pred p;\n.reg .u32 n;\nmov.u32 n, 0;\n"
               "AGAIN_%=:\n"
               "mbarrier.try_wait.parity.shared::cta.b64 p, [%0], %1, 2000;\n"
               "@p bra.uni DONE_%=;\n"
               "add.u32 n, n, 1;\n"
               "setp.lt.u32 p, n, 0x200000;\n"
               "@p bra.uni AGAIN_%=;\n"
               "trap;\n"
               "DONE_%=:\n}\n" :: "r"(bar), "r"(parity) : "memory");
}
__device__ __forceinline__ void wg_fence() { asm volatile("wgmma.fence.sync.aligned;" ::: "memory"); }
__device__ __forceinline__ void wg_commit() { asm volatile("wgmma.commit_group.sync.aligned;" ::: "memory"); }
template <int N> __device__ __forceinline__ void wg_wait() { asm volatile("wgmma.wait_group.sync.aligned %0;" :: "n"(N) : "memory"); }
#define BAR_BY_WG(OP, ID0, ID1, CNT) asm volatile("{\n.reg .pred p;\nsetp.eq.s32 p, %0, 0;\n@p " OP " " #ID0 ", " #CNT ";\n@!p " OP " " #ID1 ", " #CNT ";\n}\n" :: "r"(wg) : "memory")
__device__ __forceinline__ void wg_sync(int wg) { BAR_BY_WG("bar.sync", 1, 2, 128); }
__device__ __forceinline__ void turn_wait(int wg) { BAR_BY_WG("bar.sync", 3, 4, 256); }
__device__ __forceinline__ void turn_pass(int wg) { BAR_BY_WG("bar.arrive", 4, 3, 256); }
__device__ __forceinline__ void stsm4(uint32_t addr, uint32_t a, uint32_t b, uint32_t c, uint32_t d) {
  asm volatile("stmatrix.sync.aligned.m8n8.x4.shared.b16 [%0], {%1,%2,%3,%4};" :: "r"(addr), "r"(a), "r"(b), "r"(c), "r"(d) : "memory");
}
template <int N> __device__ __forceinline__ void keep(float (&d)[N]) {
#pragma unroll
  for (int i = 0; i < N; i++) asm volatile("" : "+f"(d[i]) :: "memory");
}
template <int N> __device__ __forceinline__ void keep(uint32_t (&d)[N]) {
#pragma unroll
  for (int i = 0; i < N; i++) asm volatile("" : "+r"(d[i]) :: "memory");
}
__host__ __device__ __forceinline__ uint64_t mkdesc(uint32_t addr, uint32_t lbo, uint32_t sbo) {
  return ((uint64_t)(sbo >> 4) << 32) | (uint64_t)(((lbo >> 4) << 16) | ((addr & 0x3FFFF) >> 4));
}

template <int SCALE_D>
__device__ __forceinline__ void wgmma_n144(uint32_t (&d)[36], uint32_t a0, uint32_t a1, uint32_t a2, uint32_t a3, uint64_t descB) {
  if (SCALE_D == 0)
  asm volatile("wgmma.mma_async.sync.aligned.m64n144k16.f16.f16.f16 "
    "{%0, %1, %2, %3, %4, %5, %6, %7, %8, %9, %10, %11, %12, %13, %14, %15, "
    "%16, %17, %18, %19, %20, %21, %22, %23, %24, %25, %26, %27, %28, %29, %30, %31, "
    "%32, %33, %34, %35}, "
    "{%36, %37, %38, %39}, %40, 0, 1, 1, 0;\n"
    : "=r"(d[0]), "=r"(d[1]), "=r"(d[2]), "=r"(d[3]), "=r"(d[4]), "=r"(d[5]), "=r"(d[6]), "=r"(d[7]),
      "=r"(d[8]), "=r"(d[9]), "=r"(d[10]), "=r"(d[11]), "=r"(d[12]), "=r"(d[13]), "=r"(d[14]), "=r"(d[15]),
      "=r"(d[16]), "=r"(d[17]), "=r"(d[18]), "=r"(d[19]), "=r"(d[20]), "=r"(d[21]), "=r"(d[22]), "=r"(d[23]),
      "=r"(d[24]), "=r"(d[25]), "=r"(d[26]), "=r"(d[27]), "=r"(d[28]), "=r"(d[29]), "=r"(d[30]), "=r"(d[31]),
      "=r"(d[32]), "=r"(d[33]), "=r"(d[34]), "=r"(d[35])
    : "r"(a0), "r"(a1), "r"(a2), "r"(a3), "l"(descB));
  else
  asm volatile("wgmma.mma_async.sync.aligned.m64n144k16.f16.f16.f16 "
    "{%0, %1, %2, %3, %4, %5, %6, %7, %8, %9, %10, %11, %12, %13, %14, %15, "
    "%16, %17, %18, %19, %20, %21, %22, %23, %24, %25, %26, %27, %28, %29, %30, %31, "
    "%32, %33, %34, %35}, "
    "{%36, %37, %38, %39}, %40, 1, 1, 1, 0;\n"
    : "+r"(d[0]), "+r"(d[1]), "+r"(d[2]), "+r"(d[3]), "+r"(d[4]), "+r"(d[5]), "+r"(d[6]), "+r"(d[7]),
      "+r"(d[8]), "+r"(d[9]), "+r"(d[10]), "+r"(d[11]), "+r"(d[12]), "+r"(d[13]), "+r"(d[14]), "+r"(d[15]),
      "+r"(d[16]), "+r"(d[17]), "+r"(d[18]), "+r"(d[19]), "+r"(d[20]), "+r"(d[21]), "+r"(d[22]), "+r"(d[23]),
      "+r"(d[24]), "+r"(d[25]), "+r"(d[26]), "+r"(d[27]), "+r"(d[28]), "+r"(d[29]), "+r"(d[30]), "+r"(d[31]),
      "+r"(d[32]), "+r"(d[33]), "+r"(d[34]), "+r"(d[35])
    : "r"(a0), "r"(a1), "r"(a2), "r"(a3), "l"(descB));
}

template <int SCALE_D>
__device__ __forceinline__ void wgmma_n192(uint32_t (&d)[48], uint32_t a0, uint32_t a1, uint32_t a2, uint32_t a3, uint64_t descB) {
  if (SCALE_D == 0)
  asm volatile("wgmma.mma_async.sync.aligned.m64n192k16.f16.f16.f16 "
    "{%0, %1, %2, %3, %4, %5, %6, %7, %8, %9, %10, %11, %12, %13, %14, %15, "
    "%16, %17, %18, %19, %20, %21, %22, %23, %24, %25, %26, %27, %28, %29, %30, %31, "
    "%32, %33, %34, %35, %36, %37, %38, %39, %40, %41, %42, %43, %44, %45, %46, %47}, "
    "{%48, %49, %50, %51}, %52, 0, 1, 1, 0;\n"
    : "=r"(d[0]), "=r"(d[1]), "=r"(d[2]), "=r"(d[3]), "=r"(d[4]), "=r"(d[5]), "=r"(d[6]), "=r"(d[7]),
      "=r"(d[8]), "=r"(d[9]), "=r"(d[10]), "=r"(d[11]), "=r"(d[12]), "=r"(d[13]), "=r"(d[14]), "=r"(d[15]),
      "=r"(d[16]), "=r"(d[17]), "=r"(d[18]), "=r"(d[19]), "=r"(d[20]), "=r"(d[21]), "=r"(d[22]), "=r"(d[23]),
      "=r"(d[24]), "=r"(d[25]), "=r"(d[26]), "=r"(d[27]), "=r"(d[28]), "=r"(d[29]), "=r"(d[30]), "=r"(d[31]),
      "=r"(d[32]), "=r"(d[33]), "=r"(d[34]), "=r"(d[35]), "=r"(d[36]), "=r"(d[37]), "=r"(d[38]), "=r"(d[39]),
      "=r"(d[40]), "=r"(d[41]), "=r"(d[42]), "=r"(d[43]), "=r"(d[44]), "=r"(d[45]), "=r"(d[46]), "=r"(d[47])
    : "r"(a0), "r"(a1), "r"(a2), "r"(a3), "l"(descB));
  else
  asm volatile("wgmma.mma_async.sync.aligned.m64n192k16.f16.f16.f16 "
    "{%0, %1, %2, %3, %4, %5, %6, %7, %8, %9, %10, %11, %12, %13, %14, %15, "
    "%16, %17, %18, %19, %20, %21, %22, %23, %24, %25, %26, %27, %28, %29, %30, %31, "
    "%32, %33, %34, %35, %36, %37, %38, %39, %40, %41, %42, %43, %44, %45, %46, %47}, "
    "{%48, %49, %50, %51}, %52, 1, 1, 1, 0;\n"
    : "+r"(d[0]), "+r"(d[1]), "+r"(d[2]), "+r"(d[3]), "+r"(d[4]), "+r"(d[5]), "+r"(d[6]), "+r"(d[7]),
      "+r"(d[8]), "+r"(d[9]), "+r"(d[10]), "+r"(d[11]), "+r"(d[12]), "+r"(d[13]), "+r"(d[14]), "+r"(d[15]),
      "+r"(d[16]), "+r"(d[17]), "+r"(d[18]), "+r"(d[19]), "+r"(d[20]), "+r"(d[21]), "+r"(d[22]), "+r"(d[23]),
      "+r"(d[24]), "+r"(d[25]), "+r"(d[26]), "+r"(d[27]), "+r"(d[28]), "+r"(d[29]), "+r"(d[30]), "+r"(d[31]),
      "+r"(d[32]), "+r"(d[33]), "+r"(d[34]), "+r"(d[35]), "+r"(d[36]), "+r"(d[37]), "+r"(d[38]), "+r"(d[39]),
      "+r"(d[40]), "+r"(d[41]), "+r"(d[42]), "+r"(d[43]), "+r"(d[44]), "+r"(d[45]), "+r"(d[46]), "+r"(d[47])
    : "r"(a0), "r"(a1), "r"(a2), "r"(a3), "l"(descB));
}

template <int SCALE_D>
__device__ __forceinline__ void wgmma_n56(uint32_t (&d)[14], uint32_t a0, uint32_t a1, uint32_t a2, uint32_t a3, uint64_t descB) {
  if (SCALE_D == 0)
  asm volatile("wgmma.mma_async.sync.aligned.m64n56k16.f16.f16.f16 "
    "{%0, %1, %2, %3, %4, %5, %6, %7, %8, %9, %10, %11, %12, %13}, "
    "{%14, %15, %16, %17}, %18, 0, 1, 1, 0;\n"
    : "=r"(d[0]), "=r"(d[1]), "=r"(d[2]), "=r"(d[3]), "=r"(d[4]), "=r"(d[5]), "=r"(d[6]), "=r"(d[7]),
      "=r"(d[8]), "=r"(d[9]), "=r"(d[10]), "=r"(d[11]), "=r"(d[12]), "=r"(d[13])
    : "r"(a0), "r"(a1), "r"(a2), "r"(a3), "l"(descB));
  else
  asm volatile("wgmma.mma_async.sync.aligned.m64n56k16.f16.f16.f16 "
    "{%0, %1, %2, %3, %4, %5, %6, %7, %8, %9, %10, %11, %12, %13}, "
    "{%14, %15, %16, %17}, %18, 1, 1, 1, 0;\n"
    : "+r"(d[0]), "+r"(d[1]), "+r"(d[2]), "+r"(d[3]), "+r"(d[4]), "+r"(d[5]), "+r"(d[6]), "+r"(d[7]),
      "+r"(d[8]), "+r"(d[9]), "+r"(d[10]), "+r"(d[11]), "+r"(d[12]), "+r"(d[13])
    : "r"(a0), "r"(a1), "r"(a2), "r"(a3), "l"(descB));
}

template <int SCALE_D>
__device__ __forceinline__ void wgmma_n56t(uint32_t (&d)[14], uint32_t a0, uint32_t a1, uint32_t a2, uint32_t a3, uint64_t descB) {
  if (SCALE_D == 0)
  asm volatile("wgmma.mma_async.sync.aligned.m64n56k16.f16.f16.f16 "
    "{%0, %1, %2, %3, %4, %5, %6, %7, %8, %9, %10, %11, %12, %13}, "
    "{%14, %15, %16, %17}, %18, 0, 1, 1, 1;\n"
    : "=r"(d[0]), "=r"(d[1]), "=r"(d[2]), "=r"(d[3]), "=r"(d[4]), "=r"(d[5]), "=r"(d[6]), "=r"(d[7]),
      "=r"(d[8]), "=r"(d[9]), "=r"(d[10]), "=r"(d[11]), "=r"(d[12]), "=r"(d[13])
    : "r"(a0), "r"(a1), "r"(a2), "r"(a3), "l"(descB));
  else
  asm volatile("wgmma.mma_async.sync.aligned.m64n56k16.f16.f16.f16 "
    "{%0, %1, %2, %3, %4, %5, %6, %7, %8, %9, %10, %11, %12, %13}, "
    "{%14, %15, %16, %17}, %18, 1, 1, 1, 1;\n"
    : "+r"(d[0]), "+r"(d[1]), "+r"(d[2]), "+r"(d[3]), "+r"(d[4]), "+r"(d[5]), "+r"(d[6]), "+r"(d[7]),
      "+r"(d[8]), "+r"(d[9]), "+r"(d[10]), "+r"(d[11]), "+r"(d[12]), "+r"(d[13])
    : "r"(a0), "r"(a1), "r"(a2), "r"(a3), "l"(descB));
}

__global__ void __launch_bounds__(384) prepack_kernel(const __nv_bfloat16* __restrict__ wqkv, const __nv_bfloat16* __restrict__ wo) {
  asm volatile("griddepcontrol.launch_dependents;");
  __shared__ float red2[2][2][6][8];
  float (*red)[6][8] = red2[threadIdx.y];
  __half* dst = reinterpret_cast<__half*>(g_wpack);
  const int c = threadIdx.x, nb = blockIdx.x * 2 + threadIdx.y;
  auto colsum = [&](int k, const float (&v)[8], float (&o)[8]) {
#pragma unroll
    for (int i = 0; i < 8; i++) {
      float t = v[i];
#pragma unroll
      for (int d = 16; d; d >>= 1) t += __shfl_xor_sync(~0u, t, d);
      if ((c & 31) == 0) red[k][c >> 5][i] = t;
    }
    __syncthreads();
#pragma unroll
    for (int i = 0; i < 8; i++) o[i] = red[k][0][i] + red[k][1][i] + red[k][2][i] + red[k][3][i] + red[k][4][i] + red[k][5][i];
  };
  float v[8], t[8];
  int base;
  if (nb < 72) {
    const int h = nb / 18, j = nb % 18, part = j / 6;
    const int col = (part == 0 ? 192 : part == 1 ? 0 : 384) + h * 48 + (j % 6) * 8;
    uint4 raw = *reinterpret_cast<const uint4*>(wqkv + c * 576 + col);
    uint32_t u[4] = {raw.x, raw.y, raw.z, raw.w};
#pragma unroll
    for (int i = 0; i < 4; i++) { v[2 * i] = lo2f(u[i]); v[2 * i + 1] = hi2f(u[i]); }
    colsum(0, v, t);
#pragma unroll
    for (int n = 0; n < 8; n++)
      v[n] = __bfloat162float(__float2bfloat16((v[n] - t[n] * (1.0f / 192.0f)) * (part == 1 ? 0.14433756729740643f * 1.4426950408889634f : 1.0f)));
    const int cc = c >> 5, q = (c >> 3) & 3, s1 = (c >> 2) & 1, hh = (c >> 1) & 1, e = c & 1;
    base = qkv_pos(h, 2 * cc + s1) / 2 + j * 128 + hh * 64 + 2 * q + e;
  } else {
    const int jb = nb - 72;
#pragma unroll
    for (int n = 0; n < 8; n++) v[n] = __bfloat162float(wo[c * 192 + 32 * (jb >> 2) + 8 * (n >> 1) + 2 * (jb & 3) + (n & 1)]);
    base = wo_pos(c >> 4) / 2 + jb * 128 + ((c >> 3) & 1) * 64 + (c & 7);
  }
#pragma unroll
  for (int n = 0; n < 8; n++) { dst[base + n * 8] = __float2half_rn(v[n]); v[n] *= v[n]; }
  colsum(1, v, t);
  if (c == 0)
    g_wnorm[nb] = make_float2(fmaxf(fmaxf(fmaxf(t[0], t[1]), fmaxf(t[2], t[3])), fmaxf(fmaxf(t[4], t[5]), fmaxf(t[6], t[7]))),
                              t[0] + t[1] + t[2] + t[3] + t[4] + t[5] + t[6] + t[7]);
}

__device__ __forceinline__ int window_of(int round, int nfull, int cta, int ncta, int wg) {
  if (round < nfull) return round * 2 * ncta + 2 * cta + wg;
  const int rem = NWIN - nfull * 2 * ncta;
  const int i = cta + wg * ncta;
  return i < rem ? nfull * 2 * ncta + i : -1;
}

template <int S0 = 0, int S1 = 12>
__device__ __forceinline__ void mma_qkv(uint32_t (&acc)[36], const uint32_t (&A)[48], const uint64_t* d) {
#pragma unroll
  for (int s = S0; s < S1; s++) {
    if (s == 0) wgmma_n144<0>(acc, A[4 * s], A[4 * s + 1], A[4 * s + 2], A[4 * s + 3], d[s]);
    else        wgmma_n144<1>(acc, A[4 * s], A[4 * s + 1], A[4 * s + 2], A[4 * s + 3], d[s]);
  }
  wg_commit();
}
__device__ __forceinline__ void mma_proj(uint32_t (&acc)[48], const uint32_t (&A)[12], const uint64_t* d) {
#pragma unroll
  for (int s = 0; s < 3; s++) wgmma_n192<1>(acc, A[4 * s], A[4 * s + 1], A[4 * s + 2], A[4 * s + 3], d[s]);
}
__device__ __forceinline__ void mma_s(uint32_t (&S)[14], const uint32_t (&Q)[12], const uint64_t* d) {
  wgmma_n56<0>(S, Q[0], Q[1], Q[2], Q[3], d[0]);
  wgmma_n56<1>(S, Q[4], Q[5], Q[6], Q[7], d[1]);
  wgmma_n56<1>(S, Q[8], Q[9], Q[10], Q[11], d[2]);
}
__device__ __forceinline__ void mma_pv(uint32_t (&O)[14], const uint32_t (&P)[12], const uint64_t* d) {
  wgmma_n56t<0>(O, P[0], P[1], P[2], P[3], d[0]);
  wgmma_n56t<1>(O, P[4], P[5], P[6], P[7], d[1]);
  wgmma_n56t<1>(O, P[8], P[9], P[10], P[11], d[2]);
}

#define PIN() asm volatile("pmevent 0;" ::: "memory")
template <int A, int B> __device__ __forceinline__ void hold(uint32_t* v) {
#pragma unroll
  for (int i = A; i < B; i++) asm volatile("" : "+r"(v[i]));
}
__device__ __forceinline__ void stsm12(const uint32_t* v, uint32_t addr) {
#pragma unroll
  for (int j = 0; j < 3; j++) stsm4(addr + 2 * j * KV_PITCH, v[4 * j], v[4 * j + 1], v[4 * j + 2], v[4 * j + 3]);
}
__device__ __forceinline__ void load_v48(uint32_t (&v)[6], uint32_t addr) {
  asm volatile("ldmatrix.sync.aligned.m8n8.x4.shared.b16 {%0,%1,%2,%3}, [%4];" : "=r"(v[0]), "=r"(v[1]), "=r"(v[2]), "=r"(v[3]) : "r"(addr) : "memory");
  asm volatile("ldmatrix.sync.aligned.m8n8.x2.shared.b16 {%0,%1}, [%2];" : "=r"(v[4]), "=r"(v[5]) : "r"(addr + 4 * KV_PITCH) : "memory");
}
__device__ __forceinline__ void finish_o(const uint32_t (&O)[14], const uint32_t (&v)[6], uint32_t p48, uint32_t vmask, uint32_t (&Of)[12]) {
  const float2 l = __half22float2(__hadd2_rn(u2h(__byte_perm(O[12], O[13], 0x5410)), u2h(p48)));
  float i0, i1;
  asm("rcp.approx.ftz.f32 %0, %1;" : "=f"(i0) : "f"(l.x));
  asm("rcp.approx.ftz.f32 %0, %1;" : "=f"(i1) : "f"(l.y));
  const uint32_t inv = packh(i0, i1) & vmask;
#pragma unroll
  for (int i = 0; i < 12; i++) {
    const uint32_t t = h2u(__hfma2(u2h(v[i >> 1]), (i & 1) ? hcast<1>(p48) : hcast<0>(p48), u2h(O[i])));
    Of[i] = (i & 1) ? fmul_b<1>(t, inv) : fmul_b<0>(t, inv);
  }
  hold<0, 12>(Of);
}
#define PSTAT 6
template <int A, int B>
__device__ __forceinline__ void ln_sums(const uint32_t (&X)[48], float (&s1)[2], float (&s2)[2]) {
  if (PSTAT) {
    static_assert(PSTAT == 0 || (A % (2 * PSTAT + !PSTAT) == 0 && B % (2 * PSTAT + !PSTAT) == 0), "whole groups");
#pragma unroll
    for (int g = A; g < B; g += 2 * PSTAT + !PSTAT)
#pragma unroll
      for (int a = 0; a < 2; a++) {
        __half2 p1 = u2h(X[g + a]), p2 = __hmul2_rn(p1, p1);
#pragma unroll
        for (int i = 1; i < PSTAT; i++) { const __half2 v = u2h(X[g + a + 2 * i]); p1 = __hadd2_rn(p1, v); p2 = __hfma2(v, v, p2); }
        const float2 f1 = __half22float2(p1), f2 = __half22float2(p2);
        s1[a] = g == 0 ? f1.x + f1.y : s1[a] + (f1.x + f1.y);
        s2[a] = g == 0 ? f2.x + f2.y : s2[a] + (f2.x + f2.y);
      }
  } else {
#pragma unroll
    for (int i = A; i < B; i++) {
      const float2 f = __half22float2(u2h(X[i]));
      s1[i & 1] = i < 2 ? f.x + f.y : s1[i & 1] + (f.x + f.y);
      s2[i & 1] = fmaf(f.x, f.x, i < 2 ? f.y * f.y : fmaf(f.y, f.y, s2[i & 1]));
    }
  }
  asm volatile("" : "+f"(s1[0]), "+f"(s1[1]), "+f"(s2[0]), "+f"(s2[1]));
}
__device__ __forceinline__ uint32_t ln_rstd(const float (&s1)[2], const float (&s2)[2], float lo, float hi, bool& ok) {
  float r[2];
  ok = true;
#pragma unroll
  for (int a = 0; a < 2; a++) {
    float m = s1[a], v = s2[a];
    m += __shfl_xor_sync(~0u, m, 1); v += __shfl_xor_sync(~0u, v, 1);
    m += __shfl_xor_sync(~0u, m, 2); v += __shfl_xor_sync(~0u, v, 2);
    ok = ok && v <= hi && (v >= lo || v == 0.f);
    m *= 1.0f / 192.0f;
    m *= m;
    v = fmaxf(fmaf(v, 1.0f / 192.0f, -m), 0.f) + 1e-5f;
    ok = ok && m <= (PSTAT ? 16.f : 64.f) * v;
    asm("rsqrt.approx.ftz.f32 %0, %1;" : "=f"(r[a]) : "f"(v));
  }
  uint32_t rk = packh(r[0], r[1]);
  hold<0, 1>(&rk);
  return rk;
}
__device__ __forceinline__ void scale12(uint32_t (&D)[12], const uint32_t* a, uint32_t r) {
#pragma unroll
  for (int i = 0; i < 12; i++) D[i] = (i & 1) ? fmul_b<1>(a[i], r) : fmul_b<0>(a[i], r);
  hold<0, 12>(D);
}
template <int CC>
__device__ __forceinline__ void store_out(const uint32_t (&Y)[48], uint8_t* o0, uint8_t* o1, uint32_t vmask) {
  uint32_t T[8];
#pragma unroll
  for (int i = 0; i < 8; i++) {
    const float2 f = __half22float2(u2h(Y[8 * CC + i]));
    T[i] = pack2(f.x, f.y);
  }
  asm volatile("{\n.reg .pred p;\nsetp.ne.u32 p, %5, 0;\n@p st.global.v4.u32 [%0], {%1,%2,%3,%4};\n}\n"
               :: "l"(o0 + CC * 64), "r"(T[0]), "r"(T[2]), "r"(T[4]), "r"(T[6]), "r"(vmask) : "memory");
  asm volatile("{\n.reg .pred p;\nsetp.lt.s32 p, %5, 0;\n@p st.global.v4.u32 [%0], {%1,%2,%3,%4};\n}\n"
               :: "l"(o1 + CC * 64), "r"(T[1]), "r"(T[3]), "r"(T[5]), "r"(T[7]), "r"(vmask) : "memory");
}
__device__ __forceinline__ void proxy_fence() { asm volatile("fence.proxy.async.shared::cta;" ::: "memory"); }
__device__ __forceinline__ uint32_t fadd2(uint32_t a, uint32_t b) { return h2u(__hadd2_rn(u2h(a), u2h(b))); }
__device__ __forceinline__ void row_max(const uint32_t (&S)[14], uint32_t& k48, uint32_t& mx) {
  k48 = __shfl_sync(~0u, __byte_perm(S[12], S[13], 0x5410), 0, 4);
  const uint32_t m0 = fmax2(fmax2(fmax2(S[0], S[2]), S[4]), fmax2(fmax2(S[6], S[8]), S[10]));
  const uint32_t m1 = fmax2(fmax2(fmax2(S[1], S[3]), S[5]), fmax2(fmax2(S[7], S[9]), S[11]));
  mx = fmax2(__byte_perm(m0, m1, 0x5410), __byte_perm(m0, m1, 0x7632));
  mx = fmax2(mx, __shfl_xor_sync(~0u, mx, 1));
  mx = fmax2(fmax2(mx, __shfl_xor_sync(~0u, mx, 2)), k48);
  hold<0, 1>(&mx);
}
__device__ __forceinline__ void row_exp(const uint32_t (&S)[14], uint32_t k48, uint32_t mx, uint32_t (&P)[12], uint32_t& p48) {
#pragma unroll
  for (int j = 0; j < 12; j++) P[j] = fex2((j & 1) ? fsub_b<1>(S[j], mx) : fsub_b<0>(S[j], mx));
  p48 = fex2(h2u(__hsub2_rn(u2h(k48), u2h(mx))));
  hold<0, 12>(P); hold<0, 1>(&p48);
}
template <int S0, int S1>
__device__ __forceinline__ void load_x(uint32_t (&X)[48], uint32_t t0) {
#pragma unroll
  for (int s = S0; s < S1; s++)
    asm volatile("ld.shared.v4.u32 {%0,%1,%2,%3}, [%4];" : "=r"(X[4 * s]), "=r"(X[4 * s + 1]), "=r"(X[4 * s + 2]), "=r"(X[4 * s + 3])
                 : "r"(((s & 1) ? (t0 ^ 16) : t0) + (s >> 1) * 128) : "memory");
}

#define WDIV 1
template <int P, int CNT, int DIV = WDIV> __device__ __forceinline__ void load_slices(uint32_t sb, const Descs& ds) {
  constexpr int st = stage_of(P);
  constexpr bool first = P == 0 || stage_of(P - 1) != st;
  if (first)
    asm volatile("{\n.reg .pred p;\nelect.sync _|p, 0xffffffff;\n@p mbarrier.arrive.expect_tx.shared::cta.b64 _, [%0], %1;\n}\n"
                 :: "r"(sb + BAR_WFULL + 8 * st), "n"((st < 4 ? 3 : st == 4 ? 2 : 1) * SLICE / DIV) : "memory");
  asm volatile("{\n.reg .pred p;\nelect.sync _|p, 0xffffffff;\n"
               "@p cp.async.bulk.shared::cluster.global.mbarrier::complete_tx::bytes [%0], [%1], %2, [%3];\n}\n"
               :: "r"(sb + OFF_W + (P & 7) * SLICE), "l"(ds.src[P]), "n"(CNT * SLICE / DIV), "r"(sb + BAR_WFULL + 8 * st) : "memory");
}
__device__ __forceinline__ void warp_arrive(uint32_t bar) {
  asm volatile("{\n.reg .pred p;\nelect.sync _|p, 0xffffffff;\n@p mbarrier.arrive.shared::cta.b64 _, [%0];\n}\n" :: "r"(bar) : "memory");
}

__device__ __forceinline__ float2 fp16_limits(int lane) {
  float mx[4] = {0.f, 0.f, 0.f, 0.f}, sm[4] = {0.f, 0.f, 0.f, 0.f};
#pragma unroll
  for (int i = 0; i < 3; i++) {
    const int nb = lane + 32 * i, part = nb < 72 ? (nb % 18) / 6 : 3;
    const float2 w = g_wnorm[nb];
#pragma unroll
    for (int k = 0; k < 4; k++) if (part == k) { mx[k] = fmaxf(mx[k], w.x); sm[k] += w.y; }
  }
#pragma unroll
  for (int k = 0; k < 4; k++)
#pragma unroll
    for (int d = 16; d; d >>= 1) { mx[k] = fmaxf(mx[k], __shfl_xor_sync(~0u, mx[k], d)); sm[k] += __shfl_xor_sync(~0u, sm[k], d); }
  const float big = fmaxf(fmaxf(mx[0], mx[1]), mx[2]);
  float small = 1.f;
  bool good = sm[0] + sm[1] + sm[2] + sm[3] < 1e30f;
#pragma unroll
  for (int k = 0; k < 4; k++) { good = good && (mx[k] == 0.f || mx[k] >= 2.5e-4f); if (k < 3 && mx[k] > 0.f) small = fminf(small, mx[k]); }
  good = good && 250.f * 48.f * sqrtf(mx[0] * mx[1]) <= 5e4f;
  good = good && 16.f * 49.f * sqrtf(mx[2]) <= 5e4f && big <= 1e6f;
  good = good && 16.f * sqrtf(sm[2] * mx[3]) <= 2e4f;
  return make_float2(192.f * 2.4e-7f / small, good ? fminf(2.5e8f, 9e8f / fmaxf(big, 1e-30f)) : -1.f);
}

__device__ __forceinline__ void slow_window(float* sm, int w, int t, const __nv_bfloat16* __restrict__ x, const __nv_bfloat16* __restrict__ dw,
                                            const __nv_bfloat16* __restrict__ wqkv, const __nv_bfloat16* __restrict__ wo, __nv_bfloat16* __restrict__ out) {
  float* x0 = sm; float* h = x0 + 49 * CH; float* qkv = h + 49 * CH; float* S = qkv + 49 * 576;
  const int wy = w / NWX, wx = w % NWX;
  auto sync = [] { asm volatile("bar.sync 6, 128;" ::: "memory"); };
#pragma unroll 1
  for (int i = t; i < 49 * CH; i += 128) {
    const int k = i / CH, c = i % CH, y = wy * 7 + k / 7, xx = wx * 7 + k % 7;
    float pe = 0.f;
#pragma unroll 1
    for (int a = 0; a < 9; a++) {
      const int yy = y + a / 3 - 1, xc = xx + a % 3 - 1;
      if (yy >= 0 && yy < IMG && xc >= 0 && xc < IMG) pe = fmaf(__bfloat162float(x[((size_t)yy * IMG + xc) * CH + c]), __bfloat162float(dw[a * CH + c]), pe);
    }
    x0[i] = __bfloat162float(__float2bfloat16(__bfloat162float(x[((size_t)y * IMG + xx) * CH + c]) + pe));
  }
  sync();
  if (t < 49) {
    float m = 0.f, v = 0.f;
#pragma unroll 1
    for (int c = 0; c < CH; c++) m += x0[t * CH + c];
    m *= 1.0f / CH;
#pragma unroll 1
    for (int c = 0; c < CH; c++) { const float d = x0[t * CH + c] - m; v = fmaf(d, d, v); }
    const float rs = 1.0f / sqrtf(v * (1.0f / CH) + 1e-5f);
#pragma unroll 1
    for (int c = 0; c < CH; c++) h[t * CH + c] = (x0[t * CH + c] - m) * rs;
  }
  sync();
#pragma unroll 1
  for (int i = t; i < 7 * 576; i += 128) {
    const int n = i % 576, k0 = i / 576 * 7;
    float a[7] = {0.f, 0.f, 0.f, 0.f, 0.f, 0.f, 0.f};
#pragma unroll 1
    for (int c = 0; c < CH; c++) {
      const float wv = __bfloat162float(wqkv[c * 576 + n]);
#pragma unroll
      for (int k = 0; k < 7; k++) a[k] = fmaf(h[(k0 + k) * CH + c], wv, a[k]);
    }
#pragma unroll
    for (int k = 0; k < 7; k++) qkv[(k0 + k) * 576 + n] = a[k];
  }
  sync();
#pragma unroll 1
  for (int hd = 0; hd < 4; hd++) {
#pragma unroll 1
    for (int i = t; i < 49 * 49; i += 128) {
      const int a = i / 49, b = i % 49;
      float v = 0.f;
#pragma unroll 1
      for (int d = 0; d < 48; d++) v = fmaf(qkv[a * 576 + hd * 48 + d], qkv[b * 576 + 192 + hd * 48 + d], v);
      S[i] = v * 0.14433756729740643f;
    }
    sync();
    if (t < 49) {
      float m = S[t * 49], l = 0.f;
#pragma unroll 1
      for (int b = 1; b < 49; b++) m = fmaxf(m, S[t * 49 + b]);
#pragma unroll 1
      for (int b = 0; b < 49; b++) { const float e = expf(S[t * 49 + b] - m); S[t * 49 + b] = e; l += e; }
#pragma unroll 1
      for (int b = 0; b < 49; b++) S[t * 49 + b] /= l;
    }
    sync();
#pragma unroll 1
    for (int i = t; i < 49 * 48; i += 128) {
      const int a = i / 48, d = i % 48;
      float v = 0.f;
#pragma unroll 1
      for (int b = 0; b < 49; b++) v = fmaf(S[a * 49 + b], qkv[b * 576 + 384 + hd * 48 + d], v);
      h[a * CH + hd * 48 + d] = v;
    }
    sync();
  }
#pragma unroll 1
  for (int i = t; i < 7 * CH; i += 128) {
    const int n = i % CH, k0 = i / CH * 7;
    float a[7] = {0.f, 0.f, 0.f, 0.f, 0.f, 0.f, 0.f};
#pragma unroll 1
    for (int c = 0; c < CH; c++) {
      const float wv = __bfloat162float(wo[c * CH + n]);
#pragma unroll
      for (int k = 0; k < 7; k++) a[k] = fmaf(h[(k0 + k) * CH + c], wv, a[k]);
    }
#pragma unroll
    for (int k = 0; k < 7; k++)
      out[((size_t)(wy * 7 + k0 / 7) * IMG + wx * 7 + k) * CH + n] = __float2bfloat16(x0[(k0 + k) * CH + n] + a[k]);
  }
  sync();
}

__global__ void __launch_bounds__(384, 1)
fused_kernel(const __grid_constant__ CUtensorMap tmx, const __grid_constant__ CUtensorMap tmp, const __grid_constant__ Descs ds, const __nv_bfloat16* __restrict__ dw, __nv_bfloat16* __restrict__ out, const int never,
             const __nv_bfloat16* __restrict__ x, const __nv_bfloat16* __restrict__ wqkv, const __nv_bfloat16* __restrict__ wo) {
  extern __shared__ __align__(1024) uint8_t smem[];
  const uint32_t sb = (uint32_t)__cvta_generic_to_shared(smem);
  const int tid = threadIdx.x, lane = tid & 31;
  const int warp = __shfl_sync(0xffffffffu, tid >> 5, 0);
  const int cta = blockIdx.x, ncta = gridDim.x;
  const int nfull = NWIN / (2 * ncta);
  const int nrounds = nfull + ((NWIN - nfull * 2 * ncta) > cta ? 1 : 0);

  if (warp == 0) GTS(0);
  auto prefetch_round = [&](int r) {
#pragma unroll
    for (int k = 0; k < 2; k++) {
      const int w = window_of(r, nfull, cta, ncta, k);
      if (w >= 0) {
        const int a = w / NWX;
        asm volatile("{\n.reg .pred p;\nelect.sync _|p, 0xffffffff;\n@p cp.async.bulk.prefetch.tensor.3d.L2.global [%0, {0, %1, %2}];\n}\n"
                     :: "l"(reinterpret_cast<uint64_t>(&tmp)), "r"((w - a * NWX) * 7 - 1), "r"(a * 7 - 1) : "memory");
      }
    }
  };
  if (warp == 11) prefetch_round(0);
  if (warp == 10 && lane == 0) asm volatile("prefetch.tensormap [%0];" :: "l"(reinterpret_cast<uint64_t>(&tmx)) : "memory");
  if (tid == 0) {
    if ((sb & 0x3FFFF) != SMEM_BASE || nrounds > 128) __trap();
    for (int i = 0; i < 7; i++) { mbar_init(sb + BAR_WFULL + 8 * i, 1); mbar_init(sb + BAR_WEMPTY + 8 * i, 8); }
    for (int i = 0; i < 9; i++) mbar_init(sb + BAR_XFULL + 8 * i, 1);
    mbar_init(sb + BAR_TFULL, 3);
    mbar_init(sb + BAR_TEMPTY, 8);
    asm volatile("fence.mbarrier_init.release.cluster;" ::: "memory");
  }
  if (tid >= 128 && tid < 320) {
    *reinterpret_cast<uint32_t*>(smem + OFF_ZERO + (tid - 128) * 4) = 0;
    if (tid < 136) *reinterpret_cast<uint32_t*>(smem + OFF_REDO + (tid - 128) * 4) = 0;
  }
  if (tid < 96) {
    *reinterpret_cast<uint4*>(smem + OFF_KV + (tid / 48) * KV_BYTES + 6 * KV_PITCH + (tid % 48) * 16) = make_uint4(0x3c003c00u, 0x3c003c00u, 0x3c003c00u, 0x3c003c00u);
    proxy_fence();
  }
  __syncthreads();

  if (warp >= 8) {
    asm volatile("setmaxnreg.dec.sync.aligned.u32 " PREGS ";");
    if (warp == 11) {
      asm volatile("griddepcontrol.wait;" ::: "memory");
      load_slices<1, 3, 1>(sb, ds);
      *reinterpret_cast<float2*>(smem + OFF_LIM) = fp16_limits(lane);
      load_slices<0, 1, 1>(sb, ds); load_slices<4, 1, 1>(sb, ds); load_slices<5, 3, 1>(sb, ds);
      for (int r = 0; r < nrounds; r++) {
        const uint32_t par = r & 1;
        const bool next_round = r + 1 < nrounds;
        mbar_wait(sb + BAR_WEMPTY + 40, par); load_slices<8, 1>(sb, ds);
        mbar_wait(sb + BAR_WEMPTY, par);      load_slices<9, 2>(sb, ds); load_slices<11, 1>(sb, ds);
        mbar_wait(sb + BAR_WEMPTY + 48, par); load_slices<12, 1>(sb, ds);
        mbar_wait(sb + BAR_WEMPTY + 8, par);  load_slices<13, 1>(sb, ds); load_slices<14, 2>(sb, ds);
        mbar_wait(sb + BAR_WEMPTY + 16, par); load_slices<0, 1>(sb, ds); if (next_round) load_slices<1, 2>(sb, ds);
        mbar_wait(sb + BAR_WEMPTY + 24, par);
        if (next_round) load_slices<3, 1>(sb, ds);
        load_slices<4, 1>(sb, ds);
        if (next_round) {
          load_slices<5, 1>(sb, ds);
          mbar_wait(sb + BAR_WEMPTY + 32, par); load_slices<6, 2>(sb, ds);
        }
      }
    } else {
      const int cw = warp - 8;
      const int win = lane >> 4;
      const int ch0 = cw * 64 + (lane & 15) * 4;
      uint32_t wt[9][2];
#pragma unroll
      for (int t = 0; t < 9; t++) {
        uint2 v = *reinterpret_cast<const uint2*>(dw + t * CH + ch0);
        wt[t][0] = v.x; wt[t][1] = v.y;
      }
      const uint32_t xs = sb + OFF_X + cw * 3 * XSLOT;
      const uint32_t xld = xs + (lane >> 4) * 1152 + (lane & 15) * 8;
      const uint32_t xbar = sb + BAR_XFULL + cw * 24;
      const uint32_t st0 = sb + OFF_TILE + win * TILE_BYTES + ch0 * 4;
      const uint64_t tm = reinterpret_cast<uint64_t>(&tmx);
      int cx0, cy0, cx1, cy1;
      auto coords = [&](int r) {
        const int w0 = window_of(r, nfull, cta, ncta, 0);
        int w1 = window_of(r, nfull, cta, ncta, 1);
        if (w1 < 0) w1 = w0;
        const int a = w0 / NWX, b = w1 / NWX;
        cx0 = (w0 - a * NWX) * 7 - 1; cy0 = a * 7 - 1;
        cx1 = (w1 - b * NWX) * 7 - 1; cy1 = b * 7 - 1;
      };
      auto issue = [&](int slot, int dy) {
        asm volatile("{\n.reg .pred p;\nelect.sync _|p, 0xffffffff;\n"
                     "@p mbarrier.arrive.expect_tx.shared::cta.b64 _, [%2], %8;\n"
                     "@p cp.async.bulk.tensor.3d.shared::cluster.global.mbarrier::complete_tx::bytes [%0], [%1, {%3, %4, %5}], [%2];\n"
                     "@p cp.async.bulk.tensor.3d.shared::cluster.global.mbarrier::complete_tx::bytes [%0 + 1152], [%1, {%3, %6, %7}], [%2];\n}\n"
                     :: "r"(xs + slot * XSLOT), "l"(tm), "r"(xbar + slot * 8), "r"(cw * 64), "r"(cx0), "r"(cy0 + dy), "r"(cx1), "r"(cy1 + dy), "n"(XSLOT) : "memory");
      };
      uint32_t accA[7][2], accB[7][2], ctr[7][2], held[2];
      auto row = [&](auto fin, auto mid, auto top, int slot, int y) {
        const uint32_t ld = xld + slot * XSLOT;
        const uint32_t sa = (st0 ^ ((y & 1) << 4)) + y * 2304;
        uint32_t cur[9][2], o[2][2];
#pragma unroll
        for (int p = 0; p < 5; p++)
          asm volatile("ld.shared.v2.u32 {%0,%1}, [%2];" : "=r"(cur[p][0]), "=r"(cur[p][1]) : "r"(ld + p * 128));
#pragma unroll
        for (int j = 0; j < 7; j++) {
          if (j >= 1 && j + 4 < 9)
            asm volatile("ld.shared.v2.u32 {%0,%1}, [%2];" : "=r"(cur[j + 4][0]), "=r"(cur[j + 4][1]) : "r"(ld + (j + 4) * 128));
          if (fin.v) {
#pragma unroll
            for (int e = 0; e < 2; e++) {
              uint32_t a = hfma(cur[j][e], wt[6][e], accA[j][e]);
              a = hfma(cur[j + 1][e], wt[7][e], a);
              a = hfma(cur[j + 2][e], wt[8][e], a);
              a = hadd(ctr[j][e], a);
              o[j & 1][e] = packh(lo2f(a), hi2f(a));
            }
            if (j & 1)
              asm volatile("st.shared.v4.u32 [%0], {%1,%2,%3,%4};" :: "r"((j == 3 ? sa ^ 16 : sa) + (j >> 1) * 768),
                           "r"(o[0][0]), "r"(o[1][0]), "r"(o[0][1]), "r"(o[1][1]) : "memory");
            if (j == 6) {
              const uint32_t sb6 = (st0 ^ ((~y & 2) << 3)) + (21 + (y >> 1)) * 768;
              if (fin.v == 2)
                asm volatile("st.shared.v4.u32 [%0], {%1,%2,%3,%2};" :: "r"(sb6), "r"(o[0][0]), "r"(0), "r"(o[0][1]) : "memory");
              else
                asm volatile("{\n.reg .pred p;\nsetp.ne.s32 p, %5, 0;\n@p st.shared.v4.u32 [%0], {%1,%2,%3,%4};\n}\n"
                             :: "r"(sb6), "r"(held[0]), "r"(o[0][0]), "r"(held[1]), "r"(o[0][1]), "r"(y & 1) : "memory");
              held[0] = o[0][0]; held[1] = o[0][1];
            }
          }
#pragma unroll
          for (int e = 0; e < 2; e++) {
            if (mid.v) {
              uint32_t a = hfma(cur[j][e], wt[3][e], accB[j][e]);
              a = hfma(cur[j + 1][e], wt[4][e], a);
              accA[j][e] = hfma(cur[j + 2][e], wt[5][e], a);
              ctr[j][e] = cur[j + 1][e];
            }
            if (top.v) {
              uint32_t a = hmul(cur[j][e], wt[0][e]);
              a = hfma(cur[j + 1][e], wt[1][e], a);
              accB[j][e] = hfma(cur[j + 2][e], wt[2][e], a);
            }
          }
        }
      };
      held[0] = held[1] = 0;
      coords(0);
      issue(0, 0); issue(1, 1); issue(2, 2);
      for (int r = 0; r < nrounds; r++) {
        const bool more = r + 1 < nrounds;
        mbar_wait(xbar, r & 1);
        if (r > 0) issue(2, 2);
        row(IC<0>{}, IC<0>{}, IC<1>{}, 0, 0);
        mbar_wait(xbar + 8, r & 1);
        issue(0, 3);
        row(IC<0>{}, IC<1>{}, IC<1>{}, 1, 0);
        if (r > 0) mbar_wait(sb + BAR_TEMPTY, (r - 1) & 1);
        TR(0);
#pragma unroll 1
        for (int k = 0; k < 2; k++) {
          mbar_wait(xbar + 16, (r + k) & 1);
          issue(1, 4 + 3 * k);
          row(IC<1>{}, IC<1>{}, IC<1>{}, 2, 3 * k);
          mbar_wait(xbar, (r + k + 1) & 1);
          issue(2, 5 + 3 * k);
          row(IC<1>{}, IC<1>{}, IC<1>{}, 0, 3 * k + 1);
          mbar_wait(xbar + 8, (r + k + 1) & 1);
          if (k == 1 && more) coords(r + 1);
          if (k == 0 || more) issue(0, k == 0 ? 6 : 0);
          row(IC<1>{}, IC<1>{}, IC<1>{}, 1, 3 * k + 2);
        }
        mbar_wait(xbar + 16, r & 1);
        if (more) issue(1, 1);
        row(IC<2>{}, IC<0>{}, IC<0>{}, 2, 6);
        warp_arrive(sb + BAR_TFULL);
        TR(1);
      }
    }
    asm volatile("bar.sync 5, 384;" ::: "memory");
#pragma unroll 1
    for (int i = 0; i < 8; i++) {
      uint32_t bits = *reinterpret_cast<volatile uint32_t*>(smem + OFF_REDO + 4 * i);
#pragma unroll 1
      for (; bits; bits &= bits - 1)
        slow_window(reinterpret_cast<float*>(smem), window_of((i & 3) * 32 + __ffs(bits) - 1, nfull, cta, ncta, i >> 2), tid - 256, x, dw, wqkv, wo, out);
    }
  } else {
    asm volatile("setmaxnreg.inc.sync.aligned.u32 " CREGS ";");
    const int wg = warp >> 2, w4 = warp & 3, g = lane >> 2, q = lane & 3;
    const int row0 = w4 * 16 + g, row1 = row0 + 8;
    const int ps = min(w4 * 8 + g, 24);
    const int pix0 = ps < 21 ? (ps / 3) * IMG + (ps % 3) * 2 : (ps - 21) * 2 * IMG + 6;
    const int pix1 = pix0 + (ps < 21 ? 1 : ps < 24 ? IMG : 0);
    const uint32_t kv = sb + OFF_KV + wg * KV_BYTES;
    const int srow = w4 * 16 + (lane & 15);
    const uint32_t vst = kv + (lane >> 4) * KV_PITCH + (srow < 56 ? srow : min(srow - 7, 55)) * 16;
    uint32_t misc = ((uint32_t)pix1 << 20) | ((uint32_t)pix0 << 8) | q;
    const uint32_t v48 = kv + (lane >> 3) * KV_PITCH + 48 * 16;
    const uint32_t vmask = (row0 < 49 ? 0xffffu : 0u) | (row1 < 49 ? 0xffff0000u : 0u);

    const uint32_t tx = sb + q * 32 + (row0 < 49 ? OFF_TILE + wg * TILE_BYTES + ps * 768 + (ps & 1) * 16 : OFF_ZERO + 16);
    const int myrounds = window_of(nrounds - 1, nfull, cta, ncta, wg) < 0 ? nrounds - 1 : nrounds;

    if (never == 2) return;
    uint32_t H[48], Y[48];
    const uint64_t* dkv = ds.kv[wg];
    uint32_t P[12], Ofc[12], p48 = 0;
#pragma unroll
    for (int i = 0; i < 48; i++) Y[i] = 0;
#pragma unroll
    for (int i = 0; i < 12; i++) P[i] = Ofc[i] = 0;
    mbar_wait(sb + BAR_TFULL, 0);
    if (warp == 0) GTS(4);
    load_x<0, 12>(H, tx);
    warp_arrive(sb + BAR_TEMPTY);
    if (wg == 1) turn_pass(1);

    uint8_t *o0, *o1;
    uint32_t omask;
    auto out_setup = [&](int r) {
      omask = r >= 0 ? vmask : 0u;
      const int w = window_of(r, nfull, cta, ncta, wg);
      const int wy = w / NWX, wx = w - wy * NWX;
      asm volatile("" : "+r"(misc));
      const uint32_t wb = (uint32_t)(wy * 7 * IMG + wx * 7) * 384u + (misc & 3) * 16;
      o0 = reinterpret_cast<uint8_t*>(out) + (wb + ((misc >> 8) & 0xfff) * 384u);
      o1 = reinterpret_cast<uint8_t*>(out) + (wb + (misc >> 20) * 384u);
    };
#define OUT(c) store_out<c>(Y, o0, o1, omask)
    auto release = [&](int stage) { warp_arrive(sb + BAR_WEMPTY + 8 * stage); };

    for (int r = 0;; r++) {
      const uint32_t par = r & 1;
      uint32_t acc[36], S[14], O[14], Q[12], V[12], Ofa[12], Ofb[12], vr[6], k48, mx;
      if (r == myrounds) {
        const bool idle = r < nrounds;
        mbar_wait(sb + BAR_WFULL + 40, par);
        turn_wait(wg);
        wg_fence(); mma_pv(O, P, dkv + 4); mma_proj(Y, Ofc, ds.p + 6); wg_commit();
        turn_pass(wg);
        load_v48(vr, v48);
        wg_wait<0>(); keep(O); keep(Y);
        finish_o(O, vr, p48, vmask, Ofa);
        if (idle) { release(5); release(0); release(1); release(2); release(3); }
        mbar_wait(sb + BAR_WFULL + 48, par);
        turn_wait(wg);
        wg_fence(); mma_proj(Y, Ofa, ds.p + 9); wg_commit();
        if (wg == 0 || idle) turn_pass(wg);
        wg_wait<0>(); keep(Y);
        if (idle) { release(6); turn_wait(wg); turn_pass(wg); }
        out_setup(r - 1);
        OUT(0); PIN(); OUT(1); PIN(); OUT(2); PIN(); OUT(3); PIN(); OUT(4); PIN(); OUT(5);
        if (idle) {
          turn_wait(wg); turn_pass(wg);
          turn_wait(wg); turn_pass(wg);
          turn_wait(wg); turn_pass(wg);
          turn_wait(wg);
        }
        if (w4 == 0) GTS(5 + wg);
        asm volatile("bar.arrive 5, 384;" ::: "memory");
        break;
      }
      float s1[2], s2[2];
      if (SA > 0) ln_sums<0, SA>(H, s1, s2);
      mbar_wait(sb + BAR_WFULL + 40, par);
      mbar_wait(sb + BAR_WFULL, par);
      TR(0);
      turn_wait(wg);
      TR(1);
      wg_fence(); mma_pv(O, P, dkv + 4); mma_proj(Y, Ofc, ds.p + 6); wg_commit(); mma_qkv<0, 3>(acc, H, ds.q[0]);
      PIN();
      ln_sums<SA, SB>(H, s1, s2);
      PIN();
      wg_fence(); mma_qkv<3, 8>(acc, H, ds.q[0]);
      PIN();
      ln_sums<SB, SC>(H, s1, s2);
      PIN();
      wg_fence(); mma_qkv<8, 12>(acc, H, ds.q[0]);
      turn_pass(wg);
      TR(2);
      load_v48(vr, v48);
      wg_wait<3>(); keep(O); keep(Y);
      release(5);
      wg_sync(wg);
      PIN();
      finish_o(O, vr, p48, vmask, Ofa);
      if (SC < 48) ln_sums<SC, 48>(H, s1, s2);
      float lim_lo, lim_hi;
      asm volatile("ld.shared.v2.f32 {%0,%1}, [%2];" : "=f"(lim_lo), "=f"(lim_hi) : "r"(sb + OFF_LIM) : "memory");
      bool ok;
      const uint32_t rk = ln_rstd(s1, s2, lim_lo, lim_hi, ok);
      asm volatile("{\n.reg .pred p;\nsetp.eq.s32 p, %2, 0;\n@p red.shared.or.b32 [%0], %1;\n}\n"
                   :: "r"(sb + OFF_REDO + wg * 16 + (r >> 5) * 4), "r"(1u << (r & 31)), "r"((int)ok) : "memory");
      PIN();
      TR(3);
      wg_wait<0>(); keep(acc);
      TR(4);
      release(0);
      scale12(V, acc, rk); stsm12(V, vst + KV_KOFF);
      scale12(V, acc + 24, rk); stsm12(V, vst);
      scale12(Q, acc + 12, rk); PIN();
      proxy_fence();
      mbar_wait(sb + BAR_WFULL + 48, par);
      mbar_wait(sb + BAR_WFULL + 8, par);
      TR(5);
      turn_wait(wg);
      TR(6);
      wg_fence(); mma_proj(Y, Ofa, ds.p + 9); wg_commit(); mma_s(S, Q, dkv); mma_qkv<0, 2>(acc, H, ds.q[1]);
      out_setup(r - 1);
      PIN();
      wg_wait<1>(); keep(Y);
      release(6);
      wg_fence(); mma_qkv<2, 6>(acc, H, ds.q[1]);
      PIN();
      OUT(0);
      PIN();
      wg_wait<1>(); keep(S);
      wg_fence(); mma_qkv<6, 9>(acc, H, ds.q[1]);
      PIN();
      row_max(S, k48, mx);
      OUT(1);
      PIN();
      wg_fence(); mma_qkv<9, 12>(acc, H, ds.q[1]);
      turn_pass(wg);
      PIN();
      OUT(2); PIN();
      OUT(3); PIN();
      row_exp(S, k48, mx, P, p48);
      PIN();
      TR(7);
      wg_wait<0>(); keep(acc);
      TR(8);
      release(1);
      wg_sync(wg);
      scale12(V, acc, rk); stsm12(V, vst + KV_KOFF);
      scale12(Q, acc + 12, rk); scale12(V, acc + 24, rk); PIN();
      proxy_fence();
#define TURN(ID, OF, G1, G2, G3, X1)                                                       \
      TR(ID + 1);                                                                       \
      turn_wait(wg);                                                                    \
      wg_fence(); mma_pv(O, P, dkv + 4); mma_s(S, Q, dkv); wg_commit(); G1;             \
      PIN();                                                                            \
      TR(ID + 2);                                                                       \
      load_v48(vr, v48);                                                                \
      X1;                                                                               \
      PIN();                                                                            \
      wg_wait<1>(); keep(S); keep(O);                                                   \
      wg_sync(wg);                                         \
      wg_fence(); G2;                                                                   \
      if (KB == 12) turn_pass(wg);                                                      \
      PIN();                                                                            \
      stsm12(V, vst);                                                                   \
      finish_o(O, vr, p48, vmask, OF);                                                    \
      row_max(S, k48, mx);                                                              \
      PIN();                                                                            \
      if (KB < 12) { wg_fence(); G3; turn_pass(wg); }                                                                 \
      PIN();                                                                            \
      TR(ID + 3);
#define NEXT_HEAD(ID, HD)                                                               \
      row_exp(S, k48, mx, P, p48);                                                      \
      PIN();                                                                            \
      TR(ID + 4);                                                                       \
      wg_wait<0>(); keep(acc);                                                          \
      release(HD);                                                                      \
      scale12(V, acc, rk); stsm12(V, vst + KV_KOFF);                                    \
      scale12(Q, acc + 12, rk); scale12(V, acc + 24, rk); PIN();
      mbar_wait(sb + BAR_WFULL + 16, par);
      TURN(8, Ofa, (mma_qkv<0, KA>(acc, H, ds.q[2])), (mma_qkv<KA, KB>(acc, H, ds.q[2])), (mma_qkv<KB, 12>(acc, H, ds.q[2])), OUT(4))
      OUT(5); PIN();
      NEXT_HEAD(8, 2)
      proxy_fence();
      mbar_wait(sb + BAR_WFULL + 24, par);
      TURN(12, Ofb, (mma_qkv<0, KA>(acc, H, ds.q[3])), (mma_qkv<KA, KB>(acc, H, ds.q[3])), (mma_qkv<KB, 12>(acc, H, ds.q[3])), )
      NEXT_HEAD(12, 3)
#pragma unroll
      for (int i = 0; i < 48; i++) Y[i] = (i & 1) ? H[i] ^ never : H[i] + never;
      hold<0, 48>(Y); PIN();
      proxy_fence();
      mbar_wait(sb + BAR_WFULL + 32, par);
      TR(17);
      turn_wait(wg);
      wg_fence(); mma_pv(O, P, dkv + 4); mma_s(S, Q, dkv); wg_commit(); mma_proj(Y, Ofa, ds.p); mma_proj(Y, Ofb, ds.p + 3); wg_commit();
      turn_pass(wg);
      PIN();
      TR(18);
      load_v48(vr, v48);
      if (r + 1 < myrounds) mbar_wait(sb + BAR_TFULL, par ^ 1);
      load_x<0, 4>(H, tx);
      wg_wait<1>(); keep(S); keep(O);
      wg_sync(wg);
      PIN();
      TR(19);
      row_max(S, k48, mx);
      finish_o(O, vr, p48, vmask, Ofc);
      stsm12(V, vst);
      PIN();
      load_x<4, 8>(H, tx);
      row_exp(S, k48, mx, P, p48);
      PIN();
      load_x<8, 12>(H, tx);
      warp_arrive(sb + BAR_TEMPTY);
      TR(20);
      wg_wait<0>(); keep(Y);
      release(4);
      proxy_fence();
      TR(21);
#undef TURN
#undef NEXT_HEAD
    }
  }
}

typedef CUresult (*EncodeFn)(CUtensorMap*, CUtensorMapDataType, cuuint32_t, void*, const cuuint64_t*, const cuuint64_t*,
                             const cuuint32_t*, const cuuint32_t*, CUtensorMapInterleave, CUtensorMapSwizzle,
                             CUtensorMapL2promotion, CUtensorMapFloatOOBfill);

}

extern "C" void kernel_launch(void* const* d_in, const int* in_sizes, int n_in, void* d_out, int out_size) {
  const __nv_bfloat16* x = (const __nv_bfloat16*)d_in[0];
  const __nv_bfloat16* dw = (const __nv_bfloat16*)d_in[1];
  const __nv_bfloat16* wqkv = (const __nv_bfloat16*)d_in[2];
  const __nv_bfloat16* wo = (const __nv_bfloat16*)d_in[3];
  static EncodeFn encode = nullptr;
  static int nsm = 0;
  static void* wpack = nullptr;
  if (!encode) {
    void* fn = nullptr;
    cudaDriverEntryPointQueryResult qr;
    cudaGetDriverEntryPoint("cuTensorMapEncodeTiled", &fn, cudaEnableDefault, &qr);
    encode = (EncodeFn)fn;
    int dev = 0;
    cudaGetDevice(&dev);
    cudaDeviceGetAttribute(&nsm, cudaDevAttrMultiProcessorCount, dev);
    cudaGetSymbolAddress(&wpack, g_wpack);
    cudaFuncSetAttribute(fused_kernel, cudaFuncAttributeMaxDynamicSharedMemorySize, SMEM_BYTES);
  }
  CUtensorMap tmx;
  cuuint64_t gdim[3] = {CH, IMG, IMG};
  cuuint64_t gstr[2] = {CH * 2, (cuuint64_t)CH * 2 * IMG};
  cuuint32_t box[3] = {64, 9, 1};
  cuuint32_t estr[3] = {1, 1, 1};
  encode(&tmx, CU_TENSOR_MAP_DATA_TYPE_BFLOAT16, 3, (void*)x, gdim, gstr, box, estr, CU_TENSOR_MAP_INTERLEAVE_NONE,
         CU_TENSOR_MAP_SWIZZLE_NONE, CU_TENSOR_MAP_L2_PROMOTION_L2_128B, CU_TENSOR_MAP_FLOAT_OOB_FILL_NONE);
  Descs ds;
  for (int i = 0; i < 12; i++) {
    for (int h = 0; h < 4; h++) ds.q[h][i] = mkdesc(SMEM_BASE + OFF_W + qkv_pos(h, i) % (8 * SLICE), 128, 256);
    ds.p[i] = mkdesc(SMEM_BASE + OFF_W + wo_pos(i) % (8 * SLICE), 128, 256);
  }
  for (int i = 0; i < 16; i++) ds.src[i] = (const uint8_t*)wpack + i * SLICE;
  for (int g = 0; g < 2; g++)
    for (int i = 0; i < 4; i++) {
      ds.kv[g][i] = mkdesc(SMEM_BASE + OFF_KV + g * KV_BYTES + KV_KOFF + 2 * i * KV_PITCH, KV_PITCH, 128);
      ds.kv[g][4 + i] = mkdesc(SMEM_BASE + OFF_KV + g * KV_BYTES + 256 * i, 128, KV_PITCH);
    }
  CUtensorMap tmp;
  cuuint32_t boxp[3] = {CH, 9, 9};
  encode(&tmp, CU_TENSOR_MAP_DATA_TYPE_BFLOAT16, 3, (void*)x, gdim, gstr, boxp, estr, CU_TENSOR_MAP_INTERLEAVE_NONE,
         CU_TENSOR_MAP_SWIZZLE_NONE, CU_TENSOR_MAP_L2_PROMOTION_L2_128B, CU_TENSOR_MAP_FLOAT_OOB_FILL_NONE);
  prepack_kernel<<<48, dim3(192, 2), 0, cudaStreamPerThread>>>(wqkv, wo);
  cudaLaunchConfig_t cfg = {};
  cfg.gridDim = dim3(nsm); cfg.blockDim = dim3(384); cfg.dynamicSmemBytes = SMEM_BYTES; cfg.stream = cudaStreamPerThread;
  cudaLaunchAttribute at[1];
  at[0].id = cudaLaunchAttributeProgrammaticStreamSerialization;
  at[0].val.programmaticStreamSerializationAllowed = 1;
  cfg.attrs = at; cfg.numAttrs = 1;
  cudaLaunchKernelEx(&cfg, fused_kernel, tmx, tmp, ds, dw, (__nv_bfloat16*)d_out, 0, x, wqkv, wo);
}
```

```cpp
#include <cuda_runtime.h>
#include <cuda_bf16.h>
#include <cuda_fp16.h>
#include <cuda.h>
#include <stdint.h>

#define CREGS "208"
#define PREGS "88"
#define KA 3
#define KB 9
#define SA 12
#define SB 36
#define SC 48
#define K48TC 0
#define EARLYX 0
#define LA 4
namespace {
constexpr int NP = K48TC ? 16 : 12;

constexpr int IMG = 511;
constexpr int CH = 192;
constexpr int NWX = 73;
constexpr int NWIN = NWX * NWX;
constexpr int SLICE = 18432;
constexpr int OFF_W = 0;
constexpr int KV_PITCH = 1792, KV_KOFF = 896, KV_BYTES = 6 * KV_PITCH + 1024;
constexpr int OFF_KV = 8 * SLICE;
constexpr int TILE_BYTES = 25 * 768;
constexpr int OFF_TILE = OFF_KV + 2 * KV_BYTES;
constexpr int XSLOT = 2304;
constexpr int OFF_ZERO = OFF_TILE + 2 * TILE_BYTES;
constexpr int OFF_X = OFF_ZERO + 768;
constexpr int OFF_BAR = OFF_X + 9 * XSLOT;
constexpr int BAR_WFULL = OFF_BAR;
constexpr int BAR_WEMPTY = OFF_BAR + 56;
constexpr int BAR_XFULL = OFF_BAR + 112;
constexpr int BAR_TFULL = OFF_BAR + 184;
constexpr int BAR_TEMPTY = OFF_BAR + 192;
constexpr int OFF_LIM = OFF_BAR + 200;
constexpr int OFF_REDO = OFF_BAR + 208;
constexpr int BAR_FIRST = OFF_BAR + 240;
constexpr int OFF_TRACE = OFF_BAR + 248;
constexpr int OFF_HALO = OFF_W + 4 * SLICE, HALO_BYTES = 81 * 384;
constexpr int SMEM_BYTES = OFF_TRACE;

__host__ __device__ constexpr int qkv_pos(int h, int s) { return (h == 0 ? 1 : 3 * h + 2) * SLICE + s * 4608; }
__host__ __device__ constexpr int wo_pos(int s) { return s < 6 ? 14 * SLICE + s * 6144 : s < 9 ? (s - 6) * 6144 : 4 * SLICE + (s - 9) * 6144; }
__host__ __device__ constexpr int stage_of(int p) { return p == 0 ? 5 : p < 4 ? 0 : p == 4 ? 6 : p < 8 ? 1 : p < 11 ? 2 : p < 14 ? 3 : 4; }
constexpr int SMEM_BASE = 1024;
struct Descs { uint64_t q[4][12]; uint64_t p[12]; uint64_t kv[2][8]; const uint8_t* src[16]; };

__device__ uint4 g_wpack[16 * SLICE / 16];
__device__ float2 g_wnorm[96];
#define TR(id)
#define GTS(i)
template <int V> struct IC { static constexpr int v = V; };
typedef __nv_bfloat162 bf2;
__device__ __forceinline__ bf2 u2b(uint32_t u) { return *reinterpret_cast<bf2*>(&u); }
__device__ __forceinline__ uint32_t b2u(bf2 b) { return *reinterpret_cast<uint32_t*>(&b); }
__device__ __forceinline__ uint32_t pack2(float lo, float hi) {
  uint32_t r; asm("cvt.rn.bf16x2.f32 %0, %1, %2;" : "=r"(r) : "f"(hi), "f"(lo)); return r;
}
__device__ __forceinline__ uint32_t hadd(uint32_t a, uint32_t b) { return b2u(__hadd2_rn(u2b(a), u2b(b))); }
__device__ __forceinline__ uint32_t hmul(uint32_t a, uint32_t b) { return b2u(__hmul2_rn(u2b(a), u2b(b))); }
__device__ __forceinline__ uint32_t hfma(uint32_t a, uint32_t b, uint32_t c) { return b2u(__hfma2(u2b(a), u2b(b), u2b(c))); }
__device__ __forceinline__ __half2 u2h(uint32_t u) { return *reinterpret_cast<__half2*>(&u); }
__device__ __forceinline__ uint32_t h2u(__half2 b) { return *reinterpret_cast<uint32_t*>(&b); }
__device__ __forceinline__ uint32_t packh(float lo, float hi) {
  uint32_t r; asm("cvt.rn.f16x2.f32 %0, %1, %2;" : "=r"(r) : "f"(hi), "f"(lo)); return r;
}
__device__ __forceinline__ uint32_t fmax2(uint32_t a, uint32_t b) { return h2u(__hmax2(u2h(a), u2h(b))); }
template <int HI> __device__ __forceinline__ __half2 hcast(uint32_t a) { return HI ? __high2half2(u2h(a)) : __low2half2(u2h(a)); }
template <int HI> __device__ __forceinline__ uint32_t fmul_b(uint32_t a, uint32_t s) { return h2u(__hmul2_rn(u2h(a), hcast<HI>(s))); }
template <int HI> __device__ __forceinline__ uint32_t fsub_b(uint32_t a, uint32_t s) { return h2u(__hsub2_rn(u2h(a), hcast<HI>(s))); }
__device__ __forceinline__ uint32_t fex2(uint32_t a) { uint32_t r; asm("ex2.approx.f16x2 %0, %1;" : "=r"(r) : "r"(a)); return r; }
__device__ __forceinline__ float lo2f(uint32_t a) { return __uint_as_float(a << 16); }
__device__ __forceinline__ float hi2f(uint32_t a) { return __uint_as_float(a & 0xffff0000u); }

__device__ __forceinline__ void mbar_init(uint32_t bar, uint32_t cnt) { asm volatile("mbarrier.init.shared::cta.b64 [%0], %1;" :: "r"(bar), "r"(cnt) : "memory"); }
__device__ __forceinline__ void mbar_wait(uint32_t bar, uint32_t parity) {
  asm volatile("{\n.reg .pred p;\n.reg .u32 n;\n"
               "mbarrier.try_wait.parity.shared::cta.b64 p, [%0], %1;\n"
               "@p bra.uni DONE_%=;\n"
               "mov.u32 n, 0;\n"
               "AGAIN_%=:\n"
               "mbarrier.try_wait.parity.shared::cta.b64 p, [%0], %1;\n"
               "@p bra.uni DONE_%=;\n"
               "add.u32 n, n, 1;\n"
               "setp.lt.u32 p, n, 0x1000000;\n"
               "@p bra.uni AGAIN_%=;\n"
               "trap;\n"
               "DONE_%=:\n}\n" :: "r"(bar), "r"(parity) : "memory");
}
__device__ __forceinline__ void wg_fence() { asm volatile("wgmma.fence.sync.aligned;" ::: "memory"); }
__device__ __forceinline__ void wg_commit() { asm volatile("wgmma.commit_group.sync.aligned;" ::: "memory"); }
template <int N> __device__ __forceinline__ void wg_wait() { asm volatile("wgmma.wait_group.sync.aligned %0;" :: "n"(N) : "memory"); }
#define BAR_BY_WG(OP, ID0, ID1, CNT) asm volatile("{\n.reg .pred p;\nsetp.eq.s32 p, %0, 0;\n@p " OP " " #ID0 ", " #CNT ";\n@!p " OP " " #ID1 ", " #CNT ";\n}\n" :: "r"(wg) : "memory")
__device__ __forceinline__ void wg_sync(int wg) { BAR_BY_WG("bar.sync", 1, 2, 128); }
__device__ __forceinline__ void turn_wait(int wg) { BAR_BY_WG("bar.sync", 3, 4, 256); }
__device__ __forceinline__ void turn_pass(int wg) { BAR_BY_WG("bar.arrive", 4, 3, 256); }
__device__ __forceinline__ void stsm4(uint32_t addr, uint32_t a, uint32_t b, uint32_t c, uint32_t d) {
  asm volatile("stmatrix.sync.aligned.m8n8.x4.shared.b16 [%0], {%1,%2,%3,%4};" :: "r"(addr), "r"(a), "r"(b), "r"(c), "r"(d) : "memory");
}
template <int N> __device__ __forceinline__ void keep(float (&d)[N]) {
#pragma unroll
  for (int i = 0; i < N; i++) asm volatile("" : "+f"(d[i]) :: "memory");
}
template <int N> __device__ __forceinline__ void keep(uint32_t (&d)[N]) {
#pragma unroll
  for (int i = 0; i < N; i++) asm volatile("" : "+r"(d[i]) :: "memory");
}
__host__ __device__ __forceinline__ uint64_t mkdesc(uint32_t addr, uint32_t lbo, uint32_t sbo) {
  return ((uint64_t)(sbo >> 4) << 32) | (uint64_t)(((lbo >> 4) << 16) | ((addr & 0x3FFFF) >> 4));
}

template <int SCALE_D>
__device__ __forceinline__ void wgmma_n144(uint32_t (&d)[36], uint32_t a0, uint32_t a1, uint32_t a2, uint32_t a3, uint64_t descB) {
  if (SCALE_D == 0)
  asm volatile("wgmma.mma_async.sync.aligned.m64n144k16.f16.f16.f16 "
    "{%0, %1, %2, %3, %4, %5, %6, %7, %8, %9, %10, %11, %12, %13, %14, %15, "
    "%16, %17, %18, %19, %20, %21, %22, %23, %24, %25, %26, %27, %28, %29, %30, %31, "
    "%32, %33, %34, %35}, "
    "{%36, %37, %38, %39}, %40, 0, 1, 1, 0;\n"
    : "=r"(d[0]), "=r"(d[1]), "=r"(d[2]), "=r"(d[3]), "=r"(d[4]), "=r"(d[5]), "=r"(d[6]), "=r"(d[7]),
      "=r"(d[8]), "=r"(d[9]), "=r"(d[10]), "=r"(d[11]), "=r"(d[12]), "=r"(d[13]), "=r"(d[14]), "=r"(d[15]),
      "=r"(d[16]), "=r"(d[17]), "=r"(d[18]), "=r"(d[19]), "=r"(d[20]), "=r"(d[21]), "=r"(d[22]), "=r"(d[23]),
      "=r"(d[24]), "=r"(d[25]), "=r"(d[26]), "=r"(d[27]), "=r"(d[28]), "=r"(d[29]), "=r"(d[30]), "=r"(d[31]),
      "=r"(d[32]), "=r"(d[33]), "=r"(d[34]), "=r"(d[35])
    : "r"(a0), "r"(a1), "r"(a2), "r"(a3), "l"(descB));
  else
  asm volatile("wgmma.mma_async.sync.aligned.m64n144k16.f16.f16.f16 "
    "{%0, %1, %2, %3, %4, %5, %6, %7, %8, %9, %10, %11, %12, %13, %14, %15, "
    "%16, %17, %18, %19, %20, %21, %22, %23, %24, %25, %26, %27, %28, %29, %30, %31, "
    "%32, %33, %34, %35}, "
    "{%36, %37, %38, %39}, %40, 1, 1, 1, 0;\n"
    : "+r"(d[0]), "+r"(d[1]), "+r"(d[2]), "+r"(d[3]), "+r"(d[4]), "+r"(d[5]), "+r"(d[6]), "+r"(d[7]),
      "+r"(d[8]), "+r"(d[9]), "+r"(d[10]), "+r"(d[11]), "+r"(d[12]), "+r"(d[13]), "+r"(d[14]), "+r"(d[15]),
      "+r"(d[16]), "+r"(d[17]), "+r"(d[18]), "+r"(d[19]), "+r"(d[20]), "+r"(d[21]), "+r"(d[22]), "+r"(d[23]),
      "+r"(d[24]), "+r"(d[25]), "+r"(d[26]), "+r"(d[27]), "+r"(d[28]), "+r"(d[29]), "+r"(d[30]), "+r"(d[31]),
      "+r"(d[32]), "+r"(d[33]), "+r"(d[34]), "+r"(d[35])
    : "r"(a0), "r"(a1), "r"(a2), "r"(a3), "l"(descB));
}

template <int SCALE_D>
__device__ __forceinline__ void wgmma_n192(uint32_t (&d)[48], uint32_t a0, uint32_t a1, uint32_t a2, uint32_t a3, uint64_t descB) {
  if (SCALE_D == 0)
  asm volatile("wgmma.mma_async.sync.aligned.m64n192k16.f16.f16.f16 "
    "{%0, %1, %2, %3, %4, %5, %6, %7, %8, %9, %10, %11, %12, %13, %14, %15, "
    "%16, %17, %18, %19, %20, %21, %22, %23, %24, %25, %26, %27, %28, %29, %30, %31, "
    "%32, %33, %34, %35, %36, %37, %38, %39, %40, %41, %42, %43, %44, %45, %46, %47}, "
    "{%48, %49, %50, %51}, %52, 0, 1, 1, 0;\n"
    : "=r"(d[0]), "=r"(d[1]), "=r"(d[2]), "=r"(d[3]), "=r"(d[4]), "=r"(d[5]), "=r"(d[6]), "=r"(d[7]),
      "=r"(d[8]), "=r"(d[9]), "=r"(d[10]), "=r"(d[11]), "=r"(d[12]), "=r"(d[13]), "=r"(d[14]), "=r"(d[15]),
      "=r"(d[16]), "=r"(d[17]), "=r"(d[18]), "=r"(d[19]), "=r"(d[20]), "=r"(d[21]), "=r"(d[22]), "=r"(d[23]),
      "=r"(d[24]), "=r"(d[25]), "=r"(d[26]), "=r"(d[27]), "=r"(d[28]), "=r"(d[29]), "=r"(d[30]), "=r"(d[31]),
      "=r"(d[32]), "=r"(d[33]), "=r"(d[34]), "=r"(d[35]), "=r"(d[36]), "=r"(d[37]), "=r"(d[38]), "=r"(d[39]),
      "=r"(d[40]), "=r"(d[41]), "=r"(d[42]), "=r"(d[43]), "=r"(d[44]), "=r"(d[45]), "=r"(d[46]), "=r"(d[47])
    : "r"(a0), "r"(a1), "r"(a2), "r"(a3), "l"(descB));
  else
  asm volatile("wgmma.mma_async.sync.aligned.m64n192k16.f16.f16.f16 "
    "{%0, %1, %2, %3, %4, %5, %6, %7, %8, %9, %10, %11, %12, %13, %14, %15, "
    "%16, %17, %18, %19, %20, %21, %22, %23, %24, %25, %26, %27, %28, %29, %30, %31, "
    "%32, %33, %34, %35, %36, %37, %38, %39, %40, %41, %42, %43, %44, %45, %46, %47}, "
    "{%48, %49, %50, %51}, %52, 1, 1, 1, 0;\n"
    : "+r"(d[0]), "+r"(d[1]), "+r"(d[2]), "+r"(d[3]), "+r"(d[4]), "+r"(d[5]), "+r"(d[6]), "+r"(d[7]),
      "+r"(d[8]), "+r"(d[9]), "+r"(d[10]), "+r"(d[11]), "+r"(d[12]), "+r"(d[13]), "+r"(d[14]), "+r"(d[15]),
      "+r"(d[16]), "+r"(d[17]), "+r"(d[18]), "+r"(d[19]), "+r"(d[20]), "+r"(d[21]), "+r"(d[22]), "+r"(d[23]),
      "+r"(d[24]), "+r"(d[25]), "+r"(d[26]), "+r"(d[27]), "+r"(d[28]), "+r"(d[29]), "+r"(d[30]), "+r"(d[31]),
      "+r"(d[32]), "+r"(d[33]), "+r"(d[34]), "+r"(d[35]), "+r"(d[36]), "+r"(d[37]), "+r"(d[38]), "+r"(d[39]),
      "+r"(d[40]), "+r"(d[41]), "+r"(d[42]), "+r"(d[43]), "+r"(d[44]), "+r"(d[45]), "+r"(d[46]), "+r"(d[47])
    : "r"(a0), "r"(a1), "r"(a2), "r"(a3), "l"(descB));
}

template <int SCALE_D>
__device__ __forceinline__ void wgmma_n56(uint32_t (&d)[14], uint32_t a0, uint32_t a1, uint32_t a2, uint32_t a3, uint64_t descB) {
  if (SCALE_D == 0)
  asm volatile("wgmma.mma_async.sync.aligned.m64n56k16.f16.f16.f16 "
    "{%0, %1, %2, %3, %4, %5, %6, %7, %8, %9, %10, %11, %12, %13}, "
    "{%14, %15, %16, %17}, %18, 0, 1, 1, 0;\n"
    : "=r"(d[0]), "=r"(d[1]), "=r"(d[2]), "=r"(d[3]), "=r"(d[4]), "=r"(d[5]), "=r"(d[6]), "=r"(d[7]),
      "=r"(d[8]), "=r"(d[9]), "=r"(d[10]), "=r"(d[11]), "=r"(d[12]), "=r"(d[13])
    : "r"(a0), "r"(a1), "r"(a2), "r"(a3), "l"(descB));
  else
  asm volatile("wgmma.mma_async.sync.aligned.m64n56k16.f16.f16.f16 "
    "{%0, %1, %2, %3, %4, %5, %6, %7, %8, %9, %10, %11, %12, %13}, "
    "{%14, %15, %16, %17}, %18, 1, 1, 1, 0;\n"
    : "+r"(d[0]), "+r"(d[1]), "+r"(d[2]), "+r"(d[3]), "+r"(d[4]), "+r"(d[5]), "+r"(d[6]), "+r"(d[7]),
      "+r"(d[8]), "+r"(d[9]), "+r"(d[10]), "+r"(d[11]), "+r"(d[12]), "+r"(d[13])
    : "r"(a0), "r"(a1), "r"(a2), "r"(a3), "l"(descB));
}

template <int SCALE_D>
__device__ __forceinline__ void wgmma_n56t(uint32_t (&d)[14], uint32_t a0, uint32_t a1, uint32_t a2, uint32_t a3, uint64_t descB) {
  if (SCALE_D == 0)
  asm volatile("wgmma.mma_async.sync.aligned.m64n56k16.f16.f16.f16 "
    "{%0, %1, %2, %3, %4, %5, %6, %7, %8, %9, %10, %11, %12, %13}, "
    "{%14, %15, %16, %17}, %18, 0, 1, 1, 1;\n"
    : "=r"(d[0]), "=r"(d[1]), "=r"(d[2]), "=r"(d[3]), "=r"(d[4]), "=r"(d[5]), "=r"(d[6]), "=r"(d[7]),
      "=r"(d[8]), "=r"(d[9]), "=r"(d[10]), "=r"(d[11]), "=r"(d[12]), "=r"(d[13])
    : "r"(a0), "r"(a1), "r"(a2), "r"(a3), "l"(descB));
  else
  asm volatile("wgmma.mma_async.sync.aligned.m64n56k16.f16.f16.f16 "
    "{%0, %1, %2, %3, %4, %5, %6, %7, %8, %9, %10, %11, %12, %13}, "
    "{%14, %15, %16, %17}, %18, 1, 1, 1, 1;\n"
    : "+r"(d[0]), "+r"(d[1]), "+r"(d[2]), "+r"(d[3]), "+r"(d[4]), "+r"(d[5]), "+r"(d[6]), "+r"(d[7]),
      "+r"(d[8]), "+r"(d[9]), "+r"(d[10]), "+r"(d[11]), "+r"(d[12]), "+r"(d[13])
    : "r"(a0), "r"(a1), "r"(a2), "r"(a3), "l"(descB));
}

__global__ void __launch_bounds__(384) prepack_kernel(const __nv_bfloat16* __restrict__ wqkv, const __nv_bfloat16* __restrict__ wo) {
  asm volatile("griddepcontrol.launch_dependents;");
  __shared__ float red2[2][2][6][8];
  float (*red)[6][8] = red2[threadIdx.y];
  __half* dst = reinterpret_cast<__half*>(g_wpack);
  const int c = threadIdx.x, nb = blockIdx.x * 2 + threadIdx.y;
  auto colsum = [&](int k, const float (&v)[8], float (&o)[8]) {
#pragma unroll
    for (int i = 0; i < 8; i++) {
      float t = v[i];
#pragma unroll
      for (int d = 16; d; d >>= 1) t += __shfl_xor_sync(~0u, t, d);
      if ((c & 31) == 0) red[k][c >> 5][i] = t;
    }
    __syncthreads();
#pragma unroll
    for (int i = 0; i < 8; i++) o[i] = red[k][0][i] + red[k][1][i] + red[k][2][i] + red[k][3][i] + red[k][4][i] + red[k][5][i];
  };
  float v[8], t[8];
  int base;
  if (nb < 72) {
    const int h = nb / 18, j = nb % 18, part = j / 6;
    const int col = (part == 0 ? 192 : part == 1 ? 0 : 384) + h * 48 + (j % 6) * 8;
    uint4 raw = *reinterpret_cast<const uint4*>(wqkv + c * 576 + col);
    uint32_t u[4] = {raw.x, raw.y, raw.z, raw.w};
#pragma unroll
    for (int i = 0; i < 4; i++) { v[2 * i] = lo2f(u[i]); v[2 * i + 1] = hi2f(u[i]); }
    colsum(0, v, t);
#pragma unroll
    for (int n = 0; n < 8; n++)
      v[n] = __bfloat162float(__float2bfloat16((v[n] - t[n] * (1.0f / 192.0f)) * (part == 1 ? 0.14433756729740643f * 1.4426950408889634f : 1.0f)));
    const int cc = c >> 5, q = (c >> 3) & 3, s1 = (c >> 2) & 1, hh = (c >> 1) & 1, e = c & 1;
    base = qkv_pos(h, 2 * cc + s1) / 2 + j * 128 + hh * 64 + 2 * q + e;
  } else {
    const int jb = nb - 72;
#pragma unroll
    for (int n = 0; n < 8; n++) v[n] = __bfloat162float(wo[c * 192 + 32 * (jb >> 2) + 8 * (n >> 1) + 2 * (jb & 3) + (n & 1)]);
    base = wo_pos(c >> 4) / 2 + jb * 128 + ((c >> 3) & 1) * 64 + (c & 7);
  }
#pragma unroll
  for (int n = 0; n < 8; n++) { dst[base + n * 8] = __float2half_rn(v[n]); v[n] *= v[n]; }
  colsum(1, v, t);
  if (c == 0)
    g_wnorm[nb] = make_float2(fmaxf(fmaxf(fmaxf(t[0], t[1]), fmaxf(t[2], t[3])), fmaxf(fmaxf(t[4], t[5]), fmaxf(t[6], t[7]))),
                              t[0] + t[1] + t[2] + t[3] + t[4] + t[5] + t[6] + t[7]);
}

__device__ __forceinline__ int window_of(int round, int nfull, int cta, int ncta, int wg) {
  if (round < nfull) return round * 2 * ncta + 2 * cta + wg;
  const int rem = NWIN - nfull * 2 * ncta;
  const int i = cta + wg * ncta;
  return i < rem ? nfull * 2 * ncta + i : -1;
}

template <int S0 = 0, int S1 = 12>
__device__ __forceinline__ void mma_qkv(uint32_t (&acc)[36], const uint32_t (&A)[48], const uint64_t* d) {
#pragma unroll
  for (int s = S0; s < S1; s++) {
    if (s == 0) wgmma_n144<0>(acc, A[4 * s], A[4 * s + 1], A[4 * s + 2], A[4 * s + 3], d[s]);
    else        wgmma_n144<1>(acc, A[4 * s], A[4 * s + 1], A[4 * s + 2], A[4 * s + 3], d[s]);
  }
  wg_commit();
}
__device__ __forceinline__ void mma_proj(uint32_t (&acc)[48], const uint32_t (&A)[12], const uint64_t* d) {
#pragma unroll
  for (int s = 0; s < 3; s++) wgmma_n192<1>(acc, A[4 * s], A[4 * s + 1], A[4 * s + 2], A[4 * s + 3], d[s]);
}
__device__ __forceinline__ void mma_s(uint32_t (&S)[14], const uint32_t (&Q)[12], const uint64_t* d) {
  wgmma_n56<0>(S, Q[0], Q[1], Q[2], Q[3], d[0]);
  wgmma_n56<1>(S, Q[4], Q[5], Q[6], Q[7], d[1]);
  wgmma_n56<1>(S, Q[8], Q[9], Q[10], Q[11], d[2]);
}
__device__ __forceinline__ void mma_pv(uint32_t (&O)[14], const uint32_t (&P)[NP], const uint64_t* d) {
  wgmma_n56t<0>(O, P[0], P[1], P[2], P[3], d[0]);
  wgmma_n56t<1>(O, P[4], P[5], P[6], P[7], d[1]);
  wgmma_n56t<1>(O, P[8], P[9], P[10], P[11], d[2]);
  if (K48TC) wgmma_n56t<1>(O, P[NP - 4], P[NP - 3], P[NP - 2], P[NP - 1], d[3]);
}

#define PIN() asm volatile("pmevent 0;" ::: "memory")
template <int A, int B> __device__ __forceinline__ void hold(uint32_t* v) {
#pragma unroll
  for (int i = A; i < B; i++) asm volatile("" : "+r"(v[i]));
}
__device__ __forceinline__ void stsm12(const uint32_t* v, uint32_t addr) {
#pragma unroll
  for (int j = 0; j < 3; j++) stsm4(addr + 2 * j * KV_PITCH, v[4 * j], v[4 * j + 1], v[4 * j + 2], v[4 * j + 3]);
}
__device__ __forceinline__ void load_v48(uint32_t (&v)[6], uint32_t addr) {
  if (K48TC) return;
  asm volatile("ldmatrix.sync.aligned.m8n8.x4.shared.b16 {%0,%1,%2,%3}, [%4];" : "=r"(v[0]), "=r"(v[1]), "=r"(v[2]), "=r"(v[3]) : "r"(addr) : "memory");
  asm volatile("ldmatrix.sync.aligned.m8n8.x2.shared.b16 {%0,%1}, [%2];" : "=r"(v[4]), "=r"(v[5]) : "r"(addr + 4 * KV_PITCH) : "memory");
}
__device__ __forceinline__ void finish_o(const uint32_t (&O)[14], const uint32_t (&v)[6], uint32_t p48, uint32_t vmask, uint32_t (&Of)[12]) {
  const float2 l = K48TC ? make_float2(__low2float(u2h(O[12])), __low2float(u2h(O[13])))
                         : __half22float2(__hadd2_rn(u2h(__byte_perm(O[12], O[13], 0x5410)), u2h(p48)));
  float i0, i1;
  asm("rcp.approx.ftz.f32 %0, %1;" : "=f"(i0) : "f"(l.x));
  asm("rcp.approx.ftz.f32 %0, %1;" : "=f"(i1) : "f"(l.y));
  const uint32_t inv = packh(i0, i1) & vmask;
#pragma unroll
  for (int i = 0; i < 12; i++) {
    const uint32_t t = K48TC ? O[i] : h2u(__hfma2(u2h(v[i >> 1]), (i & 1) ? hcast<1>(p48) : hcast<0>(p48), u2h(O[i])));
    Of[i] = (i & 1) ? fmul_b<1>(t, inv) : fmul_b<0>(t, inv);
  }
  hold<0, 12>(Of);
}
#define PSTAT 6
template <int A, int B>
__device__ __forceinline__ void ln_sums(const uint32_t (&X)[48], float (&s1)[2], float (&s2)[2]) {
  if (PSTAT) {
    static_assert(PSTAT == 0 || (A % (2 * PSTAT + !PSTAT) == 0 && B % (2 * PSTAT + !PSTAT) == 0), "whole groups");
#pragma unroll
    for (int g = A; g < B; g += 2 * PSTAT + !PSTAT)
#pragma unroll
      for (int a = 0; a < 2; a++) {
        __half2 p1 = u2h(X[g + a]), p2 = __hmul2_rn(p1, p1);
#pragma unroll
        for (int i = 1; i < PSTAT; i++) { const __half2 v = u2h(X[g + a + 2 * i]); p1 = __hadd2_rn(p1, v); p2 = __hfma2(v, v, p2); }
        const float2 f1 = __half22float2(p1), f2 = __half22float2(p2);
        s1[a] = g == 0 ? f1.x + f1.y : s1[a] + (f1.x + f1.y);
        s2[a] = g == 0 ? f2.x + f2.y : s2[a] + (f2.x + f2.y);
      }
  } else {
#pragma unroll
    for (int i = A; i < B; i++) {
      const float2 f = __half22float2(u2h(X[i]));
      s1[i & 1] = i < 2 ? f.x + f.y : s1[i & 1] + (f.x + f.y);
      s2[i & 1] = fmaf(f.x, f.x, i < 2 ? f.y * f.y : fmaf(f.y, f.y, s2[i & 1]));
    }
  }
  asm volatile("" : "+f"(s1[0]), "+f"(s1[1]), "+f"(s2[0]), "+f"(s2[1]));
}
__device__ __forceinline__ uint32_t ln_rstd(const float (&s1)[2], const float (&s2)[2], float lo, float hi, bool& ok) {
  float r[2];
  ok = true;
#pragma unroll
  for (int a = 0; a < 2; a++) {
    float m = s1[a], v = s2[a];
    m += __shfl_xor_sync(~0u, m, 1); v += __shfl_xor_sync(~0u, v, 1);
    m += __shfl_xor_sync(~0u, m, 2); v += __shfl_xor_sync(~0u, v, 2);
    ok = ok && v <= hi && (v >= lo || v == 0.f);
    m *= 1.0f / 192.0f;
    m *= m;
    v = fmaxf(fmaf(v, 1.0f / 192.0f, -m), 0.f) + 1e-5f;
    ok = ok && m <= (PSTAT ? 16.f : 64.f) * v;
    asm("rsqrt.approx.ftz.f32 %0, %1;" : "=f"(r[a]) : "f"(v));
  }
  uint32_t rk = packh(r[0], r[1]);
  hold<0, 1>(&rk);
  return rk;
}
__device__ __forceinline__ void scale12(uint32_t (&D)[12], const uint32_t* a, uint32_t r) {
#pragma unroll
  for (int i = 0; i < 12; i++) D[i] = (i & 1) ? fmul_b<1>(a[i], r) : fmul_b<0>(a[i], r);
  hold<0, 12>(D);
}
template <int CC>
__device__ __forceinline__ void store_out(const uint32_t (&Y)[48], uint8_t* o0, uint8_t* o1, uint32_t vmask) {
  uint32_t T[8];
#pragma unroll
  for (int i = 0; i < 8; i++) {
    const float2 f = __half22float2(u2h(Y[8 * CC + i]));
    T[i] = pack2(f.x, f.y);
  }
  asm volatile("{\n.reg .pred p;\nsetp.ne.u32 p, %5, 0;\n@p st.global.v4.u32 [%0], {%1,%2,%3,%4};\n}\n"
               :: "l"(o0 + CC * 64), "r"(T[0]), "r"(T[2]), "r"(T[4]), "r"(T[6]), "r"(vmask) : "memory");
  asm volatile("{\n.reg .pred p;\nsetp.lt.s32 p, %5, 0;\n@p st.global.v4.u32 [%0], {%1,%2,%3,%4};\n}\n"
               :: "l"(o1 + CC * 64), "r"(T[1]), "r"(T[3]), "r"(T[5]), "r"(T[7]), "r"(vmask) : "memory");
}
__device__ __forceinline__ void proxy_fence() { asm volatile("fence.proxy.async.shared::cta;" ::: "memory"); }
__device__ __forceinline__ uint32_t fadd2(uint32_t a, uint32_t b) { return h2u(__hadd2_rn(u2h(a), u2h(b))); }
__device__ __forceinline__ void row_max(const uint32_t (&S)[14], uint32_t& k48, uint32_t& mx, uint32_t ninf) {
  k48 = K48TC ? __byte_perm(S[12], S[13], 0x5410) | ninf : __shfl_sync(~0u, __byte_perm(S[12], S[13], 0x5410), 0, 4);
  const uint32_t m0 = fmax2(fmax2(fmax2(S[0], S[2]), S[4]), fmax2(fmax2(S[6], S[8]), S[10]));
  const uint32_t m1 = fmax2(fmax2(fmax2(S[1], S[3]), S[5]), fmax2(fmax2(S[7], S[9]), S[11]));
  mx = fmax2(__byte_perm(m0, m1, 0x5410), __byte_perm(m0, m1, 0x7632));
  if (K48TC) mx = fmax2(mx, k48);
  mx = fmax2(mx, __shfl_xor_sync(~0u, mx, 1));
  mx = fmax2(mx, __shfl_xor_sync(~0u, mx, 2));
  if (!K48TC) mx = fmax2(mx, k48);
  hold<0, 1>(&mx);
}
__device__ __forceinline__ void row_exp(const uint32_t (&S)[14], uint32_t k48, uint32_t mx, uint32_t (&P)[NP], uint32_t& p48) {
#pragma unroll
  for (int j = 0; j < 12; j++) P[j] = fex2((j & 1) ? fsub_b<1>(S[j], mx) : fsub_b<0>(S[j], mx));
  if (K48TC) {
    uint16_t el, eh;
    asm("{\n.reg .b16 l, h;\nmov.b32 {l, h}, %2;\nex2.approx.f16 %0, l;\nex2.approx.f16 %1, h;\n}\n" : "=h"(el), "=h"(eh) : "r"(h2u(__hsub2_rn(u2h(k48), u2h(mx)))));
    P[NP - 4] = el; P[NP - 3] = eh; P[NP - 2] = 0; P[NP - 1] = 0;
  } else {
    p48 = fex2(h2u(__hsub2_rn(u2h(k48), u2h(mx))));
    hold<0, 1>(&p48);
  }
  hold<0, NP>(P);
}
template <int S0, int S1>
__device__ __forceinline__ void load_x(uint32_t (&X)[48], uint32_t t0) {
#pragma unroll
  for (int s = S0; s < S1; s++)
    asm volatile("ld.shared.v4.u32 {%0,%1,%2,%3}, [%4];" : "=r"(X[4 * s]), "=r"(X[4 * s + 1]), "=r"(X[4 * s + 2]), "=r"(X[4 * s + 3])
                 : "r"(((s & 1) ? (t0 ^ 16) : t0) + (s >> 1) * 128) : "memory");
}

#define WDIV 1
template <int P, int CNT, int DIV = WDIV> __device__ __forceinline__ void load_slices(uint32_t sb, const Descs& ds) {
  constexpr int st = stage_of(P);
  constexpr bool first = P == 0 || stage_of(P - 1) != st;
  if (first)
    asm volatile("{\n.reg .pred p;\nelect.sync _|p, 0xffffffff;\n@p mbarrier.arrive.expect_tx.shared::cta.b64 _, [%0], %1;\n}\n"
                 :: "r"(sb + BAR_WFULL + 8 * st), "n"((st < 4 ? 3 : st == 4 ? 2 : 1) * SLICE / DIV) : "memory");
  asm volatile("{\n.reg .pred p;\nelect.sync _|p, 0xffffffff;\n"
               "@p cp.async.bulk.shared::cluster.global.mbarrier::complete_tx::bytes [%0], [%1], %2, [%3];\n}\n"
               :: "r"(sb + OFF_W + (P & 7) * SLICE), "l"(ds.src[P]), "n"(CNT * SLICE / DIV), "r"(sb + BAR_WFULL + 8 * st) : "memory");
}
__device__ __forceinline__ void warp_arrive(uint32_t bar) {
  asm volatile("{\n.reg .pred p;\nelect.sync _|p, 0xffffffff;\n@p mbarrier.arrive.shared::cta.b64 _, [%0];\n}\n" :: "r"(bar) : "memory");
}

__device__ __forceinline__ float2 fp16_limits(int lane) {
  float mx[4] = {0.f, 0.f, 0.f, 0.f}, sm[4] = {0.f, 0.f, 0.f, 0.f};
#pragma unroll
  for (int i = 0; i < 3; i++) {
    const int nb = lane + 32 * i, part = nb < 72 ? (nb % 18) / 6 : 3;
    const float2 w = g_wnorm[nb];
#pragma unroll
    for (int k = 0; k < 4; k++) if (part == k) { mx[k] = fmaxf(mx[k], w.x); sm[k] += w.y; }
  }
#pragma unroll
  for (int k = 0; k < 4; k++)
#pragma unroll
    for (int d = 16; d; d >>= 1) { mx[k] = fmaxf(mx[k], __shfl_xor_sync(~0u, mx[k], d)); sm[k] += __shfl_xor_sync(~0u, sm[k], d); }
  const float big = fmaxf(fmaxf(mx[0], mx[1]), mx[2]);
  float small = 1.f;
  bool good = sm[0] + sm[1] + sm[2] + sm[3] < 1e30f;
#pragma unroll
  for (int k = 0; k < 4; k++) { good = good && (mx[k] == 0.f || mx[k] >= 2.5e-4f); if (k < 3 && mx[k] > 0.f) small = fminf(small, mx[k]); }
  good = good && 250.f * 48.f * sqrtf(mx[0] * mx[1]) <= 5e4f;
  good = good && 16.f * 49.f * sqrtf(mx[2]) <= 5e4f && big <= 1e6f;
  good = good && 16.f * sqrtf(sm[2] * mx[3]) <= 2e4f;
  return make_float2(192.f * 2.4e-7f / small, good ? fminf(2.5e8f, 9e8f / fmaxf(big, 1e-30f)) : -1.f);
}

__device__ __forceinline__ void slow_window(float* sm, int w, int t, const __nv_bfloat16* __restrict__ x, const __nv_bfloat16* __restrict__ dw,
                                            const __nv_bfloat16* __restrict__ wqkv, const __nv_bfloat16* __restrict__ wo, __nv_bfloat16* __restrict__ out) {
  float* x0 = sm; float* h = x0 + 49 * CH; float* qkv = h + 49 * CH; float* S = qkv + 49 * 576;
  const int wy = w / NWX, wx = w % NWX;
  auto sync = [] { asm volatile("bar.sync 6, 128;" ::: "memory"); };
#pragma unroll 1
  for (int i = t; i < 49 * CH; i += 128) {
    const int k = i / CH, c = i % CH, y = wy * 7 + k / 7, xx = wx * 7 + k % 7;
    float pe = 0.f;
#pragma unroll 1
    for (int a = 0; a < 9; a++) {
      const int yy = y + a / 3 - 1, xc = xx + a % 3 - 1;
      if (yy >= 0 && yy < IMG && xc >= 0 && xc < IMG) pe = fmaf(__bfloat162float(x[((size_t)yy * IMG + xc) * CH + c]), __bfloat162float(dw[a * CH + c]), pe);
    }
    x0[i] = __bfloat162float(__float2bfloat16(__bfloat162float(x[((size_t)y * IMG + xx) * CH + c]) + pe));
  }
  sync();
  if (t < 49) {
    float m = 0.f, v = 0.f;
#pragma unroll 1
    for (int c = 0; c < CH; c++) m += x0[t * CH + c];
    m *= 1.0f / CH;
#pragma unroll 1
    for (int c = 0; c < CH; c++) { const float d = x0[t * CH + c] - m; v = fmaf(d, d, v); }
    const float rs = 1.0f / sqrtf(v * (1.0f / CH) + 1e-5f);
#pragma unroll 1
    for (int c = 0; c < CH; c++) h[t * CH + c] = (x0[t * CH + c] - m) * rs;
  }
  sync();
#pragma unroll 1
  for (int i = t; i < 7 * 576; i += 128) {
    const int n = i % 576, k0 = i / 576 * 7;
    float a[7] = {0.f, 0.f, 0.f, 0.f, 0.f, 0.f, 0.f};
#pragma unroll 1
    for (int c = 0; c < CH; c++) {
      const float wv = __bfloat162float(wqkv[c * 576 + n]);
#pragma unroll
      for (int k = 0; k < 7; k++) a[k] = fmaf(h[(k0 + k) * CH + c], wv, a[k]);
    }
#pragma unroll
    for (int k = 0; k < 7; k++) qkv[(k0 + k) * 576 + n] = a[k];
  }
  sync();
#pragma unroll 1
  for (int hd = 0; hd < 4; hd++) {
#pragma unroll 1
    for (int i = t; i < 49 * 49; i += 128) {
      const int a = i / 49, b = i % 49;
      float v = 0.f;
#pragma unroll 1
      for (int d = 0; d < 48; d++) v = fmaf(qkv[a * 576 + hd * 48 + d], qkv[b * 576 + 192 + hd * 48 + d], v);
      S[i] = v * 0.14433756729740643f;
    }
    sync();
    if (t < 49) {
      float m = S[t * 49], l = 0.f;
#pragma unroll 1
      for (int b = 1; b < 49; b++) m = fmaxf(m, S[t * 49 + b]);
#pragma unroll 1
      for (int b = 0; b < 49; b++) { const float e = expf(S[t * 49 + b] - m); S[t * 49 + b] = e; l += e; }
#pragma unroll 1
      for (int b = 0; b < 49; b++) S[t * 49 + b] /= l;
    }
    sync();
#pragma unroll 1
    for (int i = t; i < 49 * 48; i += 128) {
      const int a = i / 48, d = i % 48;
      float v = 0.f;
#pragma unroll 1
      for (int b = 0; b < 49; b++) v = fmaf(S[a * 49 + b], qkv[b * 576 + 384 + hd * 48 + d], v);
      h[a * CH + hd * 48 + d] = v;
    }
    sync();
  }
#pragma unroll 1
  for (int i = t; i < 7 * CH; i += 128) {
    const int n = i % CH, k0 = i / CH * 7;
    float a[7] = {0.f, 0.f, 0.f, 0.f, 0.f, 0.f, 0.f};
#pragma unroll 1
    for (int c = 0; c < CH; c++) {
      const float wv = __bfloat162float(wo[c * CH + n]);
#pragma unroll
      for (int k = 0; k < 7; k++) a[k] = fmaf(h[(k0 + k) * CH + c], wv, a[k]);
    }
#pragma unroll
    for (int k = 0; k < 7; k++)
      out[((size_t)(wy * 7 + k0 / 7) * IMG + wx * 7 + k) * CH + n] = __float2bfloat16(x0[(k0 + k) * CH + n] + a[k]);
  }
  sync();
}

__global__ void __launch_bounds__(384, 1)
fused_kernel(const __grid_constant__ CUtensorMap tmx, const __grid_constant__ CUtensorMap tmp, const __grid_constant__ Descs ds, const __nv_bfloat16* __restrict__ dw, __nv_bfloat16* __restrict__ out, const int never,
             const __nv_bfloat16* __restrict__ x, const __nv_bfloat16* __restrict__ wqkv, const __nv_bfloat16* __restrict__ wo) {
  extern __shared__ __align__(1024) uint8_t smem[];
  const uint32_t sb = (uint32_t)__cvta_generic_to_shared(smem);
  const int tid = threadIdx.x, lane = tid & 31;
  const int warp = __shfl_sync(0xffffffffu, tid >> 5, 0);
  const int cta = blockIdx.x, ncta = gridDim.x;
  const int nfull = NWIN / (2 * ncta);
  const int nrounds = nfull + ((NWIN - nfull * 2 * ncta) > cta ? 1 : 0);

  if (warp == 0) GTS(0);
  if (warp == 10 && lane == 0) asm volatile("prefetch.tensormap [%0];" :: "l"(reinterpret_cast<uint64_t>(&tmx)) : "memory");
  if (tid == 0) {
    mbar_init(sb + BAR_FIRST, 1);
    asm volatile("fence.mbarrier_init.release.cluster;" ::: "memory");
    asm volatile("mbarrier.arrive.expect_tx.shared::cta.b64 _, [%0], %1;" :: "r"(sb + BAR_FIRST), "n"(2 * HALO_BYTES) : "memory");
#pragma unroll
    for (int k = 0; k < 2; k++) {
      const int w = max(window_of(0, nfull, cta, ncta, k), 0), a = w / NWX;
      asm volatile("cp.async.bulk.tensor.3d.shared::cluster.global.mbarrier::complete_tx::bytes [%0], [%1, {0, %3, %4}], [%2];"
                   :: "r"(sb + OFF_HALO + k * HALO_BYTES), "l"(reinterpret_cast<uint64_t>(&tmp)), "r"(sb + BAR_FIRST),
                      "r"((w - a * NWX) * 7 - 1), "r"(a * 7 - 1) : "memory");
    }
    if ((sb & 0x3FFFF) != SMEM_BASE || nrounds > 128) __trap();
    for (int i = 0; i < 7; i++) { mbar_init(sb + BAR_WFULL + 8 * i, 1); mbar_init(sb + BAR_WEMPTY + 8 * i, 8); }
    for (int i = 0; i < 9; i++) mbar_init(sb + BAR_XFULL + 8 * i, 1);
    mbar_init(sb + BAR_TFULL, 3);
    mbar_init(sb + BAR_TEMPTY, 8);
    asm volatile("fence.mbarrier_init.release.cluster;" ::: "memory");
  }
  if (tid >= 128 && tid < 320) {
    *reinterpret_cast<uint32_t*>(smem + OFF_ZERO + (tid - 128) * 4) = 0;
    if (tid < 136) *reinterpret_cast<uint32_t*>(smem + OFF_REDO + (tid - 128) * 4) = 0;
  }
  if (tid < 128) {
    *reinterpret_cast<uint4*>(smem + OFF_KV + (tid / 64) * KV_BYTES + 6 * KV_PITCH + (tid % 64) * 16) = make_uint4(0x3c003c00u, 0x3c003c00u, 0x3c003c00u, 0x3c003c00u);
    proxy_fence();
  }
  __syncthreads();

  if (warp < 11) {
#pragma unroll 1
    for (int u = 0; u < (warp < 10 ? 2 : 1); u++) {
      const int cb = warp < 9 ? warp % 3 : 2 * (warp - 9) + u, y = warp < 9 ? 2 * (warp / 3) + u : 6;
      const int ch0 = cb * 64 + (lane & 15) * 4;
      uint32_t wt[9][2], px[3][9][2];
#pragma unroll
      for (int t = 0; t < 9; t++) {
        const uint2 v = *reinterpret_cast<const uint2*>(dw + t * CH + ch0);
        wt[t][0] = v.x; wt[t][1] = v.y;
      }
      mbar_wait(sb + BAR_FIRST, 0);
      const uint32_t ld = sb + OFF_HALO + (lane >> 4) * HALO_BYTES + y * 3456 + ch0 * 2;
#pragma unroll
      for (int p = 0; p < 27; p++)
        asm volatile("ld.shared.v2.u32 {%0,%1}, [%2];" : "=r"(px[p / 9][p % 9][0]), "=r"(px[p / 9][p % 9][1]) : "r"(ld + p * 384));
      const uint32_t st0 = sb + OFF_TILE + (lane >> 4) * TILE_BYTES + ch0 * 4;
      const uint32_t sa = (st0 ^ ((y & 1) << 4)) + y * 2304;
      uint32_t o[2][2];
#pragma unroll
      for (int j = 0; j < 7; j++) {
#pragma unroll
        for (int e = 0; e < 2; e++) {
          uint32_t a = hmul(px[0][j][e], wt[0][e]);
#pragma unroll
          for (int t = 1; t < 9; t++) a = hfma(px[t / 3][j + t % 3][e], wt[t][e], a);
          a = hadd(px[1][j + 1][e], a);
          o[j & 1][e] = packh(lo2f(a), hi2f(a));
        }
        if (j & 1)
          asm volatile("st.shared.v4.u32 [%0], {%1,%2,%3,%4};" :: "r"((j == 3 ? sa ^ 16 : sa) + (j >> 1) * 768),
                       "r"(o[0][0]), "r"(o[1][0]), "r"(o[0][1]), "r"(o[1][1]) : "memory");
      }
      const uint32_t sb6 = (st0 ^ ((~y & 2) << 3)) + (21 + (y >> 1)) * 768 + (y & 1) * 4;
      asm volatile("st.shared.u32 [%0], %1;\nst.shared.u32 [%0 + 8], %2;" :: "r"(sb6), "r"(o[0][0]), "r"(o[0][1]) : "memory");
      if (y == 6) asm volatile("st.shared.u32 [%0 + 4], %1;\nst.shared.u32 [%0 + 12], %1;" :: "r"(sb6), "r"(0) : "memory");
    }
    asm volatile("bar.arrive 8, 384;\nbar.sync 7, 352;" ::: "memory");
  }

  if (warp >= 8) {
    asm volatile("setmaxnreg.dec.sync.aligned.u32 " PREGS ";");
    if (warp == 11) {
      asm volatile("griddepcontrol.wait;" ::: "memory");
      load_slices<1, 3, 1>(sb, ds);
      *reinterpret_cast<float2*>(smem + OFF_LIM) = fp16_limits(lane);
      load_slices<0, 1, 1>(sb, ds);
      asm volatile("bar.sync 8, 384;" ::: "memory");
      load_slices<5, 3, 1>(sb, ds); load_slices<4, 1, 1>(sb, ds);
      for (int r = 0; r < nrounds; r++) {
        const uint32_t par = r & 1;
        const bool next_round = r + 1 < nrounds;
        mbar_wait(sb + BAR_WEMPTY + 40, par); load_slices<8, 1>(sb, ds);
        mbar_wait(sb + BAR_WEMPTY, par);      load_slices<9, 2>(sb, ds); load_slices<11, 1>(sb, ds);
        mbar_wait(sb + BAR_WEMPTY + 48, par); load_slices<12, 1>(sb, ds);
        mbar_wait(sb + BAR_WEMPTY + 8, par);  load_slices<13, 1>(sb, ds); load_slices<14, 2>(sb, ds);
        mbar_wait(sb + BAR_WEMPTY + 16, par); load_slices<0, 1>(sb, ds); if (next_round) load_slices<1, 2>(sb, ds);
        mbar_wait(sb + BAR_WEMPTY + 24, par);
        if (next_round) load_slices<3, 1>(sb, ds);
        load_slices<4, 1>(sb, ds);
        if (next_round) {
          load_slices<5, 1>(sb, ds);
          mbar_wait(sb + BAR_WEMPTY + 32, par); load_slices<6, 2>(sb, ds);
        }
      }
    } else {
      const int cw = warp - 8;
      const int win = lane >> 4;
      const int ch0 = cw * 64 + (lane & 15) * 4;
      uint32_t wt[9][2];
#pragma unroll
      for (int t = 0; t < 9; t++) {
        uint2 v = *reinterpret_cast<const uint2*>(dw + t * CH + ch0);
        wt[t][0] = v.x; wt[t][1] = v.y;
      }
      const uint32_t xs = sb + OFF_X + cw * 3 * XSLOT;
      const uint32_t xld = xs + (lane >> 4) * 1152 + (lane & 15) * 8;
      const uint32_t xbar = sb + BAR_XFULL + cw * 24;
      const uint32_t st0 = sb + OFF_TILE + win * TILE_BYTES + ch0 * 4;
      const uint64_t tm = reinterpret_cast<uint64_t>(&tmx);
      int cx0, cy0, cx1, cy1;
      auto coords = [&](int r) {
        const int w0 = window_of(r, nfull, cta, ncta, 0);
        int w1 = window_of(r, nfull, cta, ncta, 1);
        if (w1 < 0) w1 = w0;
        const int a = w0 / NWX, b = w1 / NWX;
        cx0 = (w0 - a * NWX) * 7 - 1; cy0 = a * 7 - 1;
        cx1 = (w1 - b * NWX) * 7 - 1; cy1 = b * 7 - 1;
      };
      auto issue = [&](int slot, int dy) {
        asm volatile("{\n.reg .pred p;\nelect.sync _|p, 0xffffffff;\n"
                     "@p mbarrier.arrive.expect_tx.shared::cta.b64 _, [%2], %8;\n"
                     "@p cp.async.bulk.tensor.3d.shared::cluster.global.mbarrier::complete_tx::bytes [%0], [%1, {%3, %4, %5}], [%2];\n"
                     "@p cp.async.bulk.tensor.3d.shared::cluster.global.mbarrier::complete_tx::bytes [%0 + 1152], [%1, {%3, %6, %7}], [%2];\n}\n"
                     :: "r"(xs + slot * XSLOT), "l"(tm), "r"(xbar + slot * 8), "r"(cw * 64), "r"(cx0), "r"(cy0 + dy), "r"(cx1), "r"(cy1 + dy), "n"(XSLOT) : "memory");
      };
      uint32_t accA[7][2], accB[7][2], ctr[7][2], held[2];
      auto row = [&](auto fin, auto mid, auto top, int slot, int y) {
        const uint32_t ld = xld + slot * XSLOT;
        const uint32_t sa = (st0 ^ ((y & 1) << 4)) + y * 2304;
        uint32_t cur[9][2], o[2][2];
#pragma unroll
        for (int p = 0; p < LA; p++)
          asm volatile("ld.shared.v2.u32 {%0,%1}, [%2];" : "=r"(cur[p][0]), "=r"(cur[p][1]) : "r"(ld + p * 128));
#pragma unroll
        for (int j = 0; j < 7; j++) {
          if (j >= 1 && j + LA - 1 < 9)
            asm volatile("ld.shared.v2.u32 {%0,%1}, [%2];" : "=r"(cur[j + LA - 1][0]), "=r"(cur[j + LA - 1][1]) : "r"(ld + (j + LA - 1) * 128));
          if (fin.v) {
#pragma unroll
            for (int e = 0; e < 2; e++) {
              uint32_t a = hfma(cur[j][e], wt[6][e], accA[j][e]);
              a = hfma(cur[j + 1][e], wt[7][e], a);
              a = hfma(cur[j + 2][e], wt[8][e], a);
              if (!EARLYX) a = hadd(ctr[j][e], a);
              o[j & 1][e] = packh(lo2f(a), hi2f(a));
            }
            if (j & 1)
              asm volatile("st.shared.v4.u32 [%0], {%1,%2,%3,%4};" :: "r"((j == 3 ? sa ^ 16 : sa) + (j >> 1) * 768),
                           "r"(o[0][0]), "r"(o[1][0]), "r"(o[0][1]), "r"(o[1][1]) : "memory");
            if (j == 6) {
              const uint32_t sb6 = (st0 ^ ((~y & 2) << 3)) + (21 + (y >> 1)) * 768;
              if (fin.v == 2)
                asm volatile("st.shared.v4.u32 [%0], {%1,%2,%3,%2};" :: "r"(sb6), "r"(o[0][0]), "r"(0), "r"(o[0][1]) : "memory");
              else
                asm volatile("{\n.reg .pred p;\nsetp.ne.s32 p, %5, 0;\n@p st.shared.v4.u32 [%0], {%1,%2,%3,%4};\n}\n"
                             :: "r"(sb6), "r"(held[0]), "r"(o[0][0]), "r"(held[1]), "r"(o[0][1]), "r"(y & 1) : "memory");
              held[0] = o[0][0]; held[1] = o[0][1];
            }
          }
#pragma unroll
          for (int e = 0; e < 2; e++) {
            if (mid.v) {
              uint32_t a = hfma(cur[j][e], wt[3][e], accB[j][e]);
              a = hfma(cur[j + 1][e], wt[4][e], a);
              a = hfma(cur[j + 2][e], wt[5][e], a);
              accA[j][e] = EARLYX == 1 ? hadd(cur[j + 1][e], a) : a;
              if (!EARLYX) ctr[j][e] = cur[j + 1][e];
            }
            if (top.v) {
              uint32_t a = hmul(cur[j][e], wt[0][e]);
              a = hfma(cur[j + 1][e], wt[1][e], a);
              accB[j][e] = hfma(cur[j + 2][e], wt[2][e], a);
            }
          }
        }
      };
      held[0] = held[1] = 0;
      if (nrounds > 1) { coords(1); issue(0, 0); issue(1, 1); issue(2, 2); }
      for (int r = 0; r + 1 < nrounds; r++) {
        const bool more = r + 2 < nrounds;
        mbar_wait(xbar, r & 1);
        if (r > 0) issue(2, 2);
        row(IC<0>{}, IC<0>{}, IC<1>{}, 0, 0);
        mbar_wait(xbar + 8, r & 1);
        issue(0, 3);
        row(IC<0>{}, IC<1>{}, IC<1>{}, 1, 0);
        mbar_wait(sb + BAR_TEMPTY, r & 1);
        TR(0);
#pragma unroll 1
        for (int k = 0; k < 2; k++) {
          mbar_wait(xbar + 16, (r + k) & 1);
          issue(1, 4 + 3 * k);
          row(IC<1>{}, IC<1>{}, IC<1>{}, 2, 3 * k);
          mbar_wait(xbar, (r + k + 1) & 1);
          issue(2, 5 + 3 * k);
          row(IC<1>{}, IC<1>{}, IC<1>{}, 0, 3 * k + 1);
          mbar_wait(xbar + 8, (r + k + 1) & 1);
          if (k == 1 && more) coords(r + 2);
          if (k == 0 || more) issue(0, k == 0 ? 6 : 0);
          row(IC<1>{}, IC<1>{}, IC<1>{}, 1, 3 * k + 2);
        }
        mbar_wait(xbar + 16, r & 1);
        if (more) issue(1, 1);
        row(IC<2>{}, IC<0>{}, IC<0>{}, 2, 6);
        warp_arrive(sb + BAR_TFULL);
        TR(1);
      }
    }
    asm volatile("bar.sync 5, 384;" ::: "memory");
#pragma unroll 1
    for (int i = 0; i < 8; i++) {
      uint32_t bits = *reinterpret_cast<volatile uint32_t*>(smem + OFF_REDO + 4 * i);
#pragma unroll 1
      for (; bits; bits &= bits - 1)
        slow_window(reinterpret_cast<float*>(smem), window_of((i & 3) * 32 + __ffs(bits) - 1, nfull, cta, ncta, i >> 2), tid - 256, x, dw, wqkv, wo, out);
    }
  } else {
    asm volatile("setmaxnreg.inc.sync.aligned.u32 " CREGS ";");
    const int wg = warp >> 2, w4 = warp & 3, g = lane >> 2, q = lane & 3;
    const int row0 = w4 * 16 + g, row1 = row0 + 8;
    const int ps = min(w4 * 8 + g, 24);
    const int pix0 = ps < 21 ? (ps / 3) * IMG + (ps % 3) * 2 : (ps - 21) * 2 * IMG + 6;
    const int pix1 = pix0 + (ps < 21 ? 1 : ps < 24 ? IMG : 0);
    const uint32_t kv = sb + OFF_KV + wg * KV_BYTES;
    const int srow = w4 * 16 + (lane & 15);
    const uint32_t vst = kv + (lane >> 4) * KV_PITCH + (srow < 56 ? srow : min(srow - 7, 55)) * 16;
    uint32_t misc = ((uint32_t)pix1 << 20) | ((uint32_t)pix0 << 8) | q;
    const uint32_t ninf = q ? 0xfc00fc00u : 0u;
    const uint32_t v48 = kv + (lane >> 3) * KV_PITCH + 48 * 16;
    const uint32_t vmask = (row0 < 49 ? 0xffffu : 0u) | (row1 < 49 ? 0xffff0000u : 0u);

    const uint32_t tx = sb + q * 32 + (row0 < 49 ? OFF_TILE + wg * TILE_BYTES + ps * 768 + (ps & 1) * 16 : OFF_ZERO + 16);
    const int myrounds = window_of(nrounds - 1, nfull, cta, ncta, wg) < 0 ? nrounds - 1 : nrounds;

    if (never == 2) return;
    uint32_t H[48], Y[48];
    const uint64_t* dkv = ds.kv[wg];
    uint32_t P[NP], Ofc[12], p48 = 0;
#pragma unroll
    for (int i = 0; i < 48; i++) Y[i] = 0;
#pragma unroll
    for (int i = 0; i < NP; i++) P[i] = Ofc[i % 12] = 0;
    if (warp == 0) GTS(4);
    load_x<0, 12>(H, tx);
    warp_arrive(sb + BAR_TEMPTY);
    if (wg == 1) turn_pass(1);

    uint8_t *o0, *o1;
    uint32_t omask;
    auto out_setup = [&](int r) {
      omask = r >= 0 ? vmask : 0u;
      const int w = window_of(r, nfull, cta, ncta, wg);
      const int wy = w / NWX, wx = w - wy * NWX;
      asm volatile("" : "+r"(misc));
      const uint32_t wb = (uint32_t)(wy * 7 * IMG + wx * 7) * 384u + (misc & 3) * 16;
      o0 = reinterpret_cast<uint8_t*>(out) + (wb + ((misc >> 8) & 0xfff) * 384u);
      o1 = reinterpret_cast<uint8_t*>(out) + (wb + (misc >> 20) * 384u);
    };
#define OUT(c) store_out<c>(Y, o0, o1, omask)
    auto release = [&](int stage) { warp_arrive(sb + BAR_WEMPTY + 8 * stage); };

    for (int r = 0;; r++) {
      const uint32_t par = r & 1;
      uint32_t acc[36], S[14], O[14], Q[12], V[12], Ofa[12], Ofb[12], vr[6], k48, mx;
      if (r == myrounds) {
        const bool idle = r < nrounds;
        mbar_wait(sb + BAR_WFULL + 40, par);
        turn_wait(wg);
        wg_fence(); mma_pv(O, P, dkv + 4); mma_proj(Y, Ofc, ds.p + 6); wg_commit();
        turn_pass(wg);
        load_v48(vr, v48);
        wg_wait<0>(); keep(O); keep(Y);
        finish_o(O, vr, p48, vmask, Ofa);
        if (idle) { release(5); release(0); release(1); release(2); release(3); }
        mbar_wait(sb + BAR_WFULL + 48, par);
        turn_wait(wg);
        wg_fence(); mma_proj(Y, Ofa, ds.p + 9); wg_commit();
        if (wg == 0 || idle) turn_pass(wg);
        wg_wait<0>(); keep(Y);
        if (idle) { release(6); turn_wait(wg); turn_pass(wg); }
        out_setup(r - 1);
        OUT(0); PIN(); OUT(1); PIN(); OUT(2); PIN(); OUT(3); PIN(); OUT(4); PIN(); OUT(5);
        if (idle) {
          turn_wait(wg); turn_pass(wg);
          turn_wait(wg); turn_pass(wg);
          turn_wait(wg); turn_pass(wg);
          turn_wait(wg);
        }
        if (w4 == 0) GTS(5 + wg);
        asm volatile("bar.arrive 5, 384;" ::: "memory");
        break;
      }
      float s1[2], s2[2];
      if (SA > 0) ln_sums<0, SA>(H, s1, s2);
      mbar_wait(sb + BAR_WFULL + 40, par);
      mbar_wait(sb + BAR_WFULL, par);
      TR(0);
      turn_wait(wg);
      TR(1);
      wg_fence(); mma_pv(O, P, dkv + 4); mma_proj(Y, Ofc, ds.p + 6); wg_commit(); mma_qkv<0, 3>(acc, H, ds.q[0]);
      PIN();
      ln_sums<SA, SB>(H, s1, s2);
      PIN();
      wg_fence(); mma_qkv<3, 8>(acc, H, ds.q[0]);
      PIN();
      ln_sums<SB, SC>(H, s1, s2);
      PIN();
      wg_fence(); mma_qkv<8, 12>(acc, H, ds.q[0]);
      turn_pass(wg);
      TR(2);
      load_v48(vr, v48);
      wg_wait<3>(); keep(O); keep(Y);
      release(5);
      wg_sync(wg);
      PIN();
      finish_o(O, vr, p48, vmask, Ofa);
      if (SC < 48) ln_sums<SC, 48>(H, s1, s2);
      float lim_lo, lim_hi;
      asm volatile("ld.shared.v2.f32 {%0,%1}, [%2];" : "=f"(lim_lo), "=f"(lim_hi) : "r"(sb + OFF_LIM) : "memory");
      bool ok;
      const uint32_t rk = ln_rstd(s1, s2, lim_lo, lim_hi, ok);
      asm volatile("{\n.reg .pred p;\nsetp.eq.s32 p, %2, 0;\n@p red.shared.or.b32 [%0], %1;\n}\n"
                   :: "r"(sb + OFF_REDO + wg * 16 + (r >> 5) * 4), "r"(1u << (r & 31)), "r"((int)ok) : "memory");
      PIN();
      TR(3);
      wg_wait<0>(); keep(acc);
      TR(4);
      release(0);
      scale12(V, acc, rk); stsm12(V, vst + KV_KOFF);
      scale12(V, acc + 24, rk); stsm12(V, vst);
      scale12(Q, acc + 12, rk); PIN();
      proxy_fence();
      mbar_wait(sb + BAR_WFULL + 48, par);
      mbar_wait(sb + BAR_WFULL + 8, par);
      TR(5);
      turn_wait(wg);
      TR(6);
      wg_fence(); mma_proj(Y, Ofa, ds.p + 9); wg_commit(); mma_s(S, Q, dkv); mma_qkv<0, 2>(acc, H, ds.q[1]);
      out_setup(r - 1);
      PIN();
      wg_wait<1>(); keep(Y);
      release(6);
      wg_fence(); mma_qkv<2, 6>(acc, H, ds.q[1]);
      PIN();
      OUT(0);
      PIN();
      wg_wait<1>(); keep(S);
      wg_fence(); mma_qkv<6, 9>(acc, H, ds.q[1]);
      PIN();
      row_max(S, k48, mx, ninf);
      OUT(1);
      PIN();
      wg_fence(); mma_qkv<9, 12>(acc, H, ds.q[1]);
      turn_pass(wg);
      PIN();
      OUT(2); PIN();
      OUT(3); PIN();
      row_exp(S, k48, mx, P, p48);
      PIN();
      TR(7);
      wg_wait<0>(); keep(acc);
      TR(8);
      release(1);
      wg_sync(wg);
      scale12(V, acc, rk); stsm12(V, vst + KV_KOFF);
      scale12(Q, acc + 12, rk); scale12(V, acc + 24, rk); PIN();
      proxy_fence();
#define TURN(ID, OF, G1, G2, G3, X1)                                                       \
      TR(ID + 1);                                                                       \
      turn_wait(wg);                                                                    \
      wg_fence(); mma_pv(O, P, dkv + 4); mma_s(S, Q, dkv); wg_commit(); G1;             \
      PIN();                                                                            \
      TR(ID + 2);                                                                       \
      load_v48(vr, v48);                                                                \
      X1;                                                                               \
      PIN();                                                                            \
      wg_wait<1>(); keep(S); keep(O);                                                   \
      wg_sync(wg);                                         \
      wg_fence(); G2;                                                                   \
      if (KB == 12) turn_pass(wg);                                                      \
      PIN();                                                                            \
      stsm12(V, vst);                                                                   \
      finish_o(O, vr, p48, vmask, OF);                                                    \
      row_max(S, k48, mx, ninf);                                                              \
      PIN();                                                                            \
      if (KB < 12) { wg_fence(); G3; turn_pass(wg); }                                                                 \
      PIN();                                                                            \
      TR(ID + 3);
#define NEXT_HEAD(ID, HD)                                                               \
      row_exp(S, k48, mx, P, p48);                                                      \
      PIN();                                                                            \
      TR(ID + 4);                                                                       \
      wg_wait<0>(); keep(acc);                                                          \
      release(HD);                                                                      \
      scale12(V, acc, rk); stsm12(V, vst + KV_KOFF);                                    \
      scale12(Q, acc + 12, rk); scale12(V, acc + 24, rk); PIN();
      mbar_wait(sb + BAR_WFULL + 16, par);
      TURN(8, Ofa, (mma_qkv<0, KA>(acc, H, ds.q[2])), (mma_qkv<KA, KB>(acc, H, ds.q[2])), (mma_qkv<KB, 12>(acc, H, ds.q[2])), OUT(4))
      OUT(5); PIN();
      NEXT_HEAD(8, 2)
      proxy_fence();
      mbar_wait(sb + BAR_WFULL + 24, par);
      TURN(12, Ofb, (mma_qkv<0, KA>(acc, H, ds.q[3])), (mma_qkv<KA, KB>(acc, H, ds.q[3])), (mma_qkv<KB, 12>(acc, H, ds.q[3])), )
      NEXT_HEAD(12, 3)
#pragma unroll
      for (int i = 0; i < 48; i++) Y[i] = (i & 1) ? H[i] ^ never : H[i] + never;
      hold<0, 48>(Y); PIN();
      proxy_fence();
      mbar_wait(sb + BAR_WFULL + 32, par);
      TR(17);
      turn_wait(wg);
      wg_fence(); mma_pv(O, P, dkv + 4); mma_s(S, Q, dkv); wg_commit(); mma_proj(Y, Ofa, ds.p); mma_proj(Y, Ofb, ds.p + 3); wg_commit();
      turn_pass(wg);
      PIN();
      TR(18);
      load_v48(vr, v48);
      if (r + 1 < myrounds) mbar_wait(sb + BAR_TFULL, par);
      load_x<0, 4>(H, tx);
      wg_wait<1>(); keep(S); keep(O);
      wg_sync(wg);
      PIN();
      TR(19);
      row_max(S, k48, mx, ninf);
      finish_o(O, vr, p48, vmask, Ofc);
      stsm12(V, vst);
      PIN();
      load_x<4, 8>(H, tx);
      row_exp(S, k48, mx, P, p48);
      PIN();
      load_x<8, 12>(H, tx);
      warp_arrive(sb + BAR_TEMPTY);
      TR(20);
      wg_wait<0>(); keep(Y);
      release(4);
      proxy_fence();
      TR(21);
#undef TURN
#undef NEXT_HEAD
    }
  }
}

typedef CUresult (*EncodeFn)(CUtensorMap*, CUtensorMapDataType, cuuint32_t, void*, const cuuint64_t*, const cuuint64_t*,
                             const cuuint32_t*, const cuuint32_t*, CUtensorMapInterleave, CUtensorMapSwizzle,
                             CUtensorMapL2promotion, CUtensorMapFloatOOBfill);

}

extern "C" void kernel_launch(void* const* d_in, const int* in_sizes, int n_in, void* d_out, int out_size) {
  const __nv_bfloat16* x = (const __nv_bfloat16*)d_in[0];
  const __nv_bfloat16* dw = (const __nv_bfloat16*)d_in[1];
  const __nv_bfloat16* wqkv = (const __nv_bfloat16*)d_in[2];
  const __nv_bfloat16* wo = (const __nv_bfloat16*)d_in[3];
  static EncodeFn encode = nullptr;
  static int nsm = 0;
  static void* wpack = nullptr;
  if (!encode) {
    void* fn = nullptr;
    cudaDriverEntryPointQueryResult qr;
    cudaGetDriverEntryPoint("cuTensorMapEncodeTiled", &fn, cudaEnableDefault, &qr);
    encode = (EncodeFn)fn;
    int dev = 0;
    cudaGetDevice(&dev);
    cudaDeviceGetAttribute(&nsm, cudaDevAttrMultiProcessorCount, dev);
    cudaGetSymbolAddress(&wpack, g_wpack);
    cudaFuncSetAttribute(fused_kernel, cudaFuncAttributeMaxDynamicSharedMemorySize, SMEM_BYTES);
  }
  CUtensorMap tmx;
  cuuint64_t gdim[3] = {CH, IMG, IMG};
  cuuint64_t gstr[2] = {CH * 2, (cuuint64_t)CH * 2 * IMG};
  cuuint32_t box[3] = {64, 9, 1};
  cuuint32_t estr[3] = {1, 1, 1};
  encode(&tmx, CU_TENSOR_MAP_DATA_TYPE_BFLOAT16, 3, (void*)x, gdim, gstr, box, estr, CU_TENSOR_MAP_INTERLEAVE_NONE,
         CU_TENSOR_MAP_SWIZZLE_NONE, CU_TENSOR_MAP_L2_PROMOTION_L2_128B, CU_TENSOR_MAP_FLOAT_OOB_FILL_NONE);
  Descs ds;
  for (int i = 0; i < 12; i++) {
    for (int h = 0; h < 4; h++) ds.q[h][i] = mkdesc(SMEM_BASE + OFF_W + qkv_pos(h, i) % (8 * SLICE), 128, 256);
    ds.p[i] = mkdesc(SMEM_BASE + OFF_W + wo_pos(i) % (8 * SLICE), 128, 256);
  }
  for (int i = 0; i < 16; i++) ds.src[i] = (const uint8_t*)wpack + i * SLICE;
  for (int g = 0; g < 2; g++)
    for (int i = 0; i < 4; i++) {
      ds.kv[g][i] = mkdesc(SMEM_BASE + OFF_KV + g * KV_BYTES + KV_KOFF + 2 * i * KV_PITCH, KV_PITCH, 128);
      ds.kv[g][4 + i] = mkdesc(SMEM_BASE + OFF_KV + g * KV_BYTES + 256 * i, 128, KV_PITCH);
    }
  CUtensorMap tmp;
  cuuint32_t boxp[3] = {CH, 9, 9};
  encode(&tmp, CU_TENSOR_MAP_DATA_TYPE_BFLOAT16, 3, (void*)x, gdim, gstr, boxp, estr, CU_TENSOR_MAP_INTERLEAVE_NONE,
         CU_TENSOR_MAP_SWIZZLE_NONE, CU_TENSOR_MAP_L2_PROMOTION_L2_128B, CU_TENSOR_MAP_FLOAT_OOB_FILL_NONE);
  prepack_kernel<<<48, dim3(192, 2), 0, cudaStreamPerThread>>>(wqkv, wo);
  cudaLaunchConfig_t cfg = {};
  cfg.gridDim = dim3(nsm); cfg.blockDim = dim3(384); cfg.dynamicSmemBytes = SMEM_BYTES; cfg.stream = cudaStreamPerThread;
  cudaLaunchAttribute at[1];
  at[0].id = cudaLaunchAttributeProgrammaticStreamSerialization;
  at[0].val.programmaticStreamSerializationAllowed = 1;
  cfg.attrs = at; cfg.numAttrs = 1;
  cudaLaunchKernelEx(&cfg, fused_kernel, tmx, tmp, ds, dw, (__nv_bfloat16*)d_out, 0, x, wqkv, wo);
}
```

```cpp
#include <cuda_runtime.h>
#include <cuda_bf16.h>
#include <cuda_fp16.h>
#include <cuda.h>
#include <stdint.h>

#define CREGS "208"
#define PREGS "88"
#define KA 3
#define KB 9
#define SA 0
#define SB 24
#define SC 48
#define K48TC 0
#define EARLYX 0
#define LA 4
#define YEARLY 0
#define STHINT ".cs"
namespace {
constexpr int NP = K48TC ? 16 : 12;

constexpr int IMG = 511;
constexpr int CH = 192;
constexpr int NWX = 73;
constexpr int NWIN = NWX * NWX;
constexpr int SLICE = 18432;
constexpr int OFF_W = 0;
constexpr int KV_PITCH = 1792, KV_KOFF = 896, KV_BYTES = 6 * KV_PITCH + 1024;
constexpr int OFF_KV = 8 * SLICE;
constexpr int TILE_BYTES = 25 * 768;
constexpr int OFF_TILE = OFF_KV + 2 * KV_BYTES;
constexpr int XSLOT = 2304;
constexpr int OFF_ZERO = OFF_TILE + 2 * TILE_BYTES;
constexpr int OFF_X = OFF_ZERO + 768;
constexpr int OFF_BAR = OFF_X + 9 * XSLOT;
constexpr int BAR_WFULL = OFF_BAR;
constexpr int BAR_WEMPTY = OFF_BAR + 56;
constexpr int BAR_XFULL = OFF_BAR + 112;
constexpr int BAR_TFULL = OFF_BAR + 184;
constexpr int BAR_TEMPTY = OFF_BAR + 192;
constexpr int OFF_LIM = OFF_BAR + 200;
constexpr int OFF_REDO = OFF_BAR + 208;
constexpr int BAR_FIRST = OFF_BAR + 240;
constexpr int OFF_TRACE = OFF_BAR + 248;
constexpr int OFF_HALO = OFF_W + 4 * SLICE, HALO_BYTES = 81 * 384;
constexpr int SMEM_BYTES = OFF_TRACE;

__host__ __device__ constexpr int qkv_pos(int h, int s) { return (h == 0 ? 1 : 3 * h + 2) * SLICE + s * 4608; }
__host__ __device__ constexpr int wo_pos(int s) { return s < 6 ? 14 * SLICE + s * 6144 : s < 9 ? (s - 6) * 6144 : 4 * SLICE + (s - 9) * 6144; }
__host__ __device__ constexpr int stage_of(int p) { return p == 0 ? 5 : p < 4 ? 0 : p == 4 ? 6 : p < 8 ? 1 : p < 11 ? 2 : p < 14 ? 3 : 4; }
constexpr int SMEM_BASE = 1024;
struct Descs { uint64_t q[4][12]; uint64_t p[12]; uint64_t kv[2][8]; const uint8_t* src[16]; };

__device__ uint4 g_wpack[16 * SLICE / 16];
__device__ float2 g_wnorm[96];
#define TR(id)
#define GTS(i)
template <int V> struct IC { static constexpr int v = V; };
typedef __nv_bfloat162 bf2;
__device__ __forceinline__ bf2 u2b(uint32_t u) { return *reinterpret_cast<bf2*>(&u); }
__device__ __forceinline__ uint32_t b2u(bf2 b) { return *reinterpret_cast<uint32_t*>(&b); }
__device__ __forceinline__ uint32_t pack2(float lo, float hi) {
  uint32_t r; asm("cvt.rn.bf16x2.f32 %0, %1, %2;" : "=r"(r) : "f"(hi), "f"(lo)); return r;
}
__device__ __forceinline__ uint32_t hadd(uint32_t a, uint32_t b) { return b2u(__hadd2_rn(u2b(a), u2b(b))); }
__device__ __forceinline__ uint32_t hmul(uint32_t a, uint32_t b) { return b2u(__hmul2_rn(u2b(a), u2b(b))); }
__device__ __forceinline__ uint32_t hfma(uint32_t a, uint32_t b, uint32_t c) { return b2u(__hfma2(u2b(a), u2b(b), u2b(c))); }
__device__ __forceinline__ __half2 u2h(uint32_t u) { return *reinterpret_cast<__half2*>(&u); }
__device__ __forceinline__ uint32_t h2u(__half2 b) { return *reinterpret_cast<uint32_t*>(&b); }
__device__ __forceinline__ uint32_t packh(float lo, float hi) {
  uint32_t r; asm("cvt.rn.f16x2.f32 %0, %1, %2;" : "=r"(r) : "f"(hi), "f"(lo)); return r;
}
__device__ __forceinline__ uint32_t fmax2(uint32_t a, uint32_t b) { return h2u(__hmax2(u2h(a), u2h(b))); }
template <int HI> __device__ __forceinline__ __half2 hcast(uint32_t a) { return HI ? __high2half2(u2h(a)) : __low2half2(u2h(a)); }
template <int HI> __device__ __forceinline__ uint32_t fmul_b(uint32_t a, uint32_t s) { return h2u(__hmul2_rn(u2h(a), hcast<HI>(s))); }
template <int HI> __device__ __forceinline__ uint32_t fsub_b(uint32_t a, uint32_t s) { return h2u(__hsub2_rn(u2h(a), hcast<HI>(s))); }
__device__ __forceinline__ uint32_t fex2(uint32_t a) { uint32_t r; asm("ex2.approx.f16x2 %0, %1;" : "=r"(r) : "r"(a)); return r; }
__device__ __forceinline__ float lo2f(uint32_t a) { return __uint_as_float(a << 16); }
__device__ __forceinline__ float hi2f(uint32_t a) { return __uint_as_float(a & 0xffff0000u); }

__device__ __forceinline__ void mbar_init(uint32_t bar, uint32_t cnt) { asm volatile("mbarrier.init.shared::cta.b64 [%0], %1;" :: "r"(bar), "r"(cnt) : "memory"); }
__device__ __forceinline__ void mbar_wait(uint32_t bar, uint32_t parity) {
  asm volatile("{\n.reg .pred p;\n.reg .u32 n;\n"
               "mbarrier.try_wait.parity.shared::cta.b64 p, [%0], %1;\n"
               "@p bra.uni DONE_%=;\n"
               "mov.u32 n, 0;\n"
               "AGAIN_%=:\n"
               "mbarrier.try_wait.parity.shared::cta.b64 p, [%0], %1;\n"
               "@p bra.uni DONE_%=;\n"
               "add.u32 n, n, 1;\n"
               "setp.lt.u32 p, n, 0x1000000;\n"
               "@p bra.uni AGAIN_%=;\n"
               "trap;\n"
               "DONE_%=:\n}\n" :: "r"(bar), "r"(parity) : "memory");
}
__device__ __forceinline__ void wg_fence() { asm volatile("wgmma.fence.sync.aligned;" ::: "memory"); }
__device__ __forceinline__ void wg_commit() { asm volatile("wgmma.commit_group.sync.aligned;" ::: "memory"); }
template <int N> __device__ __forceinline__ void wg_wait() { asm volatile("wgmma.wait_group.sync.aligned %0;" :: "n"(N) : "memory"); }
#define BAR_BY_WG(OP, ID0, ID1, CNT) asm volatile("{\n.reg .pred p;\nsetp.eq.s32 p, %0, 0;\n@p " OP " " #ID0 ", " #CNT ";\n@!p " OP " " #ID1 ", " #CNT ";\n}\n" :: "r"(wg) : "memory")
__device__ __forceinline__ void wg_sync(int wg) { BAR_BY_WG("bar.sync", 1, 2, 128); }
__device__ __forceinline__ void turn_wait(int wg) { BAR_BY_WG("bar.sync", 3, 4, 256); }
__device__ __forceinline__ void turn_pass(int wg) { BAR_BY_WG("bar.arrive", 4, 3, 256); }
__device__ __forceinline__ void stsm4(uint32_t addr, uint32_t a, uint32_t b, uint32_t c, uint32_t d) {
  asm volatile("stmatrix.sync.aligned.m8n8.x4.shared.b16 [%0], {%1,%2,%3,%4};" :: "r"(addr), "r"(a), "r"(b), "r"(c), "r"(d) : "memory");
}
template <int N> __device__ __forceinline__ void keep(float (&d)[N]) {
#pragma unroll
  for (int i = 0; i < N; i++) asm volatile("" : "+f"(d[i]) :: "memory");
}
template <int N> __device__ __forceinline__ void keep(uint32_t (&d)[N]) {
#pragma unroll
  for (int i = 0; i < N; i++) asm volatile("" : "+r"(d[i]) :: "memory");
}
__host__ __device__ __forceinline__ uint64_t mkdesc(uint32_t addr, uint32_t lbo, uint32_t sbo) {
  return ((uint64_t)(sbo >> 4) << 32) | (uint64_t)(((lbo >> 4) << 16) | ((addr & 0x3FFFF) >> 4));
}

template <int SCALE_D>
__device__ __forceinline__ void wgmma_n144(uint32_t (&d)[36], uint32_t a0, uint32_t a1, uint32_t a2, uint32_t a3, uint64_t descB) {
  if (SCALE_D == 0)
  asm volatile("wgmma.mma_async.sync.aligned.m64n144k16.f16.f16.f16 "
    "{%0, %1, %2, %3, %4, %5, %6, %7, %8, %9, %10, %11, %12, %13, %14, %15, "
    "%16, %17, %18, %19, %20, %21, %22, %23, %24, %25, %26, %27, %28, %29, %30, %31, "
    "%32, %33, %34, %35}, "
    "{%36, %37, %38, %39}, %40, 0, 1, 1, 0;\n"
    : "=r"(d[0]), "=r"(d[1]), "=r"(d[2]), "=r"(d[3]), "=r"(d[4]), "=r"(d[5]), "=r"(d[6]), "=r"(d[7]),
      "=r"(d[8]), "=r"(d[9]), "=r"(d[10]), "=r"(d[11]), "=r"(d[12]), "=r"(d[13]), "=r"(d[14]), "=r"(d[15]),
      "=r"(d[16]), "=r"(d[17]), "=r"(d[18]), "=r"(d[19]), "=r"(d[20]), "=r"(d[21]), "=r"(d[22]), "=r"(d[23]),
      "=r"(d[24]), "=r"(d[25]), "=r"(d[26]), "=r"(d[27]), "=r"(d[28]), "=r"(d[29]), "=r"(d[30]), "=r"(d[31]),
      "=r"(d[32]), "=r"(d[33]), "=r"(d[34]), "=r"(d[35])
    : "r"(a0), "r"(a1), "r"(a2), "r"(a3), "l"(descB));
  else
  asm volatile("wgmma.mma_async.sync.aligned.m64n144k16.f16.f16.f16 "
    "{%0, %1, %2, %3, %4, %5, %6, %7, %8, %9, %10, %11, %12, %13, %14, %15, "
    "%16, %17, %18, %19, %20, %21, %22, %23, %24, %25, %26, %27, %28, %29, %30, %31, "
    "%32, %33, %34, %35}, "
    "{%36, %37, %38, %39}, %40, 1, 1, 1, 0;\n"
    : "+r"(d[0]), "+r"(d[1]), "+r"(d[2]), "+r"(d[3]), "+r"(d[4]), "+r"(d[5]), "+r"(d[6]), "+r"(d[7]),
      "+r"(d[8]), "+r"(d[9]), "+r"(d[10]), "+r"(d[11]), "+r"(d[12]), "+r"(d[13]), "+r"(d[14]), "+r"(d[15]),
      "+r"(d[16]), "+r"(d[17]), "+r"(d[18]), "+r"(d[19]), "+r"(d[20]), "+r"(d[21]), "+r"(d[22]), "+r"(d[23]),
      "+r"(d[24]), "+r"(d[25]), "+r"(d[26]), "+r"(d[27]), "+r"(d[28]), "+r"(d[29]), "+r"(d[30]), "+r"(d[31]),
      "+r"(d[32]), "+r"(d[33]), "+r"(d[34]), "+r"(d[35])
    : "r"(a0), "r"(a1), "r"(a2), "r"(a3), "l"(descB));
}

template <int SCALE_D>
__device__ __forceinline__ void wgmma_n192(uint32_t (&d)[48], uint32_t a0, uint32_t a1, uint32_t a2, uint32_t a3, uint64_t descB) {
  if (SCALE_D == 0)
  asm volatile("wgmma.mma_async.sync.aligned.m64n192k16.f16.f16.f16 "
    "{%0, %1, %2, %3, %4, %5, %6, %7, %8, %9, %10, %11, %12, %13, %14, %15, "
    "%16, %17, %18, %19, %20, %21, %22, %23, %24, %25, %26, %27, %28, %29, %30, %31, "
    "%32, %33, %34, %35, %36, %37, %38, %39, %40, %41, %42, %43, %44, %45, %46, %47}, "
    "{%48, %49, %50, %51}, %52, 0, 1, 1, 0;\n"
    : "=r"(d[0]), "=r"(d[1]), "=r"(d[2]), "=r"(d[3]), "=r"(d[4]), "=r"(d[5]), "=r"(d[6]), "=r"(d[7]),
      "=r"(d[8]), "=r"(d[9]), "=r"(d[10]), "=r"(d[11]), "=r"(d[12]), "=r"(d[13]), "=r"(d[14]), "=r"(d[15]),
      "=r"(d[16]), "=r"(d[17]), "=r"(d[18]), "=r"(d[19]), "=r"(d[20]), "=r"(d[21]), "=r"(d[22]), "=r"(d[23]),
      "=r"(d[24]), "=r"(d[25]), "=r"(d[26]), "=r"(d[27]), "=r"(d[28]), "=r"(d[29]), "=r"(d[30]), "=r"(d[31]),
      "=r"(d[32]), "=r"(d[33]), "=r"(d[34]), "=r"(d[35]), "=r"(d[36]), "=r"(d[37]), "=r"(d[38]), "=r"(d[39]),
      "=r"(d[40]), "=r"(d[41]), "=r"(d[42]), "=r"(d[43]), "=r"(d[44]), "=r"(d[45]), "=r"(d[46]), "=r"(d[47])
    : "r"(a0), "r"(a1), "r"(a2), "r"(a3), "l"(descB));
  else
  asm volatile("wgmma.mma_async.sync.aligned.m64n192k16.f16.f16.f16 "
    "{%0, %1, %2, %3, %4, %5, %6, %7, %8, %9, %10, %11, %12, %13, %14, %15, "
    "%16, %17, %18, %19, %20, %21, %22, %23, %24, %25, %26, %27, %28, %29, %30, %31, "
    "%32, %33, %34, %35, %36, %37, %38, %39, %40, %41, %42, %43, %44, %45, %46, %47}, "
    "{%48, %49, %50, %51}, %52, 1, 1, 1, 0;\n"
    : "+r"(d[0]), "+r"(d[1]), "+r"(d[2]), "+r"(d[3]), "+r"(d[4]), "+r"(d[5]), "+r"(d[6]), "+r"(d[7]),
      "+r"(d[8]), "+r"(d[9]), "+r"(d[10]), "+r"(d[11]), "+r"(d[12]), "+r"(d[13]), "+r"(d[14]), "+r"(d[15]),
      "+r"(d[16]), "+r"(d[17]), "+r"(d[18]), "+r"(d[19]), "+r"(d[20]), "+r"(d[21]), "+r"(d[22]), "+r"(d[23]),
      "+r"(d[24]), "+r"(d[25]), "+r"(d[26]), "+r"(d[27]), "+r"(d[28]), "+r"(d[29]), "+r"(d[30]), "+r"(d[31]),
      "+r"(d[32]), "+r"(d[33]), "+r"(d[34]), "+r"(d[35]), "+r"(d[36]), "+r"(d[37]), "+r"(d[38]), "+r"(d[39]),
      "+r"(d[40]), "+r"(d[41]), "+r"(d[42]), "+r"(d[43]), "+r"(d[44]), "+r"(d[45]), "+r"(d[46]), "+r"(d[47])
    : "r"(a0), "r"(a1), "r"(a2), "r"(a3), "l"(descB));
}

template <int SCALE_D>
__device__ __forceinline__ void wgmma_n56(uint32_t (&d)[14], uint32_t a0, uint32_t a1, uint32_t a2, uint32_t a3, uint64_t descB) {
  if (SCALE_D == 0)
  asm volatile("wgmma.mma_async.sync.aligned.m64n56k16.f16.f16.f16 "
    "{%0, %1, %2, %3, %4, %5, %6, %7, %8, %9, %10, %11, %12, %13}, "
    "{%14, %15, %16, %17}, %18, 0, 1, 1, 0;\n"
    : "=r"(d[0]), "=r"(d[1]), "=r"(d[2]), "=r"(d[3]), "=r"(d[4]), "=r"(d[5]), "=r"(d[6]), "=r"(d[7]),
      "=r"(d[8]), "=r"(d[9]), "=r"(d[10]), "=r"(d[11]), "=r"(d[12]), "=r"(d[13])
    : "r"(a0), "r"(a1), "r"(a2), "r"(a3), "l"(descB));
  else
  asm volatile("wgmma.mma_async.sync.aligned.m64n56k16.f16.f16.f16 "
    "{%0, %1, %2, %3, %4, %5, %6, %7, %8, %9, %10, %11, %12, %13}, "
    "{%14, %15, %16, %17}, %18, 1, 1, 1, 0;\n"
    : "+r"(d[0]), "+r"(d[1]), "+r"(d[2]), "+r"(d[3]), "+r"(d[4]), "+r"(d[5]), "+r"(d[6]), "+r"(d[7]),
      "+r"(d[8]), "+r"(d[9]), "+r"(d[10]), "+r"(d[11]), "+r"(d[12]), "+r"(d[13])
    : "r"(a0), "r"(a1), "r"(a2), "r"(a3), "l"(descB));
}

template <int SCALE_D>
__device__ __forceinline__ void wgmma_n56t(uint32_t (&d)[14], uint32_t a0, uint32_t a1, uint32_t a2, uint32_t a3, uint64_t descB) {
  if (SCALE_D == 0)
  asm volatile("wgmma.mma_async.sync.aligned.m64n56k16.f16.f16.f16 "
    "{%0, %1, %2, %3, %4, %5, %6, %7, %8, %9, %10, %11, %12, %13}, "
    "{%14, %15, %16, %17}, %18, 0, 1, 1, 1;\n"
    : "=r"(d[0]), "=r"(d[1]), "=r"(d[2]), "=r"(d[3]), "=r"(d[4]), "=r"(d[5]), "=r"(d[6]), "=r"(d[7]),
      "=r"(d[8]), "=r"(d[9]), "=r"(d[10]), "=r"(d[11]), "=r"(d[12]), "=r"(d[13])
    : "r"(a0), "r"(a1), "r"(a2), "r"(a3), "l"(descB));
  else
  asm volatile("wgmma.mma_async.sync.aligned.m64n56k16.f16.f16.f16 "
    "{%0, %1, %2, %3, %4, %5, %6, %7, %8, %9, %10, %11, %12, %13}, "
    "{%14, %15, %16, %17}, %18, 1, 1, 1, 1;\n"
    : "+r"(d[0]), "+r"(d[1]), "+r"(d[2]), "+r"(d[3]), "+r"(d[4]), "+r"(d[5]), "+r"(d[6]), "+r"(d[7]),
      "+r"(d[8]), "+r"(d[9]), "+r"(d[10]), "+r"(d[11]), "+r"(d[12]), "+r"(d[13])
    : "r"(a0), "r"(a1), "r"(a2), "r"(a3), "l"(descB));
}

__global__ void __launch_bounds__(384) prepack_kernel(const __nv_bfloat16* __restrict__ wqkv, const __nv_bfloat16* __restrict__ wo) {
  asm volatile("griddepcontrol.launch_dependents;");
  __shared__ float red2[2][2][6][8];
  float (*red)[6][8] = red2[threadIdx.y];
  __half* dst = reinterpret_cast<__half*>(g_wpack);
  const int c = threadIdx.x, nb = blockIdx.x * 2 + threadIdx.y;
  auto colsum = [&](int k, const float (&v)[8], float (&o)[8]) {
#pragma unroll
    for (int i = 0; i < 8; i++) {
      float t = v[i];
#pragma unroll
      for (int d = 16; d; d >>= 1) t += __shfl_xor_sync(~0u, t, d);
      if ((c & 31) == 0) red[k][c >> 5][i] = t;
    }
    __syncthreads();
#pragma unroll
    for (int i = 0; i < 8; i++) o[i] = red[k][0][i] + red[k][1][i] + red[k][2][i] + red[k][3][i] + red[k][4][i] + red[k][5][i];
  };
  float v[8], t[8];
  int base;
  if (nb < 72) {
    const int h = nb / 18, j = nb % 18, part = j / 6;
    const int col = (part == 0 ? 192 : part == 1 ? 0 : 384) + h * 48 + (j % 6) * 8;
    uint4 raw = *reinterpret_cast<const uint4*>(wqkv + c * 576 + col);
    uint32_t u[4] = {raw.x, raw.y, raw.z, raw.w};
#pragma unroll
    for (int i = 0; i < 4; i++) { v[2 * i] = lo2f(u[i]); v[2 * i + 1] = hi2f(u[i]); }
    colsum(0, v, t);
#pragma unroll
    for (int n = 0; n < 8; n++)
      v[n] = __bfloat162float(__float2bfloat16((v[n] - t[n] * (1.0f / 192.0f)) * (part == 1 ? 0.14433756729740643f * 1.4426950408889634f : 1.0f)));
    const int cc = c >> 5, q = (c >> 3) & 3, s1 = (c >> 2) & 1, hh = (c >> 1) & 1, e = c & 1;
    base = qkv_pos(h, 2 * cc + s1) / 2 + j * 128 + hh * 64 + 2 * q + e;
  } else {
    const int jb = nb - 72;
#pragma unroll
    for (int n = 0; n < 8; n++) v[n] = __bfloat162float(wo[c * 192 + 32 * (jb >> 2) + 8 * (n >> 1) + 2 * (jb & 3) + (n & 1)]);
    base = wo_pos(c >> 4) / 2 + jb * 128 + ((c >> 3) & 1) * 64 + (c & 7);
  }
#pragma unroll
  for (int n = 0; n < 8; n++) { dst[base + n * 8] = __float2half_rn(v[n]); v[n] *= v[n]; }
  colsum(1, v, t);
  if (c == 0)
    g_wnorm[nb] = make_float2(fmaxf(fmaxf(fmaxf(t[0], t[1]), fmaxf(t[2], t[3])), fmaxf(fmaxf(t[4], t[5]), fmaxf(t[6], t[7]))),
                              t[0] + t[1] + t[2] + t[3] + t[4] + t[5] + t[6] + t[7]);
}

__device__ __forceinline__ int window_of(int round, int nfull, int cta, int ncta, int wg) {
  if (round < nfull) return round * 2 * ncta + 2 * cta + wg;
  const int rem = NWIN - nfull * 2 * ncta;
  const int i = cta + wg * ncta;
  return i < rem ? nfull * 2 * ncta + i : -1;
}

template <int S0 = 0, int S1 = 12>
__device__ __forceinline__ void mma_qkv(uint32_t (&acc)[36], const uint32_t (&A)[48], const uint64_t* d) {
#pragma unroll
  for (int s = S0; s < S1; s++) {
    if (s == 0) wgmma_n144<0>(acc, A[4 * s], A[4 * s + 1], A[4 * s + 2], A[4 * s + 3], d[s]);
    else        wgmma_n144<1>(acc, A[4 * s], A[4 * s + 1], A[4 * s + 2], A[4 * s + 3], d[s]);
  }
  wg_commit();
}
__device__ __forceinline__ void mma_proj(uint32_t (&acc)[48], const uint32_t (&A)[12], const uint64_t* d) {
#pragma unroll
  for (int s = 0; s < 3; s++) wgmma_n192<1>(acc, A[4 * s], A[4 * s + 1], A[4 * s + 2], A[4 * s + 3], d[s]);
}
__device__ __forceinline__ void mma_s(uint32_t (&S)[14], const uint32_t (&Q)[12], const uint64_t* d) {
  wgmma_n56<0>(S, Q[0], Q[1], Q[2], Q[3], d[0]);
  wgmma_n56<1>(S, Q[4], Q[5], Q[6], Q[7], d[1]);
  wgmma_n56<1>(S, Q[8], Q[9], Q[10], Q[11], d[2]);
}
__device__ __forceinline__ void mma_pv(uint32_t (&O)[14], const uint32_t (&P)[NP], const uint64_t* d) {
  wgmma_n56t<0>(O, P[0], P[1], P[2], P[3], d[0]);
  wgmma_n56t<1>(O, P[4], P[5], P[6], P[7], d[1]);
  wgmma_n56t<1>(O, P[8], P[9], P[10], P[11], d[2]);
  if (K48TC) wgmma_n56t<1>(O, P[NP - 4], P[NP - 3], P[NP - 2], P[NP - 1], d[3]);
}

#define PIN() asm volatile("pmevent 0;" ::: "memory")
template <int A, int B> __device__ __forceinline__ void hold(uint32_t* v) {
#pragma unroll
  for (int i = A; i < B; i++) asm volatile("" : "+r"(v[i]));
}
__device__ __forceinline__ void stsm12(const uint32_t* v, uint32_t addr) {
#pragma unroll
  for (int j = 0; j < 3; j++) stsm4(addr + 2 * j * KV_PITCH, v[4 * j], v[4 * j + 1], v[4 * j + 2], v[4 * j + 3]);
}
__device__ __forceinline__ void load_v48(uint32_t (&v)[6], uint32_t addr) {
  if (K48TC) return;
  asm volatile("ldmatrix.sync.aligned.m8n8.x4.shared.b16 {%0,%1,%2,%3}, [%4];" : "=r"(v[0]), "=r"(v[1]), "=r"(v[2]), "=r"(v[3]) : "r"(addr) : "memory");
  asm volatile("ldmatrix.sync.aligned.m8n8.x2.shared.b16 {%0,%1}, [%2];" : "=r"(v[4]), "=r"(v[5]) : "r"(addr + 4 * KV_PITCH) : "memory");
}
__device__ __forceinline__ void finish_o(const uint32_t (&O)[14], const uint32_t (&v)[6], uint32_t p48, uint32_t vmask, uint32_t (&Of)[12]) {
  const float2 l = K48TC ? make_float2(__low2float(u2h(O[12])), __low2float(u2h(O[13])))
                         : __half22float2(__hadd2_rn(u2h(__byte_perm(O[12], O[13], 0x5410)), u2h(p48)));
  float i0, i1;
  asm("rcp.approx.ftz.f32 %0, %1;" : "=f"(i0) : "f"(l.x));
  asm("rcp.approx.ftz.f32 %0, %1;" : "=f"(i1) : "f"(l.y));
  const uint32_t inv = packh(i0, i1) & vmask;
#pragma unroll
  for (int i = 0; i < 12; i++) {
    const uint32_t t = K48TC ? O[i] : h2u(__hfma2(u2h(v[i >> 1]), (i & 1) ? hcast<1>(p48) : hcast<0>(p48), u2h(O[i])));
    Of[i] = (i & 1) ? fmul_b<1>(t, inv) : fmul_b<0>(t, inv);
  }
  hold<0, 12>(Of);
}
#define PSTAT 12
template <int A, int B>
__device__ __forceinline__ void ln_sums(const uint32_t (&X)[48], float (&s1)[2], float (&s2)[2]) {
  if (PSTAT) {
    static_assert(PSTAT == 0 || (A % (2 * PSTAT + !PSTAT) == 0 && B % (2 * PSTAT + !PSTAT) == 0), "whole groups");
#pragma unroll
    for (int g = A; g < B; g += 2 * PSTAT + !PSTAT)
#pragma unroll
      for (int a = 0; a < 2; a++) {
        __half2 p1 = u2h(X[g + a]), p2 = __hmul2_rn(p1, p1);
#pragma unroll
        for (int i = 1; i < PSTAT; i++) { const __half2 v = u2h(X[g + a + 2 * i]); p1 = __hadd2_rn(p1, v); p2 = __hfma2(v, v, p2); }
        const float2 f1 = __half22float2(p1), f2 = __half22float2(p2);
        s1[a] = g == 0 ? f1.x + f1.y : s1[a] + (f1.x + f1.y);
        s2[a] = g == 0 ? f2.x + f2.y : s2[a] + (f2.x + f2.y);
      }
  } else {
#pragma unroll
    for (int i = A; i < B; i++) {
      const float2 f = __half22float2(u2h(X[i]));
      s1[i & 1] = i < 2 ? f.x + f.y : s1[i & 1] + (f.x + f.y);
      s2[i & 1] = fmaf(f.x, f.x, i < 2 ? f.y * f.y : fmaf(f.y, f.y, s2[i & 1]));
    }
  }
  asm volatile("" : "+f"(s1[0]), "+f"(s1[1]), "+f"(s2[0]), "+f"(s2[1]));
}
__device__ __forceinline__ uint32_t ln_rstd(const float (&s1)[2], const float (&s2)[2], float lo, float hi, bool& ok) {
  float r[2];
  ok = true;
#pragma unroll
  for (int a = 0; a < 2; a++) {
    float m = s1[a], v = s2[a];
    m += __shfl_xor_sync(~0u, m, 1); v += __shfl_xor_sync(~0u, v, 1);
    m += __shfl_xor_sync(~0u, m, 2); v += __shfl_xor_sync(~0u, v, 2);
    ok = ok && v <= hi && (v >= lo || v == 0.f);
    m *= 1.0f / 192.0f;
    m *= m;
    v = fmaxf(fmaf(v, 1.0f / 192.0f, -m), 0.f) + 1e-5f;
    ok = ok && m <= (PSTAT ? 16.f : 64.f) * v;
    asm("rsqrt.approx.ftz.f32 %0, %1;" : "=f"(r[a]) : "f"(v));
  }
  uint32_t rk = packh(r[0], r[1]);
  hold<0, 1>(&rk);
  return rk;
}
__device__ __forceinline__ void scale12(uint32_t (&D)[12], const uint32_t* a, uint32_t r) {
#pragma unroll
  for (int i = 0; i < 12; i++) D[i] = (i & 1) ? fmul_b<1>(a[i], r) : fmul_b<0>(a[i], r);
  hold<0, 12>(D);
}
template <int CC>
__device__ __forceinline__ void store_out(const uint32_t (&Y)[48], uint8_t* o0, uint8_t* o1, uint32_t vmask) {
  uint32_t T[8];
#pragma unroll
  for (int i = 0; i < 8; i++) {
    const float2 f = __half22float2(u2h(Y[8 * CC + i]));
    T[i] = pack2(f.x, f.y);
  }
  asm volatile("{\n.reg .pred p;\nsetp.ne.u32 p, %5, 0;\n@p st.global" STHINT ".v4.u32 [%0], {%1,%2,%3,%4};\n}\n"
               :: "l"(o0 + CC * 64), "r"(T[0]), "r"(T[2]), "r"(T[4]), "r"(T[6]), "r"(vmask) : "memory");
  asm volatile("{\n.reg .pred p;\nsetp.lt.s32 p, %5, 0;\n@p st.global" STHINT ".v4.u32 [%0], {%1,%2,%3,%4};\n}\n"
               :: "l"(o1 + CC * 64), "r"(T[1]), "r"(T[3]), "r"(T[5]), "r"(T[7]), "r"(vmask) : "memory");
}
__device__ __forceinline__ void proxy_fence() { asm volatile("fence.proxy.async.shared::cta;" ::: "memory"); }
__device__ __forceinline__ uint32_t fadd2(uint32_t a, uint32_t b) { return h2u(__hadd2_rn(u2h(a), u2h(b))); }
__device__ __forceinline__ void row_max(const uint32_t (&S)[14], uint32_t& k48, uint32_t& mx, uint32_t ninf) {
  k48 = K48TC ? __byte_perm(S[12], S[13], 0x5410) | ninf : __shfl_sync(~0u, __byte_perm(S[12], S[13], 0x5410), 0, 4);
  const uint32_t m0 = fmax2(fmax2(fmax2(S[0], S[2]), S[4]), fmax2(fmax2(S[6], S[8]), S[10]));
  const uint32_t m1 = fmax2(fmax2(fmax2(S[1], S[3]), S[5]), fmax2(fmax2(S[7], S[9]), S[11]));
  mx = fmax2(__byte_perm(m0, m1, 0x5410), __byte_perm(m0, m1, 0x7632));
  if (K48TC) mx = fmax2(mx, k48);
  mx = fmax2(mx, __shfl_xor_sync(~0u, mx, 1));
  mx = fmax2(mx, __shfl_xor_sync(~0u, mx, 2));
  if (!K48TC) mx = fmax2(mx, k48);
  hold<0, 1>(&mx);
}
__device__ __forceinline__ void row_exp(const uint32_t (&S)[14], uint32_t k48, uint32_t mx, uint32_t (&P)[NP], uint32_t& p48) {
#pragma unroll
  for (int j = 0; j < 12; j++) P[j] = fex2((j & 1) ? fsub_b<1>(S[j], mx) : fsub_b<0>(S[j], mx));
  if (K48TC) {
    uint16_t el, eh;
    asm("{\n.reg .b16 l, h;\nmov.b32 {l, h}, %2;\nex2.approx.f16 %0, l;\nex2.approx.f16 %1, h;\n}\n" : "=h"(el), "=h"(eh) : "r"(h2u(__hsub2_rn(u2h(k48), u2h(mx)))));
    P[NP - 4] = el; P[NP - 3] = eh; P[NP - 2] = 0; P[NP - 1] = 0;
  } else {
    p48 = fex2(h2u(__hsub2_rn(u2h(k48), u2h(mx))));
    hold<0, 1>(&p48);
  }
  hold<0, NP>(P);
}
template <int S0, int S1>
__device__ __forceinline__ void load_x(uint32_t (&X)[48], uint32_t t0) {
#pragma unroll
  for (int s = S0; s < S1; s++)
    asm volatile("ld.shared.v4.u32 {%0,%1,%2,%3}, [%4];" : "=r"(X[4 * s]), "=r"(X[4 * s + 1]), "=r"(X[4 * s + 2]), "=r"(X[4 * s + 3])
                 : "r"(((s & 1) ? (t0 ^ 16) : t0) + (s >> 1) * 128) : "memory");
}

#define WDIV 1
template <int P, int CNT, int DIV = WDIV> __device__ __forceinline__ void load_slices(uint32_t sb, const Descs& ds) {
  constexpr int st = stage_of(P);
  constexpr bool first = P == 0 || stage_of(P - 1) != st;
  if (first)
    asm volatile("{\n.reg .pred p;\nelect.sync _|p, 0xffffffff;\n@p mbarrier.arrive.expect_tx.shared::cta.b64 _, [%0], %1;\n}\n"
                 :: "r"(sb + BAR_WFULL + 8 * st), "n"((st < 4 ? 3 : st == 4 ? 2 : 1) * SLICE / DIV) : "memory");
  asm volatile("{\n.reg .pred p;\nelect.sync _|p, 0xffffffff;\n"
               "@p cp.async.bulk.shared::cluster.global.mbarrier::complete_tx::bytes [%0], [%1], %2, [%3];\n}\n"
               :: "r"(sb + OFF_W + (P & 7) * SLICE), "l"(ds.src[P]), "n"(CNT * SLICE / DIV), "r"(sb + BAR_WFULL + 8 * st) : "memory");
}
__device__ __forceinline__ void warp_arrive(uint32_t bar) {
  asm volatile("{\n.reg .pred p;\nelect.sync _|p, 0xffffffff;\n@p mbarrier.arrive.shared::cta.b64 _, [%0];\n}\n" :: "r"(bar) : "memory");
}

__device__ __forceinline__ float2 fp16_limits(int lane) {
  float mx[4] = {0.f, 0.f, 0.f, 0.f}, sm[4] = {0.f, 0.f, 0.f, 0.f};
#pragma unroll
  for (int i = 0; i < 3; i++) {
    const int nb = lane + 32 * i, part = nb < 72 ? (nb % 18) / 6 : 3;
    const float2 w = g_wnorm[nb];
#pragma unroll
    for (int k = 0; k < 4; k++) if (part == k) { mx[k] = fmaxf(mx[k], w.x); sm[k] += w.y; }
  }
#pragma unroll
  for (int k = 0; k < 4; k++)
#pragma unroll
    for (int d = 16; d; d >>= 1) { mx[k] = fmaxf(mx[k], __shfl_xor_sync(~0u, mx[k], d)); sm[k] += __shfl_xor_sync(~0u, sm[k], d); }
  const float big = fmaxf(fmaxf(mx[0], mx[1]), mx[2]);
  float small = 1.f;
  bool good = sm[0] + sm[1] + sm[2] + sm[3] < 1e30f;
#pragma unroll
  for (int k = 0; k < 4; k++) { good = good && (mx[k] == 0.f || mx[k] >= 2.5e-4f); if (k < 3 && mx[k] > 0.f) small = fminf(small, mx[k]); }
  good = good && 250.f * 48.f * sqrtf(mx[0] * mx[1]) <= 5e4f;
  good = good && 16.f * 49.f * sqrtf(mx[2]) <= 5e4f && big <= 1e6f;
  good = good && 16.f * sqrtf(sm[2] * mx[3]) <= 2e4f;
  return make_float2(192.f * 2.4e-7f / small, good ? fminf(2.5e8f, 9e8f / fmaxf(big, 1e-30f)) : -1.f);
}

__device__ __forceinline__ void slow_window(float* sm, int w, int t, const __nv_bfloat16* __restrict__ x, const __nv_bfloat16* __restrict__ dw,
                                            const __nv_bfloat16* __restrict__ wqkv, const __nv_bfloat16* __restrict__ wo, __nv_bfloat16* __restrict__ out) {
  float* x0 = sm; float* h = x0 + 49 * CH; float* qkv = h + 49 * CH; float* S = qkv + 49 * 576;
  const int wy = w / NWX, wx = w % NWX;
  auto sync = [] { asm volatile("bar.sync 6, 128;" ::: "memory"); };
#pragma unroll 1
  for (int i = t; i < 49 * CH; i += 128) {
    const int k = i / CH, c = i % CH, y = wy * 7 + k / 7, xx = wx * 7 + k % 7;
    float pe = 0.f;
#pragma unroll 1
    for (int a = 0; a < 9; a++) {
      const int yy = y + a / 3 - 1, xc = xx + a % 3 - 1;
      if (yy >= 0 && yy < IMG && xc >= 0 && xc < IMG) pe = fmaf(__bfloat162float(x[((size_t)yy * IMG + xc) * CH + c]), __bfloat162float(dw[a * CH + c]), pe);
    }
    x0[i] = __bfloat162float(__float2bfloat16(__bfloat162float(x[((size_t)y * IMG + xx) * CH + c]) + pe));
  }
  sync();
  if (t < 49) {
    float m = 0.f, v = 0.f;
#pragma unroll 1
    for (int c = 0; c < CH; c++) m += x0[t * CH + c];
    m *= 1.0f / CH;
#pragma unroll 1
    for (int c = 0; c < CH; c++) { const float d = x0[t * CH + c] - m; v = fmaf(d, d, v); }
    const float rs = 1.0f / sqrtf(v * (1.0f / CH) + 1e-5f);
#pragma unroll 1
    for (int c = 0; c < CH; c++) h[t * CH + c] = (x0[t * CH + c] - m) * rs;
  }
  sync();
#pragma unroll 1
  for (int i = t; i < 7 * 576; i += 128) {
    const int n = i % 576, k0 = i / 576 * 7;
    float a[7] = {0.f, 0.f, 0.f, 0.f, 0.f, 0.f, 0.f};
#pragma unroll 1
    for (int c = 0; c < CH; c++) {
      const float wv = __bfloat162float(wqkv[c * 576 + n]);
#pragma unroll
      for (int k = 0; k < 7; k++) a[k] = fmaf(h[(k0 + k) * CH + c], wv, a[k]);
    }
#pragma unroll
    for (int k = 0; k < 7; k++) qkv[(k0 + k) * 576 + n] = a[k];
  }
  sync();
#pragma unroll 1
  for (int hd = 0; hd < 4; hd++) {
#pragma unroll 1
    for (int i = t; i < 49 * 49; i += 128) {
      const int a = i / 49, b = i % 49;
      float v = 0.f;
#pragma unroll 1
      for (int d = 0; d < 48; d++) v = fmaf(qkv[a * 576 + hd * 48 + d], qkv[b * 576 + 192 + hd * 48 + d], v);
      S[i] = v * 0.14433756729740643f;
    }
    sync();
    if (t < 49) {
      float m = S[t * 49], l = 0.f;
#pragma unroll 1
      for (int b = 1; b < 49; b++) m = fmaxf(m, S[t * 49 + b]);
#pragma unroll 1
      for (int b = 0; b < 49; b++) { const float e = expf(S[t * 49 + b] - m); S[t * 49 + b] = e; l += e; }
#pragma unroll 1
      for (int b = 0; b < 49; b++) S[t * 49 + b] /= l;
    }
    sync();
#pragma unroll 1
    for (int i = t; i < 49 * 48; i += 128) {
      const int a = i / 48, d = i % 48;
      float v = 0.f;
#pragma unroll 1
      for (int b = 0; b < 49; b++) v = fmaf(S[a * 49 + b], qkv[b * 576 + 384 + hd * 48 + d], v);
      h[a * CH + hd * 48 + d] = v;
    }
    sync();
  }
#pragma unroll 1
  for (int i = t; i < 7 * CH; i += 128) {
    const int n = i % CH, k0 = i / CH * 7;
    float a[7] = {0.f, 0.f, 0.f, 0.f, 0.f, 0.f, 0.f};
#pragma unroll 1
    for (int c = 0; c < CH; c++) {
      const float wv = __bfloat162float(wo[c * CH + n]);
#pragma unroll
      for (int k = 0; k < 7; k++) a[k] = fmaf(h[(k0 + k) * CH + c], wv, a[k]);
    }
#pragma unroll
    for (int k = 0; k < 7; k++)
      out[((size_t)(wy * 7 + k0 / 7) * IMG + wx * 7 + k) * CH + n] = __float2bfloat16(x0[(k0 + k) * CH + n] + a[k]);
  }
  sync();
}

__global__ void __launch_bounds__(384, 1)
fused_kernel(const __grid_constant__ CUtensorMap tmx, const __grid_constant__ CUtensorMap tmp, const __grid_constant__ Descs ds, const __nv_bfloat16* __restrict__ dw, __nv_bfloat16* __restrict__ out, const int never,
             const __nv_bfloat16* __restrict__ x, const __nv_bfloat16* __restrict__ wqkv, const __nv_bfloat16* __restrict__ wo) {
  extern __shared__ __align__(1024) uint8_t smem[];
  const uint32_t sb = (uint32_t)__cvta_generic_to_shared(smem);
  const int tid = threadIdx.x, lane = tid & 31;
  const int warp = __shfl_sync(0xffffffffu, tid >> 5, 0);
  const int cta = blockIdx.x, ncta = gridDim.x;
  const int nfull = NWIN / (2 * ncta);
  const int nrounds = nfull + ((NWIN - nfull * 2 * ncta) > cta ? 1 : 0);

  if (warp == 0) GTS(0);
  if (warp == 10 && lane == 0) asm volatile("prefetch.tensormap [%0];" :: "l"(reinterpret_cast<uint64_t>(&tmx)) : "memory");
  if (tid == 0) {
    mbar_init(sb + BAR_FIRST, 1);
    asm volatile("fence.mbarrier_init.release.cluster;" ::: "memory");
    asm volatile("mbarrier.arrive.expect_tx.shared::cta.b64 _, [%0], %1;" :: "r"(sb + BAR_FIRST), "n"(2 * HALO_BYTES) : "memory");
#pragma unroll
    for (int k = 0; k < 2; k++) {
      const int w = max(window_of(0, nfull, cta, ncta, k), 0), a = w / NWX;
      asm volatile("cp.async.bulk.tensor.3d.shared::cluster.global.mbarrier::complete_tx::bytes [%0], [%1, {0, %3, %4}], [%2];"
                   :: "r"(sb + OFF_HALO + k * HALO_BYTES), "l"(reinterpret_cast<uint64_t>(&tmp)), "r"(sb + BAR_FIRST),
                      "r"((w - a * NWX) * 7 - 1), "r"(a * 7 - 1) : "memory");
    }
    if ((sb & 0x3FFFF) != SMEM_BASE || nrounds > 128) __trap();
    for (int i = 0; i < 7; i++) { mbar_init(sb + BAR_WFULL + 8 * i, 1); mbar_init(sb + BAR_WEMPTY + 8 * i, 8); }
    for (int i = 0; i < 9; i++) mbar_init(sb + BAR_XFULL + 8 * i, 1);
    mbar_init(sb + BAR_TFULL, 3);
    mbar_init(sb + BAR_TEMPTY, 8);
    asm volatile("fence.mbarrier_init.release.cluster;" ::: "memory");
  }
  if (tid >= 128 && tid < 320) {
    *reinterpret_cast<uint32_t*>(smem + OFF_ZERO + (tid - 128) * 4) = 0;
    if (tid < 136) *reinterpret_cast<uint32_t*>(smem + OFF_REDO + (tid - 128) * 4) = 0;
  }
  if (tid < 128) {
    *reinterpret_cast<uint4*>(smem + OFF_KV + (tid / 64) * KV_BYTES + 6 * KV_PITCH + (tid % 64) * 16) = make_uint4(0x3c003c00u, 0x3c003c00u, 0x3c003c00u, 0x3c003c00u);
    proxy_fence();
  }
  __syncthreads();

  if (warp < 11) {
#pragma unroll 1
    for (int u = 0; u < (warp < 10 ? 2 : 1); u++) {
      const int cb = warp < 9 ? warp % 3 : 2 * (warp - 9) + u, y = warp < 9 ? 2 * (warp / 3) + u : 6;
      const int ch0 = cb * 64 + (lane & 15) * 4;
      uint32_t wt[9][2], px[3][9][2];
#pragma unroll
      for (int t = 0; t < 9; t++) {
        const uint2 v = *reinterpret_cast<const uint2*>(dw + t * CH + ch0);
        wt[t][0] = v.x; wt[t][1] = v.y;
      }
      mbar_wait(sb + BAR_FIRST, 0);
      const uint32_t ld = sb + OFF_HALO + (lane >> 4) * HALO_BYTES + y * 3456 + ch0 * 2;
#pragma unroll
      for (int p = 0; p < 27; p++)
        asm volatile("ld.shared.v2.u32 {%0,%1}, [%2];" : "=r"(px[p / 9][p % 9][0]), "=r"(px[p / 9][p % 9][1]) : "r"(ld + p * 384));
      const uint32_t st0 = sb + OFF_TILE + (lane >> 4) * TILE_BYTES + ch0 * 4;
      const uint32_t sa = (st0 ^ ((y & 1) << 4)) + y * 2304;
      uint32_t o[2][2];
#pragma unroll
      for (int j = 0; j < 7; j++) {
#pragma unroll
        for (int e = 0; e < 2; e++) {
          uint32_t a = hmul(px[0][j][e], wt[0][e]);
#pragma unroll
          for (int t = 1; t < 9; t++) a = hfma(px[t / 3][j + t % 3][e], wt[t][e], a);
          a = hadd(px[1][j + 1][e], a);
          o[j & 1][e] = packh(lo2f(a), hi2f(a));
        }
        if (j & 1)
          asm volatile("st.shared.v4.u32 [%0], {%1,%2,%3,%4};" :: "r"((j == 3 ? sa ^ 16 : sa) + (j >> 1) * 768),
                       "r"(o[0][0]), "r"(o[1][0]), "r"(o[0][1]), "r"(o[1][1]) : "memory");
      }
      const uint32_t sb6 = (st0 ^ ((~y & 2) << 3)) + (21 + (y >> 1)) * 768 + (y & 1) * 4;
      asm volatile("st.shared.u32 [%0], %1;\nst.shared.u32 [%0 + 8], %2;" :: "r"(sb6), "r"(o[0][0]), "r"(o[0][1]) : "memory");
      if (y == 6) asm volatile("st.shared.u32 [%0 + 4], %1;\nst.shared.u32 [%0 + 12], %1;" :: "r"(sb6), "r"(0) : "memory");
    }
    asm volatile("bar.arrive 8, 384;\nbar.sync 7, 352;" ::: "memory");
  }

  if (warp >= 8) {
    asm volatile("setmaxnreg.dec.sync.aligned.u32 " PREGS ";");
    if (warp == 11) {
      asm volatile("griddepcontrol.wait;" ::: "memory");
      load_slices<1, 3, 1>(sb, ds);
      *reinterpret_cast<float2*>(smem + OFF_LIM) = fp16_limits(lane);
      load_slices<0, 1, 1>(sb, ds);
      asm volatile("bar.sync 8, 384;" ::: "memory");
      load_slices<5, 3, 1>(sb, ds); load_slices<4, 1, 1>(sb, ds);
      for (int r = 0; r < nrounds; r++) {
        const uint32_t par = r & 1;
        const bool next_round = r + 1 < nrounds;
        mbar_wait(sb + BAR_WEMPTY + 40, par); load_slices<8, 1>(sb, ds);
        mbar_wait(sb + BAR_WEMPTY, par);      load_slices<9, 2>(sb, ds); load_slices<11, 1>(sb, ds);
        mbar_wait(sb + BAR_WEMPTY + 48, par); load_slices<12, 1>(sb, ds);
        mbar_wait(sb + BAR_WEMPTY + 8, par);  load_slices<13, 1>(sb, ds); load_slices<14, 2>(sb, ds);
        mbar_wait(sb + BAR_WEMPTY + 16, par); load_slices<0, 1>(sb, ds); if (next_round) load_slices<1, 2>(sb, ds);
        mbar_wait(sb + BAR_WEMPTY + 24, par);
        if (next_round) load_slices<3, 1>(sb, ds);
        load_slices<4, 1>(sb, ds);
        if (next_round) {
          load_slices<5, 1>(sb, ds);
          mbar_wait(sb + BAR_WEMPTY + 32, par); load_slices<6, 2>(sb, ds);
        }
      }
    } else {
      const int cw = warp - 8;
      const int win = lane >> 4;
      const int ch0 = cw * 64 + (lane & 15) * 4;
      uint32_t wt[9][2];
#pragma unroll
      for (int t = 0; t < 9; t++) {
        uint2 v = *reinterpret_cast<const uint2*>(dw + t * CH + ch0);
        wt[t][0] = v.x; wt[t][1] = v.y;
      }
      const uint32_t xs = sb + OFF_X + cw * 3 * XSLOT;
      const uint32_t xld = xs + (lane >> 4) * 1152 + (lane & 15) * 8;
      const uint32_t xbar = sb + BAR_XFULL + cw * 24;
      const uint32_t st0 = sb + OFF_TILE + win * TILE_BYTES + ch0 * 4;
      const uint64_t tm = reinterpret_cast<uint64_t>(&tmx);
      int cx0, cy0, cx1, cy1;
      auto coords = [&](int r) {
        const int w0 = window_of(r, nfull, cta, ncta, 0);
        int w1 = window_of(r, nfull, cta, ncta, 1);
        if (w1 < 0) w1 = w0;
        const int a = w0 / NWX, b = w1 / NWX;
        cx0 = (w0 - a * NWX) * 7 - 1; cy0 = a * 7 - 1;
        cx1 = (w1 - b * NWX) * 7 - 1; cy1 = b * 7 - 1;
      };
      auto issue = [&](int slot, int dy) {
        asm volatile("{\n.reg .pred p;\nelect.sync _|p, 0xffffffff;\n"
                     "@p mbarrier.arrive.expect_tx.shared::cta.b64 _, [%2], %8;\n"
                     "@p cp.async.bulk.tensor.3d.shared::cluster.global.mbarrier::complete_tx::bytes [%0], [%1, {%3, %4, %5}], [%2];\n"
                     "@p cp.async.bulk.tensor.3d.shared::cluster.global.mbarrier::complete_tx::bytes [%0 + 1152], [%1, {%3, %6, %7}], [%2];\n}\n"
                     :: "r"(xs + slot * XSLOT), "l"(tm), "r"(xbar + slot * 8), "r"(cw * 64), "r"(cx0), "r"(cy0 + dy), "r"(cx1), "r"(cy1 + dy), "n"(XSLOT) : "memory");
      };
      uint32_t accA[7][2], accB[7][2], ctr[7][2], held[2];
      auto row = [&](auto fin, auto mid, auto top, int slot, int y) {
        const uint32_t ld = xld + slot * XSLOT;
        const uint32_t sa = (st0 ^ ((y & 1) << 4)) + y * 2304;
        uint32_t cur[9][2], o[2][2];
#pragma unroll
        for (int p = 0; p < LA; p++)
          asm volatile("ld.shared.v2.u32 {%0,%1}, [%2];" : "=r"(cur[p][0]), "=r"(cur[p][1]) : "r"(ld + p * 128));
#pragma unroll
        for (int j = 0; j < 7; j++) {
          if (j >= 1 && j + LA - 1 < 9)
            asm volatile("ld.shared.v2.u32 {%0,%1}, [%2];" : "=r"(cur[j + LA - 1][0]), "=r"(cur[j + LA - 1][1]) : "r"(ld + (j + LA - 1) * 128));
          if (fin.v) {
#pragma unroll
            for (int e = 0; e < 2; e++) {
              uint32_t a = hfma(cur[j][e], wt[6][e], accA[j][e]);
              a = hfma(cur[j + 1][e], wt[7][e], a);
              a = hfma(cur[j + 2][e], wt[8][e], a);
              if (!EARLYX) a = hadd(ctr[j][e], a);
              o[j & 1][e] = packh(lo2f(a), hi2f(a));
            }
            if (j & 1)
              asm volatile("st.shared.v4.u32 [%0], {%1,%2,%3,%4};" :: "r"((j == 3 ? sa ^ 16 : sa) + (j >> 1) * 768),
                           "r"(o[0][0]), "r"(o[1][0]), "r"(o[0][1]), "r"(o[1][1]) : "memory");
            if (j == 6) {
              const uint32_t sb6 = (st0 ^ ((~y & 2) << 3)) + (21 + (y >> 1)) * 768;
              if (fin.v == 2)
                asm volatile("st.shared.v4.u32 [%0], {%1,%2,%3,%2};" :: "r"(sb6), "r"(o[0][0]), "r"(0), "r"(o[0][1]) : "memory");
              else
                asm volatile("{\n.reg .pred p;\nsetp.ne.s32 p, %5, 0;\n@p st.shared.v4.u32 [%0], {%1,%2,%3,%4};\n}\n"
                             :: "r"(sb6), "r"(held[0]), "r"(o[0][0]), "r"(held[1]), "r"(o[0][1]), "r"(y & 1) : "memory");
              held[0] = o[0][0]; held[1] = o[0][1];
            }
          }
#pragma unroll
          for (int e = 0; e < 2; e++) {
            if (mid.v) {
              uint32_t a = hfma(cur[j][e], wt[3][e], accB[j][e]);
              a = hfma(cur[j + 1][e], wt[4][e], a);
              a = hfma(cur[j + 2][e], wt[5][e], a);
              accA[j][e] = EARLYX == 1 ? hadd(cur[j + 1][e], a) : a;
              if (!EARLYX) ctr[j][e] = cur[j + 1][e];
            }
            if (top.v) {
              uint32_t a = hmul(cur[j][e], wt[0][e]);
              a = hfma(cur[j + 1][e], wt[1][e], a);
              accB[j][e] = hfma(cur[j + 2][e], wt[2][e], a);
            }
          }
        }
      };
      held[0] = held[1] = 0;
      if (nrounds > 1) { coords(1); issue(0, 0); issue(1, 1); issue(2, 2); }
      for (int r = 0; r + 1 < nrounds; r++) {
        const bool more = r + 2 < nrounds;
        mbar_wait(xbar, r & 1);
        if (r > 0) issue(2, 2);
        row(IC<0>{}, IC<0>{}, IC<1>{}, 0, 0);
        mbar_wait(xbar + 8, r & 1);
        issue(0, 3);
        row(IC<0>{}, IC<1>{}, IC<1>{}, 1, 0);
        mbar_wait(sb + BAR_TEMPTY, r & 1);
        TR(0);
#pragma unroll 1
        for (int k = 0; k < 2; k++) {
          mbar_wait(xbar + 16, (r + k) & 1);
          issue(1, 4 + 3 * k);
          row(IC<1>{}, IC<1>{}, IC<1>{}, 2, 3 * k);
          mbar_wait(xbar, (r + k + 1) & 1);
          issue(2, 5 + 3 * k);
          row(IC<1>{}, IC<1>{}, IC<1>{}, 0, 3 * k + 1);
          mbar_wait(xbar + 8, (r + k + 1) & 1);
          if (k == 1 && more) coords(r + 2);
          if (k == 0 || more) issue(0, k == 0 ? 6 : 0);
          row(IC<1>{}, IC<1>{}, IC<1>{}, 1, 3 * k + 2);
        }
        mbar_wait(xbar + 16, r & 1);
        if (more) issue(1, 1);
        row(IC<2>{}, IC<0>{}, IC<0>{}, 2, 6);
        warp_arrive(sb + BAR_TFULL);
        TR(1);
      }
    }
    asm volatile("bar.sync 5, 384;" ::: "memory");
#pragma unroll 1
    for (int i = 0; i < 8; i++) {
      uint32_t bits = *reinterpret_cast<volatile uint32_t*>(smem + OFF_REDO + 4 * i);
#pragma unroll 1
      for (; bits; bits &= bits - 1)
        slow_window(reinterpret_cast<float*>(smem), window_of((i & 3) * 32 + __ffs(bits) - 1, nfull, cta, ncta, i >> 2), tid - 256, x, dw, wqkv, wo, out);
    }
  } else {
    asm volatile("setmaxnreg.inc.sync.aligned.u32 " CREGS ";");
    const int wg = warp >> 2, w4 = warp & 3, g = lane >> 2, q = lane & 3;
    const int row0 = w4 * 16 + g, row1 = row0 + 8;
    const int ps = min(w4 * 8 + g, 24);
    const int pix0 = ps < 21 ? (ps / 3) * IMG + (ps % 3) * 2 : (ps - 21) * 2 * IMG + 6;
    const int pix1 = pix0 + (ps < 21 ? 1 : ps < 24 ? IMG : 0);
    const uint32_t kv = sb + OFF_KV + wg * KV_BYTES;
    const int srow = w4 * 16 + (lane & 15);
    const uint32_t vst = kv + (lane >> 4) * KV_PITCH + (srow < 56 ? srow : min(srow - 7, 55)) * 16;
    uint32_t misc = ((uint32_t)pix1 << 20) | ((uint32_t)pix0 << 8) | q;
    const uint32_t ninf = q ? 0xfc00fc00u : 0u;
    const uint32_t v48 = kv + (lane >> 3) * KV_PITCH + 48 * 16;
    const uint32_t vmask = (row0 < 49 ? 0xffffu : 0u) | (row1 < 49 ? 0xffff0000u : 0u);

    const uint32_t tx = sb + q * 32 + (row0 < 49 ? OFF_TILE + wg * TILE_BYTES + ps * 768 + (ps & 1) * 16 : OFF_ZERO + 16);
    const int myrounds = window_of(nrounds - 1, nfull, cta, ncta, wg) < 0 ? nrounds - 1 : nrounds;

    if (never == 2) return;
    uint32_t H[48], Y[48];
    const uint64_t* dkv = ds.kv[wg];
    uint32_t P[NP], Ofc[12], p48 = 0;
#pragma unroll
    for (int i = 0; i < 48; i++) Y[i] = 0;
#pragma unroll
    for (int i = 0; i < NP; i++) P[i] = Ofc[i % 12] = 0;
    if (warp == 0) GTS(4);
    load_x<0, 12>(H, tx);
    warp_arrive(sb + BAR_TEMPTY);
    if (wg == 1) turn_pass(1);

    uint8_t *o0, *o1;
    uint32_t omask;
    auto out_setup = [&](int r) {
      omask = r >= 0 ? vmask : 0u;
      const int w = window_of(r, nfull, cta, ncta, wg);
      const int wy = w / NWX, wx = w - wy * NWX;
      asm volatile("" : "+r"(misc));
      const uint32_t wb = (uint32_t)(wy * 7 * IMG + wx * 7) * 384u + (misc & 3) * 16;
      o0 = reinterpret_cast<uint8_t*>(out) + (wb + ((misc >> 8) & 0xfff) * 384u);
      o1 = reinterpret_cast<uint8_t*>(out) + (wb + (misc >> 20) * 384u);
    };
#define OUT(c) store_out<c>(Y, o0, o1, omask)
    auto release = [&](int stage) { warp_arrive(sb + BAR_WEMPTY + 8 * stage); };

    for (int r = 0;; r++) {
      const uint32_t par = r & 1;
      uint32_t acc[36], S[14], O[14], Q[12], V[12], Ofa[12], Ofb[12], vr[6], k48, mx;
      if (r == myrounds) {
        const bool idle = r < nrounds;
        mbar_wait(sb + BAR_WFULL + 40, par);
        turn_wait(wg);
        wg_fence(); mma_pv(O, P, dkv + 4); mma_proj(Y, Ofc, ds.p + 6); wg_commit();
        turn_pass(wg);
        load_v48(vr, v48);
        wg_wait<0>(); keep(O); keep(Y);
        finish_o(O, vr, p48, vmask, Ofa);
        if (idle) { release(5); release(0); release(1); release(2); release(3); }
        mbar_wait(sb + BAR_WFULL + 48, par);
        turn_wait(wg);
        wg_fence(); mma_proj(Y, Ofa, ds.p + 9); wg_commit();
        if (wg == 0 || idle) turn_pass(wg);
        wg_wait<0>(); keep(Y);
        if (idle) { release(6); turn_wait(wg); turn_pass(wg); }
        out_setup(r - 1);
        OUT(0); PIN(); OUT(1); PIN(); OUT(2); PIN(); OUT(3); PIN(); OUT(4); PIN(); OUT(5);
        if (idle) {
          turn_wait(wg); turn_pass(wg);
          turn_wait(wg); turn_pass(wg);
          turn_wait(wg); turn_pass(wg);
          turn_wait(wg);
        }
        if (w4 == 0) GTS(5 + wg);
        asm volatile("bar.arrive 5, 384;" ::: "memory");
        break;
      }
      float s1[2], s2[2];
      if (SA > 0) ln_sums<0, SA>(H, s1, s2);
      mbar_wait(sb + BAR_WFULL + 40, par);
      mbar_wait(sb + BAR_WFULL, par);
      TR(0);
      turn_wait(wg);
      TR(1);
      wg_fence(); mma_pv(O, P, dkv + 4); mma_proj(Y, Ofc, ds.p + 6); wg_commit(); mma_qkv<0, 3>(acc, H, ds.q[0]);
      PIN();
      ln_sums<SA, SB>(H, s1, s2);
      PIN();
      wg_fence(); mma_qkv<3, 8>(acc, H, ds.q[0]);
      PIN();
      ln_sums<SB, SC>(H, s1, s2);
      PIN();
      wg_fence(); mma_qkv<8, 12>(acc, H, ds.q[0]);
      turn_pass(wg);
      TR(2);
      load_v48(vr, v48);
      wg_wait<3>(); keep(O); keep(Y);
      release(5);
      wg_sync(wg);
      PIN();
      finish_o(O, vr, p48, vmask, Ofa);
      if (SC < 48) ln_sums<SC, 48>(H, s1, s2);
      float lim_lo, lim_hi;
      asm volatile("ld.shared.v2.f32 {%0,%1}, [%2];" : "=f"(lim_lo), "=f"(lim_hi) : "r"(sb + OFF_LIM) : "memory");
      bool ok;
      const uint32_t rk = ln_rstd(s1, s2, lim_lo, lim_hi, ok);
      asm volatile("{\n.reg .pred p;\nsetp.eq.s32 p, %2, 0;\n@p red.shared.or.b32 [%0], %1;\n}\n"
                   :: "r"(sb + OFF_REDO + wg * 16 + (r >> 5) * 4), "r"(1u << (r & 31)), "r"((int)ok) : "memory");
      PIN();
      TR(3);
      wg_wait<0>(); keep(acc);
      TR(4);
      release(0);
      scale12(V, acc, rk); stsm12(V, vst + KV_KOFF);
      scale12(V, acc + 24, rk); stsm12(V, vst);
      scale12(Q, acc + 12, rk); PIN();
      proxy_fence();
      mbar_wait(sb + BAR_WFULL + 48, par);
      mbar_wait(sb + BAR_WFULL + 8, par);
      TR(5);
      turn_wait(wg);
      TR(6);
      wg_fence(); mma_proj(Y, Ofa, ds.p + 9); wg_commit(); mma_s(S, Q, dkv); mma_qkv<0, 2>(acc, H, ds.q[1]);
      out_setup(r - 1);
      PIN();
      wg_wait<1>(); keep(Y);
      release(6);
      wg_fence(); mma_qkv<2, 6>(acc, H, ds.q[1]);
      PIN();
      OUT(0);
      PIN();
      wg_wait<1>(); keep(S);
      wg_fence(); mma_qkv<6, 9>(acc, H, ds.q[1]);
      PIN();
      row_max(S, k48, mx, ninf);
      OUT(1);
      PIN();
      wg_fence(); mma_qkv<9, 12>(acc, H, ds.q[1]);
      turn_pass(wg);
      PIN();
      OUT(2); PIN();
      OUT(3); PIN();
      row_exp(S, k48, mx, P, p48);
      PIN();
      TR(7);
      wg_wait<0>(); keep(acc);
      TR(8);
      release(1);
      wg_sync(wg);
      scale12(V, acc, rk); stsm12(V, vst + KV_KOFF);
      scale12(Q, acc + 12, rk); scale12(V, acc + 24, rk); PIN();
      proxy_fence();
#define TURN(ID, OF, G1, G2, G3, X1)                                                       \
      TR(ID + 1);                                                                       \
      turn_wait(wg);                                                                    \
      wg_fence(); mma_pv(O, P, dkv + 4); mma_s(S, Q, dkv); wg_commit(); G1;             \
      PIN();                                                                            \
      TR(ID + 2);                                                                       \
      load_v48(vr, v48);                                                                \
      X1;                                                                               \
      PIN();                                                                            \
      wg_wait<1>(); keep(S); keep(O);                                                   \
      wg_sync(wg);                                         \
      wg_fence(); G2;                                                                   \
      if (KB == 12) turn_pass(wg);                                                      \
      PIN();                                                                            \
      stsm12(V, vst);                                                                   \
      finish_o(O, vr, p48, vmask, OF);                                                    \
      row_max(S, k48, mx, ninf);                                                              \
      PIN();                                                                            \
      if (KB < 12) { wg_fence(); G3; turn_pass(wg); }                                                                 \
      PIN();                                                                            \
      TR(ID + 3);
#define NEXT_HEAD(ID, HD, X2)                                                           \
      row_exp(S, k48, mx, P, p48);                                                      \
      PIN();                                                                            \
      X2;                                                                               \
      TR(ID + 4);                                                                       \
      wg_wait<0>(); keep(acc);                                                          \
      release(HD);                                                                      \
      scale12(V, acc, rk); stsm12(V, vst + KV_KOFF);                                    \
      scale12(Q, acc + 12, rk); scale12(V, acc + 24, rk); PIN();
      mbar_wait(sb + BAR_WFULL + 16, par);
      TURN(8, Ofa, (mma_qkv<0, KA>(acc, H, ds.q[2])), (mma_qkv<KA, KB>(acc, H, ds.q[2])), (mma_qkv<KB, 12>(acc, H, ds.q[2])), OUT(4))
      OUT(5); PIN();
      NEXT_HEAD(8, 2, )
      proxy_fence();
      mbar_wait(sb + BAR_WFULL + 24, par);
      TURN(12, Ofb, (mma_qkv<0, KA>(acc, H, ds.q[3])), (mma_qkv<KA, KB>(acc, H, ds.q[3])), (mma_qkv<KB, 12>(acc, H, ds.q[3])), )
      auto init_y = [&]() {
#pragma unroll
        for (int i = 0; i < 48; i++) Y[i] = (i & 1) ? H[i] ^ never : h2u(__hadd2_rn(u2h(H[i]), u2h(never)));
        hold<0, 48>(Y); PIN();
      };
      NEXT_HEAD(12, 3, if (YEARLY) init_y())
      if (!YEARLY) init_y();
      proxy_fence();
      mbar_wait(sb + BAR_WFULL + 32, par);
      TR(17);
      turn_wait(wg);
      wg_fence(); mma_pv(O, P, dkv + 4); mma_s(S, Q, dkv); wg_commit(); mma_proj(Y, Ofa, ds.p); mma_proj(Y, Ofb, ds.p + 3); wg_commit();
      turn_pass(wg);
      PIN();
      TR(18);
      load_v48(vr, v48);
      if (r + 1 < myrounds) mbar_wait(sb + BAR_TFULL, par);
      load_x<0, 4>(H, tx);
      wg_wait<1>(); keep(S); keep(O);
      wg_sync(wg);
      PIN();
      TR(19);
      row_max(S, k48, mx, ninf);
      finish_o(O, vr, p48, vmask, Ofc);
      stsm12(V, vst);
      PIN();
      load_x<4, 8>(H, tx);
      row_exp(S, k48, mx, P, p48);
      PIN();
      load_x<8, 12>(H, tx);
      warp_arrive(sb + BAR_TEMPTY);
      TR(20);
      wg_wait<0>(); keep(Y);
      release(4);
      proxy_fence();
      TR(21);
#undef TURN
#undef NEXT_HEAD
    }
  }
}

typedef CUresult (*EncodeFn)(CUtensorMap*, CUtensorMapDataType, cuuint32_t, void*, const cuuint64_t*, const cuuint64_t*,
                             const cuuint32_t*, const cuuint32_t*, CUtensorMapInterleave, CUtensorMapSwizzle,
                             CUtensorMapL2promotion, CUtensorMapFloatOOBfill);

}

extern "C" void kernel_launch(void* const* d_in, const int* in_sizes, int n_in, void* d_out, int out_size) {
  const __nv_bfloat16* x = (const __nv_bfloat16*)d_in[0];
  const __nv_bfloat16* dw = (const __nv_bfloat16*)d_in[1];
  const __nv_bfloat16* wqkv = (const __nv_bfloat16*)d_in[2];
  const __nv_bfloat16* wo = (const __nv_bfloat16*)d_in[3];
  static EncodeFn encode = nullptr;
  static int nsm = 0;
  static void* wpack = nullptr;
  if (!encode) {
    void* fn = nullptr;
    cudaDriverEntryPointQueryResult qr;
    cudaGetDriverEntryPoint("cuTensorMapEncodeTiled", &fn, cudaEnableDefault, &qr);
    encode = (EncodeFn)fn;
    int dev = 0;
    cudaGetDevice(&dev);
    cudaDeviceGetAttribute(&nsm, cudaDevAttrMultiProcessorCount, dev);
    cudaGetSymbolAddress(&wpack, g_wpack);
    cudaFuncSetAttribute(fused_kernel, cudaFuncAttributeMaxDynamicSharedMemorySize, SMEM_BYTES);
  }
  CUtensorMap tmx;
  cuuint64_t gdim[3] = {CH, IMG, IMG};
  cuuint64_t gstr[2] = {CH * 2, (cuuint64_t)CH * 2 * IMG};
  cuuint32_t box[3] = {64, 9, 1};
  cuuint32_t estr[3] = {1, 1, 1};
  encode(&tmx, CU_TENSOR_MAP_DATA_TYPE_BFLOAT16, 3, (void*)x, gdim, gstr, box, estr, CU_TENSOR_MAP_INTERLEAVE_NONE,
         CU_TENSOR_MAP_SWIZZLE_NONE, CU_TENSOR_MAP_L2_PROMOTION_L2_128B, CU_TENSOR_MAP_FLOAT_OOB_FILL_NONE);
  Descs ds;
  for (int i = 0; i < 12; i++) {
    for (int h = 0; h < 4; h++) ds.q[h][i] = mkdesc(SMEM_BASE + OFF_W + qkv_pos(h, i) % (8 * SLICE), 128, 256);
    ds.p[i] = mkdesc(SMEM_BASE + OFF_W + wo_pos(i) % (8 * SLICE), 128, 256);
  }
  for (int i = 0; i < 16; i++) ds.src[i] = (const uint8_t*)wpack + i * SLICE;
  for (int g = 0; g < 2; g++)
    for (int i = 0; i < 4; i++) {
      ds.kv[g][i] = mkdesc(SMEM_BASE + OFF_KV + g * KV_BYTES + KV_KOFF + 2 * i * KV_PITCH, KV_PITCH, 128);
      ds.kv[g][4 + i] = mkdesc(SMEM_BASE + OFF_KV + g * KV_BYTES + 256 * i, 128, KV_PITCH);
    }
  CUtensorMap tmp;
  cuuint32_t boxp[3] = {CH, 9, 9};
  encode(&tmp, CU_TENSOR_MAP_DATA_TYPE_BFLOAT16, 3, (void*)x, gdim, gstr, boxp, estr, CU_TENSOR_MAP_INTERLEAVE_NONE,
         CU_TENSOR_MAP_SWIZZLE_NONE, CU_TENSOR_MAP_L2_PROMOTION_L2_128B, CU_TENSOR_MAP_FLOAT_OOB_FILL_NONE);
  prepack_kernel<<<48, dim3(192, 2), 0, cudaStreamPerThread>>>(wqkv, wo);
  cudaLaunchConfig_t cfg = {};
  cfg.gridDim = dim3(nsm); cfg.blockDim = dim3(384); cfg.dynamicSmemBytes = SMEM_BYTES; cfg.stream = cudaStreamPerThread;
  cudaLaunchAttribute at[1];
  at[0].id = cudaLaunchAttributeProgrammaticStreamSerialization;
  at[0].val.programmaticStreamSerializationAllowed = 1;
  cfg.attrs = at; cfg.numAttrs = 1;
  cudaLaunchKernelEx(&cfg, fused_kernel, tmx, tmp, ds, dw, (__nv_bfloat16*)d_out, 0, x, wqkv, wo);
}
```

```cpp
#include <cuda_runtime.h>
#include <cuda_bf16.h>
#include <cuda_fp16.h>
#include <cuda.h>
#include <stdint.h>

#define CREGS "208"
#define PREGS "88"
#define KA 3
#define KB 9
#define SA 0
#define SB 24
#define SC 48
#define K48TC 0
#define EARLYX 0
#define LA 4
#define YEARLY 0
#define STHINT ".cs"
namespace {
constexpr int NP = K48TC ? 16 : 12;

constexpr int IMG = 511;
constexpr int CH = 192;
constexpr int NWX = 73;
constexpr int NWIN = NWX * NWX;
constexpr int SLICE = 18432;
constexpr int OFF_W = 0;
constexpr int KV_PITCH = 1792, KV_KOFF = 896, KV_BYTES = 6 * KV_PITCH + 1024;
constexpr int OFF_KV = 8 * SLICE;
constexpr int TILE_BYTES = 25 * 768;
constexpr int OFF_TILE = OFF_KV + 2 * KV_BYTES;
constexpr int XSLOT = 2304;
constexpr int OFF_ZERO = OFF_TILE + 2 * TILE_BYTES;
constexpr int OFF_X = OFF_ZERO + 768;
constexpr int OFF_BAR = OFF_X + 9 * XSLOT;
constexpr int BAR_WFULL = OFF_BAR;
constexpr int BAR_WEMPTY = OFF_BAR + 56;
constexpr int BAR_XFULL = OFF_BAR + 112;
constexpr int BAR_TFULL = OFF_BAR + 184;
constexpr int BAR_TEMPTY = OFF_BAR + 192;
constexpr int OFF_LIM = OFF_BAR + 200;
constexpr int OFF_REDO = OFF_BAR + 208;
constexpr int BAR_FIRST = OFF_BAR + 240;
constexpr int OFF_TRACE = OFF_BAR + 248;
constexpr int OFF_HALO = OFF_W + 4 * SLICE, HALO_BYTES = 81 * 384;
constexpr int SMEM_BYTES = OFF_TRACE;

__host__ __device__ constexpr int qkv_pos(int h, int s) { return (h == 0 ? 1 : 3 * h + 2) * SLICE + s * 4608; }
__host__ __device__ constexpr int wo_pos(int s) { return s < 6 ? 14 * SLICE + s * 6144 : s < 9 ? (s - 6) * 6144 : 4 * SLICE + (s - 9) * 6144; }
__host__ __device__ constexpr int stage_of(int p) { return p == 0 ? 5 : p < 4 ? 0 : p == 4 ? 6 : p < 8 ? 1 : p < 11 ? 2 : p < 14 ? 3 : 4; }
constexpr int SMEM_BASE = 1024;
struct Descs { uint64_t q[4][12]; uint64_t p[12]; uint64_t kv[2][8]; const uint8_t* src[16]; };

__device__ uint4 g_wpack[16 * SLICE / 16];
__device__ float2 g_wnorm[96];
#define TR(id)
#define GTS(i)
template <int V> struct IC { static constexpr int v = V; };
typedef __nv_bfloat162 bf2;
__device__ __forceinline__ bf2 u2b(uint32_t u) { return *reinterpret_cast<bf2*>(&u); }
__device__ __forceinline__ uint32_t b2u(bf2 b) { return *reinterpret_cast<uint32_t*>(&b); }
__device__ __forceinline__ uint32_t pack2(float lo, float hi) {
  uint32_t r; asm("cvt.rn.bf16x2.f32 %0, %1, %2;" : "=r"(r) : "f"(hi), "f"(lo)); return r;
}
__device__ __forceinline__ uint32_t hadd(uint32_t a, uint32_t b) { return b2u(__hadd2_rn(u2b(a), u2b(b))); }
__device__ __forceinline__ uint32_t hmul(uint32_t a, uint32_t b) { return b2u(__hmul2_rn(u2b(a), u2b(b))); }
__device__ __forceinline__ uint32_t hfma(uint32_t a, uint32_t b, uint32_t c) { return b2u(__hfma2(u2b(a), u2b(b), u2b(c))); }
__device__ __forceinline__ __half2 u2h(uint32_t u) { return *reinterpret_cast<__half2*>(&u); }
__device__ __forceinline__ uint32_t h2u(__half2 b) { return *reinterpret_cast<uint32_t*>(&b); }
__device__ __forceinline__ uint32_t packh(float lo, float hi) {
  uint32_t r; asm("cvt.rn.f16x2.f32 %0, %1, %2;" : "=r"(r) : "f"(hi), "f"(lo)); return r;
}
__device__ __forceinline__ uint32_t fmax2(uint32_t a, uint32_t b) { return h2u(__hmax2(u2h(a), u2h(b))); }
template <int HI> __device__ __forceinline__ __half2 hcast(uint32_t a) { return HI ? __high2half2(u2h(a)) : __low2half2(u2h(a)); }
template <int HI> __device__ __forceinline__ uint32_t fmul_b(uint32_t a, uint32_t s) { return h2u(__hmul2_rn(u2h(a), hcast<HI>(s))); }
template <int HI> __device__ __forceinline__ uint32_t fsub_b(uint32_t a, uint32_t s) { return h2u(__hsub2_rn(u2h(a), hcast<HI>(s))); }
__device__ __forceinline__ uint32_t fex2(uint32_t a) { uint32_t r; asm("ex2.approx.f16x2 %0, %1;" : "=r"(r) : "r"(a)); return r; }
__device__ __forceinline__ float lo2f(uint32_t a) { return __uint_as_float(a << 16); }
__device__ __forceinline__ float hi2f(uint32_t a) { return __uint_as_float(a & 0xffff0000u); }

__device__ __forceinline__ void mbar_init(uint32_t bar, uint32_t cnt) { asm volatile("mbarrier.init.shared::cta.b64 [%0], %1;" :: "r"(bar), "r"(cnt) : "memory"); }
__device__ __forceinline__ void mbar_wait(uint32_t bar, uint32_t parity) {
  asm volatile("{\n.reg .pred p;\n.reg .u32 n;\n"
               "mbarrier.try_wait.parity.shared::cta.b64 p, [%0], %1;\n"
               "@p bra.uni DONE_%=;\n"
               "mov.u32 n, 0;\n"
               "AGAIN_%=:\n"
               "mbarrier.try_wait.parity.shared::cta.b64 p, [%0], %1;\n"
               "@p bra.uni DONE_%=;\n"
               "add.u32 n, n, 1;\n"
               "setp.lt.u32 p, n, 0x1000000;\n"
               "@p bra.uni AGAIN_%=;\n"
               "trap;\n"
               "DONE_%=:\n}\n" :: "r"(bar), "r"(parity) : "memory");
}
__device__ __forceinline__ void wg_fence() { asm volatile("wgmma.fence.sync.aligned;" ::: "memory"); }
__device__ __forceinline__ void wg_commit() { asm volatile("wgmma.commit_group.sync.aligned;" ::: "memory"); }
template <int N> __device__ __forceinline__ void wg_wait() { asm volatile("wgmma.wait_group.sync.aligned %0;" :: "n"(N) : "memory"); }
#define BAR_BY_WG(OP, ID0, ID1, CNT) asm volatile("{\n.reg .pred p;\nsetp.eq.s32 p, %0, 0;\n@p " OP " " #ID0 ", " #CNT ";\n@!p " OP " " #ID1 ", " #CNT ";\n}\n" :: "r"(wg) : "memory")
__device__ __forceinline__ void wg_sync(int wg) { BAR_BY_WG("bar.sync", 1, 2, 128); }
__device__ __forceinline__ void turn_wait(int wg) { BAR_BY_WG("bar.sync", 3, 4, 256); }
__device__ __forceinline__ void turn_pass(int wg) { BAR_BY_WG("bar.arrive", 4, 3, 256); }
__device__ __forceinline__ void stsm4(uint32_t addr, uint32_t a, uint32_t b, uint32_t c, uint32_t d) {
  asm volatile("stmatrix.sync.aligned.m8n8.x4.shared.b16 [%0], {%1,%2,%3,%4};" :: "r"(addr), "r"(a), "r"(b), "r"(c), "r"(d) : "memory");
}
template <int N> __device__ __forceinline__ void keep(float (&d)[N]) {
#pragma unroll
  for (int i = 0; i < N; i++) asm volatile("" : "+f"(d[i]) :: "memory");
}
template <int N> __device__ __forceinline__ void keep(uint32_t (&d)[N]) {
#pragma unroll
  for (int i = 0; i < N; i++) asm volatile("" : "+r"(d[i]) :: "memory");
}
__host__ __device__ __forceinline__ uint64_t mkdesc(uint32_t addr, uint32_t lbo, uint32_t sbo) {
  return ((uint64_t)(sbo >> 4) << 32) | (uint64_t)(((lbo >> 4) << 16) | ((addr & 0x3FFFF) >> 4));
}

template <int SCALE_D>
__device__ __forceinline__ void wgmma_n144(uint32_t (&d)[36], uint32_t a0, uint32_t a1, uint32_t a2, uint32_t a3, uint64_t descB) {
  if (SCALE_D == 0)
  asm volatile("wgmma.mma_async.sync.aligned.m64n144k16.f16.f16.f16 "
    "{%0, %1, %2, %3, %4, %5, %6, %7, %8, %9, %10, %11, %12, %13, %14, %15, "
    "%16, %17, %18, %19, %20, %21, %22, %23, %24, %25, %26, %27, %28, %29, %30, %31, "
    "%32, %33, %34, %35}, "
    "{%36, %37, %38, %39}, %40, 0, 1, 1, 0;\n"
    : "=r"(d[0]), "=r"(d[1]), "=r"(d[2]), "=r"(d[3]), "=r"(d[4]), "=r"(d[5]), "=r"(d[6]), "=r"(d[7]),
      "=r"(d[8]), "=r"(d[9]), "=r"(d[10]), "=r"(d[11]), "=r"(d[12]), "=r"(d[13]), "=r"(d[14]), "=r"(d[15]),
      "=r"(d[16]), "=r"(d[17]), "=r"(d[18]), "=r"(d[19]), "=r"(d[20]), "=r"(d[21]), "=r"(d[22]), "=r"(d[23]),
      "=r"(d[24]), "=r"(d[25]), "=r"(d[26]), "=r"(d[27]), "=r"(d[28]), "=r"(d[29]), "=r"(d[30]), "=r"(d[31]),
      "=r"(d[32]), "=r"(d[33]), "=r"(d[34]), "=r"(d[35])
    : "r"(a0), "r"(a1), "r"(a2), "r"(a3), "l"(descB));
  else
  asm volatile("wgmma.mma_async.sync.aligned.m64n144k16.f16.f16.f16 "
    "{%0, %1, %2, %3, %4, %5, %6, %7, %8, %9, %10, %11, %12, %13, %14, %15, "
    "%16, %17, %18, %19, %20, %21, %22, %23, %24, %25, %26, %27, %28, %29, %30, %31, "
    "%32, %33, %34, %35}, "
    "{%36, %37, %38, %39}, %40, 1, 1, 1, 0;\n"
    : "+r"(d[0]), "+r"(d[1]), "+r"(d[2]), "+r"(d[3]), "+r"(d[4]), "+r"(d[5]), "+r"(d[6]), "+r"(d[7]),
      "+r"(d[8]), "+r"(d[9]), "+r"(d[10]), "+r"(d[11]), "+r"(d[12]), "+r"(d[13]), "+r"(d[14]), "+r"(d[15]),
      "+r"(d[16]), "+r"(d[17]), "+r"(d[18]), "+r"(d[19]), "+r"(d[20]), "+r"(d[21]), "+r"(d[22]), "+r"(d[23]),
      "+r"(d[24]), "+r"(d[25]), "+r"(d[26]), "+r"(d[27]), "+r"(d[28]), "+r"(d[29]), "+r"(d[30]), "+r"(d[31]),
      "+r"(d[32]), "+r"(d[33]), "+r"(d[34]), "+r"(d[35])
    : "r"(a0), "r"(a1), "r"(a2), "r"(a3), "l"(descB));
}

template <int SCALE_D>
__device__ __forceinline__ void wgmma_n192(uint32_t (&d)[48], uint32_t a0, uint32_t a1, uint32_t a2, uint32_t a3, uint64_t descB) {
  if (SCALE_D == 0)
  asm volatile("wgmma.mma_async.sync.aligned.m64n192k16.f16.f16.f16 "
    "{%0, %1, %2, %3, %4, %5, %6, %7, %8, %9, %10, %11, %12, %13, %14, %15, "
    "%16, %17, %18, %19, %20, %21, %22, %23, %24, %25, %26, %27, %28, %29, %30, %31, "
    "%32, %33, %34, %35, %36, %37, %38, %39, %40, %41, %42, %43, %44, %45, %46, %47}, "
    "{%48, %49, %50, %51}, %52, 0, 1, 1, 0;\n"
    : "=r"(d[0]), "=r"(d[1]), "=r"(d[2]), "=r"(d[3]), "=r"(d[4]), "=r"(d[5]), "=r"(d[6]), "=r"(d[7]),
      "=r"(d[8]), "=r"(d[9]), "=r"(d[10]), "=r"(d[11]), "=r"(d[12]), "=r"(d[13]), "=r"(d[14]), "=r"(d[15]),
      "=r"(d[16]), "=r"(d[17]), "=r"(d[18]), "=r"(d[19]), "=r"(d[20]), "=r"(d[21]), "=r"(d[22]), "=r"(d[23]),
      "=r"(d[24]), "=r"(d[25]), "=r"(d[26]), "=r"(d[27]), "=r"(d[28]), "=r"(d[29]), "=r"(d[30]), "=r"(d[31]),
      "=r"(d[32]), "=r"(d[33]), "=r"(d[34]), "=r"(d[35]), "=r"(d[36]), "=r"(d[37]), "=r"(d[38]), "=r"(d[39]),
      "=r"(d[40]), "=r"(d[41]), "=r"(d[42]), "=r"(d[43]), "=r"(d[44]), "=r"(d[45]), "=r"(d[46]), "=r"(d[47])
    : "r"(a0), "r"(a1), "r"(a2), "r"(a3), "l"(descB));
  else
  asm volatile("wgmma.mma_async.sync.aligned.m64n192k16.f16.f16.f16 "
    "{%0, %1, %2, %3, %4, %5, %6, %7, %8, %9, %10, %11, %12, %13, %14, %15, "
    "%16, %17, %18, %19, %20, %21, %22, %23, %24, %25, %26, %27, %28, %29, %30, %31, "
    "%32, %33, %34, %35, %36, %37, %38, %39, %40, %41, %42, %43, %44, %45, %46, %47}, "
    "{%48, %49, %50, %51}, %52, 1, 1, 1, 0;\n"
    : "+r"(d[0]), "+r"(d[1]), "+r"(d[2]), "+r"(d[3]), "+r"(d[4]), "+r"(d[5]), "+r"(d[6]), "+r"(d[7]),
      "+r"(d[8]), "+r"(d[9]), "+r"(d[10]), "+r"(d[11]), "+r"(d[12]), "+r"(d[13]), "+r"(d[14]), "+r"(d[15]),
      "+r"(d[16]), "+r"(d[17]), "+r"(d[18]), "+r"(d[19]), "+r"(d[20]), "+r"(d[21]), "+r"(d[22]), "+r"(d[23]),
      "+r"(d[24]), "+r"(d[25]), "+r"(d[26]), "+r"(d[27]), "+r"(d[28]), "+r"(d[29]), "+r"(d[30]), "+r"(d[31]),
      "+r"(d[32]), "+r"(d[33]), "+r"(d[34]), "+r"(d[35]), "+r"(d[36]), "+r"(d[37]), "+r"(d[38]), "+r"(d[39]),
      "+r"(d[40]), "+r"(d[41]), "+r"(d[42]), "+r"(d[43]), "+r"(d[44]), "+r"(d[45]), "+r"(d[46]), "+r"(d[47])
    : "r"(a0), "r"(a1), "r"(a2), "r"(a3), "l"(descB));
}

template <int SCALE_D>
__device__ __forceinline__ void wgmma_n56(uint32_t (&d)[14], uint32_t a0, uint32_t a1, uint32_t a2, uint32_t a3, uint64_t descB) {
  if (SCALE_D == 0)
  asm volatile("wgmma.mma_async.sync.aligned.m64n56k16.f16.f16.f16 "
    "{%0, %1, %2, %3, %4, %5, %6, %7, %8, %9, %10, %11, %12, %13}, "
    "{%14, %15, %16, %17}, %18, 0, 1, 1, 0;\n"
    : "=r"(d[0]), "=r"(d[1]), "=r"(d[2]), "=r"(d[3]), "=r"(d[4]), "=r"(d[5]), "=r"(d[6]), "=r"(d[7]),
      "=r"(d[8]), "=r"(d[9]), "=r"(d[10]), "=r"(d[11]), "=r"(d[12]), "=r"(d[13])
    : "r"(a0), "r"(a1), "r"(a2), "r"(a3), "l"(descB));
  else
  asm volatile("wgmma.mma_async.sync.aligned.m64n56k16.f16.f16.f16 "
    "{%0, %1, %2, %3, %4, %5, %6, %7, %8, %9, %10, %11, %12, %13}, "
    "{%14, %15, %16, %17}, %18, 1, 1, 1, 0;\n"
    : "+r"(d[0]), "+r"(d[1]), "+r"(d[2]), "+r"(d[3]), "+r"(d[4]), "+r"(d[5]), "+r"(d[6]), "+r"(d[7]),
      "+r"(d[8]), "+r"(d[9]), "+r"(d[10]), "+r"(d[11]), "+r"(d[12]), "+r"(d[13])
    : "r"(a0), "r"(a1), "r"(a2), "r"(a3), "l"(descB));
}

template <int SCALE_D>
__device__ __forceinline__ void wgmma_n56t(uint32_t (&d)[14], uint32_t a0, uint32_t a1, uint32_t a2, uint32_t a3, uint64_t descB) {
  if (SCALE_D == 0)
  asm volatile("wgmma.mma_async.sync.aligned.m64n56k16.f16.f16.f16 "
    "{%0, %1, %2, %3, %4, %5, %6, %7, %8, %9, %10, %11, %12, %13}, "
    "{%14, %15, %16, %17}, %18, 0, 1, 1, 1;\n"
    : "=r"(d[0]), "=r"(d[1]), "=r"(d[2]), "=r"(d[3]), "=r"(d[4]), "=r"(d[5]), "=r"(d[6]), "=r"(d[7]),
      "=r"(d[8]), "=r"(d[9]), "=r"(d[10]), "=r"(d[11]), "=r"(d[12]), "=r"(d[13])
    : "r"(a0), "r"(a1), "r"(a2), "r"(a3), "l"(descB));
  else
  asm volatile("wgmma.mma_async.sync.aligned.m64n56k16.f16.f16.f16 "
    "{%0, %1, %2, %3, %4, %5, %6, %7, %8, %9, %10, %11, %12, %13}, "
    "{%14, %15, %16, %17}, %18, 1, 1, 1, 1;\n"
    : "+r"(d[0]), "+r"(d[1]), "+r"(d[2]), "+r"(d[3]), "+r"(d[4]), "+r"(d[5]), "+r"(d[6]), "+r"(d[7]),
      "+r"(d[8]), "+r"(d[9]), "+r"(d[10]), "+r"(d[11]), "+r"(d[12]), "+r"(d[13])
    : "r"(a0), "r"(a1), "r"(a2), "r"(a3), "l"(descB));
}

__global__ void __launch_bounds__(384) prepack_kernel(const __nv_bfloat16* __restrict__ wqkv, const __nv_bfloat16* __restrict__ wo) {
  asm volatile("griddepcontrol.launch_dependents;");
  __shared__ float red2[2][2][6][8];
  float (*red)[6][8] = red2[threadIdx.y];
  __half* dst = reinterpret_cast<__half*>(g_wpack);
  const int c = threadIdx.x, nb = blockIdx.x * 2 + threadIdx.y;
  auto colsum = [&](int k, const float (&v)[8], float (&o)[8]) {
#pragma unroll
    for (int i = 0; i < 8; i++) {
      float t = v[i];
#pragma unroll
      for (int d = 16; d; d >>= 1) t += __shfl_xor_sync(~0u, t, d);
      if ((c & 31) == 0) red[k][c >> 5][i] = t;
    }
    __syncthreads();
#pragma unroll
    for (int i = 0; i < 8; i++) o[i] = red[k][0][i] + red[k][1][i] + red[k][2][i] + red[k][3][i] + red[k][4][i] + red[k][5][i];
  };
  float v[8], t[8];
  int base;
  if (nb < 72) {
    const int h = nb / 18, j = nb % 18, part = j / 6;
    const int col = (part == 0 ? 192 : part == 1 ? 0 : 384) + h * 48 + (j % 6) * 8;
    uint4 raw = *reinterpret_cast<const uint4*>(wqkv + c * 576 + col);
    uint32_t u[4] = {raw.x, raw.y, raw.z, raw.w};
#pragma unroll
    for (int i = 0; i < 4; i++) { v[2 * i] = lo2f(u[i]); v[2 * i + 1] = hi2f(u[i]); }
    colsum(0, v, t);
#pragma unroll
    for (int n = 0; n < 8; n++)
      v[n] = __bfloat162float(__float2bfloat16((v[n] - t[n] * (1.0f / 192.0f)) * (part == 1 ? 0.14433756729740643f * 1.4426950408889634f : 1.0f)));
    const int cc = c >> 5, q = (c >> 3) & 3, s1 = (c >> 2) & 1, hh = (c >> 1) & 1, e = c & 1;
    base = qkv_pos(h, 2 * cc + s1) / 2 + j * 128 + hh * 64 + 2 * q + e;
  } else {
    const int jb = nb - 72;
#pragma unroll
    for (int n = 0; n < 8; n++) v[n] = __bfloat162float(wo[c * 192 + 32 * (jb >> 2) + 8 * (n >> 1) + 2 * (jb & 3) + (n & 1)]);
    base = wo_pos(c >> 4) / 2 + jb * 128 + ((c >> 3) & 1) * 64 + (c & 7);
  }
#pragma unroll
  for (int n = 0; n < 8; n++) { dst[base + n * 8] = __float2half_rn(v[n]); v[n] *= v[n]; }
  colsum(1, v, t);
  if (c == 0)
    g_wnorm[nb] = make_float2(fmaxf(fmaxf(fmaxf(t[0], t[1]), fmaxf(t[2], t[3])), fmaxf(fmaxf(t[4], t[5]), fmaxf(t[6], t[7]))),
                              t[0] + t[1] + t[2] + t[3] + t[4] + t[5] + t[6] + t[7]);
}

__device__ __forceinline__ int window_of(int round, int nfull, int cta, int ncta, int wg) {
  if (round < nfull) return round * 2 * ncta + 2 * cta + wg;
  const int rem = NWIN - nfull * 2 * ncta;
  const int i = cta + wg * ncta;
  return i < rem ? nfull * 2 * ncta + i : -1;
}

template <int S0 = 0, int S1 = 12>
__device__ __forceinline__ void mma_qkv(uint32_t (&acc)[36], const uint32_t (&A)[48], const uint64_t* d) {
#pragma unroll
  for (int s = S0; s < S1; s++) {
    if (s == 0) wgmma_n144<0>(acc, A[4 * s], A[4 * s + 1], A[4 * s + 2], A[4 * s + 3], d[s]);
    else        wgmma_n144<1>(acc, A[4 * s], A[4 * s + 1], A[4 * s + 2], A[4 * s + 3], d[s]);
  }
  wg_commit();
}
__device__ __forceinline__ void mma_proj(uint32_t (&acc)[48], const uint32_t (&A)[12], const uint64_t* d) {
#pragma unroll
  for (int s = 0; s < 3; s++) wgmma_n192<1>(acc, A[4 * s], A[4 * s + 1], A[4 * s + 2], A[4 * s + 3], d[s]);
}
__device__ __forceinline__ void mma_s(uint32_t (&S)[14], const uint32_t (&Q)[12], const uint64_t* d) {
  wgmma_n56<0>(S, Q[0], Q[1], Q[2], Q[3], d[0]);
  wgmma_n56<1>(S, Q[4], Q[5], Q[6], Q[7], d[1]);
  wgmma_n56<1>(S, Q[8], Q[9], Q[10], Q[11], d[2]);
}
__device__ __forceinline__ void mma_pv(uint32_t (&O)[14], const uint32_t (&P)[NP], const uint64_t* d) {
  wgmma_n56t<0>(O, P[0], P[1], P[2], P[3], d[0]);
  wgmma_n56t<1>(O, P[4], P[5], P[6], P[7], d[1]);
  wgmma_n56t<1>(O, P[8], P[9], P[10], P[11], d[2]);
  if (K48TC) wgmma_n56t<1>(O, P[NP - 4], P[NP - 3], P[NP - 2], P[NP - 1], d[3]);
}

#define PIN() asm volatile("pmevent 0;" ::: "memory")
template <int A, int B> __device__ __forceinline__ void hold(uint32_t* v) {
#pragma unroll
  for (int i = A; i < B; i++) asm volatile("" : "+r"(v[i]));
}
__device__ __forceinline__ void stsm12(const uint32_t* v, uint32_t addr) {
#pragma unroll
  for (int j = 0; j < 3; j++) stsm4(addr + 2 * j * KV_PITCH, v[4 * j], v[4 * j + 1], v[4 * j + 2], v[4 * j + 3]);
}
__device__ __forceinline__ void load_v48(uint32_t (&v)[6], uint32_t addr) {
  if (K48TC) return;
  asm volatile("ldmatrix.sync.aligned.m8n8.x4.shared.b16 {%0,%1,%2,%3}, [%4];" : "=r"(v[0]), "=r"(v[1]), "=r"(v[2]), "=r"(v[3]) : "r"(addr) : "memory");
  asm volatile("ldmatrix.sync.aligned.m8n8.x2.shared.b16 {%0,%1}, [%2];" : "=r"(v[4]), "=r"(v[5]) : "r"(addr + 4 * KV_PITCH) : "memory");
}
__device__ __forceinline__ void finish_o(const uint32_t (&O)[14], const uint32_t (&v)[6], uint32_t p48, uint32_t vmask, uint32_t (&Of)[12]) {
  const float2 l = K48TC ? make_float2(__low2float(u2h(O[12])), __low2float(u2h(O[13])))
                         : __half22float2(__hadd2_rn(u2h(__byte_perm(O[12], O[13], 0x5410)), u2h(p48)));
  float i0, i1;
  asm("rcp.approx.ftz.f32 %0, %1;" : "=f"(i0) : "f"(l.x));
  asm("rcp.approx.ftz.f32 %0, %1;" : "=f"(i1) : "f"(l.y));
  const uint32_t inv = packh(i0, i1) & vmask;
#pragma unroll
  for (int i = 0; i < 12; i++) {
    const uint32_t t = K48TC ? O[i] : h2u(__hfma2(u2h(v[i >> 1]), (i & 1) ? hcast<1>(p48) : hcast<0>(p48), u2h(O[i])));
    Of[i] = (i & 1) ? fmul_b<1>(t, inv) : fmul_b<0>(t, inv);
  }
  hold<0, 12>(Of);
}
#define PSTAT 12
template <int A, int B>
__device__ __forceinline__ void ln_sums(const uint32_t (&X)[48], float (&s1)[2], float (&s2)[2]) {
  if (PSTAT) {
    static_assert(PSTAT == 0 || (A % (2 * PSTAT + !PSTAT) == 0 && B % (2 * PSTAT + !PSTAT) == 0), "whole groups");
#pragma unroll
    for (int g = A; g < B; g += 2 * PSTAT + !PSTAT)
#pragma unroll
      for (int a = 0; a < 2; a++) {
        __half2 p1 = u2h(X[g + a]), p2 = __hmul2_rn(p1, p1);
#pragma unroll
        for (int i = 1; i < PSTAT; i++) { const __half2 v = u2h(X[g + a + 2 * i]); p1 = __hadd2_rn(p1, v); p2 = __hfma2(v, v, p2); }
        const float2 f1 = __half22float2(p1), f2 = __half22float2(p2);
        s1[a] = g == 0 ? f1.x + f1.y : s1[a] + (f1.x + f1.y);
        s2[a] = g == 0 ? f2.x + f2.y : s2[a] + (f2.x + f2.y);
      }
  } else {
#pragma unroll
    for (int i = A; i < B; i++) {
      const float2 f = __half22float2(u2h(X[i]));
      s1[i & 1] = i < 2 ? f.x + f.y : s1[i & 1] + (f.x + f.y);
      s2[i & 1] = fmaf(f.x, f.x, i < 2 ? f.y * f.y : fmaf(f.y, f.y, s2[i & 1]));
    }
  }
  asm volatile("" : "+f"(s1[0]), "+f"(s1[1]), "+f"(s2[0]), "+f"(s2[1]));
}
__device__ __forceinline__ uint32_t ln_rstd(const float (&s1)[2], const float (&s2)[2], float lo, float hi, uint32_t vmask, bool& ok) {
  float r[2];
  ok = true;
#pragma unroll
  for (int a = 0; a < 2; a++) {
    float m = s1[a], v = s2[a];
    m += __shfl_xor_sync(~0u, m, 1); v += __shfl_xor_sync(~0u, v, 1);
    m += __shfl_xor_sync(~0u, m, 2); v += __shfl_xor_sync(~0u, v, 2);
    ok = ok && v <= hi && (v >= lo || !(vmask >> (16 * a) & 1));
    m *= 1.0f / 192.0f;
    m *= m;
    v = fmaxf(fmaf(v, 1.0f / 192.0f, -m), 0.f) + 1e-5f;
    ok = ok && m <= (PSTAT ? 16.f : 64.f) * v;
    asm("rsqrt.approx.ftz.f32 %0, %1;" : "=f"(r[a]) : "f"(v));
  }
  uint32_t rk = packh(r[0], r[1]);
  hold<0, 1>(&rk);
  return rk;
}
__device__ __forceinline__ void scale12(uint32_t (&D)[12], const uint32_t* a, uint32_t r) {
#pragma unroll
  for (int i = 0; i < 12; i++) D[i] = (i & 1) ? fmul_b<1>(a[i], r) : fmul_b<0>(a[i], r);
  hold<0, 12>(D);
}
template <int CC>
__device__ __forceinline__ void store_out(const uint32_t (&Y)[48], uint8_t* o0, uint8_t* o1, uint32_t vmask) {
  uint32_t T[8];
#pragma unroll
  for (int i = 0; i < 8; i++) {
    const float2 f = __half22float2(u2h(Y[8 * CC + i]));
    T[i] = pack2(f.x, f.y);
  }
  asm volatile("{\n.reg .pred p;\nsetp.ne.u32 p, %5, 0;\n@p st.global" STHINT ".v4.u32 [%0], {%1,%2,%3,%4};\n}\n"
               :: "l"(o0 + CC * 64), "r"(T[0]), "r"(T[2]), "r"(T[4]), "r"(T[6]), "r"(vmask) : "memory");
  asm volatile("{\n.reg .pred p;\nsetp.lt.s32 p, %5, 0;\n@p st.global" STHINT ".v4.u32 [%0], {%1,%2,%3,%4};\n}\n"
               :: "l"(o1 + CC * 64), "r"(T[1]), "r"(T[3]), "r"(T[5]), "r"(T[7]), "r"(vmask) : "memory");
}
__device__ __forceinline__ void proxy_fence() { asm volatile("fence.proxy.async.shared::cta;" ::: "memory"); }
__device__ __forceinline__ uint32_t fadd2(uint32_t a, uint32_t b) { return h2u(__hadd2_rn(u2h(a), u2h(b))); }
__device__ __forceinline__ void row_max(const uint32_t (&S)[14], uint32_t& k48, uint32_t& mx, uint32_t ninf) {
  k48 = K48TC ? __byte_perm(S[12], S[13], 0x5410) | ninf : __shfl_sync(~0u, __byte_perm(S[12], S[13], 0x5410), 0, 4);
  const uint32_t m0 = fmax2(fmax2(fmax2(S[0], S[2]), S[4]), fmax2(fmax2(S[6], S[8]), S[10]));
  const uint32_t m1 = fmax2(fmax2(fmax2(S[1], S[3]), S[5]), fmax2(fmax2(S[7], S[9]), S[11]));
  mx = fmax2(__byte_perm(m0, m1, 0x5410), __byte_perm(m0, m1, 0x7632));
  if (K48TC) mx = fmax2(mx, k48);
  mx = fmax2(mx, __shfl_xor_sync(~0u, mx, 1));
  mx = fmax2(mx, __shfl_xor_sync(~0u, mx, 2));
  if (!K48TC) mx = fmax2(mx, k48);
  hold<0, 1>(&mx);
}
__device__ __forceinline__ void row_exp(const uint32_t (&S)[14], uint32_t k48, uint32_t mx, uint32_t (&P)[NP], uint32_t& p48) {
#pragma unroll
  for (int j = 0; j < 12; j++) P[j] = fex2((j & 1) ? fsub_b<1>(S[j], mx) : fsub_b<0>(S[j], mx));
  if (K48TC) {
    uint16_t el, eh;
    asm("{\n.reg .b16 l, h;\nmov.b32 {l, h}, %2;\nex2.approx.f16 %0, l;\nex2.approx.f16 %1, h;\n}\n" : "=h"(el), "=h"(eh) : "r"(h2u(__hsub2_rn(u2h(k48), u2h(mx)))));
    P[NP - 4] = el; P[NP - 3] = eh; P[NP - 2] = 0; P[NP - 1] = 0;
  } else {
    p48 = fex2(h2u(__hsub2_rn(u2h(k48), u2h(mx))));
    hold<0, 1>(&p48);
  }
  hold<0, NP>(P);
}
template <int S0, int S1>
__device__ __forceinline__ void load_x(uint32_t (&X)[48], uint32_t t0) {
#pragma unroll
  for (int s = S0; s < S1; s++)
    asm volatile("ld.shared.v4.u32 {%0,%1,%2,%3}, [%4];" : "=r"(X[4 * s]), "=r"(X[4 * s + 1]), "=r"(X[4 * s + 2]), "=r"(X[4 * s + 3])
                 : "r"(((s & 1) ? (t0 ^ 16) : t0) + (s >> 1) * 128) : "memory");
}

#define WDIV 1
template <int P, int CNT, int DIV = WDIV> __device__ __forceinline__ void load_slices(uint32_t sb, const Descs& ds) {
  constexpr int st = stage_of(P);
  constexpr bool first = P == 0 || stage_of(P - 1) != st;
  if (first)
    asm volatile("{\n.reg .pred p;\nelect.sync _|p, 0xffffffff;\n@p mbarrier.arrive.expect_tx.shared::cta.b64 _, [%0], %1;\n}\n"
                 :: "r"(sb + BAR_WFULL + 8 * st), "n"((st < 4 ? 3 : st == 4 ? 2 : 1) * SLICE / DIV) : "memory");
  asm volatile("{\n.reg .pred p;\nelect.sync _|p, 0xffffffff;\n"
               "@p cp.async.bulk.shared::cluster.global.mbarrier::complete_tx::bytes [%0], [%1], %2, [%3];\n}\n"
               :: "r"(sb + OFF_W + (P & 7) * SLICE), "l"(ds.src[P]), "n"(CNT * SLICE / DIV), "r"(sb + BAR_WFULL + 8 * st) : "memory");
}
__device__ __forceinline__ void warp_arrive(uint32_t bar) {
  asm volatile("{\n.reg .pred p;\nelect.sync _|p, 0xffffffff;\n@p mbarrier.arrive.shared::cta.b64 _, [%0];\n}\n" :: "r"(bar) : "memory");
}

__device__ __forceinline__ float2 fp16_limits(int lane) {
  float mx[4] = {0.f, 0.f, 0.f, 0.f}, sm[4] = {0.f, 0.f, 0.f, 0.f};
#pragma unroll
  for (int i = 0; i < 3; i++) {
    const int nb = lane + 32 * i, part = nb < 72 ? (nb % 18) / 6 : 3;
    const float2 w = g_wnorm[nb];
#pragma unroll
    for (int k = 0; k < 4; k++) if (part == k) { mx[k] = fmaxf(mx[k], w.x); sm[k] += w.y; }
  }
#pragma unroll
  for (int k = 0; k < 4; k++)
#pragma unroll
    for (int d = 16; d; d >>= 1) { mx[k] = fmaxf(mx[k], __shfl_xor_sync(~0u, mx[k], d)); sm[k] += __shfl_xor_sync(~0u, sm[k], d); }
  const float big = fmaxf(fmaxf(mx[0], mx[1]), mx[2]);
  float small = 1.f;
  bool good = sm[0] + sm[1] + sm[2] + sm[3] < 1e30f;
#pragma unroll
  for (int k = 0; k < 4; k++) { good = good && (mx[k] == 0.f || mx[k] >= 2.5e-4f); if (k < 3 && mx[k] > 0.f) small = fminf(small, mx[k]); }
  good = good && 250.f * 48.f * sqrtf(mx[0] * mx[1]) <= 5e4f;
  good = good && 16.f * 49.f * sqrtf(mx[2]) <= 5e4f && big <= 1e6f;
  good = good && 16.f * sqrtf(sm[2] * mx[3]) <= 2e4f;
  return make_float2(192.f * 2.4e-7f / small, good ? fminf(2.5e8f, 9e8f / fmaxf(big, 1e-30f)) : -1.f);
}

__device__ __forceinline__ void slow_window(float* sm, int w, int t, const __nv_bfloat16* __restrict__ x, const __nv_bfloat16* __restrict__ dw,
                                            const __nv_bfloat16* __restrict__ wqkv, const __nv_bfloat16* __restrict__ wo, __nv_bfloat16* __restrict__ out) {
  float* x0 = sm; float* h = x0 + 49 * CH; float* qkv = h + 49 * CH; float* S = qkv + 49 * 576;
  const int wy = w / NWX, wx = w % NWX;
  auto sync = [] { asm volatile("bar.sync 6, 128;" ::: "memory"); };
#pragma unroll 1
  for (int i = t; i < 49 * CH; i += 128) {
    const int k = i / CH, c = i % CH, y = wy * 7 + k / 7, xx = wx * 7 + k % 7;
    float pe = 0.f;
#pragma unroll 1
    for (int a = 0; a < 9; a++) {
      const int yy = y + a / 3 - 1, xc = xx + a % 3 - 1;
      if (yy >= 0 && yy < IMG && xc >= 0 && xc < IMG) pe = fmaf(__bfloat162float(x[((size_t)yy * IMG + xc) * CH + c]), __bfloat162float(dw[a * CH + c]), pe);
    }
    x0[i] = __bfloat162float(__float2bfloat16(__bfloat162float(x[((size_t)y * IMG + xx) * CH + c]) + pe));
  }
  sync();
  if (t < 49) {
    float m = 0.f, v = 0.f;
#pragma unroll 1
    for (int c = 0; c < CH; c++) m += x0[t * CH + c];
    m *= 1.0f / CH;
#pragma unroll 1
    for (int c = 0; c < CH; c++) { const float d = x0[t * CH + c] - m; v = fmaf(d, d, v); }
    const float rs = 1.0f / sqrtf(v * (1.0f / CH) + 1e-5f);
#pragma unroll 1
    for (int c = 0; c < CH; c++) h[t * CH + c] = (x0[t * CH + c] - m) * rs;
  }
  sync();
#pragma unroll 1
  for (int i = t; i < 7 * 576; i += 128) {
    const int n = i % 576, k0 = i / 576 * 7;
    float a[7] = {0.f, 0.f, 0.f, 0.f, 0.f, 0.f, 0.f};
#pragma unroll 1
    for (int c = 0; c < CH; c++) {
      const float wv = __bfloat162float(wqkv[c * 576 + n]);
#pragma unroll
      for (int k = 0; k < 7; k++) a[k] = fmaf(h[(k0 + k) * CH + c], wv, a[k]);
    }
#pragma unroll
    for (int k = 0; k < 7; k++) qkv[(k0 + k) * 576 + n] = a[k];
  }
  sync();
#pragma unroll 1
  for (int hd = 0; hd < 4; hd++) {
#pragma unroll 1
    for (int i = t; i < 49 * 49; i += 128) {
      const int a = i / 49, b = i % 49;
      float v = 0.f;
#pragma unroll 1
      for (int d = 0; d < 48; d++) v = fmaf(qkv[a * 576 + hd * 48 + d], qkv[b * 576 + 192 + hd * 48 + d], v);
      S[i] = v * 0.14433756729740643f;
    }
    sync();
    if (t < 49) {
      float m = S[t * 49], l = 0.f;
#pragma unroll 1
      for (int b = 1; b < 49; b++) m = fmaxf(m, S[t * 49 + b]);
#pragma unroll 1
      for (int b = 0; b < 49; b++) { const float e = expf(S[t * 49 + b] - m); S[t * 49 + b] = e; l += e; }
#pragma unroll 1
      for (int b = 0; b < 49; b++) S[t * 49 + b] /= l;
    }
    sync();
#pragma unroll 1
    for (int i = t; i < 49 * 48; i += 128) {
      const int a = i / 48, d = i % 48;
      float v = 0.f;
#pragma unroll 1
      for (int b = 0; b < 49; b++) v = fmaf(S[a * 49 + b], qkv[b * 576 + 384 + hd * 48 + d], v);
      h[a * CH + hd * 48 + d] = v;
    }
    sync();
  }
#pragma unroll 1
  for (int i = t; i < 7 * CH; i += 128) {
    const int n = i % CH, k0 = i / CH * 7;
    float a[7] = {0.f, 0.f, 0.f, 0.f, 0.f, 0.f, 0.f};
#pragma unroll 1
    for (int c = 0; c < CH; c++) {
      const float wv = __bfloat162float(wo[c * CH + n]);
#pragma unroll
      for (int k = 0; k < 7; k++) a[k] = fmaf(h[(k0 + k) * CH + c], wv, a[k]);
    }
#pragma unroll
    for (int k = 0; k < 7; k++)
      out[((size_t)(wy * 7 + k0 / 7) * IMG + wx * 7 + k) * CH + n] = __float2bfloat16(x0[(k0 + k) * CH + n] + a[k]);
  }
  sync();
}

__global__ void __launch_bounds__(384, 1)
fused_kernel(const __grid_constant__ CUtensorMap tmx, const __grid_constant__ CUtensorMap tmp, const __grid_constant__ Descs ds, const __nv_bfloat16* __restrict__ dw, __nv_bfloat16* __restrict__ out, const int never,
             const __nv_bfloat16* __restrict__ x, const __nv_bfloat16* __restrict__ wqkv, const __nv_bfloat16* __restrict__ wo) {
  extern __shared__ __align__(1024) uint8_t smem[];
  const uint32_t sb = (uint32_t)__cvta_generic_to_shared(smem);
  const int tid = threadIdx.x, lane = tid & 31;
  const int warp = __shfl_sync(0xffffffffu, tid >> 5, 0);
  const int cta = blockIdx.x, ncta = gridDim.x;
  const int nfull = NWIN / (2 * ncta);
  const int nrounds = nfull + ((NWIN - nfull * 2 * ncta) > cta ? 1 : 0);

  if (warp == 0) GTS(0);
  if (warp == 10 && lane == 0) asm volatile("prefetch.tensormap [%0];" :: "l"(reinterpret_cast<uint64_t>(&tmx)) : "memory");
  if (tid == 0) {
    mbar_init(sb + BAR_FIRST, 1);
    asm volatile("fence.mbarrier_init.release.cluster;" ::: "memory");
    asm volatile("mbarrier.arrive.expect_tx.shared::cta.b64 _, [%0], %1;" :: "r"(sb + BAR_FIRST), "n"(2 * HALO_BYTES) : "memory");
#pragma unroll
    for (int k = 0; k < 2; k++) {
      const int w = max(window_of(0, nfull, cta, ncta, k), 0), a = w / NWX;
      asm volatile("cp.async.bulk.tensor.3d.shared::cluster.global.mbarrier::complete_tx::bytes [%0], [%1, {0, %3, %4}], [%2];"
                   :: "r"(sb + OFF_HALO + k * HALO_BYTES), "l"(reinterpret_cast<uint64_t>(&tmp)), "r"(sb + BAR_FIRST),
                      "r"((w - a * NWX) * 7 - 1), "r"(a * 7 - 1) : "memory");
    }
    if ((sb & 0x3FFFF) != SMEM_BASE || nrounds > 128) __trap();
    for (int i = 0; i < 7; i++) { mbar_init(sb + BAR_WFULL + 8 * i, 1); mbar_init(sb + BAR_WEMPTY + 8 * i, 8); }
    for (int i = 0; i < 9; i++) mbar_init(sb + BAR_XFULL + 8 * i, 1);
    mbar_init(sb + BAR_TFULL, 3);
    mbar_init(sb + BAR_TEMPTY, 8);
    asm volatile("fence.mbarrier_init.release.cluster;" ::: "memory");
  }
  if (tid >= 128 && tid < 320) {
    *reinterpret_cast<uint32_t*>(smem + OFF_ZERO + (tid - 128) * 4) = 0;
    if (tid < 136) *reinterpret_cast<uint32_t*>(smem + OFF_REDO + (tid - 128) * 4) = 0;
  }
  if (tid < 128) {
    *reinterpret_cast<uint4*>(smem + OFF_KV + (tid / 64) * KV_BYTES + 6 * KV_PITCH + (tid % 64) * 16) = make_uint4(0x3c003c00u, 0x3c003c00u, 0x3c003c00u, 0x3c003c00u);
    proxy_fence();
  }
  __syncthreads();

  if (warp < 11) {
#pragma unroll 1
    for (int u = 0; u < (warp < 10 ? 2 : 1); u++) {
      const int cb = warp < 9 ? warp % 3 : 2 * (warp - 9) + u, y = warp < 9 ? 2 * (warp / 3) + u : 6;
      const int ch0 = cb * 64 + (lane & 15) * 4;
      uint32_t wt[9][2], px[3][9][2];
#pragma unroll
      for (int t = 0; t < 9; t++) {
        const uint2 v = *reinterpret_cast<const uint2*>(dw + t * CH + ch0);
        wt[t][0] = v.x; wt[t][1] = v.y;
      }
      mbar_wait(sb + BAR_FIRST, 0);
      const uint32_t ld = sb + OFF_HALO + (lane >> 4) * HALO_BYTES + y * 3456 + ch0 * 2;
#pragma unroll
      for (int p = 0; p < 27; p++)
        asm volatile("ld.shared.v2.u32 {%0,%1}, [%2];" : "=r"(px[p / 9][p % 9][0]), "=r"(px[p / 9][p % 9][1]) : "r"(ld + p * 384));
      const uint32_t st0 = sb + OFF_TILE + (lane >> 4) * TILE_BYTES + ch0 * 4;
      const uint32_t sa = (st0 ^ ((y & 1) << 4)) + y * 2304;
      uint32_t o[2][2];
#pragma unroll
      for (int j = 0; j < 7; j++) {
#pragma unroll
        for (int e = 0; e < 2; e++) {
          uint32_t a = hmul(px[0][j][e], wt[0][e]);
#pragma unroll
          for (int t = 1; t < 9; t++) a = hfma(px[t / 3][j + t % 3][e], wt[t][e], a);
          a = hadd(px[1][j + 1][e], a);
          o[j & 1][e] = packh(lo2f(a), hi2f(a));
        }
        if (j & 1)
          asm volatile("st.shared.v4.u32 [%0], {%1,%2,%3,%4};" :: "r"((j == 3 ? sa ^ 16 : sa) + (j >> 1) * 768),
                       "r"(o[0][0]), "r"(o[1][0]), "r"(o[0][1]), "r"(o[1][1]) : "memory");
      }
      const uint32_t sb6 = (st0 ^ ((~y & 2) << 3)) + (21 + (y >> 1)) * 768 + (y & 1) * 4;
      asm volatile("st.shared.u32 [%0], %1;\nst.shared.u32 [%0 + 8], %2;" :: "r"(sb6), "r"(o[0][0]), "r"(o[0][1]) : "memory");
      if (y == 6) asm volatile("st.shared.u32 [%0 + 4], %1;\nst.shared.u32 [%0 + 12], %1;" :: "r"(sb6), "r"(0) : "memory");
    }
    asm volatile("bar.arrive 8, 384;\nbar.sync 7, 352;" ::: "memory");
  }

  if (warp >= 8) {
    asm volatile("setmaxnreg.dec.sync.aligned.u32 " PREGS ";");
    if (warp == 11) {
      asm volatile("griddepcontrol.wait;" ::: "memory");
      load_slices<1, 3, 1>(sb, ds);
      *reinterpret_cast<float2*>(smem + OFF_LIM) = fp16_limits(lane);
      load_slices<0, 1, 1>(sb, ds);
      asm volatile("bar.sync 8, 384;" ::: "memory");
      load_slices<5, 3, 1>(sb, ds); load_slices<4, 1, 1>(sb, ds);
      for (int r = 0; r < nrounds; r++) {
        const uint32_t par = r & 1;
        const bool next_round = r + 1 < nrounds;
        mbar_wait(sb + BAR_WEMPTY + 40, par); load_slices<8, 1>(sb, ds);
        mbar_wait(sb + BAR_WEMPTY, par);      load_slices<9, 2>(sb, ds); load_slices<11, 1>(sb, ds);
        mbar_wait(sb + BAR_WEMPTY + 48, par); load_slices<12, 1>(sb, ds);
        mbar_wait(sb + BAR_WEMPTY + 8, par);  load_slices<13, 1>(sb, ds); load_slices<14, 2>(sb, ds);
        mbar_wait(sb + BAR_WEMPTY + 16, par); load_slices<0, 1>(sb, ds); if (next_round) load_slices<1, 2>(sb, ds);
        mbar_wait(sb + BAR_WEMPTY + 24, par);
        if (next_round) load_slices<3, 1>(sb, ds);
        load_slices<4, 1>(sb, ds);
        if (next_round) {
          load_slices<5, 1>(sb, ds);
          mbar_wait(sb + BAR_WEMPTY + 32, par); load_slices<6, 2>(sb, ds);
        }
      }
    } else {
      const int cw = warp - 8;
      const int win = lane >> 4;
      const int ch0 = cw * 64 + (lane & 15) * 4;
      uint32_t wt[9][2];
#pragma unroll
      for (int t = 0; t < 9; t++) {
        uint2 v = *reinterpret_cast<const uint2*>(dw + t * CH + ch0);
        wt[t][0] = v.x; wt[t][1] = v.y;
      }
      const uint32_t xs = sb + OFF_X + cw * 3 * XSLOT;
      const uint32_t xld = xs + (lane >> 4) * 1152 + (lane & 15) * 8;
      const uint32_t xbar = sb + BAR_XFULL + cw * 24;
      const uint32_t st0 = sb + OFF_TILE + win * TILE_BYTES + ch0 * 4;
      const uint64_t tm = reinterpret_cast<uint64_t>(&tmx);
      int cx0, cy0, cx1, cy1;
      auto coords = [&](int r) {
        const int w0 = window_of(r, nfull, cta, ncta, 0);
        int w1 = window_of(r, nfull, cta, ncta, 1);
        if (w1 < 0) w1 = w0;
        const int a = w0 / NWX, b = w1 / NWX;
        cx0 = (w0 - a * NWX) * 7 - 1; cy0 = a * 7 - 1;
        cx1 = (w1 - b * NWX) * 7 - 1; cy1 = b * 7 - 1;
      };
      auto issue = [&](int slot, int dy) {
        asm volatile("{\n.reg .pred p;\nelect.sync _|p, 0xffffffff;\n"
                     "@p mbarrier.arrive.expect_tx.shared::cta.b64 _, [%2], %8;\n"
                     "@p cp.async.bulk.tensor.3d.shared::cluster.global.mbarrier::complete_tx::bytes [%0], [%1, {%3, %4, %5}], [%2];\n"
                     "@p cp.async.bulk.tensor.3d.shared::cluster.global.mbarrier::complete_tx::bytes [%0 + 1152], [%1, {%3, %6, %7}], [%2];\n}\n"
                     :: "r"(xs + slot * XSLOT), "l"(tm), "r"(xbar + slot * 8), "r"(cw * 64), "r"(cx0), "r"(cy0 + dy), "r"(cx1), "r"(cy1 + dy), "n"(XSLOT) : "memory");
      };
      uint32_t accA[7][2], accB[7][2], ctr[7][2], held[2];
      auto row = [&](auto fin, auto mid, auto top, int slot, int y) {
        const uint32_t ld = xld + slot * XSLOT;
        const uint32_t sa = (st0 ^ ((y & 1) << 4)) + y * 2304;
        uint32_t cur[9][2], o[2][2];
#pragma unroll
        for (int p = 0; p < LA; p++)
          asm volatile("ld.shared.v2.u32 {%0,%1}, [%2];" : "=r"(cur[p][0]), "=r"(cur[p][1]) : "r"(ld + p * 128));
#pragma unroll
        for (int j = 0; j < 7; j++) {
          if (j >= 1 && j + LA - 1 < 9)
            asm volatile("ld.shared.v2.u32 {%0,%1}, [%2];" : "=r"(cur[j + LA - 1][0]), "=r"(cur[j + LA - 1][1]) : "r"(ld + (j + LA - 1) * 128));
          if (fin.v) {
#pragma unroll
            for (int e = 0; e < 2; e++) {
              uint32_t a = hfma(cur[j][e], wt[6][e], accA[j][e]);
              a = hfma(cur[j + 1][e], wt[7][e], a);
              a = hfma(cur[j + 2][e], wt[8][e], a);
              if (!EARLYX) a = hadd(ctr[j][e], a);
              o[j & 1][e] = packh(lo2f(a), hi2f(a));
            }
            if (j & 1)
              asm volatile("st.shared.v4.u32 [%0], {%1,%2,%3,%4};" :: "r"((j == 3 ? sa ^ 16 : sa) + (j >> 1) * 768),
                           "r"(o[0][0]), "r"(o[1][0]), "r"(o[0][1]), "r"(o[1][1]) : "memory");
            if (j == 6) {
              const uint32_t sb6 = (st0 ^ ((~y & 2) << 3)) + (21 + (y >> 1)) * 768;
              if (fin.v == 2)
                asm volatile("st.shared.v4.u32 [%0], {%1,%2,%3,%2};" :: "r"(sb6), "r"(o[0][0]), "r"(0), "r"(o[0][1]) : "memory");
              else
                asm volatile("{\n.reg .pred p;\nsetp.ne.s32 p, %5, 0;\n@p st.shared.v4.u32 [%0], {%1,%2,%3,%4};\n}\n"
                             :: "r"(sb6), "r"(held[0]), "r"(o[0][0]), "r"(held[1]), "r"(o[0][1]), "r"(y & 1) : "memory");
              held[0] = o[0][0]; held[1] = o[0][1];
            }
          }
#pragma unroll
          for (int e = 0; e < 2; e++) {
            if (mid.v) {
              uint32_t a = hfma(cur[j][e], wt[3][e], accB[j][e]);
              a = hfma(cur[j + 1][e], wt[4][e], a);
              a = hfma(cur[j + 2][e], wt[5][e], a);
              accA[j][e] = EARLYX == 1 ? hadd(cur[j + 1][e], a) : a;
              if (!EARLYX) ctr[j][e] = cur[j + 1][e];
            }
            if (top.v) {
              uint32_t a = hmul(cur[j][e], wt[0][e]);
              a = hfma(cur[j + 1][e], wt[1][e], a);
              accB[j][e] = hfma(cur[j + 2][e], wt[2][e], a);
            }
          }
        }
      };
      held[0] = held[1] = 0;
      if (nrounds > 1) { coords(1); issue(0, 0); issue(1, 1); issue(2, 2); }
      for (int r = 0; r + 1 < nrounds; r++) {
        const bool more = r + 2 < nrounds;
        mbar_wait(xbar, r & 1);
        if (r > 0) issue(2, 2);
        row(IC<0>{}, IC<0>{}, IC<1>{}, 0, 0);
        mbar_wait(xbar + 8, r & 1);
        issue(0, 3);
        row(IC<0>{}, IC<1>{}, IC<1>{}, 1, 0);
        mbar_wait(sb + BAR_TEMPTY, r & 1);
        TR(0);
#pragma unroll 1
        for (int k = 0; k < 2; k++) {
          mbar_wait(xbar + 16, (r + k) & 1);
          issue(1, 4 + 3 * k);
          row(IC<1>{}, IC<1>{}, IC<1>{}, 2, 3 * k);
          mbar_wait(xbar, (r + k + 1) & 1);
          issue(2, 5 + 3 * k);
          row(IC<1>{}, IC<1>{}, IC<1>{}, 0, 3 * k + 1);
          mbar_wait(xbar + 8, (r + k + 1) & 1);
          if (k == 1 && more) coords(r + 2);
          if (k == 0 || more) issue(0, k == 0 ? 6 : 0);
          row(IC<1>{}, IC<1>{}, IC<1>{}, 1, 3 * k + 2);
        }
        mbar_wait(xbar + 16, r & 1);
        if (more) issue(1, 1);
        row(IC<2>{}, IC<0>{}, IC<0>{}, 2, 6);
        __syncwarp();
        warp_arrive(sb + BAR_TFULL);
        TR(1);
      }
    }
    asm volatile("bar.sync 5, 384;" ::: "memory");
#pragma unroll 1
    for (int i = 0; i < 8; i++) {
      uint32_t bits = *reinterpret_cast<volatile uint32_t*>(smem + OFF_REDO + 4 * i);
#pragma unroll 1
      for (; bits; bits &= bits - 1)
        slow_window(reinterpret_cast<float*>(smem), window_of((i & 3) * 32 + __ffs(bits) - 1, nfull, cta, ncta, i >> 2), tid - 256, x, dw, wqkv, wo, out);
    }
  } else {
    asm volatile("setmaxnreg.inc.sync.aligned.u32 " CREGS ";");
    const int wg = warp >> 2, w4 = warp & 3, g = lane >> 2, q = lane & 3;
    const int row0 = w4 * 16 + g, row1 = row0 + 8;
    const int ps = min(w4 * 8 + g, 24);
    const int pix0 = ps < 21 ? (ps / 3) * IMG + (ps % 3) * 2 : (ps - 21) * 2 * IMG + 6;
    const int pix1 = pix0 + (ps < 21 ? 1 : ps < 24 ? IMG : 0);
    const uint32_t kv = sb + OFF_KV + wg * KV_BYTES;
    const int srow = w4 * 16 + (lane & 15);
    const uint32_t vst = kv + (lane >> 4) * KV_PITCH + (srow < 56 ? srow : min(srow - 7, 55)) * 16;
    uint32_t misc = ((uint32_t)pix1 << 20) | ((uint32_t)pix0 << 8) | q;
    const uint32_t ninf = q ? 0xfc00fc00u : 0u;
    const uint32_t v48 = kv + (lane >> 3) * KV_PITCH + 48 * 16;
    const uint32_t vmask = (row0 < 49 ? 0xffffu : 0u) | (row1 < 49 ? 0xffff0000u : 0u);

    const uint32_t tx = sb + q * 32 + (row0 < 49 ? OFF_TILE + wg * TILE_BYTES + ps * 768 + (ps & 1) * 16 : OFF_ZERO + 16);
    const int myrounds = window_of(nrounds - 1, nfull, cta, ncta, wg) < 0 ? nrounds - 1 : nrounds;

    if (never == 2) return;
    uint32_t H[48], Y[48];
    const uint64_t* dkv = ds.kv[wg];
    uint32_t P[NP], Ofc[12], p48 = 0;
#pragma unroll
    for (int i = 0; i < 48; i++) Y[i] = 0;
#pragma unroll
    for (int i = 0; i < NP; i++) P[i] = Ofc[i % 12] = 0;
    if (warp == 0) GTS(4);
    load_x<0, 12>(H, tx);
    warp_arrive(sb + BAR_TEMPTY);
    if (wg == 1) turn_pass(1);

    uint8_t *o0, *o1;
    uint32_t omask;
    auto out_setup = [&](int r) {
      omask = r >= 0 ? vmask : 0u;
      const int w = window_of(r, nfull, cta, ncta, wg);
      const int wy = w / NWX, wx = w - wy * NWX;
      asm volatile("" : "+r"(misc));
      const uint32_t wb = (uint32_t)(wy * 7 * IMG + wx * 7) * 384u + (misc & 3) * 16;
      o0 = reinterpret_cast<uint8_t*>(out) + (wb + ((misc >> 8) & 0xfff) * 384u);
      o1 = reinterpret_cast<uint8_t*>(out) + (wb + (misc >> 20) * 384u);
    };
#define OUT(c) store_out<c>(Y, o0, o1, omask)
    auto release = [&](int stage) { warp_arrive(sb + BAR_WEMPTY + 8 * stage); };

    for (int r = 0;; r++) {
      const uint32_t par = r & 1;
      uint32_t acc[36], S[14], O[14], Q[12], V[12], Ofa[12], Ofb[12], vr[6], k48, mx;
      if (r == myrounds) {
        const bool idle = r < nrounds;
        mbar_wait(sb + BAR_WFULL + 40, par);
        turn_wait(wg);
        wg_fence(); mma_pv(O, P, dkv + 4); mma_proj(Y, Ofc, ds.p + 6); wg_commit();
        turn_pass(wg);
        load_v48(vr, v48);
        wg_wait<0>(); keep(O); keep(Y);
        finish_o(O, vr, p48, vmask, Ofa);
        if (idle) { release(5); release(0); release(1); release(2); release(3); }
        mbar_wait(sb + BAR_WFULL + 48, par);
        turn_wait(wg);
        wg_fence(); mma_proj(Y, Ofa, ds.p + 9); wg_commit();
        if (wg == 0 || idle) turn_pass(wg);
        wg_wait<0>(); keep(Y);
        if (idle) { release(6); turn_wait(wg); turn_pass(wg); }
        out_setup(r - 1);
        OUT(0); PIN(); OUT(1); PIN(); OUT(2); PIN(); OUT(3); PIN(); OUT(4); PIN(); OUT(5);
        if (idle) {
          turn_wait(wg); turn_pass(wg);
          turn_wait(wg); turn_pass(wg);
          turn_wait(wg); turn_pass(wg);
          turn_wait(wg);
        }
        if (w4 == 0) GTS(5 + wg);
        asm volatile("bar.arrive 5, 384;" ::: "memory");
        break;
      }
      float s1[2], s2[2];
      if (SA > 0) ln_sums<0, SA>(H, s1, s2);
      mbar_wait(sb + BAR_WFULL + 40, par);
      mbar_wait(sb + BAR_WFULL, par);
      TR(0);
      turn_wait(wg);
      TR(1);
      wg_fence(); mma_pv(O, P, dkv + 4); mma_proj(Y, Ofc, ds.p + 6); wg_commit(); mma_qkv<0, 3>(acc, H, ds.q[0]);
      PIN();
      ln_sums<SA, SB>(H, s1, s2);
      PIN();
      wg_fence(); mma_qkv<3, 8>(acc, H, ds.q[0]);
      PIN();
      ln_sums<SB, SC>(H, s1, s2);
      PIN();
      wg_fence(); mma_qkv<8, 12>(acc, H, ds.q[0]);
      turn_pass(wg);
      TR(2);
      load_v48(vr, v48);
      wg_wait<3>(); keep(O); keep(Y);
      release(5);
      wg_sync(wg);
      PIN();
      finish_o(O, vr, p48, vmask, Ofa);
      if (SC < 48) ln_sums<SC, 48>(H, s1, s2);
      float lim_lo, lim_hi;
      asm volatile("ld.shared.v2.f32 {%0,%1}, [%2];" : "=f"(lim_lo), "=f"(lim_hi) : "r"(sb + OFF_LIM) : "memory");
      bool ok;
      const uint32_t rk = ln_rstd(s1, s2, lim_lo, lim_hi, vmask, ok);
      asm volatile("{\n.reg .pred p;\nsetp.eq.s32 p, %2, 0;\n@p red.shared.or.b32 [%0], %1;\n}\n"
                   :: "r"(sb + OFF_REDO + wg * 16 + (r >> 5) * 4), "r"(1u << (r & 31)), "r"((int)ok) : "memory");
      PIN();
      TR(3);
      wg_wait<0>(); keep(acc);
      TR(4);
      release(0);
      scale12(V, acc, rk); stsm12(V, vst + KV_KOFF);
      scale12(V, acc + 24, rk); stsm12(V, vst);
      scale12(Q, acc + 12, rk); PIN();
      proxy_fence();
      mbar_wait(sb + BAR_WFULL + 48, par);
      mbar_wait(sb + BAR_WFULL + 8, par);
      TR(5);
      turn_wait(wg);
      TR(6);
      wg_fence(); mma_proj(Y, Ofa, ds.p + 9); wg_commit(); mma_s(S, Q, dkv); mma_qkv<0, 2>(acc, H, ds.q[1]);
      out_setup(r - 1);
      PIN();
      wg_wait<1>(); keep(Y);
      release(6);
      wg_fence(); mma_qkv<2, 6>(acc, H, ds.q[1]);
      PIN();
      OUT(0);
      PIN();
      wg_wait<1>(); keep(S);
      wg_fence(); mma_qkv<6, 9>(acc, H, ds.q[1]);
      PIN();
      row_max(S, k48, mx, ninf);
      OUT(1);
      PIN();
      wg_fence(); mma_qkv<9, 12>(acc, H, ds.q[1]);
      turn_pass(wg);
      PIN();
      OUT(2); PIN();
      OUT(3); PIN();
      row_exp(S, k48, mx, P, p48);
      PIN();
      TR(7);
      wg_wait<0>(); keep(acc);
      TR(8);
      release(1);
      wg_sync(wg);
      scale12(V, acc, rk); stsm12(V, vst + KV_KOFF);
      scale12(Q, acc + 12, rk); scale12(V, acc + 24, rk); PIN();
      proxy_fence();
#define TURN(ID, OF, G1, G2, G3, X1)                                                       \
      TR(ID + 1);                                                                       \
      turn_wait(wg);                                                                    \
      wg_fence(); mma_pv(O, P, dkv + 4); mma_s(S, Q, dkv); wg_commit(); G1;             \
      PIN();                                                                            \
      TR(ID + 2);                                                                       \
      load_v48(vr, v48);                                                                \
      X1;                                                                               \
      PIN();                                                                            \
      wg_wait<1>(); keep(S); keep(O);                                                   \
      wg_sync(wg);                                         \
      wg_fence(); G2;                                                                   \
      if (KB == 12) turn_pass(wg);                                                      \
      PIN();                                                                            \
      stsm12(V, vst);                                                                   \
      finish_o(O, vr, p48, vmask, OF);                                                    \
      row_max(S, k48, mx, ninf);                                                              \
      PIN();                                                                            \
      if (KB < 12) { wg_fence(); G3; turn_pass(wg); }                                                                 \
      PIN();                                                                            \
      TR(ID + 3);
#define NEXT_HEAD(ID, HD, X2)                                                           \
      row_exp(S, k48, mx, P, p48);                                                      \
      PIN();                                                                            \
      X2;                                                                               \
      TR(ID + 4);                                                                       \
      wg_wait<0>(); keep(acc);                                                          \
      release(HD);                                                                      \
      scale12(V, acc, rk); stsm12(V, vst + KV_KOFF);                                    \
      scale12(Q, acc + 12, rk); scale12(V, acc + 24, rk); PIN();
      mbar_wait(sb + BAR_WFULL + 16, par);
      TURN(8, Ofa, (mma_qkv<0, KA>(acc, H, ds.q[2])), (mma_qkv<KA, KB>(acc, H, ds.q[2])), (mma_qkv<KB, 12>(acc, H, ds.q[2])), OUT(4))
      OUT(5); PIN();
      NEXT_HEAD(8, 2, )
      proxy_fence();
      mbar_wait(sb + BAR_WFULL + 24, par);
      TURN(12, Ofb, (mma_qkv<0, KA>(acc, H, ds.q[3])), (mma_qkv<KA, KB>(acc, H, ds.q[3])), (mma_qkv<KB, 12>(acc, H, ds.q[3])), )
      auto init_y = [&]() {
#pragma unroll
        for (int i = 0; i < 48; i++) Y[i] = (i & 1) ? H[i] ^ never : h2u(__hadd2_rn(u2h(H[i]), u2h(never)));
        hold<0, 48>(Y); PIN();
      };
      NEXT_HEAD(12, 3, if (YEARLY) init_y())
      if (!YEARLY) init_y();
      proxy_fence();
      mbar_wait(sb + BAR_WFULL + 32, par);
      TR(17);
      turn_wait(wg);
      wg_fence(); mma_pv(O, P, dkv + 4); mma_s(S, Q, dkv); wg_commit(); mma_proj(Y, Ofa, ds.p); mma_proj(Y, Ofb, ds.p + 3); wg_commit();
      turn_pass(wg);
      PIN();
      TR(18);
      load_v48(vr, v48);
      if (r + 1 < myrounds) mbar_wait(sb + BAR_TFULL, par);
      load_x<0, 4>(H, tx);
      wg_wait<1>(); keep(S); keep(O);
      wg_sync(wg);
      PIN();
      TR(19);
      row_max(S, k48, mx, ninf);
      finish_o(O, vr, p48, vmask, Ofc);
      stsm12(V, vst);
      PIN();
      load_x<4, 8>(H, tx);
      row_exp(S, k48, mx, P, p48);
      PIN();
      load_x<8, 12>(H, tx);
      warp_arrive(sb + BAR_TEMPTY);
      TR(20);
      wg_wait<0>(); keep(Y);
      release(4);
      proxy_fence();
      TR(21);
#undef TURN
#undef NEXT_HEAD
    }
  }
}

typedef CUresult (*EncodeFn)(CUtensorMap*, CUtensorMapDataType, cuuint32_t, void*, const cuuint64_t*, const cuuint64_t*,
                             const cuuint32_t*, const cuuint32_t*, CUtensorMapInterleave, CUtensorMapSwizzle,
                             CUtensorMapL2promotion, CUtensorMapFloatOOBfill);

}

extern "C" void kernel_launch(void* const* d_in, const int* in_sizes, int n_in, void* d_out, int out_size) {
  const __nv_bfloat16* x = (const __nv_bfloat16*)d_in[0];
  const __nv_bfloat16* dw = (const __nv_bfloat16*)d_in[1];
  const __nv_bfloat16* wqkv = (const __nv_bfloat16*)d_in[2];
  const __nv_bfloat16* wo = (const __nv_bfloat16*)d_in[3];
  static EncodeFn encode = nullptr;
  static int nsm = 0;
  static void* wpack = nullptr;
  if (!encode) {
    void* fn = nullptr;
    cudaDriverEntryPointQueryResult qr;
    cudaGetDriverEntryPoint("cuTensorMapEncodeTiled", &fn, cudaEnableDefault, &qr);
    encode = (EncodeFn)fn;
    int dev = 0;
    cudaGetDevice(&dev);
    cudaDeviceGetAttribute(&nsm, cudaDevAttrMultiProcessorCount, dev);
    cudaGetSymbolAddress(&wpack, g_wpack);
    cudaFuncSetAttribute(fused_kernel, cudaFuncAttributeMaxDynamicSharedMemorySize, SMEM_BYTES);
  }
  CUtensorMap tmx;
  cuuint64_t gdim[3] = {CH, IMG, IMG};
  cuuint64_t gstr[2] = {CH * 2, (cuuint64_t)CH * 2 * IMG};
  cuuint32_t box[3] = {64, 9, 1};
  cuuint32_t estr[3] = {1, 1, 1};
  encode(&tmx, CU_TENSOR_MAP_DATA_TYPE_BFLOAT16, 3, (void*)x, gdim, gstr, box, estr, CU_TENSOR_MAP_INTERLEAVE_NONE,
         CU_TENSOR_MAP_SWIZZLE_NONE, CU_TENSOR_MAP_L2_PROMOTION_L2_128B, CU_TENSOR_MAP_FLOAT_OOB_FILL_NONE);
  Descs ds;
  for (int i = 0; i < 12; i++) {
    for (int h = 0; h < 4; h++) ds.q[h][i] = mkdesc(SMEM_BASE + OFF_W + qkv_pos(h, i) % (8 * SLICE), 128, 256);
    ds.p[i] = mkdesc(SMEM_BASE + OFF_W + wo_pos(i) % (8 * SLICE), 128, 256);
  }
  for (int i = 0; i < 16; i++) ds.src[i] = (const uint8_t*)wpack + i * SLICE;
  for (int g = 0; g < 2; g++)
    for (int i = 0; i < 4; i++) {
      ds.kv[g][i] = mkdesc(SMEM_BASE + OFF_KV + g * KV_BYTES + KV_KOFF + 2 * i * KV_PITCH, KV_PITCH, 128);
      ds.kv[g][4 + i] = mkdesc(SMEM_BASE + OFF_KV + g * KV_BYTES + 256 * i, 128, KV_PITCH);
    }
  CUtensorMap tmp;
  cuuint32_t boxp[3] = {CH, 9, 9};
  encode(&tmp, CU_TENSOR_MAP_DATA_TYPE_BFLOAT16, 3, (void*)x, gdim, gstr, boxp, estr, CU_TENSOR_MAP_INTERLEAVE_NONE,
         CU_TENSOR_MAP_SWIZZLE_NONE, CU_TENSOR_MAP_L2_PROMOTION_L2_128B, CU_TENSOR_MAP_FLOAT_OOB_FILL_NONE);
  prepack_kernel<<<48, dim3(192, 2), 0, cudaStreamPerThread>>>(wqkv, wo);
  cudaLaunchConfig_t cfg = {};
  cfg.gridDim = dim3(nsm); cfg.blockDim = dim3(384); cfg.dynamicSmemBytes = SMEM_BYTES; cfg.stream = cudaStreamPerThread;
  cudaLaunchAttribute at[1];
  at[0].id = cudaLaunchAttributeProgrammaticStreamSerialization;
  at[0].val.programmaticStreamSerializationAllowed = 1;
  cfg.attrs = at; cfg.numAttrs = 1;
  cudaLaunchKernelEx(&cfg, fused_kernel, tmx, tmp, ds, dw, (__nv_bfloat16*)d_out, 0, x, wqkv, wo);
}
```

```cpp
#include <cuda_runtime.h>
#include <cuda_bf16.h>
#include <cuda_fp16.h>
#include <cuda.h>
#include <stdint.h>

#define CREGS "208"
#define PREGS "88"
#define KA 3
#define KB 9
#define SA 0
#define SB 24
#define SC 48
#define K48TC 0
#define EARLYX 0
#define LA 4
#define YEARLY 0
#define STHINT ".cs"
#define SKIP0 1
namespace {
constexpr int NP = K48TC ? 16 : 12;

constexpr int IMG = 511;
constexpr int CH = 192;
constexpr int NWX = 73;
constexpr int NWIN = NWX * NWX;
constexpr int SLICE = 18432;
constexpr int OFF_W = 0;
constexpr int KV_PITCH = 1792, KV_KOFF = 896, KV_BYTES = 6 * KV_PITCH + 1024;
constexpr int OFF_KV = 8 * SLICE;
constexpr int TILE_BYTES = 25 * 768;
constexpr int OFF_TILE = OFF_KV + 2 * KV_BYTES;
constexpr int XSLOT = 2304;
constexpr int OFF_ZERO = OFF_TILE + 2 * TILE_BYTES;
constexpr int OFF_X = OFF_ZERO + 768;
constexpr int OFF_BAR = OFF_X + 9 * XSLOT;
constexpr int BAR_WFULL = OFF_BAR;
constexpr int BAR_WEMPTY = OFF_BAR + 56;
constexpr int BAR_XFULL = OFF_BAR + 112;
constexpr int BAR_TFULL = OFF_BAR + 184;
constexpr int BAR_TEMPTY = OFF_BAR + 192;
constexpr int OFF_LIM = OFF_BAR + 200;
constexpr int OFF_REDO = OFF_BAR + 208;
constexpr int BAR_FIRST = OFF_BAR + 240;
constexpr int OFF_TRACE = OFF_BAR + 248;
constexpr int OFF_HALO = OFF_W + 4 * SLICE, HALO_BYTES = 81 * 384;
constexpr int SMEM_BYTES = OFF_TRACE;

__host__ __device__ constexpr int qkv_pos(int h, int s) { return (h == 0 ? 1 : 3 * h + 2) * SLICE + s * 4608; }
__host__ __device__ constexpr int wo_pos(int s) { return s < 6 ? 14 * SLICE + s * 6144 : s < 9 ? (s - 6) * 6144 : 4 * SLICE + (s - 9) * 6144; }
__host__ __device__ constexpr int stage_of(int p) { return p == 0 ? 5 : p < 4 ? 0 : p == 4 ? 6 : p < 8 ? 1 : p < 11 ? 2 : p < 14 ? 3 : 4; }
constexpr int SMEM_BASE = 1024;
struct Descs { uint64_t q[4][12]; uint64_t p[12]; uint64_t kv[2][8]; const uint8_t* src[16]; };

__device__ uint4 g_wpack[16 * SLICE / 16];
__device__ float2 g_wnorm[96];
#define TR(id)
#define GTS(i)
template <int V> struct IC { static constexpr int v = V; };
typedef __nv_bfloat162 bf2;
__device__ __forceinline__ bf2 u2b(uint32_t u) { return *reinterpret_cast<bf2*>(&u); }
__device__ __forceinline__ uint32_t b2u(bf2 b) { return *reinterpret_cast<uint32_t*>(&b); }
__device__ __forceinline__ uint32_t pack2(float lo, float hi) {
  uint32_t r; asm("cvt.rn.bf16x2.f32 %0, %1, %2;" : "=r"(r) : "f"(hi), "f"(lo)); return r;
}
__device__ __forceinline__ uint32_t hadd(uint32_t a, uint32_t b) { return b2u(__hadd2_rn(u2b(a), u2b(b))); }
__device__ __forceinline__ uint32_t hmul(uint32_t a, uint32_t b) { return b2u(__hmul2_rn(u2b(a), u2b(b))); }
__device__ __forceinline__ uint32_t hfma(uint32_t a, uint32_t b, uint32_t c) { return b2u(__hfma2(u2b(a), u2b(b), u2b(c))); }
__device__ __forceinline__ __half2 u2h(uint32_t u) { return *reinterpret_cast<__half2*>(&u); }
__device__ __forceinline__ uint32_t h2u(__half2 b) { return *reinterpret_cast<uint32_t*>(&b); }
__device__ __forceinline__ uint32_t packh(float lo, float hi) {
  uint32_t r; asm("cvt.rn.f16x2.f32 %0, %1, %2;" : "=r"(r) : "f"(hi), "f"(lo)); return r;
}
__device__ __forceinline__ uint32_t fmax2(uint32_t a, uint32_t b) { return h2u(__hmax2(u2h(a), u2h(b))); }
template <int HI> __device__ __forceinline__ __half2 hcast(uint32_t a) { return HI ? __high2half2(u2h(a)) : __low2half2(u2h(a)); }
template <int HI> __device__ __forceinline__ uint32_t fmul_b(uint32_t a, uint32_t s) { return h2u(__hmul2_rn(u2h(a), hcast<HI>(s))); }
template <int HI> __device__ __forceinline__ uint32_t fsub_b(uint32_t a, uint32_t s) { return h2u(__hsub2_rn(u2h(a), hcast<HI>(s))); }
__device__ __forceinline__ uint32_t fex2(uint32_t a) { uint32_t r; asm("ex2.approx.f16x2 %0, %1;" : "=r"(r) : "r"(a)); return r; }
__device__ __forceinline__ float lo2f(uint32_t a) { return __uint_as_float(a << 16); }
__device__ __forceinline__ float hi2f(uint32_t a) { return __uint_as_float(a & 0xffff0000u); }

__device__ __forceinline__ void mbar_init(uint32_t bar, uint32_t cnt) { asm volatile("mbarrier.init.shared::cta.b64 [%0], %1;" :: "r"(bar), "r"(cnt) : "memory"); }
__device__ __forceinline__ void mbar_wait(uint32_t bar, uint32_t parity) {
  asm volatile("{\n.reg .pred p;\n.reg .u32 n;\n"
               "mbarrier.try_wait.parity.shared::cta.b64 p, [%0], %1;\n"
               "@p bra.uni DONE_%=;\n"
               "mov.u32 n, 0;\n"
               "AGAIN_%=:\n"
               "mbarrier.try_wait.parity.shared::cta.b64 p, [%0], %1;\n"
               "@p bra.uni DONE_%=;\n"
               "add.u32 n, n, 1;\n"
               "setp.lt.u32 p, n, 0x1000000;\n"
               "@p bra.uni AGAIN_%=;\n"
               "trap;\n"
               "DONE_%=:\n}\n" :: "r"(bar), "r"(parity) : "memory");
}
__device__ __forceinline__ void wg_fence() { asm volatile("wgmma.fence.sync.aligned;" ::: "memory"); }
__device__ __forceinline__ void wg_commit() { asm volatile("wgmma.commit_group.sync.aligned;" ::: "memory"); }
template <int N> __device__ __forceinline__ void wg_wait() { asm volatile("wgmma.wait_group.sync.aligned %0;" :: "n"(N) : "memory"); }
#define BAR_BY_WG(OP, ID0, ID1, CNT) asm volatile("{\n.reg .pred p;\nsetp.eq.s32 p, %0, 0;\n@p " OP " " #ID0 ", " #CNT ";\n@!p " OP " " #ID1 ", " #CNT ";\n}\n" :: "r"(wg) : "memory")
__device__ __forceinline__ void wg_sync(int wg) { BAR_BY_WG("bar.sync", 1, 2, 128); }
__device__ __forceinline__ void turn_wait(int wg) { BAR_BY_WG("bar.sync", 3, 4, 256); }
__device__ __forceinline__ void turn_pass(int wg) { BAR_BY_WG("bar.arrive", 4, 3, 256); }
__device__ __forceinline__ void stsm4(uint32_t addr, uint32_t a, uint32_t b, uint32_t c, uint32_t d) {
  asm volatile("stmatrix.sync.aligned.m8n8.x4.shared.b16 [%0], {%1,%2,%3,%4};" :: "r"(addr), "r"(a), "r"(b), "r"(c), "r"(d) : "memory");
}
template <int N> __device__ __forceinline__ void keep(float (&d)[N]) {
#pragma unroll
  for (int i = 0; i < N; i++) asm volatile("" : "+f"(d[i]) :: "memory");
}
template <int N> __device__ __forceinline__ void keep(uint32_t (&d)[N]) {
#pragma unroll
  for (int i = 0; i < N; i++) asm volatile("" : "+r"(d[i]) :: "memory");
}
__host__ __device__ __forceinline__ uint64_t mkdesc(uint32_t addr, uint32_t lbo, uint32_t sbo) {
  return ((uint64_t)(sbo >> 4) << 32) | (uint64_t)(((lbo >> 4) << 16) | ((addr & 0x3FFFF) >> 4));
}

template <int SCALE_D>
__device__ __forceinline__ void wgmma_n144(uint32_t (&d)[36], uint32_t a0, uint32_t a1, uint32_t a2, uint32_t a3, uint64_t descB) {
  if (SCALE_D == 0)
  asm volatile("wgmma.mma_async.sync.aligned.m64n144k16.f16.f16.f16 "
    "{%0, %1, %2, %3, %4, %5, %6, %7, %8, %9, %10, %11, %12, %13, %14, %15, "
    "%16, %17, %18, %19, %20, %21, %22, %23, %24, %25, %26, %27, %28, %29, %30, %31, "
    "%32, %33, %34, %35}, "
    "{%36, %37, %38, %39}, %40, 0, 1, 1, 0;\n"
    : "=r"(d[0]), "=r"(d[1]), "=r"(d[2]), "=r"(d[3]), "=r"(d[4]), "=r"(d[5]), "=r"(d[6]), "=r"(d[7]),
      "=r"(d[8]), "=r"(d[9]), "=r"(d[10]), "=r"(d[11]), "=r"(d[12]), "=r"(d[13]), "=r"(d[14]), "=r"(d[15]),
      "=r"(d[16]), "=r"(d[17]), "=r"(d[18]), "=r"(d[19]), "=r"(d[20]), "=r"(d[21]), "=r"(d[22]), "=r"(d[23]),
      "=r"(d[24]), "=r"(d[25]), "=r"(d[26]), "=r"(d[27]), "=r"(d[28]), "=r"(d[29]), "=r"(d[30]), "=r"(d[31]),
      "=r"(d[32]), "=r"(d[33]), "=r"(d[34]), "=r"(d[35])
    : "r"(a0), "r"(a1), "r"(a2), "r"(a3), "l"(descB));
  else
  asm volatile("wgmma.mma_async.sync.aligned.m64n144k16.f16.f16.f16 "
    "{%0, %1, %2, %3, %4, %5, %6, %7, %8, %9, %10, %11, %12, %13, %14, %15, "
    "%16, %17, %18, %19, %20, %21, %22, %23, %24, %25, %26, %27, %28, %29, %30, %31, "
    "%32, %33, %34, %35}, "
    "{%36, %37, %38, %39}, %40, 1, 1, 1, 0;\n"
    : "+r"(d[0]), "+r"(d[1]), "+r"(d[2]), "+r"(d[3]), "+r"(d[4]), "+r"(d[5]), "+r"(d[6]), "+r"(d[7]),
      "+r"(d[8]), "+r"(d[9]), "+r"(d[10]), "+r"(d[11]), "+r"(d[12]), "+r"(d[13]), "+r"(d[14]), "+r"(d[15]),
      "+r"(d[16]), "+r"(d[17]), "+r"(d[18]), "+r"(d[19]), "+r"(d[20]), "+r"(d[21]), "+r"(d[22]), "+r"(d[23]),
      "+r"(d[24]), "+r"(d[25]), "+r"(d[26]), "+r"(d[27]), "+r"(d[28]), "+r"(d[29]), "+r"(d[30]), "+r"(d[31]),
      "+r"(d[32]), "+r"(d[33]), "+r"(d[34]), "+r"(d[35])
    : "r"(a0), "r"(a1), "r"(a2), "r"(a3), "l"(descB));
}

template <int SCALE_D>
__device__ __forceinline__ void wgmma_n192(uint32_t (&d)[48], uint32_t a0, uint32_t a1, uint32_t a2, uint32_t a3, uint64_t descB) {
  if (SCALE_D == 0)
  asm volatile("wgmma.mma_async.sync.aligned.m64n192k16.f16.f16.f16 "
    "{%0, %1, %2, %3, %4, %5, %6, %7, %8, %9, %10, %11, %12, %13, %14, %15, "
    "%16, %17, %18, %19, %20, %21, %22, %23, %24, %25, %26, %27, %28, %29, %30, %31, "
    "%32, %33, %34, %35, %36, %37, %38, %39, %40, %41, %42, %43, %44, %45, %46, %47}, "
    "{%48, %49, %50, %51}, %52, 0, 1, 1, 0;\n"
    : "=r"(d[0]), "=r"(d[1]), "=r"(d[2]), "=r"(d[3]), "=r"(d[4]), "=r"(d[5]), "=r"(d[6]), "=r"(d[7]),
      "=r"(d[8]), "=r"(d[9]), "=r"(d[10]), "=r"(d[11]), "=r"(d[12]), "=r"(d[13]), "=r"(d[14]), "=r"(d[15]),
      "=r"(d[16]), "=r"(d[17]), "=r"(d[18]), "=r"(d[19]), "=r"(d[20]), "=r"(d[21]), "=r"(d[22]), "=r"(d[23]),
      "=r"(d[24]), "=r"(d[25]), "=r"(d[26]), "=r"(d[27]), "=r"(d[28]), "=r"(d[29]), "=r"(d[30]), "=r"(d[31]),
      "=r"(d[32]), "=r"(d[33]), "=r"(d[34]), "=r"(d[35]), "=r"(d[36]), "=r"(d[37]), "=r"(d[38]), "=r"(d[39]),
      "=r"(d[40]), "=r"(d[41]), "=r"(d[42]), "=r"(d[43]), "=r"(d[44]), "=r"(d[45]), "=r"(d[46]), "=r"(d[47])
    : "r"(a0), "r"(a1), "r"(a2), "r"(a3), "l"(descB));
  else
  asm volatile("wgmma.mma_async.sync.aligned.m64n192k16.f16.f16.f16 "
    "{%0, %1, %2, %3, %4, %5, %6, %7, %8, %9, %10, %11, %12, %13, %14, %15, "
    "%16, %17, %18, %19, %20, %21, %22, %23, %24, %25, %26, %27, %28, %29, %30, %31, "
    "%32, %33, %34, %35, %36, %37, %38, %39, %40, %41, %42, %43, %44, %45, %46, %47}, "
    "{%48, %49, %50, %51}, %52, 1, 1, 1, 0;\n"
    : "+r"(d[0]), "+r"(d[1]), "+r"(d[2]), "+r"(d[3]), "+r"(d[4]), "+r"(d[5]), "+r"(d[6]), "+r"(d[7]),
      "+r"(d[8]), "+r"(d[9]), "+r"(d[10]), "+r"(d[11]), "+r"(d[12]), "+r"(d[13]), "+r"(d[14]), "+r"(d[15]),
      "+r"(d[16]), "+r"(d[17]), "+r"(d[18]), "+r"(d[19]), "+r"(d[20]), "+r"(d[21]), "+r"(d[22]), "+r"(d[23]),
      "+r"(d[24]), "+r"(d[25]), "+r"(d[26]), "+r"(d[27]), "+r"(d[28]), "+r"(d[29]), "+r"(d[30]), "+r"(d[31]),
      "+r"(d[32]), "+r"(d[33]), "+r"(d[34]), "+r"(d[35]), "+r"(d[36]), "+r"(d[37]), "+r"(d[38]), "+r"(d[39]),
      "+r"(d[40]), "+r"(d[41]), "+r"(d[42]), "+r"(d[43]), "+r"(d[44]), "+r"(d[45]), "+r"(d[46]), "+r"(d[47])
    : "r"(a0), "r"(a1), "r"(a2), "r"(a3), "l"(descB));
}

template <int SCALE_D>
__device__ __forceinline__ void wgmma_n56(uint32_t (&d)[14], uint32_t a0, uint32_t a1, uint32_t a2, uint32_t a3, uint64_t descB) {
  if (SCALE_D == 0)
  asm volatile("wgmma.mma_async.sync.aligned.m64n56k16.f16.f16.f16 "
    "{%0, %1, %2, %3, %4, %5, %6, %7, %8, %9, %10, %11, %12, %13}, "
    "{%14, %15, %16, %17}, %18, 0, 1, 1, 0;\n"
    : "=r"(d[0]), "=r"(d[1]), "=r"(d[2]), "=r"(d[3]), "=r"(d[4]), "=r"(d[5]), "=r"(d[6]), "=r"(d[7]),
      "=r"(d[8]), "=r"(d[9]), "=r"(d[10]), "=r"(d[11]), "=r"(d[12]), "=r"(d[13])
    : "r"(a0), "r"(a1), "r"(a2), "r"(a3), "l"(descB));
  else
  asm volatile("wgmma.mma_async.sync.aligned.m64n56k16.f16.f16.f16 "
    "{%0, %1, %2, %3, %4, %5, %6, %7, %8, %9, %10, %11, %12, %13}, "
    "{%14, %15, %16, %17}, %18, 1, 1, 1, 0;\n"
    : "+r"(d[0]), "+r"(d[1]), "+r"(d[2]), "+r"(d[3]), "+r"(d[4]), "+r"(d[5]), "+r"(d[6]), "+r"(d[7]),
      "+r"(d[8]), "+r"(d[9]), "+r"(d[10]), "+r"(d[11]), "+r"(d[12]), "+r"(d[13])
    : "r"(a0), "r"(a1), "r"(a2), "r"(a3), "l"(descB));
}

template <int SCALE_D>
__device__ __forceinline__ void wgmma_n56t(uint32_t (&d)[14], uint32_t a0, uint32_t a1, uint32_t a2, uint32_t a3, uint64_t descB) {
  if (SCALE_D == 0)
  asm volatile("wgmma.mma_async.sync.aligned.m64n56k16.f16.f16.f16 "
    "{%0, %1, %2, %3, %4, %5, %6, %7, %8, %9, %10, %11, %12, %13}, "
    "{%14, %15, %16, %17}, %18, 0, 1, 1, 1;\n"
    : "=r"(d[0]), "=r"(d[1]), "=r"(d[2]), "=r"(d[3]), "=r"(d[4]), "=r"(d[5]), "=r"(d[6]), "=r"(d[7]),
      "=r"(d[8]), "=r"(d[9]), "=r"(d[10]), "=r"(d[11]), "=r"(d[12]), "=r"(d[13])
    : "r"(a0), "r"(a1), "r"(a2), "r"(a3), "l"(descB));
  else
  asm volatile("wgmma.mma_async.sync.aligned.m64n56k16.f16.f16.f16 "
    "{%0, %1, %2, %3, %4, %5, %6, %7, %8, %9, %10, %11, %12, %13}, "
    "{%14, %15, %16, %17}, %18, 1, 1, 1, 1;\n"
    : "+r"(d[0]), "+r"(d[1]), "+r"(d[2]), "+r"(d[3]), "+r"(d[4]), "+r"(d[5]), "+r"(d[6]), "+r"(d[7]),
      "+r"(d[8]), "+r"(d[9]), "+r"(d[10]), "+r"(d[11]), "+r"(d[12]), "+r"(d[13])
    : "r"(a0), "r"(a1), "r"(a2), "r"(a3), "l"(descB));
}

__global__ void __launch_bounds__(384) prepack_kernel(const __nv_bfloat16* __restrict__ wqkv, const __nv_bfloat16* __restrict__ wo) {
  asm volatile("griddepcontrol.launch_dependents;");
  __shared__ float red2[2][2][6][8];
  float (*red)[6][8] = red2[threadIdx.y];
  __half* dst = reinterpret_cast<__half*>(g_wpack);
  const int c = threadIdx.x, nb = blockIdx.x * 2 + threadIdx.y;
  auto colsum = [&](int k, const float (&v)[8], float (&o)[8]) {
#pragma unroll
    for (int i = 0; i < 8; i++) {
      float t = v[i];
#pragma unroll
      for (int d = 16; d; d >>= 1) t += __shfl_xor_sync(~0u, t, d);
      if ((c & 31) == 0) red[k][c >> 5][i] = t;
    }
    __syncthreads();
#pragma unroll
    for (int i = 0; i < 8; i++) o[i] = red[k][0][i] + red[k][1][i] + red[k][2][i] + red[k][3][i] + red[k][4][i] + red[k][5][i];
  };
  float v[8], t[8];
  int base;
  if (nb < 72) {
    const int h = nb / 18, j = nb % 18, part = j / 6;
    const int col = (part == 0 ? 192 : part == 1 ? 0 : 384) + h * 48 + (j % 6) * 8;
    uint4 raw = *reinterpret_cast<const uint4*>(wqkv + c * 576 + col);
    uint32_t u[4] = {raw.x, raw.y, raw.z, raw.w};
#pragma unroll
    for (int i = 0; i < 4; i++) { v[2 * i] = lo2f(u[i]); v[2 * i + 1] = hi2f(u[i]); }
    colsum(0, v, t);
#pragma unroll
    for (int n = 0; n < 8; n++)
      v[n] = __bfloat162float(__float2bfloat16((v[n] - t[n] * (1.0f / 192.0f)) * (part == 1 ? 0.14433756729740643f * 1.4426950408889634f : 1.0f)));
    const int cc = c >> 5, q = (c >> 3) & 3, s1 = (c >> 2) & 1, hh = (c >> 1) & 1, e = c & 1;
    base = qkv_pos(h, 2 * cc + s1) / 2 + j * 128 + hh * 64 + 2 * q + e;
  } else {
    const int jb = nb - 72;
#pragma unroll
    for (int n = 0; n < 8; n++) v[n] = __bfloat162float(wo[c * 192 + 32 * (jb >> 2) + 8 * (n >> 1) + 2 * (jb & 3) + (n & 1)]);
    base = wo_pos(c >> 4) / 2 + jb * 128 + ((c >> 3) & 1) * 64 + (c & 7);
  }
#pragma unroll
  for (int n = 0; n < 8; n++) { dst[base + n * 8] = __float2half_rn(v[n]); v[n] *= v[n]; }
  colsum(1, v, t);
  if (c == 0)
    g_wnorm[nb] = make_float2(fmaxf(fmaxf(fmaxf(t[0], t[1]), fmaxf(t[2], t[3])), fmaxf(fmaxf(t[4], t[5]), fmaxf(t[6], t[7]))),
                              t[0] + t[1] + t[2] + t[3] + t[4] + t[5] + t[6] + t[7]);
}

__device__ __forceinline__ int window_of(int round, int nfull, int cta, int ncta, int wg) {
  if (round < nfull) return round * 2 * ncta + 2 * cta + wg;
  const int rem = NWIN - nfull * 2 * ncta;
  const int i = cta + wg * ncta;
  return i < rem ? nfull * 2 * ncta + i : -1;
}

template <int S0 = 0, int S1 = 12>
__device__ __forceinline__ void mma_qkv(uint32_t (&acc)[36], const uint32_t (&A)[48], const uint64_t* d) {
#pragma unroll
  for (int s = S0; s < S1; s++) {
    if (s == 0) wgmma_n144<0>(acc, A[4 * s], A[4 * s + 1], A[4 * s + 2], A[4 * s + 3], d[s]);
    else        wgmma_n144<1>(acc, A[4 * s], A[4 * s + 1], A[4 * s + 2], A[4 * s + 3], d[s]);
  }
  wg_commit();
}
__device__ __forceinline__ void mma_proj(uint32_t (&acc)[48], const uint32_t (&A)[12], const uint64_t* d) {
#pragma unroll
  for (int s = 0; s < 3; s++) wgmma_n192<1>(acc, A[4 * s], A[4 * s + 1], A[4 * s + 2], A[4 * s + 3], d[s]);
}
__device__ __forceinline__ void mma_s(uint32_t (&S)[14], const uint32_t (&Q)[12], const uint64_t* d) {
  wgmma_n56<0>(S, Q[0], Q[1], Q[2], Q[3], d[0]);
  wgmma_n56<1>(S, Q[4], Q[5], Q[6], Q[7], d[1]);
  wgmma_n56<1>(S, Q[8], Q[9], Q[10], Q[11], d[2]);
}
__device__ __forceinline__ void mma_pv(uint32_t (&O)[14], const uint32_t (&P)[NP], const uint64_t* d) {
  wgmma_n56t<0>(O, P[0], P[1], P[2], P[3], d[0]);
  wgmma_n56t<1>(O, P[4], P[5], P[6], P[7], d[1]);
  wgmma_n56t<1>(O, P[8], P[9], P[10], P[11], d[2]);
  if (K48TC) wgmma_n56t<1>(O, P[NP - 4], P[NP - 3], P[NP - 2], P[NP - 1], d[3]);
}

#define PIN() asm volatile("pmevent 0;" ::: "memory")
template <int A, int B> __device__ __forceinline__ void hold(uint32_t* v) {
#pragma unroll
  for (int i = A; i < B; i++) asm volatile("" : "+r"(v[i]));
}
__device__ __forceinline__ void stsm12(const uint32_t* v, uint32_t addr) {
#pragma unroll
  for (int j = 0; j < 3; j++) stsm4(addr + 2 * j * KV_PITCH, v[4 * j], v[4 * j + 1], v[4 * j + 2], v[4 * j + 3]);
}
__device__ __forceinline__ void load_v48(uint32_t (&v)[6], uint32_t addr) {
  if (K48TC) return;
  asm volatile("ldmatrix.sync.aligned.m8n8.x4.shared.b16 {%0,%1,%2,%3}, [%4];" : "=r"(v[0]), "=r"(v[1]), "=r"(v[2]), "=r"(v[3]) : "r"(addr) : "memory");
  asm volatile("ldmatrix.sync.aligned.m8n8.x2.shared.b16 {%0,%1}, [%2];" : "=r"(v[4]), "=r"(v[5]) : "r"(addr + 4 * KV_PITCH) : "memory");
}
__device__ __forceinline__ void finish_o(const uint32_t (&O)[14], const uint32_t (&v)[6], uint32_t p48, uint32_t vmask, uint32_t (&Of)[12]) {
  const float2 l = K48TC ? make_float2(__low2float(u2h(O[12])), __low2float(u2h(O[13])))
                         : __half22float2(__hadd2_rn(u2h(__byte_perm(O[12], O[13], 0x5410)), u2h(p48)));
  float i0, i1;
  asm("rcp.approx.ftz.f32 %0, %1;" : "=f"(i0) : "f"(l.x));
  asm("rcp.approx.ftz.f32 %0, %1;" : "=f"(i1) : "f"(l.y));
  const uint32_t inv = packh(i0, i1) & vmask;
#pragma unroll
  for (int i = 0; i < 12; i++) {
    const uint32_t t = K48TC ? O[i] : h2u(__hfma2(u2h(v[i >> 1]), (i & 1) ? hcast<1>(p48) : hcast<0>(p48), u2h(O[i])));
    Of[i] = (i & 1) ? fmul_b<1>(t, inv) : fmul_b<0>(t, inv);
  }
  hold<0, 12>(Of);
}
#define PSTAT 12
template <int A, int B>
__device__ __forceinline__ void ln_sums(const uint32_t (&X)[48], float (&s1)[2], float (&s2)[2]) {
  if (PSTAT) {
    static_assert(PSTAT == 0 || (A % (2 * PSTAT + !PSTAT) == 0 && B % (2 * PSTAT + !PSTAT) == 0), "whole groups");
#pragma unroll
    for (int g = A; g < B; g += 2 * PSTAT + !PSTAT)
#pragma unroll
      for (int a = 0; a < 2; a++) {
        __half2 p1 = u2h(X[g + a]), p2 = __hmul2_rn(p1, p1);
#pragma unroll
        for (int i = 1; i < PSTAT; i++) { const __half2 v = u2h(X[g + a + 2 * i]); p1 = __hadd2_rn(p1, v); p2 = __hfma2(v, v, p2); }
        const float2 f1 = __half22float2(p1), f2 = __half22float2(p2);
        s1[a] = g == 0 ? f1.x + f1.y : s1[a] + (f1.x + f1.y);
        s2[a] = g == 0 ? f2.x + f2.y : s2[a] + (f2.x + f2.y);
      }
  } else {
#pragma unroll
    for (int i = A; i < B; i++) {
      const float2 f = __half22float2(u2h(X[i]));
      s1[i & 1] = i < 2 ? f.x + f.y : s1[i & 1] + (f.x + f.y);
      s2[i & 1] = fmaf(f.x, f.x, i < 2 ? f.y * f.y : fmaf(f.y, f.y, s2[i & 1]));
    }
  }
  asm volatile("" : "+f"(s1[0]), "+f"(s1[1]), "+f"(s2[0]), "+f"(s2[1]));
}
__device__ __forceinline__ uint32_t ln_rstd(const float (&s1)[2], const float (&s2)[2], float lo, float hi, uint32_t vmask, bool& ok) {
  float r[2];
  ok = true;
#pragma unroll
  for (int a = 0; a < 2; a++) {
    float m = s1[a], v = s2[a];
    m += __shfl_xor_sync(~0u, m, 1); v += __shfl_xor_sync(~0u, v, 1);
    m += __shfl_xor_sync(~0u, m, 2); v += __shfl_xor_sync(~0u, v, 2);
    ok = ok && v <= hi && (v >= lo || !(vmask >> (16 * a) & 1));
    m *= 1.0f / 192.0f;
    m *= m;
    v = fmaxf(fmaf(v, 1.0f / 192.0f, -m), 0.f) + 1e-5f;
    ok = ok && m <= (PSTAT ? 16.f : 64.f) * v;
    asm("rsqrt.approx.ftz.f32 %0, %1;" : "=f"(r[a]) : "f"(v));
  }
  uint32_t rk = packh(r[0], r[1]);
  hold<0, 1>(&rk);
  return rk;
}
__device__ __forceinline__ void scale12(uint32_t (&D)[12], const uint32_t* a, uint32_t r) {
#pragma unroll
  for (int i = 0; i < 12; i++) D[i] = (i & 1) ? fmul_b<1>(a[i], r) : fmul_b<0>(a[i], r);
  hold<0, 12>(D);
}
template <int CC>
__device__ __forceinline__ void store_out(const uint32_t (&Y)[48], uint8_t* o0, uint8_t* o1, uint32_t vmask) {
  uint32_t T[8];
#pragma unroll
  for (int i = 0; i < 8; i++) {
    const float2 f = __half22float2(u2h(Y[8 * CC + i]));
    T[i] = pack2(f.x, f.y);
  }
  asm volatile("{\n.reg .pred p;\nsetp.ne.u32 p, %5, 0;\n@p st.global" STHINT ".v4.u32 [%0], {%1,%2,%3,%4};\n}\n"
               :: "l"(o0 + CC * 64), "r"(T[0]), "r"(T[2]), "r"(T[4]), "r"(T[6]), "r"(vmask) : "memory");
  asm volatile("{\n.reg .pred p;\nsetp.lt.s32 p, %5, 0;\n@p st.global" STHINT ".v4.u32 [%0], {%1,%2,%3,%4};\n}\n"
               :: "l"(o1 + CC * 64), "r"(T[1]), "r"(T[3]), "r"(T[5]), "r"(T[7]), "r"(vmask) : "memory");
}
__device__ __forceinline__ void proxy_fence() { asm volatile("fence.proxy.async.shared::cta;" ::: "memory"); }
__device__ __forceinline__ uint32_t fadd2(uint32_t a, uint32_t b) { return h2u(__hadd2_rn(u2h(a), u2h(b))); }
__device__ __forceinline__ void row_max(const uint32_t (&S)[14], uint32_t& k48, uint32_t& mx, uint32_t ninf) {
  k48 = K48TC ? __byte_perm(S[12], S[13], 0x5410) | ninf : __shfl_sync(~0u, __byte_perm(S[12], S[13], 0x5410), 0, 4);
  const uint32_t m0 = fmax2(fmax2(fmax2(S[0], S[2]), S[4]), fmax2(fmax2(S[6], S[8]), S[10]));
  const uint32_t m1 = fmax2(fmax2(fmax2(S[1], S[3]), S[5]), fmax2(fmax2(S[7], S[9]), S[11]));
  mx = fmax2(__byte_perm(m0, m1, 0x5410), __byte_perm(m0, m1, 0x7632));
  if (K48TC) mx = fmax2(mx, k48);
  mx = fmax2(mx, __shfl_xor_sync(~0u, mx, 1));
  mx = fmax2(mx, __shfl_xor_sync(~0u, mx, 2));
  if (!K48TC) mx = fmax2(mx, k48);
  hold<0, 1>(&mx);
}
__device__ __forceinline__ void row_exp(const uint32_t (&S)[14], uint32_t k48, uint32_t mx, uint32_t (&P)[NP], uint32_t& p48) {
#pragma unroll
  for (int j = 0; j < 12; j++) P[j] = fex2((j & 1) ? fsub_b<1>(S[j], mx) : fsub_b<0>(S[j], mx));
  if (K48TC) {
    uint16_t el, eh;
    asm("{\n.reg .b16 l, h;\nmov.b32 {l, h}, %2;\nex2.approx.f16 %0, l;\nex2.approx.f16 %1, h;\n}\n" : "=h"(el), "=h"(eh) : "r"(h2u(__hsub2_rn(u2h(k48), u2h(mx)))));
    P[NP - 4] = el; P[NP - 3] = eh; P[NP - 2] = 0; P[NP - 1] = 0;
  } else {
    p48 = fex2(h2u(__hsub2_rn(u2h(k48), u2h(mx))));
    hold<0, 1>(&p48);
  }
  hold<0, NP>(P);
}
template <int S0, int S1>
__device__ __forceinline__ void load_x(uint32_t (&X)[48], uint32_t t0) {
#pragma unroll
  for (int s = S0; s < S1; s++)
    asm volatile("ld.shared.v4.u32 {%0,%1,%2,%3}, [%4];" : "=r"(X[4 * s]), "=r"(X[4 * s + 1]), "=r"(X[4 * s + 2]), "=r"(X[4 * s + 3])
                 : "r"(((s & 1) ? (t0 ^ 16) : t0) + (s >> 1) * 128) : "memory");
}

#define WDIV 1
template <int P, int CNT, int DIV = WDIV> __device__ __forceinline__ void load_slices(uint32_t sb, const Descs& ds) {
  constexpr int st = stage_of(P);
  constexpr bool first = P == 0 || stage_of(P - 1) != st;
  if (first)
    asm volatile("{\n.reg .pred p;\nelect.sync _|p, 0xffffffff;\n@p mbarrier.arrive.expect_tx.shared::cta.b64 _, [%0], %1;\n}\n"
                 :: "r"(sb + BAR_WFULL + 8 * st), "n"((st < 4 ? 3 : st == 4 ? 2 : 1) * SLICE / DIV) : "memory");
  asm volatile("{\n.reg .pred p;\nelect.sync _|p, 0xffffffff;\n"
               "@p cp.async.bulk.shared::cluster.global.mbarrier::complete_tx::bytes [%0], [%1], %2, [%3];\n}\n"
               :: "r"(sb + OFF_W + (P & 7) * SLICE), "l"(ds.src[P]), "n"(CNT * SLICE / DIV), "r"(sb + BAR_WFULL + 8 * st) : "memory");
}
__device__ __forceinline__ void warp_arrive(uint32_t bar) {
  asm volatile("{\n.reg .pred p;\nelect.sync _|p, 0xffffffff;\n@p mbarrier.arrive.shared::cta.b64 _, [%0];\n}\n" :: "r"(bar) : "memory");
}

__device__ __forceinline__ float2 fp16_limits(int lane) {
  float mx[4] = {0.f, 0.f, 0.f, 0.f}, sm[4] = {0.f, 0.f, 0.f, 0.f};
#pragma unroll
  for (int i = 0; i < 3; i++) {
    const int nb = lane + 32 * i, part = nb < 72 ? (nb % 18) / 6 : 3;
    const float2 w = g_wnorm[nb];
#pragma unroll
    for (int k = 0; k < 4; k++) if (part == k) { mx[k] = fmaxf(mx[k], w.x); sm[k] += w.y; }
  }
#pragma unroll
  for (int k = 0; k < 4; k++)
#pragma unroll
    for (int d = 16; d; d >>= 1) { mx[k] = fmaxf(mx[k], __shfl_xor_sync(~0u, mx[k], d)); sm[k] += __shfl_xor_sync(~0u, sm[k], d); }
  const float big = fmaxf(fmaxf(mx[0], mx[1]), mx[2]);
  float small = 1.f;
  bool good = sm[0] + sm[1] + sm[2] + sm[3] < 1e30f;
#pragma unroll
  for (int k = 0; k < 4; k++) { good = good && (mx[k] == 0.f || mx[k] >= 2.5e-4f); if (k < 3 && mx[k] > 0.f) small = fminf(small, mx[k]); }
  good = good && 250.f * 48.f * sqrtf(mx[0] * mx[1]) <= 5e4f;
  good = good && 16.f * 49.f * sqrtf(mx[2]) <= 5e4f && big <= 1e6f;
  good = good && 16.f * sqrtf(sm[2] * mx[3]) <= 2e4f;
  return make_float2(192.f * 2.4e-7f / small, good ? fminf(2.5e8f, 9e8f / fmaxf(big, 1e-30f)) : -1.f);
}

__device__ __forceinline__ void slow_window(float* sm, int w, int t, const __nv_bfloat16* __restrict__ x, const __nv_bfloat16* __restrict__ dw,
                                            const __nv_bfloat16* __restrict__ wqkv, const __nv_bfloat16* __restrict__ wo, __nv_bfloat16* __restrict__ out) {
  float* x0 = sm; float* h = x0 + 49 * CH; float* qkv = h + 49 * CH; float* S = qkv + 49 * 576;
  const int wy = w / NWX, wx = w % NWX;
  auto sync = [] { asm volatile("bar.sync 6, 128;" ::: "memory"); };
#pragma unroll 1
  for (int i = t; i < 49 * CH; i += 128) {
    const int k = i / CH, c = i % CH, y = wy * 7 + k / 7, xx = wx * 7 + k % 7;
    float pe = 0.f;
#pragma unroll 1
    for (int a = 0; a < 9; a++) {
      const int yy = y + a / 3 - 1, xc = xx + a % 3 - 1;
      if (yy >= 0 && yy < IMG && xc >= 0 && xc < IMG) pe = fmaf(__bfloat162float(x[((size_t)yy * IMG + xc) * CH + c]), __bfloat162float(dw[a * CH + c]), pe);
    }
    x0[i] = __bfloat162float(__float2bfloat16(__bfloat162float(x[((size_t)y * IMG + xx) * CH + c]) + pe));
  }
  sync();
  if (t < 49) {
    float m = 0.f, v = 0.f;
#pragma unroll 1
    for (int c = 0; c < CH; c++) m += x0[t * CH + c];
    m *= 1.0f / CH;
#pragma unroll 1
    for (int c = 0; c < CH; c++) { const float d = x0[t * CH + c] - m; v = fmaf(d, d, v); }
    const float rs = 1.0f / sqrtf(v * (1.0f / CH) + 1e-5f);
#pragma unroll 1
    for (int c = 0; c < CH; c++) h[t * CH + c] = (x0[t * CH + c] - m) * rs;
  }
  sync();
#pragma unroll 1
  for (int i = t; i < 7 * 576; i += 128) {
    const int n = i % 576, k0 = i / 576 * 7;
    float a[7] = {0.f, 0.f, 0.f, 0.f, 0.f, 0.f, 0.f};
#pragma unroll 1
    for (int c = 0; c < CH; c++) {
      const float wv = __bfloat162float(wqkv[c * 576 + n]);
#pragma unroll
      for (int k = 0; k < 7; k++) a[k] = fmaf(h[(k0 + k) * CH + c], wv, a[k]);
    }
#pragma unroll
    for (int k = 0; k < 7; k++) qkv[(k0 + k) * 576 + n] = a[k];
  }
  sync();
#pragma unroll 1
  for (int hd = 0; hd < 4; hd++) {
#pragma unroll 1
    for (int i = t; i < 49 * 49; i += 128) {
      const int a = i / 49, b = i % 49;
      float v = 0.f;
#pragma unroll 1
      for (int d = 0; d < 48; d++) v = fmaf(qkv[a * 576 + hd * 48 + d], qkv[b * 576 + 192 + hd * 48 + d], v);
      S[i] = v * 0.14433756729740643f;
    }
    sync();
    if (t < 49) {
      float m = S[t * 49], l = 0.f;
#pragma unroll 1
      for (int b = 1; b < 49; b++) m = fmaxf(m, S[t * 49 + b]);
#pragma unroll 1
      for (int b = 0; b < 49; b++) { const float e = expf(S[t * 49 + b] - m); S[t * 49 + b] = e; l += e; }
#pragma unroll 1
      for (int b = 0; b < 49; b++) S[t * 49 + b] /= l;
    }
    sync();
#pragma unroll 1
    for (int i = t; i < 49 * 48; i += 128) {
      const int a = i / 48, d = i % 48;
      float v = 0.f;
#pragma unroll 1
      for (int b = 0; b < 49; b++) v = fmaf(S[a * 49 + b], qkv[b * 576 + 384 + hd * 48 + d], v);
      h[a * CH + hd * 48 + d] = v;
    }
    sync();
  }
#pragma unroll 1
  for (int i = t; i < 7 * CH; i += 128) {
    const int n = i % CH, k0 = i / CH * 7;
    float a[7] = {0.f, 0.f, 0.f, 0.f, 0.f, 0.f, 0.f};
#pragma unroll 1
    for (int c = 0; c < CH; c++) {
      const float wv = __bfloat162float(wo[c * CH + n]);
#pragma unroll
      for (int k = 0; k < 7; k++) a[k] = fmaf(h[(k0 + k) * CH + c], wv, a[k]);
    }
#pragma unroll
    for (int k = 0; k < 7; k++)
      out[((size_t)(wy * 7 + k0 / 7) * IMG + wx * 7 + k) * CH + n] = __float2bfloat16(x0[(k0 + k) * CH + n] + a[k]);
  }
  sync();
}

__global__ void __launch_bounds__(384, 1)
fused_kernel(const __grid_constant__ CUtensorMap tmx, const __grid_constant__ CUtensorMap tmp, const __grid_constant__ Descs ds, const __nv_bfloat16* __restrict__ dw, __nv_bfloat16* __restrict__ out, const int never,
             const __nv_bfloat16* __restrict__ x, const __nv_bfloat16* __restrict__ wqkv, const __nv_bfloat16* __restrict__ wo) {
  extern __shared__ __align__(1024) uint8_t smem[];
  const uint32_t sb = (uint32_t)__cvta_generic_to_shared(smem);
  const int tid = threadIdx.x, lane = tid & 31;
  const int warp = __shfl_sync(0xffffffffu, tid >> 5, 0);
  const int cta = blockIdx.x, ncta = gridDim.x;
  const int nfull = NWIN / (2 * ncta);
  const int nrounds = nfull + ((NWIN - nfull * 2 * ncta) > cta ? 1 : 0);

  if (warp == 0) GTS(0);
  if (warp == 10 && lane == 0) asm volatile("prefetch.tensormap [%0];" :: "l"(reinterpret_cast<uint64_t>(&tmx)) : "memory");
  if (tid == 0) {
    mbar_init(sb + BAR_FIRST, 1);
    asm volatile("fence.mbarrier_init.release.cluster;" ::: "memory");
    asm volatile("mbarrier.arrive.expect_tx.shared::cta.b64 _, [%0], %1;" :: "r"(sb + BAR_FIRST), "n"(2 * HALO_BYTES) : "memory");
#pragma unroll
    for (int k = 0; k < 2; k++) {
      const int w = max(window_of(0, nfull, cta, ncta, k), 0), a = w / NWX;
      asm volatile("cp.async.bulk.tensor.3d.shared::cluster.global.mbarrier::complete_tx::bytes [%0], [%1, {0, %3, %4}], [%2];"
                   :: "r"(sb + OFF_HALO + k * HALO_BYTES), "l"(reinterpret_cast<uint64_t>(&tmp)), "r"(sb + BAR_FIRST),
                      "r"((w - a * NWX) * 7 - 1), "r"(a * 7 - 1) : "memory");
    }
    if ((sb & 0x3FFFF) != SMEM_BASE || nrounds > 128) __trap();
    for (int i = 0; i < 7; i++) { mbar_init(sb + BAR_WFULL + 8 * i, 1); mbar_init(sb + BAR_WEMPTY + 8 * i, 8); }
    for (int i = 0; i < 9; i++) mbar_init(sb + BAR_XFULL + 8 * i, 1);
    mbar_init(sb + BAR_TFULL, 3);
    mbar_init(sb + BAR_TEMPTY, 8);
    asm volatile("fence.mbarrier_init.release.cluster;" ::: "memory");
  }
  if (tid >= 128 && tid < 320) {
    *reinterpret_cast<uint32_t*>(smem + OFF_ZERO + (tid - 128) * 4) = 0;
    if (tid < 136) *reinterpret_cast<uint32_t*>(smem + OFF_REDO + (tid - 128) * 4) = 0;
  }
  if (tid < 128) {
    *reinterpret_cast<uint4*>(smem + OFF_KV + (tid / 64) * KV_BYTES + 6 * KV_PITCH + (tid % 64) * 16) = make_uint4(0x3c003c00u, 0x3c003c00u, 0x3c003c00u, 0x3c003c00u);
    proxy_fence();
  }
  __syncthreads();

  if (warp < 11) {
#pragma unroll 1
    for (int u = 0; u < (warp < 10 ? 2 : 1); u++) {
      const int cb = warp < 9 ? warp % 3 : 2 * (warp - 9) + u, y = warp < 9 ? 2 * (warp / 3) + u : 6;
      const int ch0 = cb * 64 + (lane & 15) * 4;
      uint32_t wt[9][2], px[3][9][2];
#pragma unroll
      for (int t = 0; t < 9; t++) {
        const uint2 v = *reinterpret_cast<const uint2*>(dw + t * CH + ch0);
        wt[t][0] = v.x; wt[t][1] = v.y;
      }
      mbar_wait(sb + BAR_FIRST, 0);
      const uint32_t ld = sb + OFF_HALO + (lane >> 4) * HALO_BYTES + y * 3456 + ch0 * 2;
#pragma unroll
      for (int p = 0; p < 27; p++)
        asm volatile("ld.shared.v2.u32 {%0,%1}, [%2];" : "=r"(px[p / 9][p % 9][0]), "=r"(px[p / 9][p % 9][1]) : "r"(ld + p * 384));
      const uint32_t st0 = sb + OFF_TILE + (lane >> 4) * TILE_BYTES + ch0 * 4;
      const uint32_t sa = (st0 ^ ((y & 1) << 4)) + y * 2304;
      uint32_t o[2][2];
#pragma unroll
      for (int j = 0; j < 7; j++) {
#pragma unroll
        for (int e = 0; e < 2; e++) {
          uint32_t a = hmul(px[0][j][e], wt[0][e]);
#pragma unroll
          for (int t = 1; t < 9; t++) a = hfma(px[t / 3][j + t % 3][e], wt[t][e], a);
          a = hadd(px[1][j + 1][e], a);
          o[j & 1][e] = packh(lo2f(a), hi2f(a));
        }
        if (j & 1)
          asm volatile("st.shared.v4.u32 [%0], {%1,%2,%3,%4};" :: "r"((j == 3 ? sa ^ 16 : sa) + (j >> 1) * 768),
                       "r"(o[0][0]), "r"(o[1][0]), "r"(o[0][1]), "r"(o[1][1]) : "memory");
      }
      const uint32_t sb6 = (st0 ^ ((~y & 2) << 3)) + (21 + (y >> 1)) * 768 + (y & 1) * 4;
      asm volatile("st.shared.u32 [%0], %1;\nst.shared.u32 [%0 + 8], %2;" :: "r"(sb6), "r"(o[0][0]), "r"(o[0][1]) : "memory");
      if (y == 6) asm volatile("st.shared.u32 [%0 + 4], %1;\nst.shared.u32 [%0 + 12], %1;" :: "r"(sb6), "r"(0) : "memory");
    }
    asm volatile("bar.arrive 8, 384;\nbar.sync 7, 352;" ::: "memory");
  }

  if (warp >= 8) {
    asm volatile("setmaxnreg.dec.sync.aligned.u32 " PREGS ";");
    if (warp == 11) {
      asm volatile("griddepcontrol.wait;" ::: "memory");
      load_slices<1, 3, 1>(sb, ds);
      *reinterpret_cast<float2*>(smem + OFF_LIM) = fp16_limits(lane);
      load_slices<0, 1, 1>(sb, ds);
      asm volatile("bar.sync 8, 384;" ::: "memory");
      load_slices<5, 3, 1>(sb, ds); load_slices<4, 1, 1>(sb, ds);
      for (int r = 0; r < nrounds; r++) {
        const uint32_t par = r & 1;
        const bool next_round = r + 1 < nrounds;
        mbar_wait(sb + BAR_WEMPTY + 40, par); load_slices<8, 1>(sb, ds);
        mbar_wait(sb + BAR_WEMPTY, par);      load_slices<9, 2>(sb, ds); load_slices<11, 1>(sb, ds);
        mbar_wait(sb + BAR_WEMPTY + 48, par); load_slices<12, 1>(sb, ds);
        mbar_wait(sb + BAR_WEMPTY + 8, par);  load_slices<13, 1>(sb, ds); load_slices<14, 2>(sb, ds);
        mbar_wait(sb + BAR_WEMPTY + 16, par); load_slices<0, 1>(sb, ds); if (next_round) load_slices<1, 2>(sb, ds);
        mbar_wait(sb + BAR_WEMPTY + 24, par);
        if (next_round) load_slices<3, 1>(sb, ds);
        load_slices<4, 1>(sb, ds);
        if (next_round) {
          load_slices<5, 1>(sb, ds);
          mbar_wait(sb + BAR_WEMPTY + 32, par); load_slices<6, 2>(sb, ds);
        }
      }
    } else {
      const int cw = warp - 8;
      const int win = lane >> 4;
      const int ch0 = cw * 64 + (lane & 15) * 4;
      uint32_t wt[9][2];
#pragma unroll
      for (int t = 0; t < 9; t++) {
        uint2 v = *reinterpret_cast<const uint2*>(dw + t * CH + ch0);
        wt[t][0] = v.x; wt[t][1] = v.y;
      }
      const uint32_t xs = sb + OFF_X + cw * 3 * XSLOT;
      const uint32_t xld = xs + (lane >> 4) * 1152 + (lane & 15) * 8;
      const uint32_t xbar = sb + BAR_XFULL + cw * 24;
      const uint32_t st0 = sb + OFF_TILE + win * TILE_BYTES + ch0 * 4;
      const uint64_t tm = reinterpret_cast<uint64_t>(&tmx);
      int cx0, cy0, cx1, cy1;
      auto coords = [&](int r) {
        const int w0 = window_of(r, nfull, cta, ncta, 0);
        int w1 = window_of(r, nfull, cta, ncta, 1);
        if (w1 < 0) w1 = w0;
        const int a = w0 / NWX, b = w1 / NWX;
        cx0 = (w0 - a * NWX) * 7 - 1; cy0 = a * 7 - 1;
        cx1 = (w1 - b * NWX) * 7 - 1; cy1 = b * 7 - 1;
      };
      auto issue = [&](int slot, int dy) {
        asm volatile("{\n.reg .pred p;\nelect.sync _|p, 0xffffffff;\n"
                     "@p mbarrier.arrive.expect_tx.shared::cta.b64 _, [%2], %8;\n"
                     "@p cp.async.bulk.tensor.3d.shared::cluster.global.mbarrier::complete_tx::bytes [%0], [%1, {%3, %4, %5}], [%2];\n"
                     "@p cp.async.bulk.tensor.3d.shared::cluster.global.mbarrier::complete_tx::bytes [%0 + 1152], [%1, {%3, %6, %7}], [%2];\n}\n"
                     :: "r"(xs + slot * XSLOT), "l"(tm), "r"(xbar + slot * 8), "r"(cw * 64), "r"(cx0), "r"(cy0 + dy), "r"(cx1), "r"(cy1 + dy), "n"(XSLOT) : "memory");
      };
      uint32_t accA[7][2], accB[7][2], ctr[7][2], held[2];
      auto row = [&](auto fin, auto mid, auto top, int slot, int y) {
        const uint32_t ld = xld + slot * XSLOT;
        const uint32_t sa = (st0 ^ ((y & 1) << 4)) + y * 2304;
        uint32_t cur[9][2], o[2][2];
#pragma unroll
        for (int p = 0; p < LA; p++)
          asm volatile("ld.shared.v2.u32 {%0,%1}, [%2];" : "=r"(cur[p][0]), "=r"(cur[p][1]) : "r"(ld + p * 128));
#pragma unroll
        for (int j = 0; j < 7; j++) {
          if (j >= 1 && j + LA - 1 < 9)
            asm volatile("ld.shared.v2.u32 {%0,%1}, [%2];" : "=r"(cur[j + LA - 1][0]), "=r"(cur[j + LA - 1][1]) : "r"(ld + (j + LA - 1) * 128));
          if (fin.v) {
#pragma unroll
            for (int e = 0; e < 2; e++) {
              uint32_t a = hfma(cur[j][e], wt[6][e], accA[j][e]);
              a = hfma(cur[j + 1][e], wt[7][e], a);
              a = hfma(cur[j + 2][e], wt[8][e], a);
              if (!EARLYX) a = hadd(ctr[j][e], a);
              o[j & 1][e] = packh(lo2f(a), hi2f(a));
            }
            if (j & 1)
              asm volatile("st.shared.v4.u32 [%0], {%1,%2,%3,%4};" :: "r"((j == 3 ? sa ^ 16 : sa) + (j >> 1) * 768),
                           "r"(o[0][0]), "r"(o[1][0]), "r"(o[0][1]), "r"(o[1][1]) : "memory");
            if (j == 6) {
              const uint32_t sb6 = (st0 ^ ((~y & 2) << 3)) + (21 + (y >> 1)) * 768;
              if (fin.v == 2)
                asm volatile("st.shared.v4.u32 [%0], {%1,%2,%3,%2};" :: "r"(sb6), "r"(o[0][0]), "r"(0), "r"(o[0][1]) : "memory");
              else
                asm volatile("{\n.reg .pred p;\nsetp.ne.s32 p, %5, 0;\n@p st.shared.v4.u32 [%0], {%1,%2,%3,%4};\n}\n"
                             :: "r"(sb6), "r"(held[0]), "r"(o[0][0]), "r"(held[1]), "r"(o[0][1]), "r"(y & 1) : "memory");
              held[0] = o[0][0]; held[1] = o[0][1];
            }
          }
#pragma unroll
          for (int e = 0; e < 2; e++) {
            if (mid.v) {
              uint32_t a = hfma(cur[j][e], wt[3][e], accB[j][e]);
              a = hfma(cur[j + 1][e], wt[4][e], a);
              a = hfma(cur[j + 2][e], wt[5][e], a);
              accA[j][e] = EARLYX == 1 ? hadd(cur[j + 1][e], a) : a;
              if (!EARLYX) ctr[j][e] = cur[j + 1][e];
            }
            if (top.v) {
              uint32_t a = hmul(cur[j][e], wt[0][e]);
              a = hfma(cur[j + 1][e], wt[1][e], a);
              accB[j][e] = hfma(cur[j + 2][e], wt[2][e], a);
            }
          }
        }
      };
      held[0] = held[1] = 0;
      if (nrounds > 1) { coords(1); issue(0, 0); issue(1, 1); issue(2, 2); }
      for (int r = 0; r + 1 < nrounds; r++) {
        const bool more = r + 2 < nrounds;
        mbar_wait(xbar, r & 1);
        if (r > 0) issue(2, 2);
        row(IC<0>{}, IC<0>{}, IC<1>{}, 0, 0);
        mbar_wait(xbar + 8, r & 1);
        issue(0, 3);
        row(IC<0>{}, IC<1>{}, IC<1>{}, 1, 0);
        mbar_wait(sb + BAR_TEMPTY, r & 1);
        TR(0);
#pragma unroll 1
        for (int k = 0; k < 2; k++) {
          mbar_wait(xbar + 16, (r + k) & 1);
          issue(1, 4 + 3 * k);
          row(IC<1>{}, IC<1>{}, IC<1>{}, 2, 3 * k);
          mbar_wait(xbar, (r + k + 1) & 1);
          issue(2, 5 + 3 * k);
          row(IC<1>{}, IC<1>{}, IC<1>{}, 0, 3 * k + 1);
          mbar_wait(xbar + 8, (r + k + 1) & 1);
          if (k == 1 && more) coords(r + 2);
          if (k == 0 || more) issue(0, k == 0 ? 6 : 0);
          row(IC<1>{}, IC<1>{}, IC<1>{}, 1, 3 * k + 2);
        }
        mbar_wait(xbar + 16, r & 1);
        if (more) issue(1, 1);
        row(IC<2>{}, IC<0>{}, IC<0>{}, 2, 6);
        __syncwarp();
        warp_arrive(sb + BAR_TFULL);
        TR(1);
      }
    }
    asm volatile("bar.sync 5, 384;" ::: "memory");
#pragma unroll 1
    for (int i = 0; i < 8; i++) {
      uint32_t bits = *reinterpret_cast<volatile uint32_t*>(smem + OFF_REDO + 4 * i);
#pragma unroll 1
      for (; bits; bits &= bits - 1)
        slow_window(reinterpret_cast<float*>(smem), window_of((i & 3) * 32 + __ffs(bits) - 1, nfull, cta, ncta, i >> 2), tid - 256, x, dw, wqkv, wo, out);
    }
  } else {
    asm volatile("setmaxnreg.inc.sync.aligned.u32 " CREGS ";");
    const int wg = warp >> 2, w4 = warp & 3, g = lane >> 2, q = lane & 3;
    const int row0 = w4 * 16 + g, row1 = row0 + 8;
    const int ps = min(w4 * 8 + g, 24);
    const int pix0 = ps < 21 ? (ps / 3) * IMG + (ps % 3) * 2 : (ps - 21) * 2 * IMG + 6;
    const int pix1 = pix0 + (ps < 21 ? 1 : ps < 24 ? IMG : 0);
    const uint32_t kv = sb + OFF_KV + wg * KV_BYTES;
    const int srow = w4 * 16 + (lane & 15);
    const uint32_t vst = kv + (lane >> 4) * KV_PITCH + (srow < 56 ? srow : min(srow - 7, 55)) * 16;
    uint32_t misc = ((uint32_t)pix1 << 20) | ((uint32_t)pix0 << 8) | q;
    const uint32_t ninf = q ? 0xfc00fc00u : 0u;
    const uint32_t v48 = kv + (lane >> 3) * KV_PITCH + 48 * 16;
    const uint32_t vmask = (row0 < 49 ? 0xffffu : 0u) | (row1 < 49 ? 0xffff0000u : 0u);

    const uint32_t tx = sb + q * 32 + (row0 < 49 ? OFF_TILE + wg * TILE_BYTES + ps * 768 + (ps & 1) * 16 : OFF_ZERO + 16);
    const int myrounds = window_of(nrounds - 1, nfull, cta, ncta, wg) < 0 ? nrounds - 1 : nrounds;

    if (never == 2) return;
    uint32_t H[48], Y[48];
    const uint64_t* dkv = ds.kv[wg];
    uint32_t P[NP], Ofc[12], p48 = 0;
#pragma unroll
    for (int i = 0; i < 48; i++) Y[i] = 0;
#pragma unroll
    for (int i = 0; i < NP; i++) P[i] = Ofc[i % 12] = 0;
    if (warp == 0) GTS(4);
    load_x<0, 12>(H, tx);
    warp_arrive(sb + BAR_TEMPTY);
    if (wg == 1) turn_pass(1);

    uint8_t *o0, *o1;
    uint32_t omask;
    auto out_setup = [&](int r) {
      omask = r >= 0 ? vmask : 0u;
      const int w = window_of(r, nfull, cta, ncta, wg);
      const int wy = w / NWX, wx = w - wy * NWX;
      asm volatile("" : "+r"(misc));
      const uint32_t wb = (uint32_t)(wy * 7 * IMG + wx * 7) * 384u + (misc & 3) * 16;
      o0 = reinterpret_cast<uint8_t*>(out) + (wb + ((misc >> 8) & 0xfff) * 384u);
      o1 = reinterpret_cast<uint8_t*>(out) + (wb + (misc >> 20) * 384u);
    };
#define OUT(c) store_out<c>(Y, o0, o1, omask)
    auto release = [&](int stage) { warp_arrive(sb + BAR_WEMPTY + 8 * stage); };

    for (int r = 0;; r++) {
      const uint32_t par = r & 1;
      uint32_t acc[36], S[14], O[14], Q[12], V[12], Ofa[12], Ofb[12], vr[6], k48, mx;
      if (r == myrounds) {
        const bool idle = r < nrounds;
        mbar_wait(sb + BAR_WFULL + 40, par);
        turn_wait(wg);
        wg_fence(); mma_pv(O, P, dkv + 4); mma_proj(Y, Ofc, ds.p + 6); wg_commit();
        turn_pass(wg);
        load_v48(vr, v48);
        wg_wait<0>(); keep(O); keep(Y);
        finish_o(O, vr, p48, vmask, Ofa);
        if (idle) { release(5); release(0); release(1); release(2); release(3); }
        mbar_wait(sb + BAR_WFULL + 48, par);
        turn_wait(wg);
        wg_fence(); mma_proj(Y, Ofa, ds.p + 9); wg_commit();
        if (wg == 0 || idle) turn_pass(wg);
        wg_wait<0>(); keep(Y);
        if (idle) { release(6); turn_wait(wg); turn_pass(wg); }
        out_setup(r - 1);
        OUT(0); PIN(); OUT(1); PIN(); OUT(2); PIN(); OUT(3); PIN(); OUT(4); PIN(); OUT(5);
        if (idle) {
          turn_wait(wg); turn_pass(wg);
          turn_wait(wg); turn_pass(wg);
          turn_wait(wg); turn_pass(wg);
          turn_wait(wg);
        }
        if (w4 == 0) GTS(5 + wg);
        asm volatile("bar.arrive 5, 384;" ::: "memory");
        break;
      }
      float s1[2], s2[2];
      if (SA > 0) ln_sums<0, SA>(H, s1, s2);
      mbar_wait(sb + BAR_WFULL + 40, par);
      mbar_wait(sb + BAR_WFULL, par);
      TR(0);
      turn_wait(wg);
      TR(1);
      wg_fence(); mma_pv(O, P, dkv + 4); wg_commit();
      if (r > 0) { wg_fence(); mma_proj(Y, Ofc, ds.p + 6); wg_commit(); }
      wg_fence(); mma_qkv<0, 3>(acc, H, ds.q[0]);
      PIN();
      ln_sums<SA, SB>(H, s1, s2);
      PIN();
      wg_fence(); mma_qkv<3, 8>(acc, H, ds.q[0]);
      PIN();
      ln_sums<SB, SC>(H, s1, s2);
      PIN();
      wg_fence(); mma_qkv<8, 12>(acc, H, ds.q[0]);
      turn_pass(wg);
      TR(2);
      load_v48(vr, v48);
      wg_wait<3>(); keep(O); keep(Y);
      release(5);
      wg_sync(wg);
      PIN();
      finish_o(O, vr, p48, vmask, Ofa);
      if (SC < 48) ln_sums<SC, 48>(H, s1, s2);
      float lim_lo, lim_hi;
      asm volatile("ld.shared.v2.f32 {%0,%1}, [%2];" : "=f"(lim_lo), "=f"(lim_hi) : "r"(sb + OFF_LIM) : "memory");
      bool ok;
      const uint32_t rk = ln_rstd(s1, s2, lim_lo, lim_hi, vmask, ok);
      asm volatile("{\n.reg .pred p;\nsetp.eq.s32 p, %2, 0;\n@p red.shared.or.b32 [%0], %1;\n}\n"
                   :: "r"(sb + OFF_REDO + wg * 16 + (r >> 5) * 4), "r"(1u << (r & 31)), "r"((int)ok) : "memory");
      PIN();
      TR(3);
      wg_wait<0>(); keep(acc);
      TR(4);
      release(0);
      scale12(V, acc, rk); stsm12(V, vst + KV_KOFF);
      scale12(V, acc + 24, rk); stsm12(V, vst);
      scale12(Q, acc + 12, rk); PIN();
      proxy_fence();
      mbar_wait(sb + BAR_WFULL + 48, par);
      mbar_wait(sb + BAR_WFULL + 8, par);
      TR(5);
      turn_wait(wg);
      TR(6);
      if (r > 0) { wg_fence(); mma_proj(Y, Ofa, ds.p + 9); wg_commit(); }
      wg_fence(); mma_s(S, Q, dkv); mma_qkv<0, 2>(acc, H, ds.q[1]);
      out_setup(r - 1);
      PIN();
      wg_wait<1>(); keep(Y);
      release(6);
      wg_fence(); mma_qkv<2, 6>(acc, H, ds.q[1]);
      PIN();
      OUT(0);
      PIN();
      wg_wait<1>(); keep(S);
      wg_fence(); mma_qkv<6, 9>(acc, H, ds.q[1]);
      PIN();
      row_max(S, k48, mx, ninf);
      OUT(1);
      PIN();
      wg_fence(); mma_qkv<9, 12>(acc, H, ds.q[1]);
      turn_pass(wg);
      PIN();
      OUT(2); PIN();
      OUT(3); PIN();
      row_exp(S, k48, mx, P, p48);
      PIN();
      TR(7);
      wg_wait<0>(); keep(acc);
      TR(8);
      release(1);
      wg_sync(wg);
      scale12(V, acc, rk); stsm12(V, vst + KV_KOFF);
      scale12(Q, acc + 12, rk); scale12(V, acc + 24, rk); PIN();
      proxy_fence();
#define TURN(ID, OF, G1, G2, G3, X1)                                                       \
      TR(ID + 1);                                                                       \
      turn_wait(wg);                                                                    \
      wg_fence(); mma_pv(O, P, dkv + 4); mma_s(S, Q, dkv); wg_commit(); G1;             \
      PIN();                                                                            \
      TR(ID + 2);                                                                       \
      load_v48(vr, v48);                                                                \
      X1;                                                                               \
      PIN();                                                                            \
      wg_wait<1>(); keep(S); keep(O);                                                   \
      wg_sync(wg);                                         \
      wg_fence(); G2;                                                                   \
      if (KB == 12) turn_pass(wg);                                                      \
      PIN();                                                                            \
      stsm12(V, vst);                                                                   \
      finish_o(O, vr, p48, vmask, OF);                                                    \
      row_max(S, k48, mx, ninf);                                                              \
      PIN();                                                                            \
      if (KB < 12) { wg_fence(); G3; turn_pass(wg); }                                                                 \
      PIN();                                                                            \
      TR(ID + 3);
#define NEXT_HEAD(ID, HD, X2)                                                           \
      row_exp(S, k48, mx, P, p48);                                                      \
      PIN();                                                                            \
      X2;                                                                               \
      TR(ID + 4);                                                                       \
      wg_wait<0>(); keep(acc);                                                          \
      release(HD);                                                                      \
      scale12(V, acc, rk); stsm12(V, vst + KV_KOFF);                                    \
      scale12(Q, acc + 12, rk); scale12(V, acc + 24, rk); PIN();
      mbar_wait(sb + BAR_WFULL + 16, par);
      TURN(8, Ofa, (mma_qkv<0, KA>(acc, H, ds.q[2])), (mma_qkv<KA, KB>(acc, H, ds.q[2])), (mma_qkv<KB, 12>(acc, H, ds.q[2])), OUT(4))
      OUT(5); PIN();
      NEXT_HEAD(8, 2, )
      proxy_fence();
      mbar_wait(sb + BAR_WFULL + 24, par);
      TURN(12, Ofb, (mma_qkv<0, KA>(acc, H, ds.q[3])), (mma_qkv<KA, KB>(acc, H, ds.q[3])), (mma_qkv<KB, 12>(acc, H, ds.q[3])), )
      auto init_y = [&]() {
#pragma unroll
        for (int i = 0; i < 48; i++) Y[i] = (i & 1) ? H[i] ^ never : h2u(__hadd2_rn(u2h(H[i]), u2h(never)));
        hold<0, 48>(Y); PIN();
      };
      NEXT_HEAD(12, 3, if (YEARLY) init_y())
      if (!YEARLY) init_y();
      proxy_fence();
      mbar_wait(sb + BAR_WFULL + 32, par);
      TR(17);
      turn_wait(wg);
      wg_fence(); mma_pv(O, P, dkv + 4); mma_s(S, Q, dkv); wg_commit(); mma_proj(Y, Ofa, ds.p); mma_proj(Y, Ofb, ds.p + 3); wg_commit();
      turn_pass(wg);
      PIN();
      TR(18);
      load_v48(vr, v48);
      if (r + 1 < myrounds) mbar_wait(sb + BAR_TFULL, par);
      load_x<0, 4>(H, tx);
      wg_wait<1>(); keep(S); keep(O);
      wg_sync(wg);
      PIN();
      TR(19);
      row_max(S, k48, mx, ninf);
      finish_o(O, vr, p48, vmask, Ofc);
      stsm12(V, vst);
      PIN();
      load_x<4, 8>(H, tx);
      row_exp(S, k48, mx, P, p48);
      PIN();
      load_x<8, 12>(H, tx);
      warp_arrive(sb + BAR_TEMPTY);
      TR(20);
      wg_wait<0>(); keep(Y);
      release(4);
      proxy_fence();
      TR(21);
#undef TURN
#undef NEXT_HEAD
    }
  }
}

typedef CUresult (*EncodeFn)(CUtensorMap*, CUtensorMapDataType, cuuint32_t, void*, const cuuint64_t*, const cuuint64_t*,
                             const cuuint32_t*, const cuuint32_t*, CUtensorMapInterleave, CUtensorMapSwizzle,
                             CUtensorMapL2promotion, CUtensorMapFloatOOBfill);

}

extern "C" void kernel_launch(void* const* d_in, const int* in_sizes, int n_in, void* d_out, int out_size) {
  const __nv_bfloat16* x = (const __nv_bfloat16*)d_in[0];
  const __nv_bfloat16* dw = (const __nv_bfloat16*)d_in[1];
  const __nv_bfloat16* wqkv = (const __nv_bfloat16*)d_in[2];
  const __nv_bfloat16* wo = (const __nv_bfloat16*)d_in[3];
  static EncodeFn encode = nullptr;
  static int nsm = 0;
  static void* wpack = nullptr;
  if (!encode) {
    void* fn = nullptr;
    cudaDriverEntryPointQueryResult qr;
    cudaGetDriverEntryPoint("cuTensorMapEncodeTiled", &fn, cudaEnableDefault, &qr);
    encode = (EncodeFn)fn;
    int dev = 0;
    cudaGetDevice(&dev);
    cudaDeviceGetAttribute(&nsm, cudaDevAttrMultiProcessorCount, dev);
    cudaGetSymbolAddress(&wpack, g_wpack);
    cudaFuncSetAttribute(fused_kernel, cudaFuncAttributeMaxDynamicSharedMemorySize, SMEM_BYTES);
  }
  CUtensorMap tmx;
  cuuint64_t gdim[3] = {CH, IMG, IMG};
  cuuint64_t gstr[2] = {CH * 2, (cuuint64_t)CH * 2 * IMG};
  cuuint32_t box[3] = {64, 9, 1};
  cuuint32_t estr[3] = {1, 1, 1};
  encode(&tmx, CU_TENSOR_MAP_DATA_TYPE_BFLOAT16, 3, (void*)x, gdim, gstr, box, estr, CU_TENSOR_MAP_INTERLEAVE_NONE,
         CU_TENSOR_MAP_SWIZZLE_NONE, CU_TENSOR_MAP_L2_PROMOTION_L2_128B, CU_TENSOR_MAP_FLOAT_OOB_FILL_NONE);
  Descs ds;
  for (int i = 0; i < 12; i++) {
    for (int h = 0; h < 4; h++) ds.q[h][i] = mkdesc(SMEM_BASE + OFF_W + qkv_pos(h, i) % (8 * SLICE), 128, 256);
    ds.p[i] = mkdesc(SMEM_BASE + OFF_W + wo_pos(i) % (8 * SLICE), 128, 256);
  }
  for (int i = 0; i < 16; i++) ds.src[i] = (const uint8_t*)wpack + i * SLICE;
  for (int g = 0; g < 2; g++)
    for (int i = 0; i < 4; i++) {
      ds.kv[g][i] = mkdesc(SMEM_BASE + OFF_KV + g * KV_BYTES + KV_KOFF + 2 * i * KV_PITCH, KV_PITCH, 128);
      ds.kv[g][4 + i] = mkdesc(SMEM_BASE + OFF_KV + g * KV_BYTES + 256 * i, 128, KV_PITCH);
    }
  CUtensorMap tmp;
  cuuint32_t boxp[3] = {CH, 9, 9};
  encode(&tmp, CU_TENSOR_MAP_DATA_TYPE_BFLOAT16, 3, (void*)x, gdim, gstr, boxp, estr, CU_TENSOR_MAP_INTERLEAVE_NONE,
         CU_TENSOR_MAP_SWIZZLE_NONE, CU_TENSOR_MAP_L2_PROMOTION_L2_128B, CU_TENSOR_MAP_FLOAT_OOB_FILL_NONE);
  prepack_kernel<<<48, dim3(192, 2), 0, cudaStreamPerThread>>>(wqkv, wo);
  cudaLaunchConfig_t cfg = {};
  cfg.gridDim = dim3(nsm); cfg.blockDim = dim3(384); cfg.dynamicSmemBytes = SMEM_BYTES; cfg.stream = cudaStreamPerThread;
  cudaLaunchAttribute at[1];
  at[0].id = cudaLaunchAttributeProgrammaticStreamSerialization;
  at[0].val.programmaticStreamSerializationAllowed = 1;
  cfg.attrs = at; cfg.numAttrs = 1;
  cudaLaunchKernelEx(&cfg, fused_kernel, tmx, tmp, ds, dw, (__nv_bfloat16*)d_out, 0, x, wqkv, wo);
}
```

```cpp
#include <cuda_runtime.h>
#include <cuda_bf16.h>
#include <cuda_fp16.h>
#include <cuda.h>
#include <stdint.h>

#define CREGS "208"
#define PREGS "88"
#define K48TC 0
#define EARLYX 0
#define LA 4
#define STHINT ".cs"
#define K0A 6
#define K0B 10
#define B4ORD 0
#define FINE 0
#define KA (FINE ? 4 : 3)
#define KB (FINE ? 8 : 9)
#define SPOS 2
#define SKIPU 0
namespace {
constexpr int NP = K48TC ? 16 : 12;

constexpr int IMG = 511;
constexpr int CH = 192;
constexpr int NWX = 73;
constexpr int NWIN = NWX * NWX;
constexpr int SLICE = 18432;
constexpr int OFF_W = 0;
constexpr int KV_PITCH = 1792, KV_KOFF = 896, KV_BYTES = 6 * KV_PITCH + 1024;
constexpr int OFF_KV = 8 * SLICE;
constexpr int TILE_BYTES = 25 * 768;
constexpr int OFF_TILE = OFF_KV + 2 * KV_BYTES;
constexpr int XSLOT = 2304;
constexpr int OFF_ZERO = OFF_TILE + 2 * TILE_BYTES;
constexpr int OFF_X = OFF_ZERO + 768;
constexpr int OFF_BAR = OFF_X + 9 * XSLOT;
constexpr int BAR_FH = OFF_BAR;
constexpr int BAR_FU = OFF_BAR + 48, BAR_FV = OFF_BAR + 56;
constexpr int BAR_F0 = OFF_BAR + 64, BAR_F1 = OFF_BAR + 72;
constexpr int BAR_E = OFF_BAR + 80;
constexpr int BAR_XFULL = OFF_BAR + 112;
constexpr int BAR_TFULL = OFF_BAR + 184;
constexpr int BAR_TEMPTY = OFF_BAR + 192;
constexpr int OFF_LIM = OFF_BAR + 200;
constexpr int OFF_REDO = OFF_BAR + 208;
constexpr int BAR_FIRST = OFF_BAR + 240;
constexpr int OFF_TRACE = OFF_BAR + 248;
constexpr int OFF_HALO = OFF_W + 3 * SLICE, HALO_BYTES = 81 * 384;
constexpr int SMEM_BYTES = OFF_TRACE;

__host__ __device__ constexpr int qkv_pos(int h, int s) { return 3 * h * SLICE + s * 4608; }
__host__ __device__ constexpr int wo_pos(int s) { return 12 * SLICE + s * 6144; }
constexpr int SLOT_U = 6, SLOT_V = 7;
constexpr int SMEM_BASE = 1024;
struct Descs { uint64_t q[5][12]; uint64_t pu[2][3], pv[2][3]; uint64_t kv[2][8]; const uint8_t* src; };

__device__ uint4 g_wpack[16 * SLICE / 16];
__device__ float2 g_wnorm[96];
#define TR(id)
#define GTS(i)
template <int V> struct IC { static constexpr int v = V; };
typedef __nv_bfloat162 bf2;
__device__ __forceinline__ bf2 u2b(uint32_t u) { return *reinterpret_cast<bf2*>(&u); }
__device__ __forceinline__ uint32_t b2u(bf2 b) { return *reinterpret_cast<uint32_t*>(&b); }
__device__ __forceinline__ uint32_t pack2(float lo, float hi) {
  uint32_t r; asm("cvt.rn.bf16x2.f32 %0, %1, %2;" : "=r"(r) : "f"(hi), "f"(lo)); return r;
}
__device__ __forceinline__ uint32_t hadd(uint32_t a, uint32_t b) { return b2u(__hadd2_rn(u2b(a), u2b(b))); }
__device__ __forceinline__ uint32_t hmul(uint32_t a, uint32_t b) { return b2u(__hmul2_rn(u2b(a), u2b(b))); }
__device__ __forceinline__ uint32_t hfma(uint32_t a, uint32_t b, uint32_t c) { return b2u(__hfma2(u2b(a), u2b(b), u2b(c))); }
__device__ __forceinline__ __half2 u2h(uint32_t u) { return *reinterpret_cast<__half2*>(&u); }
__device__ __forceinline__ uint32_t h2u(__half2 b) { return *reinterpret_cast<uint32_t*>(&b); }
__device__ __forceinline__ uint32_t packh(float lo, float hi) {
  uint32_t r; asm("cvt.rn.f16x2.f32 %0, %1, %2;" : "=r"(r) : "f"(hi), "f"(lo)); return r;
}
__device__ __forceinline__ uint32_t fmax2(uint32_t a, uint32_t b) { return h2u(__hmax2(u2h(a), u2h(b))); }
template <int HI> __device__ __forceinline__ __half2 hcast(uint32_t a) { return HI ? __high2half2(u2h(a)) : __low2half2(u2h(a)); }
template <int HI> __device__ __forceinline__ uint32_t fmul_b(uint32_t a, uint32_t s) { return h2u(__hmul2_rn(u2h(a), hcast<HI>(s))); }
template <int HI> __device__ __forceinline__ uint32_t fsub_b(uint32_t a, uint32_t s) { return h2u(__hsub2_rn(u2h(a), hcast<HI>(s))); }
__device__ __forceinline__ uint32_t fex2(uint32_t a) { uint32_t r; asm("ex2.approx.f16x2 %0, %1;" : "=r"(r) : "r"(a)); return r; }
__device__ __forceinline__ float lo2f(uint32_t a) { return __uint_as_float(a << 16); }
__device__ __forceinline__ float hi2f(uint32_t a) { return __uint_as_float(a & 0xffff0000u); }

__device__ __forceinline__ void mbar_init(uint32_t bar, uint32_t cnt) { asm volatile("mbarrier.init.shared::cta.b64 [%0], %1;" :: "r"(bar), "r"(cnt) : "memory"); }
__device__ __forceinline__ void mbar_wait(uint32_t bar, uint32_t parity) {
  asm volatile("{\n.reg .pred p;\n.reg .u32 n;\n"
               "mbarrier.try_wait.parity.shared::cta.b64 p, [%0], %1;\n"
               "@p bra.uni DONE_%=;\n"
               "mov.u32 n, 0;\n"
               "AGAIN_%=:\n"
               "mbarrier.try_wait.parity.shared::cta.b64 p, [%0], %1;\n"
               "@p bra.uni DONE_%=;\n"
               "add.u32 n, n, 1;\n"
               "setp.lt.u32 p, n, 0x1000000;\n"
               "@p bra.uni AGAIN_%=;\n"
               "trap;\n"
               "DONE_%=:\n}\n" :: "r"(bar), "r"(parity) : "memory");
}
__device__ __forceinline__ void wg_fence() { asm volatile("wgmma.fence.sync.aligned;" ::: "memory"); }
__device__ __forceinline__ void wg_commit() { asm volatile("wgmma.commit_group.sync.aligned;" ::: "memory"); }
template <int N> __device__ __forceinline__ void wg_wait() { asm volatile("wgmma.wait_group.sync.aligned %0;" :: "n"(N) : "memory"); }
#define BAR_BY_WG(OP, ID0, ID1, CNT) asm volatile("{\n.reg .pred p;\nsetp.eq.s32 p, %0, 0;\n@p " OP " " #ID0 ", " #CNT ";\n@!p " OP " " #ID1 ", " #CNT ";\n}\n" :: "r"(wg) : "memory")
__device__ __forceinline__ void wg_sync(int wg) { BAR_BY_WG("bar.sync", 1, 2, 128); }
__device__ __forceinline__ void turn_wait(int wg) { BAR_BY_WG("bar.sync", 3, 4, 256); }
__device__ __forceinline__ void turn_pass(int wg) { BAR_BY_WG("bar.arrive", 4, 3, 256); }
__device__ __forceinline__ void stsm4(uint32_t addr, uint32_t a, uint32_t b, uint32_t c, uint32_t d) {
  asm volatile("stmatrix.sync.aligned.m8n8.x4.shared.b16 [%0], {%1,%2,%3,%4};" :: "r"(addr), "r"(a), "r"(b), "r"(c), "r"(d) : "memory");
}
template <int N> __device__ __forceinline__ void keep(float (&d)[N]) {
#pragma unroll
  for (int i = 0; i < N; i++) asm volatile("" : "+f"(d[i]) :: "memory");
}
template <int N> __device__ __forceinline__ void keep(uint32_t (&d)[N]) {
#pragma unroll
  for (int i = 0; i < N; i++) asm volatile("" : "+r"(d[i]) :: "memory");
}
__host__ __device__ __forceinline__ uint64_t mkdesc(uint32_t addr, uint32_t lbo, uint32_t sbo) {
  return ((uint64_t)(sbo >> 4) << 32) | (uint64_t)(((lbo >> 4) << 16) | ((addr & 0x3FFFF) >> 4));
}

template <int SCALE_D>
__device__ __forceinline__ void wgmma_n144(uint32_t (&d)[36], uint32_t a0, uint32_t a1, uint32_t a2, uint32_t a3, uint64_t descB) {
  if (SCALE_D == 0)
  asm volatile("wgmma.mma_async.sync.aligned.m64n144k16.f16.f16.f16 "
    "{%0, %1, %2, %3, %4, %5, %6, %7, %8, %9, %10, %11, %12, %13, %14, %15, "
    "%16, %17, %18, %19, %20, %21, %22, %23, %24, %25, %26, %27, %28, %29, %30, %31, "
    "%32, %33, %34, %35}, "
    "{%36, %37, %38, %39}, %40, 0, 1, 1, 0;\n"
    : "=r"(d[0]), "=r"(d[1]), "=r"(d[2]), "=r"(d[3]), "=r"(d[4]), "=r"(d[5]), "=r"(d[6]), "=r"(d[7]),
      "=r"(d[8]), "=r"(d[9]), "=r"(d[10]), "=r"(d[11]), "=r"(d[12]), "=r"(d[13]), "=r"(d[14]), "=r"(d[15]),
      "=r"(d[16]), "=r"(d[17]), "=r"(d[18]), "=r"(d[19]), "=r"(d[20]), "=r"(d[21]), "=r"(d[22]), "=r"(d[23]),
      "=r"(d[24]), "=r"(d[25]), "=r"(d[26]), "=r"(d[27]), "=r"(d[28]), "=r"(d[29]), "=r"(d[30]), "=r"(d[31]),
      "=r"(d[32]), "=r"(d[33]), "=r"(d[34]), "=r"(d[35])
    : "r"(a0), "r"(a1), "r"(a2), "r"(a3), "l"(descB));
  else
  asm volatile("wgmma.mma_async.sync.aligned.m64n144k16.f16.f16.f16 "
    "{%0, %1, %2, %3, %4, %5, %6, %7, %8, %9, %10, %11, %12, %13, %14, %15, "
    "%16, %17, %18, %19, %20, %21, %22, %23, %24, %25, %26, %27, %28, %29, %30, %31, "
    "%32, %33, %34, %35}, "
    "{%36, %37, %38, %39}, %40, 1, 1, 1, 0;\n"
    : "+r"(d[0]), "+r"(d[1]), "+r"(d[2]), "+r"(d[3]), "+r"(d[4]), "+r"(d[5]), "+r"(d[6]), "+r"(d[7]),
      "+r"(d[8]), "+r"(d[9]), "+r"(d[10]), "+r"(d[11]), "+r"(d[12]), "+r"(d[13]), "+r"(d[14]), "+r"(d[15]),
      "+r"(d[16]), "+r"(d[17]), "+r"(d[18]), "+r"(d[19]), "+r"(d[20]), "+r"(d[21]), "+r"(d[22]), "+r"(d[23]),
      "+r"(d[24]), "+r"(d[25]), "+r"(d[26]), "+r"(d[27]), "+r"(d[28]), "+r"(d[29]), "+r"(d[30]), "+r"(d[31]),
      "+r"(d[32]), "+r"(d[33]), "+r"(d[34]), "+r"(d[35])
    : "r"(a0), "r"(a1), "r"(a2), "r"(a3), "l"(descB));
}

template <int SCALE_D>
__device__ __forceinline__ void wgmma_n192(uint32_t (&d)[48], uint32_t a0, uint32_t a1, uint32_t a2, uint32_t a3, uint64_t descB) {
  if (SCALE_D == 0)
  asm volatile("wgmma.mma_async.sync.aligned.m64n192k16.f16.f16.f16 "
    "{%0, %1, %2, %3, %4, %5, %6, %7, %8, %9, %10, %11, %12, %13, %14, %15, "
    "%16, %17, %18, %19, %20, %21, %22, %23, %24, %25, %26, %27, %28, %29, %30, %31, "
    "%32, %33, %34, %35, %36, %37, %38, %39, %40, %41, %42, %43, %44, %45, %46, %47}, "
    "{%48, %49, %50, %51}, %52, 0, 1, 1, 0;\n"
    : "=r"(d[0]), "=r"(d[1]), "=r"(d[2]), "=r"(d[3]), "=r"(d[4]), "=r"(d[5]), "=r"(d[6]), "=r"(d[7]),
      "=r"(d[8]), "=r"(d[9]), "=r"(d[10]), "=r"(d[11]), "=r"(d[12]), "=r"(d[13]), "=r"(d[14]), "=r"(d[15]),
      "=r"(d[16]), "=r"(d[17]), "=r"(d[18]), "=r"(d[19]), "=r"(d[20]), "=r"(d[21]), "=r"(d[22]), "=r"(d[23]),
      "=r"(d[24]), "=r"(d[25]), "=r"(d[26]), "=r"(d[27]), "=r"(d[28]), "=r"(d[29]), "=r"(d[30]), "=r"(d[31]),
      "=r"(d[32]), "=r"(d[33]), "=r"(d[34]), "=r"(d[35]), "=r"(d[36]), "=r"(d[37]), "=r"(d[38]), "=r"(d[39]),
      "=r"(d[40]), "=r"(d[41]), "=r"(d[42]), "=r"(d[43]), "=r"(d[44]), "=r"(d[45]), "=r"(d[46]), "=r"(d[47])
    : "r"(a0), "r"(a1), "r"(a2), "r"(a3), "l"(descB));
  else
  asm volatile("wgmma.mma_async.sync.aligned.m64n192k16.f16.f16.f16 "
    "{%0, %1, %2, %3, %4, %5, %6, %7, %8, %9, %10, %11, %12, %13, %14, %15, "
    "%16, %17, %18, %19, %20, %21, %22, %23, %24, %25, %26, %27, %28, %29, %30, %31, "
    "%32, %33, %34, %35, %36, %37, %38, %39, %40, %41, %42, %43, %44, %45, %46, %47}, "
    "{%48, %49, %50, %51}, %52, 1, 1, 1, 0;\n"
    : "+r"(d[0]), "+r"(d[1]), "+r"(d[2]), "+r"(d[3]), "+r"(d[4]), "+r"(d[5]), "+r"(d[6]), "+r"(d[7]),
      "+r"(d[8]), "+r"(d[9]), "+r"(d[10]), "+r"(d[11]), "+r"(d[12]), "+r"(d[13]), "+r"(d[14]), "+r"(d[15]),
      "+r"(d[16]), "+r"(d[17]), "+r"(d[18]), "+r"(d[19]), "+r"(d[20]), "+r"(d[21]), "+r"(d[22]), "+r"(d[23]),
      "+r"(d[24]), "+r"(d[25]), "+r"(d[26]), "+r"(d[27]), "+r"(d[28]), "+r"(d[29]), "+r"(d[30]), "+r"(d[31]),
      "+r"(d[32]), "+r"(d[33]), "+r"(d[34]), "+r"(d[35]), "+r"(d[36]), "+r"(d[37]), "+r"(d[38]), "+r"(d[39]),
      "+r"(d[40]), "+r"(d[41]), "+r"(d[42]), "+r"(d[43]), "+r"(d[44]), "+r"(d[45]), "+r"(d[46]), "+r"(d[47])
    : "r"(a0), "r"(a1), "r"(a2), "r"(a3), "l"(descB));
}

template <int SCALE_D>
__device__ __forceinline__ void wgmma_n56(uint32_t (&d)[14], uint32_t a0, uint32_t a1, uint32_t a2, uint32_t a3, uint64_t descB) {
  if (SCALE_D == 0)
  asm volatile("wgmma.mma_async.sync.aligned.m64n56k16.f16.f16.f16 "
    "{%0, %1, %2, %3, %4, %5, %6, %7, %8, %9, %10, %11, %12, %13}, "
    "{%14, %15, %16, %17}, %18, 0, 1, 1, 0;\n"
    : "=r"(d[0]), "=r"(d[1]), "=r"(d[2]), "=r"(d[3]), "=r"(d[4]), "=r"(d[5]), "=r"(d[6]), "=r"(d[7]),
      "=r"(d[8]), "=r"(d[9]), "=r"(d[10]), "=r"(d[11]), "=r"(d[12]), "=r"(d[13])
    : "r"(a0), "r"(a1), "r"(a2), "r"(a3), "l"(descB));
  else
  asm volatile("wgmma.mma_async.sync.aligned.m64n56k16.f16.f16.f16 "
    "{%0, %1, %2, %3, %4, %5, %6, %7, %8, %9, %10, %11, %12, %13}, "
    "{%14, %15, %16, %17}, %18, 1, 1, 1, 0;\n"
    : "+r"(d[0]), "+r"(d[1]), "+r"(d[2]), "+r"(d[3]), "+r"(d[4]), "+r"(d[5]), "+r"(d[6]), "+r"(d[7]),
      "+r"(d[8]), "+r"(d[9]), "+r"(d[10]), "+r"(d[11]), "+r"(d[12]), "+r"(d[13])
    : "r"(a0), "r"(a1), "r"(a2), "r"(a3), "l"(descB));
}

template <int SCALE_D>
__device__ __forceinline__ void wgmma_n56t(uint32_t (&d)[14], uint32_t a0, uint32_t a1, uint32_t a2, uint32_t a3, uint64_t descB) {
  if (SCALE_D == 0)
  asm volatile("wgmma.mma_async.sync.aligned.m64n56k16.f16.f16.f16 "
    "{%0, %1, %2, %3, %4, %5, %6, %7, %8, %9, %10, %11, %12, %13}, "
    "{%14, %15, %16, %17}, %18, 0, 1, 1, 1;\n"
    : "=r"(d[0]), "=r"(d[1]), "=r"(d[2]), "=r"(d[3]), "=r"(d[4]), "=r"(d[5]), "=r"(d[6]), "=r"(d[7]),
      "=r"(d[8]), "=r"(d[9]), "=r"(d[10]), "=r"(d[11]), "=r"(d[12]), "=r"(d[13])
    : "r"(a0), "r"(a1), "r"(a2), "r"(a3), "l"(descB));
  else
  asm volatile("wgmma.mma_async.sync.aligned.m64n56k16.f16.f16.f16 "
    "{%0, %1, %2, %3, %4, %5, %6, %7, %8, %9, %10, %11, %12, %13}, "
    "{%14, %15, %16, %17}, %18, 1, 1, 1, 1;\n"
    : "+r"(d[0]), "+r"(d[1]), "+r"(d[2]), "+r"(d[3]), "+r"(d[4]), "+r"(d[5]), "+r"(d[6]), "+r"(d[7]),
      "+r"(d[8]), "+r"(d[9]), "+r"(d[10]), "+r"(d[11]), "+r"(d[12]), "+r"(d[13])
    : "r"(a0), "r"(a1), "r"(a2), "r"(a3), "l"(descB));
}

__global__ void __launch_bounds__(384) prepack_kernel(const __nv_bfloat16* __restrict__ wqkv, const __nv_bfloat16* __restrict__ wo) {
  asm volatile("griddepcontrol.launch_dependents;");
  __shared__ float red2[2][2][6][8];
  float (*red)[6][8] = red2[threadIdx.y];
  __half* dst = reinterpret_cast<__half*>(g_wpack);
  const int c = threadIdx.x, nb = blockIdx.x * 2 + threadIdx.y;
  auto colsum = [&](int k, const float (&v)[8], float (&o)[8]) {
#pragma unroll
    for (int i = 0; i < 8; i++) {
      float t = v[i];
#pragma unroll
      for (int d = 16; d; d >>= 1) t += __shfl_xor_sync(~0u, t, d);
      if ((c & 31) == 0) red[k][c >> 5][i] = t;
    }
    __syncthreads();
#pragma unroll
    for (int i = 0; i < 8; i++) o[i] = red[k][0][i] + red[k][1][i] + red[k][2][i] + red[k][3][i] + red[k][4][i] + red[k][5][i];
  };
  float v[8], t[8];
  int base;
  if (nb < 72) {
    const int h = nb / 18, j = nb % 18, part = j / 6;
    const int col = (part == 0 ? 192 : part == 1 ? 0 : 384) + h * 48 + (j % 6) * 8;
    uint4 raw = *reinterpret_cast<const uint4*>(wqkv + c * 576 + col);
    uint32_t u[4] = {raw.x, raw.y, raw.z, raw.w};
#pragma unroll
    for (int i = 0; i < 4; i++) { v[2 * i] = lo2f(u[i]); v[2 * i + 1] = hi2f(u[i]); }
    colsum(0, v, t);
#pragma unroll
    for (int n = 0; n < 8; n++)
      v[n] = __bfloat162float(__float2bfloat16((v[n] - t[n] * (1.0f / 192.0f)) * (part == 1 ? 0.14433756729740643f * 1.4426950408889634f : 1.0f)));
    const int cc = c >> 5, q = (c >> 3) & 3, s1 = (c >> 2) & 1, hh = (c >> 1) & 1, e = c & 1;
    base = qkv_pos(h, 2 * cc + s1) / 2 + j * 128 + hh * 64 + 2 * q + e;
  } else {
    const int jb = nb - 72;
#pragma unroll
    for (int n = 0; n < 8; n++) v[n] = __bfloat162float(wo[c * 192 + 32 * (jb >> 2) + 8 * (n >> 1) + 2 * (jb & 3) + (n & 1)]);
    base = wo_pos(c >> 4) / 2 + jb * 128 + ((c >> 3) & 1) * 64 + (c & 7);
  }
#pragma unroll
  for (int n = 0; n < 8; n++) { dst[base + n * 8] = __float2half_rn(v[n]); v[n] *= v[n]; }
  colsum(1, v, t);
  if (c == 0)
    g_wnorm[nb] = make_float2(fmaxf(fmaxf(fmaxf(t[0], t[1]), fmaxf(t[2], t[3])), fmaxf(fmaxf(t[4], t[5]), fmaxf(t[6], t[7]))),
                              t[0] + t[1] + t[2] + t[3] + t[4] + t[5] + t[6] + t[7]);
}

__device__ __forceinline__ int window_of(int round, int nfull, int cta, int ncta, int wg) {
  if (round < nfull) return round * 2 * ncta + 2 * cta + wg;
  const int rem = NWIN - nfull * 2 * ncta;
  const int i = cta + wg * ncta;
  return i < rem ? nfull * 2 * ncta + i : -1;
}

template <int S0 = 0, int S1 = 12>
__device__ __forceinline__ void mma_qkv(uint32_t (&acc)[36], const uint32_t (&A)[48], const uint64_t* d) {
#pragma unroll
  for (int s = S0; s < S1; s++) {
    if (s == 0) wgmma_n144<0>(acc, A[4 * s], A[4 * s + 1], A[4 * s + 2], A[4 * s + 3], d[s]);
    else        wgmma_n144<1>(acc, A[4 * s], A[4 * s + 1], A[4 * s + 2], A[4 * s + 3], d[s]);
  }
  wg_commit();
}
__device__ __forceinline__ void mma_proj(uint32_t (&acc)[48], const uint32_t (&A)[12], const uint64_t* d) {
#pragma unroll
  for (int s = 0; s < 3; s++) wgmma_n192<1>(acc, A[4 * s], A[4 * s + 1], A[4 * s + 2], A[4 * s + 3], d[s]);
}
__device__ __forceinline__ void mma_s(uint32_t (&S)[14], const uint32_t (&Q)[12], const uint64_t* d) {
  wgmma_n56<0>(S, Q[0], Q[1], Q[2], Q[3], d[0]);
  wgmma_n56<1>(S, Q[4], Q[5], Q[6], Q[7], d[1]);
  wgmma_n56<1>(S, Q[8], Q[9], Q[10], Q[11], d[2]);
}
__device__ __forceinline__ void mma_pv(uint32_t (&O)[14], const uint32_t (&P)[NP], const uint64_t* d) {
  wgmma_n56t<0>(O, P[0], P[1], P[2], P[3], d[0]);
  wgmma_n56t<1>(O, P[4], P[5], P[6], P[7], d[1]);
  wgmma_n56t<1>(O, P[8], P[9], P[10], P[11], d[2]);
  if (K48TC) wgmma_n56t<1>(O, P[NP - 4], P[NP - 3], P[NP - 2], P[NP - 1], d[3]);
}

#define PIN() asm volatile("pmevent 0;" ::: "memory")
template <int A, int B> __device__ __forceinline__ void hold(uint32_t* v) {
#pragma unroll
  for (int i = A; i < B; i++) asm volatile("" : "+r"(v[i]));
}
__device__ __forceinline__ void stsm12(const uint32_t* v, uint32_t addr) {
#pragma unroll
  for (int j = 0; j < 3; j++) stsm4(addr + 2 * j * KV_PITCH, v[4 * j], v[4 * j + 1], v[4 * j + 2], v[4 * j + 3]);
}
__device__ __forceinline__ void load_v48(uint32_t (&v)[6], uint32_t addr) {
  if (K48TC) return;
  asm volatile("ldmatrix.sync.aligned.m8n8.x4.shared.b16 {%0,%1,%2,%3}, [%4];" : "=r"(v[0]), "=r"(v[1]), "=r"(v[2]), "=r"(v[3]) : "r"(addr) : "memory");
  asm volatile("ldmatrix.sync.aligned.m8n8.x2.shared.b16 {%0,%1}, [%2];" : "=r"(v[4]), "=r"(v[5]) : "r"(addr + 4 * KV_PITCH) : "memory");
}
__device__ __forceinline__ void finish_o(const uint32_t (&O)[14], const uint32_t (&v)[6], uint32_t p48, uint32_t vmask, uint32_t (&Of)[12]) {
  const float2 l = K48TC ? make_float2(__low2float(u2h(O[12])), __low2float(u2h(O[13])))
                         : __half22float2(__hadd2_rn(u2h(__byte_perm(O[12], O[13], 0x5410)), u2h(p48)));
  float i0, i1;
  asm("rcp.approx.ftz.f32 %0, %1;" : "=f"(i0) : "f"(l.x));
  asm("rcp.approx.ftz.f32 %0, %1;" : "=f"(i1) : "f"(l.y));
  const uint32_t inv = packh(i0, i1) & vmask;
#pragma unroll
  for (int i = 0; i < 12; i++) {
    const uint32_t t = K48TC ? O[i] : h2u(__hfma2(u2h(v[i >> 1]), (i & 1) ? hcast<1>(p48) : hcast<0>(p48), u2h(O[i])));
    Of[i] = (i & 1) ? fmul_b<1>(t, inv) : fmul_b<0>(t, inv);
  }
  hold<0, 12>(Of);
}
#define PSTAT 12
template <int A, int B>
__device__ __forceinline__ void ln_sums(const uint32_t (&X)[48], float (&s1)[2], float (&s2)[2]) {
  if (PSTAT) {
    static_assert(PSTAT == 0 || (A % (2 * PSTAT + !PSTAT) == 0 && B % (2 * PSTAT + !PSTAT) == 0), "whole groups");
#pragma unroll
    for (int g = A; g < B; g += 2 * PSTAT + !PSTAT)
#pragma unroll
      for (int a = 0; a < 2; a++) {
        __half2 p1 = u2h(X[g + a]), p2 = __hmul2_rn(p1, p1);
#pragma unroll
        for (int i = 1; i < PSTAT; i++) { const __half2 v = u2h(X[g + a + 2 * i]); p1 = __hadd2_rn(p1, v); p2 = __hfma2(v, v, p2); }
        const float2 f1 = __half22float2(p1), f2 = __half22float2(p2);
        s1[a] = g == 0 ? f1.x + f1.y : s1[a] + (f1.x + f1.y);
        s2[a] = g == 0 ? f2.x + f2.y : s2[a] + (f2.x + f2.y);
      }
  } else {
#pragma unroll
    for (int i = A; i < B; i++) {
      const float2 f = __half22float2(u2h(X[i]));
      s1[i & 1] = i < 2 ? f.x + f.y : s1[i & 1] + (f.x + f.y);
      s2[i & 1] = fmaf(f.x, f.x, i < 2 ? f.y * f.y : fmaf(f.y, f.y, s2[i & 1]));
    }
  }
  asm volatile("" : "+f"(s1[0]), "+f"(s1[1]), "+f"(s2[0]), "+f"(s2[1]));
}
__device__ __forceinline__ uint32_t ln_rstd(const float (&s1)[2], const float (&s2)[2], float lo, float hi, uint32_t vmask, bool& ok) {
  float r[2];
  ok = true;
#pragma unroll
  for (int a = 0; a < 2; a++) {
    float m = s1[a], v = s2[a];
    m += __shfl_xor_sync(~0u, m, 1); v += __shfl_xor_sync(~0u, v, 1);
    m += __shfl_xor_sync(~0u, m, 2); v += __shfl_xor_sync(~0u, v, 2);
    ok = ok & (v <= hi) & ((v >= lo) | !(vmask >> (16 * a) & 1));
    m *= 1.0f / 192.0f;
    m *= m;
    v = fmaxf(fmaf(v, 1.0f / 192.0f, -m), 0.f) + 1e-5f;
    ok = ok & (m <= (PSTAT ? 16.f : 64.f) * v);
    asm("rsqrt.approx.ftz.f32 %0, %1;" : "=f"(r[a]) : "f"(v));
  }
  uint32_t rk = packh(r[0], r[1]);
  hold<0, 1>(&rk);
  return rk;
}
__device__ __forceinline__ void scale12(uint32_t (&D)[12], const uint32_t* a, uint32_t r) {
#pragma unroll
  for (int i = 0; i < 12; i++) D[i] = (i & 1) ? fmul_b<1>(a[i], r) : fmul_b<0>(a[i], r);
  hold<0, 12>(D);
}
template <int CC>
__device__ __forceinline__ void store_out(const uint32_t (&Y)[48], uint8_t* o0, uint8_t* o1, uint32_t vmask) {
  uint32_t T[8];
#pragma unroll
  for (int i = 0; i < 8; i++) {
    const float2 f = __half22float2(u2h(Y[8 * CC + i]));
    T[i] = pack2(f.x, f.y);
  }
  asm volatile("{\n.reg .pred p;\nsetp.ne.u32 p, %5, 0;\n@p st.global" STHINT ".v4.u32 [%0], {%1,%2,%3,%4};\n}\n"
               :: "l"(o0 + CC * 64), "r"(T[0]), "r"(T[2]), "r"(T[4]), "r"(T[6]), "r"(vmask) : "memory");
  asm volatile("{\n.reg .pred p;\nsetp.lt.s32 p, %5, 0;\n@p st.global" STHINT ".v4.u32 [%0], {%1,%2,%3,%4};\n}\n"
               :: "l"(o1 + CC * 64), "r"(T[1]), "r"(T[3]), "r"(T[5]), "r"(T[7]), "r"(vmask) : "memory");
}
__device__ __forceinline__ void proxy_fence() { asm volatile("fence.proxy.async.shared::cta;" ::: "memory"); }
__device__ __forceinline__ uint32_t fadd2(uint32_t a, uint32_t b) { return h2u(__hadd2_rn(u2h(a), u2h(b))); }
__device__ __forceinline__ void row_max(const uint32_t (&S)[14], uint32_t& k48, uint32_t& mx, uint32_t ninf) {
  k48 = K48TC ? __byte_perm(S[12], S[13], 0x5410) | ninf : __shfl_sync(~0u, __byte_perm(S[12], S[13], 0x5410), 0, 4);
  const uint32_t m0 = fmax2(fmax2(fmax2(S[0], S[2]), S[4]), fmax2(fmax2(S[6], S[8]), S[10]));
  const uint32_t m1 = fmax2(fmax2(fmax2(S[1], S[3]), S[5]), fmax2(fmax2(S[7], S[9]), S[11]));
  mx = fmax2(__byte_perm(m0, m1, 0x5410), __byte_perm(m0, m1, 0x7632));
  if (K48TC) mx = fmax2(mx, k48);
  mx = fmax2(mx, __shfl_xor_sync(~0u, mx, 1));
  mx = fmax2(mx, __shfl_xor_sync(~0u, mx, 2));
  if (!K48TC) mx = fmax2(mx, k48);
  hold<0, 1>(&mx);
}
__device__ __forceinline__ void row_exp(const uint32_t (&S)[14], uint32_t k48, uint32_t mx, uint32_t (&P)[NP], uint32_t& p48) {
#pragma unroll
  for (int j = 0; j < 12; j++) P[j] = fex2((j & 1) ? fsub_b<1>(S[j], mx) : fsub_b<0>(S[j], mx));
  if (K48TC) {
    uint16_t el, eh;
    asm("{\n.reg .b16 l, h;\nmov.b32 {l, h}, %2;\nex2.approx.f16 %0, l;\nex2.approx.f16 %1, h;\n}\n" : "=h"(el), "=h"(eh) : "r"(h2u(__hsub2_rn(u2h(k48), u2h(mx)))));
    P[NP - 4] = el; P[NP - 3] = eh; P[NP - 2] = 0; P[NP - 1] = 0;
  } else {
    p48 = fex2(h2u(__hsub2_rn(u2h(k48), u2h(mx))));
    hold<0, 1>(&p48);
  }
  hold<0, NP>(P);
}
template <int S0, int S1>
__device__ __forceinline__ void load_x(uint32_t (&X)[48], uint32_t t0) {
#pragma unroll
  for (int s = S0; s < S1; s++)
    asm volatile("ld.shared.v4.u32 {%0,%1,%2,%3}, [%4];" : "=r"(X[4 * s]), "=r"(X[4 * s + 1]), "=r"(X[4 * s + 2]), "=r"(X[4 * s + 3])
                 : "r"(((s & 1) ? (t0 ^ 16) : t0) + (s >> 1) * 128) : "memory");
}

template <int CNT, int EXPECT = CNT * SLICE>
__device__ __forceinline__ void load_slices(uint32_t sb, const uint8_t* src, int slice, int slot, int bar) {
  if (EXPECT)
    asm volatile("{\n.reg .pred p;\nelect.sync _|p, 0xffffffff;\n@p mbarrier.arrive.expect_tx.shared::cta.b64 _, [%0], %1;\n}\n"
                 :: "r"(sb + bar), "n"(EXPECT) : "memory");
  asm volatile("{\n.reg .pred p;\nelect.sync _|p, 0xffffffff;\n"
               "@p cp.async.bulk.shared::cluster.global.mbarrier::complete_tx::bytes [%0], [%1], %2, [%3];\n}\n"
               :: "r"(sb + OFF_W + slot * SLICE), "l"(src + slice * SLICE), "n"(CNT * SLICE), "r"(sb + bar) : "memory");
}
__device__ __forceinline__ void warp_arrive(uint32_t bar) {
  asm volatile("{\n.reg .pred p;\nelect.sync _|p, 0xffffffff;\n@p mbarrier.arrive.shared::cta.b64 _, [%0];\n}\n" :: "r"(bar) : "memory");
}

__device__ __forceinline__ float2 fp16_limits(int lane) {
  float mx[4] = {0.f, 0.f, 0.f, 0.f}, sm[4] = {0.f, 0.f, 0.f, 0.f};
#pragma unroll
  for (int i = 0; i < 3; i++) {
    const int nb = lane + 32 * i, part = nb < 72 ? (nb % 18) / 6 : 3;
    const float2 w = g_wnorm[nb];
#pragma unroll
    for (int k = 0; k < 4; k++) if (part == k) { mx[k] = fmaxf(mx[k], w.x); sm[k] += w.y; }
  }
#pragma unroll
  for (int k = 0; k < 4; k++)
#pragma unroll
    for (int d = 16; d; d >>= 1) { mx[k] = fmaxf(mx[k], __shfl_xor_sync(~0u, mx[k], d)); sm[k] += __shfl_xor_sync(~0u, sm[k], d); }
  const float big = fmaxf(fmaxf(mx[0], mx[1]), mx[2]);
  float small = 1.f;
  bool good = sm[0] + sm[1] + sm[2] + sm[3] < 1e30f;
#pragma unroll
  for (int k = 0; k < 4; k++) { good = good && (mx[k] == 0.f || mx[k] >= 2.5e-4f); if (k < 3 && mx[k] > 0.f) small = fminf(small, mx[k]); }
  good = good && 250.f * 48.f * sqrtf(mx[0] * mx[1]) <= 5e4f;
  good = good && 16.f * 49.f * sqrtf(mx[2]) <= 5e4f && big <= 1e6f;
  good = good && 16.f * sqrtf(sm[2] * mx[3]) <= 2e4f;
  return make_float2(192.f * 2.4e-7f / small, good ? fminf(2.5e8f, 9e8f / fmaxf(big, 1e-30f)) : -1.f);
}

__device__ __forceinline__ void slow_window(float* sm, int w, int t, const __nv_bfloat16* __restrict__ x, const __nv_bfloat16* __restrict__ dw,
                                            const __nv_bfloat16* __restrict__ wqkv, const __nv_bfloat16* __restrict__ wo, __nv_bfloat16* __restrict__ out) {
  float* x0 = sm; float* h = x0 + 49 * CH; float* qkv = h + 49 * CH; float* S = qkv + 49 * 576;
  const int wy = w / NWX, wx = w % NWX;
  auto sync = [] { asm volatile("bar.sync 6, 128;" ::: "memory"); };
#pragma unroll 1
  for (int i = t; i < 49 * CH; i += 128) {
    const int k = i / CH, c = i % CH, y = wy * 7 + k / 7, xx = wx * 7 + k % 7;
    float pe = 0.f;
#pragma unroll 1
    for (int a = 0; a < 9; a++) {
      const int yy = y + a / 3 - 1, xc = xx + a % 3 - 1;
      if (yy >= 0 && yy < IMG && xc >= 0 && xc < IMG) pe = fmaf(__bfloat162float(x[((size_t)yy * IMG + xc) * CH + c]), __bfloat162float(dw[a * CH + c]), pe);
    }
    x0[i] = __bfloat162float(__float2bfloat16(__bfloat162float(x[((size_t)y * IMG + xx) * CH + c]) + pe));
  }
  sync();
  if (t < 49) {
    float m = 0.f, v = 0.f;
#pragma unroll 1
    for (int c = 0; c < CH; c++) m += x0[t * CH + c];
    m *= 1.0f / CH;
#pragma unroll 1
    for (int c = 0; c < CH; c++) { const float d = x0[t * CH + c] - m; v = fmaf(d, d, v); }
    const float rs = 1.0f / sqrtf(v * (1.0f / CH) + 1e-5f);
#pragma unroll 1
    for (int c = 0; c < CH; c++) h[t * CH + c] = (x0[t * CH + c] - m) * rs;
  }
  sync();
#pragma unroll 1
  for (int i = t; i < 7 * 576; i += 128) {
    const int n = i % 576, k0 = i / 576 * 7;
    float a[7] = {0.f, 0.f, 0.f, 0.f, 0.f, 0.f, 0.f};
#pragma unroll 1
    for (int c = 0; c < CH; c++) {
      const float wv = __bfloat162float(wqkv[c * 576 + n]);
#pragma unroll
      for (int k = 0; k < 7; k++) a[k] = fmaf(h[(k0 + k) * CH + c], wv, a[k]);
    }
#pragma unroll
    for (int k = 0; k < 7; k++) qkv[(k0 + k) * 576 + n] = a[k];
  }
  sync();
#pragma unroll 1
  for (int hd = 0; hd < 4; hd++) {
#pragma unroll 1
    for (int i = t; i < 49 * 49; i += 128) {
      const int a = i / 49, b = i % 49;
      float v = 0.f;
#pragma unroll 1
      for (int d = 0; d < 48; d++) v = fmaf(qkv[a * 576 + hd * 48 + d], qkv[b * 576 + 192 + hd * 48 + d], v);
      S[i] = v * 0.14433756729740643f;
    }
    sync();
    if (t < 49) {
      float m = S[t * 49], l = 0.f;
#pragma unroll 1
      for (int b = 1; b < 49; b++) m = fmaxf(m, S[t * 49 + b]);
#pragma unroll 1
      for (int b = 0; b < 49; b++) { const float e = expf(S[t * 49 + b] - m); S[t * 49 + b] = e; l += e; }
#pragma unroll 1
      for (int b = 0; b < 49; b++) S[t * 49 + b] /= l;
    }
    sync();
#pragma unroll 1
    for (int i = t; i < 49 * 48; i += 128) {
      const int a = i / 48, d = i % 48;
      float v = 0.f;
#pragma unroll 1
      for (int b = 0; b < 49; b++) v = fmaf(S[a * 49 + b], qkv[b * 576 + 384 + hd * 48 + d], v);
      h[a * CH + hd * 48 + d] = v;
    }
    sync();
  }
#pragma unroll 1
  for (int i = t; i < 7 * CH; i += 128) {
    const int n = i % CH, k0 = i / CH * 7;
    float a[7] = {0.f, 0.f, 0.f, 0.f, 0.f, 0.f, 0.f};
#pragma unroll 1
    for (int c = 0; c < CH; c++) {
      const float wv = __bfloat162float(wo[c * CH + n]);
#pragma unroll
      for (int k = 0; k < 7; k++) a[k] = fmaf(h[(k0 + k) * CH + c], wv, a[k]);
    }
#pragma unroll
    for (int k = 0; k < 7; k++)
      out[((size_t)(wy * 7 + k0 / 7) * IMG + wx * 7 + k) * CH + n] = __float2bfloat16(x0[(k0 + k) * CH + n] + a[k]);
  }
  sync();
}

__global__ void __launch_bounds__(384, 1)
fused_kernel(const __grid_constant__ CUtensorMap tmx, const __grid_constant__ CUtensorMap tmp, const __grid_constant__ Descs ds, const __nv_bfloat16* __restrict__ dw, __nv_bfloat16* __restrict__ out, const int never,
             const __nv_bfloat16* __restrict__ x, const __nv_bfloat16* __restrict__ wqkv, const __nv_bfloat16* __restrict__ wo) {
  extern __shared__ __align__(1024) uint8_t smem[];
  const uint32_t sb = (uint32_t)__cvta_generic_to_shared(smem);
  const int tid = threadIdx.x, lane = tid & 31;
  const int warp = __shfl_sync(0xffffffffu, tid >> 5, 0);
  const int cta = blockIdx.x, ncta = gridDim.x;
  const int nfull = NWIN / (2 * ncta);
  const int nrounds = nfull + ((NWIN - nfull * 2 * ncta) > cta ? 1 : 0);

  if (warp == 0) GTS(0);
  if (warp == 10 && lane == 0) asm volatile("prefetch.tensormap [%0];" :: "l"(reinterpret_cast<uint64_t>(&tmx)) : "memory");
  if (tid == 0) {
    mbar_init(sb + BAR_FIRST, 1);
    asm volatile("fence.mbarrier_init.release.cluster;" ::: "memory");
    asm volatile("mbarrier.arrive.expect_tx.shared::cta.b64 _, [%0], %1;" :: "r"(sb + BAR_FIRST), "n"(2 * HALO_BYTES) : "memory");
#pragma unroll
    for (int k = 0; k < 2; k++) {
      const int w = max(window_of(0, nfull, cta, ncta, k), 0), a = w / NWX;
      asm volatile("cp.async.bulk.tensor.3d.shared::cluster.global.mbarrier::complete_tx::bytes [%0], [%1, {0, %3, %4}], [%2];"
                   :: "r"(sb + OFF_HALO + k * HALO_BYTES), "l"(reinterpret_cast<uint64_t>(&tmp)), "r"(sb + BAR_FIRST),
                      "r"((w - a * NWX) * 7 - 1), "r"(a * 7 - 1) : "memory");
    }
    if ((sb & 0x3FFFF) != SMEM_BASE || nrounds > 128) __trap();
    for (int i = 0; i < 10; i++) mbar_init(sb + BAR_FH + 8 * i, 1);
    for (int i = 0; i < 4; i++) mbar_init(sb + BAR_E + 8 * i, 8);
    for (int i = 0; i < 9; i++) mbar_init(sb + BAR_XFULL + 8 * i, 1);
    mbar_init(sb + BAR_TFULL, 3);
    mbar_init(sb + BAR_TEMPTY, 8);
    asm volatile("fence.mbarrier_init.release.cluster;" ::: "memory");
  }
  if (tid >= 128 && tid < 320) {
    *reinterpret_cast<uint32_t*>(smem + OFF_ZERO + (tid - 128) * 4) = 0;
    if (tid < 136) *reinterpret_cast<uint32_t*>(smem + OFF_REDO + (tid - 128) * 4) = 0;
  }
  if (tid < 128) {
    *reinterpret_cast<uint4*>(smem + OFF_KV + (tid / 64) * KV_BYTES + 6 * KV_PITCH + (tid % 64) * 16) = make_uint4(0x3c003c00u, 0x3c003c00u, 0x3c003c00u, 0x3c003c00u);
    proxy_fence();
  }
  __syncthreads();

  if (warp < 11) {
#pragma unroll 1
    for (int u = 0; u < (warp < 10 ? 2 : 1); u++) {
      const int cb = warp < 9 ? warp % 3 : 2 * (warp - 9) + u, y = warp < 9 ? 2 * (warp / 3) + u : 6;
      const int ch0 = cb * 64 + (lane & 15) * 4;
      uint32_t wt[9][2], px[3][9][2];
#pragma unroll
      for (int t = 0; t < 9; t++) {
        const uint2 v = *reinterpret_cast<const uint2*>(dw + t * CH + ch0);
        wt[t][0] = v.x; wt[t][1] = v.y;
      }
      mbar_wait(sb + BAR_FIRST, 0);
      const uint32_t ld = sb + OFF_HALO + (lane >> 4) * HALO_BYTES + y * 3456 + ch0 * 2;
#pragma unroll
      for (int p = 0; p < 27; p++)
        asm volatile("ld.shared.v2.u32 {%0,%1}, [%2];" : "=r"(px[p / 9][p % 9][0]), "=r"(px[p / 9][p % 9][1]) : "r"(ld + p * 384));
      const uint32_t st0 = sb + OFF_TILE + (lane >> 4) * TILE_BYTES + ch0 * 4;
      const uint32_t sa = (st0 ^ ((y & 1) << 4)) + y * 2304;
      uint32_t o[2][2];
#pragma unroll
      for (int j = 0; j < 7; j++) {
#pragma unroll
        for (int e = 0; e < 2; e++) {
          uint32_t a = hmul(px[0][j][e], wt[0][e]);
#pragma unroll
          for (int t = 1; t < 9; t++) a = hfma(px[t / 3][j + t % 3][e], wt[t][e], a);
          a = hadd(px[1][j + 1][e], a);
          o[j & 1][e] = packh(lo2f(a), hi2f(a));
        }
        if (j & 1)
          asm volatile("st.shared.v4.u32 [%0], {%1,%2,%3,%4};" :: "r"((j == 3 ? sa ^ 16 : sa) + (j >> 1) * 768),
                       "r"(o[0][0]), "r"(o[1][0]), "r"(o[0][1]), "r"(o[1][1]) : "memory");
      }
      const uint32_t sb6 = (st0 ^ ((~y & 2) << 3)) + (21 + (y >> 1)) * 768 + (y & 1) * 4;
      asm volatile("st.shared.u32 [%0], %1;\nst.shared.u32 [%0 + 8], %2;" :: "r"(sb6), "r"(o[0][0]), "r"(o[0][1]) : "memory");
      if (y == 6) asm volatile("st.shared.u32 [%0 + 4], %1;\nst.shared.u32 [%0 + 12], %1;" :: "r"(sb6), "r"(0) : "memory");
    }
    asm volatile("bar.arrive 8, 384;\nbar.sync 7, 352;" ::: "memory");
  }

  if (warp >= 8) {
    asm volatile("setmaxnreg.dec.sync.aligned.u32 " PREGS ";");
    if (warp == 11) {
      asm volatile("griddepcontrol.wait;" ::: "memory");
      load_slices<3, 0>(sb, ds.src, 0, 0, BAR_F0);
      *reinterpret_cast<float2*>(smem + OFF_LIM) = fp16_limits(lane);
      asm volatile("{\n.reg .pred p;\nelect.sync _|p, 0xffffffff;\n@p mbarrier.arrive.expect_tx.shared::cta.b64 _, [%0], %1;\n}\n"
                   :: "r"(sb + BAR_F0), "n"(3 * SLICE) : "memory");
      asm volatile("bar.sync 8, 384;" ::: "memory");
      load_slices<3, 5 * SLICE>(sb, ds.src, 3, 3, BAR_F1);
      load_slices<1, 0>(sb, ds.src, 13, SLOT_U, BAR_F1);
      load_slices<1, 0>(sb, ds.src, 12, SLOT_V, BAR_F1);
      for (int r = 0; r < nrounds; r++) {
        const int par = r & 1;
        const int h2 = par ? 1 : 2, h3 = par ? 0 : 3;
        mbar_wait(sb + BAR_E, par);
#pragma unroll
        for (int i = 0; i < (FINE ? 3 : 1); i++) load_slices<FINE ? 1 : 3>(sb, ds.src, 3 * h2 + i, 3 * (h2 & 1) + i, BAR_FH + 8 * i);
        mbar_wait(sb + BAR_E + 8, par);
#pragma unroll
        for (int i = 0; i < (FINE ? 3 : 1); i++) load_slices<FINE ? 1 : 3>(sb, ds.src, 3 * h3 + i, 3 * (h3 & 1) + i, BAR_FH + 24 + 8 * i);
        mbar_wait(sb + BAR_E + 16, par);
        load_slices<1>(sb, ds.src, 12 + h2, SLOT_U, BAR_FU);
        mbar_wait(sb + BAR_E + 24, par);
        load_slices<1>(sb, ds.src, 12 + h3, SLOT_V, BAR_FV);
      }
    } else {
      const int cw = warp - 8;
      const int win = lane >> 4;
      const int ch0 = cw * 64 + (lane & 15) * 4;
      uint32_t wt[9][2];
#pragma unroll
      for (int t = 0; t < 9; t++) {
        uint2 v = *reinterpret_cast<const uint2*>(dw + t * CH + ch0);
        wt[t][0] = v.x; wt[t][1] = v.y;
      }
      const uint32_t xs = sb + OFF_X + cw * 3 * XSLOT;
      const uint32_t xld = xs + (lane >> 4) * 1152 + (lane & 15) * 8;
      const uint32_t xbar = sb + BAR_XFULL + cw * 24;
      const uint32_t st0 = sb + OFF_TILE + win * TILE_BYTES + ch0 * 4;
      const uint64_t tm = reinterpret_cast<uint64_t>(&tmx);
      int cx0, cy0, cx1, cy1;
      auto coords = [&](int r) {
        const int w0 = window_of(r, nfull, cta, ncta, 0);
        int w1 = window_of(r, nfull, cta, ncta, 1);
        if (w1 < 0) w1 = w0;
        const int a = w0 / NWX, b = w1 / NWX;
        cx0 = (w0 - a * NWX) * 7 - 1; cy0 = a * 7 - 1;
        cx1 = (w1 - b * NWX) * 7 - 1; cy1 = b * 7 - 1;
      };
      auto issue = [&](int slot, int dy) {
        asm volatile("{\n.reg .pred p;\nelect.sync _|p, 0xffffffff;\n"
                     "@p mbarrier.arrive.expect_tx.shared::cta.b64 _, [%2], %8;\n"
                     "@p cp.async.bulk.tensor.3d.shared::cluster.global.mbarrier::complete_tx::bytes [%0], [%1, {%3, %4, %5}], [%2];\n"
                     "@p cp.async.bulk.tensor.3d.shared::cluster.global.mbarrier::complete_tx::bytes [%0 + 1152], [%1, {%3, %6, %7}], [%2];\n}\n"
                     :: "r"(xs + slot * XSLOT), "l"(tm), "r"(xbar + slot * 8), "r"(cw * 64), "r"(cx0), "r"(cy0 + dy), "r"(cx1), "r"(cy1 + dy), "n"(XSLOT) : "memory");
      };
      uint32_t accA[7][2], accB[7][2], ctr[7][2], held[2];
      auto row = [&](auto fin, auto mid, auto top, int slot, int y) {
        const uint32_t ld = xld + slot * XSLOT;
        const uint32_t sa = (st0 ^ ((y & 1) << 4)) + y * 2304;
        uint32_t cur[9][2], o[2][2];
#pragma unroll
        for (int p = 0; p < LA; p++)
          asm volatile("ld.shared.v2.u32 {%0,%1}, [%2];" : "=r"(cur[p][0]), "=r"(cur[p][1]) : "r"(ld + p * 128));
#pragma unroll
        for (int j = 0; j < 7; j++) {
          if (j >= 1 && j + LA - 1 < 9)
            asm volatile("ld.shared.v2.u32 {%0,%1}, [%2];" : "=r"(cur[j + LA - 1][0]), "=r"(cur[j + LA - 1][1]) : "r"(ld + (j + LA - 1) * 128));
          if (fin.v) {
#pragma unroll
            for (int e = 0; e < 2; e++) {
              uint32_t a = hfma(cur[j][e], wt[6][e], accA[j][e]);
              a = hfma(cur[j + 1][e], wt[7][e], a);
              a = hfma(cur[j + 2][e], wt[8][e], a);
              if (!EARLYX) a = hadd(ctr[j][e], a);
              o[j & 1][e] = packh(lo2f(a), hi2f(a));
            }
            if (j & 1)
              asm volatile("st.shared.v4.u32 [%0], {%1,%2,%3,%4};" :: "r"((j == 3 ? sa ^ 16 : sa) + (j >> 1) * 768),
                           "r"(o[0][0]), "r"(o[1][0]), "r"(o[0][1]), "r"(o[1][1]) : "memory");
            if (j == 6) {
              const uint32_t sb6 = (st0 ^ ((~y & 2) << 3)) + (21 + (y >> 1)) * 768;
              if (fin.v == 2)
                asm volatile("st.shared.v4.u32 [%0], {%1,%2,%3,%2};" :: "r"(sb6), "r"(o[0][0]), "r"(0), "r"(o[0][1]) : "memory");
              else
                asm volatile("{\n.reg .pred p;\nsetp.ne.s32 p, %5, 0;\n@p st.shared.v4.u32 [%0], {%1,%2,%3,%4};\n}\n"
                             :: "r"(sb6), "r"(held[0]), "r"(o[0][0]), "r"(held[1]), "r"(o[0][1]), "r"(y & 1) : "memory");
              held[0] = o[0][0]; held[1] = o[0][1];
            }
          }
#pragma unroll
          for (int e = 0; e < 2; e++) {
            if (mid.v) {
              uint32_t a = hfma(cur[j][e], wt[3][e], accB[j][e]);
              a = hfma(cur[j + 1][e], wt[4][e], a);
              a = hfma(cur[j + 2][e], wt[5][e], a);
              accA[j][e] = EARLYX == 1 ? hadd(cur[j + 1][e], a) : a;
              if (!EARLYX) ctr[j][e] = cur[j + 1][e];
            }
            if (top.v) {
              uint32_t a = hmul(cur[j][e], wt[0][e]);
              a = hfma(cur[j + 1][e], wt[1][e], a);
              accB[j][e] = hfma(cur[j + 2][e], wt[2][e], a);
            }
          }
        }
      };
      held[0] = held[1] = 0;
      if (nrounds > 1) { coords(1); issue(0, 0); issue(1, 1); issue(2, 2); }
      for (int r = 0; r + 1 < nrounds; r++) {
        const bool more = r + 2 < nrounds;
        mbar_wait(xbar, r & 1);
        if (r > 0) issue(2, 2);
        row(IC<0>{}, IC<0>{}, IC<1>{}, 0, 0);
        mbar_wait(xbar + 8, r & 1);
        issue(0, 3);
        row(IC<0>{}, IC<1>{}, IC<1>{}, 1, 0);
        mbar_wait(sb + BAR_TEMPTY, r & 1);
        TR(0);
#pragma unroll 1
        for (int k = 0; k < 2; k++) {
          mbar_wait(xbar + 16, (r + k) & 1);
          issue(1, 4 + 3 * k);
          row(IC<1>{}, IC<1>{}, IC<1>{}, 2, 3 * k);
          mbar_wait(xbar, (r + k + 1) & 1);
          issue(2, 5 + 3 * k);
          row(IC<1>{}, IC<1>{}, IC<1>{}, 0, 3 * k + 1);
          mbar_wait(xbar + 8, (r + k + 1) & 1);
          if (k == 1 && more) coords(r + 2);
          if (k == 0 || more) issue(0, k == 0 ? 6 : 0);
          row(IC<1>{}, IC<1>{}, IC<1>{}, 1, 3 * k + 2);
        }
        mbar_wait(xbar + 16, r & 1);
        if (more) issue(1, 1);
        row(IC<2>{}, IC<0>{}, IC<0>{}, 2, 6);
        __syncwarp();
        warp_arrive(sb + BAR_TFULL);
        TR(1);
      }
    }
    asm volatile("bar.sync 5, 384;" ::: "memory");
#pragma unroll 1
    for (int i = 0; i < 8; i++) {
      uint32_t bits = *reinterpret_cast<volatile uint32_t*>(smem + OFF_REDO + 4 * i);
#pragma unroll 1
      for (; bits; bits &= bits - 1)
        slow_window(reinterpret_cast<float*>(smem), window_of((i & 3) * 32 + __ffs(bits) - 1, nfull, cta, ncta, i >> 2), tid - 256, x, dw, wqkv, wo, out);
    }
  } else {
    asm volatile("setmaxnreg.inc.sync.aligned.u32 " CREGS ";");
    const int wg = warp >> 2, w4 = warp & 3, g = lane >> 2, q = lane & 3;
    const int row0 = w4 * 16 + g, row1 = row0 + 8;
    const int ps = min(w4 * 8 + g, 24);
    const int pix0 = ps < 21 ? (ps / 3) * IMG + (ps % 3) * 2 : (ps - 21) * 2 * IMG + 6;
    const int pix1 = pix0 + (ps < 21 ? 1 : ps < 24 ? IMG : 0);
    const uint32_t kv = sb + OFF_KV + wg * KV_BYTES;
    const int srow = w4 * 16 + (lane & 15);
    const uint32_t vst = kv + (lane >> 4) * KV_PITCH + (srow < 56 ? srow : min(srow - 7, 55)) * 16;
    uint32_t misc = ((uint32_t)pix1 << 20) | ((uint32_t)pix0 << 8) | q;
    const uint32_t ninf = q ? 0xfc00fc00u : 0u;
    const uint32_t v48 = kv + (lane >> 3) * KV_PITCH + 48 * 16;
    const uint32_t vmask = (row0 < 49 ? 0xffffu : 0u) | (row1 < 49 ? 0xffff0000u : 0u);

    const uint32_t tx = sb + q * 32 + (row0 < 49 ? OFF_TILE + wg * TILE_BYTES + ps * 768 + (ps & 1) * 16 : OFF_ZERO + 16);
    const int myrounds = window_of(nrounds - 1, nfull, cta, ncta, wg) < 0 ? nrounds - 1 : nrounds;

    if (never == 2) return;
    uint32_t H[48], Y[48];
    const uint64_t* dkv = ds.kv[wg];
    uint32_t P[NP], Ofc[12], p48 = 0;
#pragma unroll
    for (int i = 0; i < 48; i++) Y[i] = 0;
#pragma unroll
    for (int i = 0; i < NP; i++) P[i] = Ofc[i % 12] = 0;
    if (warp == 0) GTS(4);
    load_x<0, 12>(H, tx);
    warp_arrive(sb + BAR_TEMPTY);
    mbar_wait(sb + BAR_F0, 0);
    if (wg == 1) turn_pass(1);

    uint8_t *o0, *o1;
    uint32_t omask;
    auto out_setup = [&](int r) {
      omask = r >= 0 ? vmask : 0u;
      const int w = window_of(r, nfull, cta, ncta, wg);
      const int wy = w / NWX, wx = w - wy * NWX;
      asm volatile("" : "+r"(misc));
      const uint32_t wb = (uint32_t)(wy * 7 * IMG + wx * 7) * 384u + (misc & 3) * 16;
      o0 = reinterpret_cast<uint8_t*>(out) + (wb + ((misc >> 8) & 0xfff) * 384u);
      o1 = reinterpret_cast<uint8_t*>(out) + (wb + (misc >> 20) * 384u);
    };
#define OUT(c) store_out<c>(Y, o0, o1, omask)
    auto release = [&](int i) { warp_arrive(sb + BAR_E + 8 * i); };

    for (int r = 0;; r++) {
      const uint32_t par = r & 1;
      uint32_t acc[36], S[14], O[14], Q[12], V[12], Ofa[12], Ofb[12], vr[6], k48, mx;
      if (r == myrounds) {
        const bool idle = r < nrounds;
        if (idle) { release(0); release(1); }
        mbar_wait(sb + BAR_FU, par ^ 1);
        turn_wait(wg);
        wg_fence(); mma_pv(O, P, dkv + 4); mma_proj(Y, Ofc, ds.pu[0]); wg_commit();
        turn_pass(wg);
        load_v48(vr, v48);
        wg_wait<0>(); keep(O); keep(Y);
        finish_o(O, vr, p48, vmask, Ofa);
        mbar_wait(sb + BAR_FV, par ^ 1);
        turn_wait(wg);
        wg_fence(); mma_proj(Y, Ofa, ds.pv[0]); wg_commit();
        if (wg == 0 || idle) turn_pass(wg);
        wg_wait<0>(); keep(Y);
        if (idle) { release(2); release(3); turn_wait(wg); turn_pass(wg); }
        out_setup(r - 1);
        OUT(0); PIN(); OUT(1); PIN(); OUT(2); PIN(); OUT(3); PIN(); OUT(4); PIN(); OUT(5);
        if (idle) {
          turn_wait(wg); turn_pass(wg);
          turn_wait(wg); turn_pass(wg);
          turn_wait(wg); turn_pass(wg);
          turn_wait(wg);
        }
        if (w4 == 0) GTS(5 + wg);
        asm volatile("bar.arrive 5, 384;" ::: "memory");
        break;
      }
      const uint64_t* dq0 = ds.q[par];
      float s1[2], s2[2];
      TR(0);
      turn_wait(wg);
      TR(1);
      wg_fence(); mma_pv(O, P, dkv + 4); wg_commit(); mma_qkv<0, K0A>(acc, H, dq0);
      PIN();
      if (SPOS != 3) ln_sums<0, 24>(H, s1, s2);
      PIN();
      wg_fence(); mma_qkv<K0A, K0B>(acc, H, dq0);
      if (SPOS == 0) PIN();
      if (SPOS == 0) { ln_sums<24, 48>(H, s1, s2); PIN(); }
      wg_fence(); mma_qkv<K0B, 12>(acc, H, dq0);
      if (SPOS == 1) { PIN(); ln_sums<24, 48>(H, s1, s2); }
      if (r > 0) mbar_wait(sb + BAR_FU, par ^ 1);
      wg_fence(); mma_proj(Y, Ofc, ds.pu[0]); wg_commit();
      turn_pass(wg);
      TR(2);
      load_v48(vr, v48);
      wg_wait<4>(); keep(O);
      wg_sync(wg);
      PIN();
      finish_o(O, vr, p48, vmask, Ofa);
      if (SPOS == 3) ln_sums<0, 24>(H, s1, s2);
      if (SPOS >= 2) ln_sums<24, 48>(H, s1, s2);
      float lim_lo, lim_hi;
      asm volatile("ld.shared.v2.f32 {%0,%1}, [%2];" : "=f"(lim_lo), "=f"(lim_hi) : "r"(sb + OFF_LIM) : "memory");
      bool ok;
      const uint32_t rk = ln_rstd(s1, s2, lim_lo, lim_hi, vmask, ok);
      asm volatile("{\n.reg .pred p;\nsetp.eq.s32 p, %2, 0;\n@p red.shared.or.b32 [%0], %1;\n}\n"
                   :: "r"(sb + OFF_REDO + wg * 16 + (r >> 5) * 4), "r"(1u << (r & 31)), "r"((int)ok) : "memory");
      PIN();
      TR(3);
      wg_wait<1>(); keep(acc);
      TR(4);
      release(0);
      scale12(V, acc, rk); stsm12(V, vst + KV_KOFF);
      scale12(V, acc + 24, rk); stsm12(V, vst);
      PIN();
      wg_wait<0>(); keep(Y);
      PIN();
      proxy_fence();
      scale12(Q, acc + 12, rk);
      if (r > 0) mbar_wait(sb + BAR_FV, par ^ 1); else mbar_wait(sb + BAR_F1, 0);
      TR(5);
      turn_wait(wg);
      TR(6);
      if (r > 0) { wg_fence(); mma_proj(Y, Ofa, ds.pv[0]); wg_commit(); }
      wg_fence(); mma_s(S, Q, dkv); mma_qkv<0, 2>(acc, H, dq0 + 12);
      out_setup(r - 1);
      PIN();
      wg_wait<1>(); keep(Y);
      wg_fence(); mma_qkv<2, 6>(acc, H, dq0 + 12);
      PIN();
      OUT(0);
      PIN();
      wg_wait<1>(); keep(S);
      wg_fence(); mma_qkv<6, 9>(acc, H, dq0 + 12);
      PIN();
      row_max(S, k48, mx, ninf);
      OUT(1);
      PIN();
      wg_fence(); mma_qkv<9, 12>(acc, H, dq0 + 12);
      turn_pass(wg);
      PIN();
      OUT(2); PIN();
      OUT(3); PIN();
      row_exp(S, k48, mx, P, p48);
      PIN();
      TR(7);
      wg_wait<0>(); keep(acc);
      TR(8);
      release(1);
      wg_sync(wg);
      scale12(V, acc, rk); stsm12(V, vst + KV_KOFF);
      scale12(Q, acc + 12, rk); scale12(V, acc + 24, rk); PIN();
      proxy_fence();
#define TURN(ID, OF, DQ, FB, X1)                                                        \
      mbar_wait(sb + FB, par);                                                          \
      TR(ID + 1);                                                                       \
      turn_wait(wg);                                                                    \
      wg_fence(); mma_pv(O, P, dkv + 4); mma_s(S, Q, dkv); wg_commit(); mma_qkv<0, KA>(acc, H, DQ); \
      PIN();                                                                            \
      TR(ID + 2);                                                                       \
      load_v48(vr, v48);                                                                \
      X1;                                                                               \
      if (FINE) mbar_wait(sb + FB + 8, par); else PIN();                                                \
      wg_wait<1>(); keep(S); keep(O);                                                   \
      wg_sync(wg);                                         \
      wg_fence(); mma_qkv<KA, KB>(acc, H, DQ);                                            \
      PIN();                                                                            \
      stsm12(V, vst);                                                                   \
      finish_o(O, vr, p48, vmask, OF);                                                  \
      row_max(S, k48, mx, ninf);                                                        \
      if (FINE) mbar_wait(sb + FB + 16, par); else PIN();                                                \
      wg_fence(); mma_qkv<KB, 12>(acc, H, DQ);                                           \
      turn_pass(wg);                                                                    \
      PIN();                                                                            \
      TR(ID + 3);
#define NEXT_HEAD(ID)                                                                   \
      row_exp(S, k48, mx, P, p48);                                                      \
      PIN();                                                                            \
      TR(ID + 4);                                                                       \
      wg_wait<0>(); keep(acc);                                                          \
      scale12(V, acc, rk); stsm12(V, vst + KV_KOFF);                                    \
      scale12(Q, acc + 12, rk); scale12(V, acc + 24, rk); PIN();
      TURN(8, Ofa, dq0 + 24, BAR_FH, OUT(4))
      OUT(5); PIN();
      NEXT_HEAD(8)
      proxy_fence();
      TURN(12, Ofb, dq0 + 36, BAR_FH + 24, )
      auto init_y = [&]() {
#pragma unroll
        for (int i = 0; i < 48; i++) Y[i] = (i & 1) ? H[i] ^ never : h2u(__hadd2_rn(u2h(H[i]), u2h(never)));
        hold<0, 48>(Y); PIN();
      };
      NEXT_HEAD(12)
      init_y();
      proxy_fence();
      TR(17);
      turn_wait(wg);
      wg_fence();
      if (B4ORD) { mma_proj(Y, Ofb, ds.pu[1]); wg_commit(); }
      mma_pv(O, P, dkv + 4); mma_s(S, Q, dkv); wg_commit();
      if (!B4ORD) { mma_proj(Y, Ofb, ds.pu[1]); wg_commit(); }
      mma_proj(Y, Ofa, ds.pv[1]); wg_commit();
      turn_pass(wg);
      PIN();
      TR(18);
      load_v48(vr, v48);
      if (r + 1 < myrounds) mbar_wait(sb + BAR_TFULL, par);
      load_x<0, 4>(H, tx);
      wg_wait<2>();
      if (B4ORD) { release(2); wg_wait<1>(); }
      keep(S); keep(O);
      wg_sync(wg);
      PIN();
      TR(19);
      row_max(S, k48, mx, ninf);
      finish_o(O, vr, p48, vmask, Ofc);
      stsm12(V, vst);
      PIN();
      if (!B4ORD) { wg_wait<1>(); release(2); }
      load_x<4, 8>(H, tx);
      row_exp(S, k48, mx, P, p48);
      PIN();
      load_x<8, 12>(H, tx);
      warp_arrive(sb + BAR_TEMPTY);
      TR(20);
      wg_wait<0>(); keep(Y);
      release(3);
      proxy_fence();
      TR(21);
#undef TURN
#undef NEXT_HEAD
    }
  }
}

typedef CUresult (*EncodeFn)(CUtensorMap*, CUtensorMapDataType, cuuint32_t, void*, const cuuint64_t*, const cuuint64_t*,
                             const cuuint32_t*, const cuuint32_t*, CUtensorMapInterleave, CUtensorMapSwizzle,
                             CUtensorMapL2promotion, CUtensorMapFloatOOBfill);

}

extern "C" void kernel_launch(void* const* d_in, const int* in_sizes, int n_in, void* d_out, int out_size) {
  const __nv_bfloat16* x = (const __nv_bfloat16*)d_in[0];
  const __nv_bfloat16* dw = (const __nv_bfloat16*)d_in[1];
  const __nv_bfloat16* wqkv = (const __nv_bfloat16*)d_in[2];
  const __nv_bfloat16* wo = (const __nv_bfloat16*)d_in[3];
  static EncodeFn encode = nullptr;
  static int nsm = 0;
  static void* wpack = nullptr;
  if (!encode) {
    void* fn = nullptr;
    cudaDriverEntryPointQueryResult qr;
    cudaGetDriverEntryPoint("cuTensorMapEncodeTiled", &fn, cudaEnableDefault, &qr);
    encode = (EncodeFn)fn;
    int dev = 0;
    cudaGetDevice(&dev);
    cudaDeviceGetAttribute(&nsm, cudaDevAttrMultiProcessorCount, dev);
    cudaGetSymbolAddress(&wpack, g_wpack);
    cudaFuncSetAttribute(fused_kernel, cudaFuncAttributeMaxDynamicSharedMemorySize, SMEM_BYTES);
  }
  CUtensorMap tmx;
  cuuint64_t gdim[3] = {CH, IMG, IMG};
  cuuint64_t gstr[2] = {CH * 2, (cuuint64_t)CH * 2 * IMG};
  cuuint32_t box[3] = {64, 9, 1};
  cuuint32_t estr[3] = {1, 1, 1};
  encode(&tmx, CU_TENSOR_MAP_DATA_TYPE_BFLOAT16, 3, (void*)x, gdim, gstr, box, estr, CU_TENSOR_MAP_INTERLEAVE_NONE,
         CU_TENSOR_MAP_SWIZZLE_NONE, CU_TENSOR_MAP_L2_PROMOTION_L2_128B, CU_TENSOR_MAP_FLOAT_OOB_FILL_NONE);
  Descs ds;
  for (int i = 0; i < 12; i++)
    for (int b = 0; b < 5; b++) ds.q[b][i] = mkdesc(SMEM_BASE + OFF_W + qkv_pos(b & 1, i), 128, 256);
  for (int i = 0; i < 3; i++) {
    ds.pu[0][i] = ds.pu[1][i] = mkdesc(SMEM_BASE + OFF_W + SLOT_U * SLICE + i * 6144, 128, 256);
    ds.pv[0][i] = ds.pv[1][i] = mkdesc(SMEM_BASE + OFF_W + SLOT_V * SLICE + i * 6144, 128, 256);
  }
  ds.src = (const uint8_t*)wpack;
  for (int g = 0; g < 2; g++)
    for (int i = 0; i < 4; i++) {
      ds.kv[g][i] = mkdesc(SMEM_BASE + OFF_KV + g * KV_BYTES + KV_KOFF + 2 * i * KV_PITCH, KV_PITCH, 128);
      ds.kv[g][4 + i] = mkdesc(SMEM_BASE + OFF_KV + g * KV_BYTES + 256 * i, 128, KV_PITCH);
    }
  CUtensorMap tmp;
  cuuint32_t boxp[3] = {CH, 9, 9};
  encode(&tmp, CU_TENSOR_MAP_DATA_TYPE_BFLOAT16, 3, (void*)x, gdim, gstr, boxp, estr, CU_TENSOR_MAP_INTERLEAVE_NONE,
         CU_TENSOR_MAP_SWIZZLE_NONE, CU_TENSOR_MAP_L2_PROMOTION_L2_128B, CU_TENSOR_MAP_FLOAT_OOB_FILL_NONE);
  prepack_kernel<<<48, dim3(192, 2), 0, cudaStreamPerThread>>>(wqkv, wo);
  cudaLaunchConfig_t cfg = {};
  cfg.gridDim = dim3(nsm); cfg.blockDim = dim3(384); cfg.dynamicSmemBytes = SMEM_BYTES; cfg.stream = cudaStreamPerThread;
  cudaLaunchAttribute at[1];
  at[0].id = cudaLaunchAttributeProgrammaticStreamSerialization;
  at[0].val.programmaticStreamSerializationAllowed = 1;
  cfg.attrs = at; cfg.numAttrs = 1;
  cudaLaunchKernelEx(&cfg, fused_kernel, tmx, tmp, ds, dw, (__nv_bfloat16*)d_out, 0, x, wqkv, wo);
}
```

```cpp
#include <cuda_runtime.h>
#include <cuda_bf16.h>
#include <cuda_fp16.h>
#include <cuda.h>
#include <stdint.h>

#define CREGS "208"
#define PREGS "88"
#define K48TC 0
#define LA 4
#define K0A 6
#define KA 3
#define KB 9
namespace {
constexpr int NP = K48TC ? 16 : 12;

constexpr int IMG = 511;
constexpr int CH = 192;
constexpr int NWX = 73;
constexpr int NWIN = NWX * NWX;
constexpr int SLICE = 18432;
constexpr int OFF_W = 0;
constexpr int KV_PITCH = 1792, KV_KOFF = 896, KV_BYTES = 6 * KV_PITCH + 1024;
constexpr int OFF_KV = 8 * SLICE;
constexpr int TILE_BYTES = 25 * 768;
constexpr int OFF_TILE = OFF_KV + 2 * KV_BYTES;
constexpr int XSLOT = 2304;
constexpr int OFF_ZERO = OFF_TILE + 2 * TILE_BYTES;
constexpr int OFF_X = OFF_ZERO + 768;
constexpr int OFF_BAR = OFF_X + 9 * XSLOT;
constexpr int BAR_FH = OFF_BAR;
constexpr int BAR_FU = OFF_BAR + 16, BAR_FV = OFF_BAR + 24;
constexpr int BAR_F0 = OFF_BAR + 32, BAR_F1 = OFF_BAR + 40;
constexpr int BAR_E = OFF_BAR + 80;
constexpr int BAR_XFULL = OFF_BAR + 112;
constexpr int BAR_TFULL = OFF_BAR + 184;
constexpr int BAR_TEMPTY = OFF_BAR + 192;
constexpr int OFF_LIM = OFF_BAR + 200;
constexpr int OFF_REDO = OFF_BAR + 208;
constexpr int BAR_FIRST = OFF_BAR + 240;
constexpr int OFF_TRACE = OFF_BAR + 248;
constexpr int OFF_HALO = OFF_W + 3 * SLICE, HALO_BYTES = 81 * 384;
constexpr int SMEM_BYTES = OFF_TRACE;

__host__ __device__ constexpr int qkv_pos(int h, int s) { return 3 * h * SLICE + s * 4608; }
__host__ __device__ constexpr int wo_pos(int s) { return 12 * SLICE + s * 6144; }
constexpr int SLOT_U = 6, SLOT_V = 7;
constexpr int SMEM_BASE = 1024;
struct Descs { uint64_t q[5][12]; uint64_t pu[2][3], pv[2][3]; uint64_t kv[2][8]; const uint8_t* src; };

__device__ uint4 g_wpack[16 * SLICE / 16];
__device__ float2 g_wnorm[96];
#define TR(id)
#define GTS(i)
template <int V> struct IC { static constexpr int v = V; };
typedef __nv_bfloat162 bf2;
__device__ __forceinline__ bf2 u2b(uint32_t u) { return *reinterpret_cast<bf2*>(&u); }
__device__ __forceinline__ uint32_t b2u(bf2 b) { return *reinterpret_cast<uint32_t*>(&b); }
__device__ __forceinline__ uint32_t pack2(float lo, float hi) {
  uint32_t r; asm("cvt.rn.bf16x2.f32 %0, %1, %2;" : "=r"(r) : "f"(hi), "f"(lo)); return r;
}
__device__ __forceinline__ uint32_t hadd(uint32_t a, uint32_t b) { return b2u(__hadd2_rn(u2b(a), u2b(b))); }
__device__ __forceinline__ uint32_t hmul(uint32_t a, uint32_t b) { return b2u(__hmul2_rn(u2b(a), u2b(b))); }
__device__ __forceinline__ uint32_t hfma(uint32_t a, uint32_t b, uint32_t c) { return b2u(__hfma2(u2b(a), u2b(b), u2b(c))); }
__device__ __forceinline__ __half2 u2h(uint32_t u) { return *reinterpret_cast<__half2*>(&u); }
__device__ __forceinline__ uint32_t h2u(__half2 b) { return *reinterpret_cast<uint32_t*>(&b); }
__device__ __forceinline__ uint32_t packh(float lo, float hi) {
  uint32_t r; asm("cvt.rn.f16x2.f32 %0, %1, %2;" : "=r"(r) : "f"(hi), "f"(lo)); return r;
}
__device__ __forceinline__ uint32_t fmax2(uint32_t a, uint32_t b) { return h2u(__hmax2(u2h(a), u2h(b))); }
template <int HI> __device__ __forceinline__ __half2 hcast(uint32_t a) { return HI ? __high2half2(u2h(a)) : __low2half2(u2h(a)); }
template <int HI> __device__ __forceinline__ uint32_t fmul_b(uint32_t a, uint32_t s) { return h2u(__hmul2_rn(u2h(a), hcast<HI>(s))); }
template <int HI> __device__ __forceinline__ uint32_t fsub_b(uint32_t a, uint32_t s) { return h2u(__hsub2_rn(u2h(a), hcast<HI>(s))); }
__device__ __forceinline__ uint32_t fex2(uint32_t a) { uint32_t r; asm("ex2.approx.f16x2 %0, %1;" : "=r"(r) : "r"(a)); return r; }
__device__ __forceinline__ float lo2f(uint32_t a) { return __uint_as_float(a << 16); }
__device__ __forceinline__ float hi2f(uint32_t a) { return __uint_as_float(a & 0xffff0000u); }

__device__ __forceinline__ void mbar_init(uint32_t bar, uint32_t cnt) { asm volatile("mbarrier.init.shared::cta.b64 [%0], %1;" :: "r"(bar), "r"(cnt) : "memory"); }
__device__ __forceinline__ void mbar_wait(uint32_t bar, uint32_t parity) {
  asm volatile("{\n.reg .pred p;\n.reg .u32 n;\n"
               "mbarrier.try_wait.parity.shared::cta.b64 p, [%0], %1;\n"
               "@p bra.uni DONE_%=;\n"
               "mov.u32 n, 0;\n"
               "AGAIN_%=:\n"
               "mbarrier.try_wait.parity.shared::cta.b64 p, [%0], %1;\n"
               "@p bra.uni DONE_%=;\n"
               "add.u32 n, n, 1;\n"
               "setp.lt.u32 p, n, 0x1000000;\n"
               "@p bra.uni AGAIN_%=;\n"
               "trap;\n"
               "DONE_%=:\n}\n" :: "r"(bar), "r"(parity) : "memory");
}
__device__ __forceinline__ void wg_fence() { asm volatile("wgmma.fence.sync.aligned;" ::: "memory"); }
__device__ __forceinline__ void wg_commit() { asm volatile("wgmma.commit_group.sync.aligned;" ::: "memory"); }
template <int N> __device__ __forceinline__ void wg_wait() { asm volatile("wgmma.wait_group.sync.aligned %0;" :: "n"(N) : "memory"); }
#define BAR_BY_WG(OP, ID0, ID1, CNT) asm volatile("{\n.reg .pred p;\nsetp.eq.s32 p, %0, 0;\n@p " OP " " #ID0 ", " #CNT ";\n@!p " OP " " #ID1 ", " #CNT ";\n}\n" :: "r"(wg) : "memory")
__device__ __forceinline__ void wg_sync(int wg) { BAR_BY_WG("bar.sync", 1, 2, 128); }
__device__ __forceinline__ void turn_wait(int wg) { BAR_BY_WG("bar.sync", 3, 4, 256); }
__device__ __forceinline__ void turn_pass(int wg) { BAR_BY_WG("bar.arrive", 4, 3, 256); }
__device__ __forceinline__ void stsm4(uint32_t addr, uint32_t a, uint32_t b, uint32_t c, uint32_t d) {
  asm volatile("stmatrix.sync.aligned.m8n8.x4.shared.b16 [%0], {%1,%2,%3,%4};" :: "r"(addr), "r"(a), "r"(b), "r"(c), "r"(d) : "memory");
}
template <int N> __device__ __forceinline__ void keep(float (&d)[N]) {
#pragma unroll
  for (int i = 0; i < N; i++) asm volatile("" : "+f"(d[i]) :: "memory");
}
template <int N> __device__ __forceinline__ void keep(uint32_t (&d)[N]) {
#pragma unroll
  for (int i = 0; i < N; i++) asm volatile("" : "+r"(d[i]) :: "memory");
}
__host__ __device__ __forceinline__ uint64_t mkdesc(uint32_t addr, uint32_t lbo, uint32_t sbo) {
  return ((uint64_t)(sbo >> 4) << 32) | (uint64_t)(((lbo >> 4) << 16) | ((addr & 0x3FFFF) >> 4));
}

template <int SCALE_D>
__device__ __forceinline__ void wgmma_n144(uint32_t (&d)[36], uint32_t a0, uint32_t a1, uint32_t a2, uint32_t a3, uint64_t descB) {
  if (SCALE_D == 0)
  asm volatile("wgmma.mma_async.sync.aligned.m64n144k16.f16.f16.f16 "
    "{%0, %1, %2, %3, %4, %5, %6, %7, %8, %9, %10, %11, %12, %13, %14, %15, "
    "%16, %17, %18, %19, %20, %21, %22, %23, %24, %25, %26, %27, %28, %29, %30, %31, "
    "%32, %33, %34, %35}, "
    "{%36, %37, %38, %39}, %40, 0, 1, 1, 0;\n"
    : "=r"(d[0]), "=r"(d[1]), "=r"(d[2]), "=r"(d[3]), "=r"(d[4]), "=r"(d[5]), "=r"(d[6]), "=r"(d[7]),
      "=r"(d[8]), "=r"(d[9]), "=r"(d[10]), "=r"(d[11]), "=r"(d[12]), "=r"(d[13]), "=r"(d[14]), "=r"(d[15]),
      "=r"(d[16]), "=r"(d[17]), "=r"(d[18]), "=r"(d[19]), "=r"(d[20]), "=r"(d[21]), "=r"(d[22]), "=r"(d[23]),
      "=r"(d[24]), "=r"(d[25]), "=r"(d[26]), "=r"(d[27]), "=r"(d[28]), "=r"(d[29]), "=r"(d[30]), "=r"(d[31]),
      "=r"(d[32]), "=r"(d[33]), "=r"(d[34]), "=r"(d[35])
    : "r"(a0), "r"(a1), "r"(a2), "r"(a3), "l"(descB));
  else
  asm volatile("wgmma.mma_async.sync.aligned.m64n144k16.f16.f16.f16 "
    "{%0, %1, %2, %3, %4, %5, %6, %7, %8, %9, %10, %11, %12, %13, %14, %15, "
    "%16, %17, %18, %19, %20, %21, %22, %23, %24, %25, %26, %27, %28, %29, %30, %31, "
    "%32, %33, %34, %35}, "
    "{%36, %37, %38, %39}, %40, 1, 1, 1, 0;\n"
    : "+r"(d[0]), "+r"(d[1]), "+r"(d[2]), "+r"(d[3]), "+r"(d[4]), "+r"(d[5]), "+r"(d[6]), "+r"(d[7]),
      "+r"(d[8]), "+r"(d[9]), "+r"(d[10]), "+r"(d[11]), "+r"(d[12]), "+r"(d[13]), "+r"(d[14]), "+r"(d[15]),
      "+r"(d[16]), "+r"(d[17]), "+r"(d[18]), "+r"(d[19]), "+r"(d[20]), "+r"(d[21]), "+r"(d[22]), "+r"(d[23]),
      "+r"(d[24]), "+r"(d[25]), "+r"(d[26]), "+r"(d[27]), "+r"(d[28]), "+r"(d[29]), "+r"(d[30]), "+r"(d[31]),
      "+r"(d[32]), "+r"(d[33]), "+r"(d[34]), "+r"(d[35])
    : "r"(a0), "r"(a1), "r"(a2), "r"(a3), "l"(descB));
}

template <int SCALE_D>
__device__ __forceinline__ void wgmma_n192(uint32_t (&d)[48], uint32_t a0, uint32_t a1, uint32_t a2, uint32_t a3, uint64_t descB) {
  if (SCALE_D == 0)
  asm volatile("wgmma.mma_async.sync.aligned.m64n192k16.f16.f16.f16 "
    "{%0, %1, %2, %3, %4, %5, %6, %7, %8, %9, %10, %11, %12, %13, %14, %15, "
    "%16, %17, %18, %19, %20, %21, %22, %23, %24, %25, %26, %27, %28, %29, %30, %31, "
    "%32, %33, %34, %35, %36, %37, %38, %39, %40, %41, %42, %43, %44, %45, %46, %47}, "
    "{%48, %49, %50, %51}, %52, 0, 1, 1, 0;\n"
    : "=r"(d[0]), "=r"(d[1]), "=r"(d[2]), "=r"(d[3]), "=r"(d[4]), "=r"(d[5]), "=r"(d[6]), "=r"(d[7]),
      "=r"(d[8]), "=r"(d[9]), "=r"(d[10]), "=r"(d[11]), "=r"(d[12]), "=r"(d[13]), "=r"(d[14]), "=r"(d[15]),
      "=r"(d[16]), "=r"(d[17]), "=r"(d[18]), "=r"(d[19]), "=r"(d[20]), "=r"(d[21]), "=r"(d[22]), "=r"(d[23]),
      "=r"(d[24]), "=r"(d[25]), "=r"(d[26]), "=r"(d[27]), "=r"(d[28]), "=r"(d[29]), "=r"(d[30]), "=r"(d[31]),
      "=r"(d[32]), "=r"(d[33]), "=r"(d[34]), "=r"(d[35]), "=r"(d[36]), "=r"(d[37]), "=r"(d[38]), "=r"(d[39]),
      "=r"(d[40]), "=r"(d[41]), "=r"(d[42]), "=r"(d[43]), "=r"(d[44]), "=r"(d[45]), "=r"(d[46]), "=r"(d[47])
    : "r"(a0), "r"(a1), "r"(a2), "r"(a3), "l"(descB));
  else
  asm volatile("wgmma.mma_async.sync.aligned.m64n192k16.f16.f16.f16 "
    "{%0, %1, %2, %3, %4, %5, %6, %7, %8, %9, %10, %11, %12, %13, %14, %15, "
    "%16, %17, %18, %19, %20, %21, %22, %23, %24, %25, %26, %27, %28, %29, %30, %31, "
    "%32, %33, %34, %35, %36, %37, %38, %39, %40, %41, %42, %43, %44, %45, %46, %47}, "
    "{%48, %49, %50, %51}, %52, 1, 1, 1, 0;\n"
    : "+r"(d[0]), "+r"(d[1]), "+r"(d[2]), "+r"(d[3]), "+r"(d[4]), "+r"(d[5]), "+r"(d[6]), "+r"(d[7]),
      "+r"(d[8]), "+r"(d[9]), "+r"(d[10]), "+r"(d[11]), "+r"(d[12]), "+r"(d[13]), "+r"(d[14]), "+r"(d[15]),
      "+r"(d[16]), "+r"(d[17]), "+r"(d[18]), "+r"(d[19]), "+r"(d[20]), "+r"(d[21]), "+r"(d[22]), "+r"(d[23]),
      "+r"(d[24]), "+r"(d[25]), "+r"(d[26]), "+r"(d[27]), "+r"(d[28]), "+r"(d[29]), "+r"(d[30]), "+r"(d[31]),
      "+r"(d[32]), "+r"(d[33]), "+r"(d[34]), "+r"(d[35]), "+r"(d[36]), "+r"(d[37]), "+r"(d[38]), "+r"(d[39]),
      "+r"(d[40]), "+r"(d[41]), "+r"(d[42]), "+r"(d[43]), "+r"(d[44]), "+r"(d[45]), "+r"(d[46]), "+r"(d[47])
    : "r"(a0), "r"(a1), "r"(a2), "r"(a3), "l"(descB));
}

template <int SCALE_D>
__device__ __forceinline__ void wgmma_n56(uint32_t (&d)[14], uint32_t a0, uint32_t a1, uint32_t a2, uint32_t a3, uint64_t descB) {
  if (SCALE_D == 0)
  asm volatile("wgmma.mma_async.sync.aligned.m64n56k16.f16.f16.f16 "
    "{%0, %1, %2, %3, %4, %5, %6, %7, %8, %9, %10, %11, %12, %13}, "
    "{%14, %15, %16, %17}, %18, 0, 1, 1, 0;\n"
    : "=r"(d[0]), "=r"(d[1]), "=r"(d[2]), "=r"(d[3]), "=r"(d[4]), "=r"(d[5]), "=r"(d[6]), "=r"(d[7]),
      "=r"(d[8]), "=r"(d[9]), "=r"(d[10]), "=r"(d[11]), "=r"(d[12]), "=r"(d[13])
    : "r"(a0), "r"(a1), "r"(a2), "r"(a3), "l"(descB));
  else
  asm volatile("wgmma.mma_async.sync.aligned.m64n56k16.f16.f16.f16 "
    "{%0, %1, %2, %3, %4, %5, %6, %7, %8, %9, %10, %11, %12, %13}, "
    "{%14, %15, %16, %17}, %18, 1, 1, 1, 0;\n"
    : "+r"(d[0]), "+r"(d[1]), "+r"(d[2]), "+r"(d[3]), "+r"(d[4]), "+r"(d[5]), "+r"(d[6]), "+r"(d[7]),
      "+r"(d[8]), "+r"(d[9]), "+r"(d[10]), "+r"(d[11]), "+r"(d[12]), "+r"(d[13])
    : "r"(a0), "r"(a1), "r"(a2), "r"(a3), "l"(descB));
}

template <int SCALE_D>
__device__ __forceinline__ void wgmma_n56t(uint32_t (&d)[14], uint32_t a0, uint32_t a1, uint32_t a2, uint32_t a3, uint64_t descB) {
  if (SCALE_D == 0)
  asm volatile("wgmma.mma_async.sync.aligned.m64n56k16.f16.f16.f16 "
    "{%0, %1, %2, %3, %4, %5, %6, %7, %8, %9, %10, %11, %12, %13}, "
    "{%14, %15, %16, %17}, %18, 0, 1, 1, 1;\n"
    : "=r"(d[0]), "=r"(d[1]), "=r"(d[2]), "=r"(d[3]), "=r"(d[4]), "=r"(d[5]), "=r"(d[6]), "=r"(d[7]),
      "=r"(d[8]), "=r"(d[9]), "=r"(d[10]), "=r"(d[11]), "=r"(d[12]), "=r"(d[13])
    : "r"(a0), "r"(a1), "r"(a2), "r"(a3), "l"(descB));
  else
  asm volatile("wgmma.mma_async.sync.aligned.m64n56k16.f16.f16.f16 "
    "{%0, %1, %2, %3, %4, %5, %6, %7, %8, %9, %10, %11, %12, %13}, "
    "{%14, %15, %16, %17}, %18, 1, 1, 1, 1;\n"
    : "+r"(d[0]), "+r"(d[1]), "+r"(d[2]), "+r"(d[3]), "+r"(d[4]), "+r"(d[5]), "+r"(d[6]), "+r"(d[7]),
      "+r"(d[8]), "+r"(d[9]), "+r"(d[10]), "+r"(d[11]), "+r"(d[12]), "+r"(d[13])
    : "r"(a0), "r"(a1), "r"(a2), "r"(a3), "l"(descB));
}

__global__ void __launch_bounds__(384) prepack_kernel(const __nv_bfloat16* __restrict__ wqkv, const __nv_bfloat16* __restrict__ wo) {
  asm volatile("griddepcontrol.launch_dependents;");
  __shared__ float red2[2][2][6][8];
  float (*red)[6][8] = red2[threadIdx.y];
  __half* dst = reinterpret_cast<__half*>(g_wpack);
  const int c = threadIdx.x, nb = blockIdx.x * 2 + threadIdx.y;
  auto colsum = [&](int k, const float (&v)[8], float (&o)[8]) {
#pragma unroll
    for (int i = 0; i < 8; i++) {
      float t = v[i];
#pragma unroll
      for (int d = 16; d; d >>= 1) t += __shfl_xor_sync(~0u, t, d);
      if ((c & 31) == 0) red[k][c >> 5][i] = t;
    }
    __syncthreads();
#pragma unroll
    for (int i = 0; i < 8; i++) o[i] = red[k][0][i] + red[k][1][i] + red[k][2][i] + red[k][3][i] + red[k][4][i] + red[k][5][i];
  };
  float v[8], t[8];
  int base;
  if (nb < 72) {
    const int h = nb / 18, j = nb % 18, part = j / 6;
    const int col = (part == 0 ? 192 : part == 1 ? 0 : 384) + h * 48 + (j % 6) * 8;
    uint4 raw = *reinterpret_cast<const uint4*>(wqkv + c * 576 + col);
    uint32_t u[4] = {raw.x, raw.y, raw.z, raw.w};
#pragma unroll
    for (int i = 0; i < 4; i++) { v[2 * i] = lo2f(u[i]); v[2 * i + 1] = hi2f(u[i]); }
    colsum(0, v, t);
#pragma unroll
    for (int n = 0; n < 8; n++)
      v[n] = __bfloat162float(__float2bfloat16((v[n] - t[n] * (1.0f / 192.0f)) * (part == 1 ? 0.14433756729740643f * 1.4426950408889634f : 1.0f)));
    const int cc = c >> 5, q = (c >> 3) & 3, s1 = (c >> 2) & 1, hh = (c >> 1) & 1, e = c & 1;
    base = qkv_pos(h, 2 * cc + s1) / 2 + j * 128 + hh * 64 + 2 * q + e;
  } else {
    const int jb = nb - 72;
#pragma unroll
    for (int n = 0; n < 8; n++) v[n] = __bfloat162float(wo[c * 192 + 32 * (jb >> 2) + 8 * (n >> 1) + 2 * (jb & 3) + (n & 1)]);
    base = wo_pos(c >> 4) / 2 + jb * 128 + ((c >> 3) & 1) * 64 + (c & 7);
  }
#pragma unroll
  for (int n = 0; n < 8; n++) { dst[base + n * 8] = __float2half_rn(v[n]); v[n] *= v[n]; }
  colsum(1, v, t);
  if (c == 0)
    g_wnorm[nb] = make_float2(fmaxf(fmaxf(fmaxf(t[0], t[1]), fmaxf(t[2], t[3])), fmaxf(fmaxf(t[4], t[5]), fmaxf(t[6], t[7]))),
                              t[0] + t[1] + t[2] + t[3] + t[4] + t[5] + t[6] + t[7]);
}

__device__ __forceinline__ int window_of(int round, int nfull, int cta, int ncta, int wg) {
  if (round < nfull) return round * 2 * ncta + 2 * cta + wg;
  const int rem = NWIN - nfull * 2 * ncta;
  const int i = cta + wg * ncta;
  return i < rem ? nfull * 2 * ncta + i : -1;
}

template <int S0 = 0, int S1 = 12>
__device__ __forceinline__ void mma_qkv(uint32_t (&acc)[36], const uint32_t (&A)[48], const uint64_t* d) {
#pragma unroll
  for (int s = S0; s < S1; s++) {
    if (s == 0) wgmma_n144<0>(acc, A[4 * s], A[4 * s + 1], A[4 * s + 2], A[4 * s + 3], d[s]);
    else        wgmma_n144<1>(acc, A[4 * s], A[4 * s + 1], A[4 * s + 2], A[4 * s + 3], d[s]);
  }
  wg_commit();
}
__device__ __forceinline__ void mma_proj(uint32_t (&acc)[48], const uint32_t (&A)[12], const uint64_t* d) {
#pragma unroll
  for (int s = 0; s < 3; s++) wgmma_n192<1>(acc, A[4 * s], A[4 * s + 1], A[4 * s + 2], A[4 * s + 3], d[s]);
}
__device__ __forceinline__ void mma_s(uint32_t (&S)[14], const uint32_t (&Q)[12], const uint64_t* d) {
  wgmma_n56<0>(S, Q[0], Q[1], Q[2], Q[3], d[0]);
  wgmma_n56<1>(S, Q[4], Q[5], Q[6], Q[7], d[1]);
  wgmma_n56<1>(S, Q[8], Q[9], Q[10], Q[11], d[2]);
}
__device__ __forceinline__ void mma_pv(uint32_t (&O)[14], const uint32_t (&P)[NP], const uint64_t* d) {
  wgmma_n56t<0>(O, P[0], P[1], P[2], P[3], d[0]);
  wgmma_n56t<1>(O, P[4], P[5], P[6], P[7], d[1]);
  wgmma_n56t<1>(O, P[8], P[9], P[10], P[11], d[2]);
  if (K48TC) wgmma_n56t<1>(O, P[NP - 4], P[NP - 3], P[NP - 2], P[NP - 1], d[3]);
}

#define PIN() asm volatile("pmevent 0;" ::: "memory")
template <int A, int B> __device__ __forceinline__ void hold(uint32_t* v) {
#pragma unroll
  for (int i = A; i < B; i++) asm volatile("" : "+r"(v[i]));
}
__device__ __forceinline__ void stsm12(const uint32_t* v, uint32_t addr) {
#pragma unroll
  for (int j = 0; j < 3; j++) stsm4(addr + 2 * j * KV_PITCH, v[4 * j], v[4 * j + 1], v[4 * j + 2], v[4 * j + 3]);
}
__device__ __forceinline__ void load_v48(uint32_t (&v)[6], uint32_t addr) {
  if (K48TC) return;
  asm volatile("ldmatrix.sync.aligned.m8n8.x4.shared.b16 {%0,%1,%2,%3}, [%4];" : "=r"(v[0]), "=r"(v[1]), "=r"(v[2]), "=r"(v[3]) : "r"(addr) : "memory");
  asm volatile("ldmatrix.sync.aligned.m8n8.x2.shared.b16 {%0,%1}, [%2];" : "=r"(v[4]), "=r"(v[5]) : "r"(addr + 4 * KV_PITCH) : "memory");
}
__device__ __forceinline__ void finish_o(const uint32_t (&O)[14], const uint32_t (&v)[6], uint32_t p48, uint32_t vmask, uint32_t (&Of)[12]) {
  const float2 l = K48TC ? make_float2(__low2float(u2h(O[12])), __low2float(u2h(O[13])))
                         : __half22float2(__hadd2_rn(u2h(__byte_perm(O[12], O[13], 0x5410)), u2h(p48)));
  float i0, i1;
  asm("rcp.approx.ftz.f32 %0, %1;" : "=f"(i0) : "f"(l.x));
  asm("rcp.approx.ftz.f32 %0, %1;" : "=f"(i1) : "f"(l.y));
  const uint32_t inv = packh(i0, i1) & vmask;
#pragma unroll
  for (int i = 0; i < 12; i++) {
    const uint32_t t = K48TC ? O[i] : h2u(__hfma2(u2h(v[i >> 1]), (i & 1) ? hcast<1>(p48) : hcast<0>(p48), u2h(O[i])));
    Of[i] = (i & 1) ? fmul_b<1>(t, inv) : fmul_b<0>(t, inv);
  }
  hold<0, 12>(Of);
}
#define PSTAT 12
template <int A, int B>
__device__ __forceinline__ void ln_sums(const uint32_t (&X)[48], float (&s1)[2], float (&s2)[2]) {
  if (PSTAT) {
    static_assert(PSTAT == 0 || (A % (2 * PSTAT + !PSTAT) == 0 && B % (2 * PSTAT + !PSTAT) == 0), "whole groups");
#pragma unroll
    for (int g = A; g < B; g += 2 * PSTAT + !PSTAT)
#pragma unroll
      for (int a = 0; a < 2; a++) {
        __half2 p1 = u2h(X[g + a]), p2 = __hmul2_rn(p1, p1);
#pragma unroll
        for (int i = 1; i < PSTAT; i++) { const __half2 v = u2h(X[g + a + 2 * i]); p1 = __hadd2_rn(p1, v); p2 = __hfma2(v, v, p2); }
        const float2 f1 = __half22float2(p1), f2 = __half22float2(p2);
        s1[a] = g == 0 ? f1.x + f1.y : s1[a] + (f1.x + f1.y);
        s2[a] = g == 0 ? f2.x + f2.y : s2[a] + (f2.x + f2.y);
      }
  } else {
#pragma unroll
    for (int i = A; i < B; i++) {
      const float2 f = __half22float2(u2h(X[i]));
      s1[i & 1] = i < 2 ? f.x + f.y : s1[i & 1] + (f.x + f.y);
      s2[i & 1] = fmaf(f.x, f.x, i < 2 ? f.y * f.y : fmaf(f.y, f.y, s2[i & 1]));
    }
  }
  asm volatile("" : "+f"(s1[0]), "+f"(s1[1]), "+f"(s2[0]), "+f"(s2[1]));
}
__device__ __forceinline__ uint32_t ln_rstd(const float (&s1)[2], const float (&s2)[2], float lo, float hi, uint32_t vmask, bool& ok) {
  float r[2];
  ok = true;
#pragma unroll
  for (int a = 0; a < 2; a++) {
    float m = s1[a], v = s2[a];
    m += __shfl_xor_sync(~0u, m, 1); v += __shfl_xor_sync(~0u, v, 1);
    m += __shfl_xor_sync(~0u, m, 2); v += __shfl_xor_sync(~0u, v, 2);
    ok = ok & (v <= hi) & ((v >= lo) | !(vmask >> (16 * a) & 1));
    m *= 1.0f / 192.0f;
    m *= m;
    v = fmaxf(fmaf(v, 1.0f / 192.0f, -m), 0.f) + 1e-5f;
    ok = ok & (m <= (PSTAT ? 16.f : 64.f) * v);
    asm("rsqrt.approx.ftz.f32 %0, %1;" : "=f"(r[a]) : "f"(v));
  }
  uint32_t rk = packh(r[0], r[1]);
  hold<0, 1>(&rk);
  return rk;
}
__device__ __forceinline__ void scale12(uint32_t (&D)[12], const uint32_t* a, uint32_t r) {
#pragma unroll
  for (int i = 0; i < 12; i++) D[i] = (i & 1) ? fmul_b<1>(a[i], r) : fmul_b<0>(a[i], r);
  hold<0, 12>(D);
}
template <int CC>
__device__ __forceinline__ void store_out(const uint32_t (&Y)[48], uint8_t* o0, uint8_t* o1, uint32_t vmask) {
  uint32_t T[8];
#pragma unroll
  for (int i = 0; i < 8; i++) {
    const float2 f = __half22float2(u2h(Y[8 * CC + i]));
    T[i] = pack2(f.x, f.y);
  }
  asm volatile("{\n.reg .pred p;\nsetp.ne.u32 p, %5, 0;\n@p st.global.cs.v4.u32 [%0], {%1,%2,%3,%4};\n}\n"
               :: "l"(o0 + CC * 64), "r"(T[0]), "r"(T[2]), "r"(T[4]), "r"(T[6]), "r"(vmask) : "memory");
  asm volatile("{\n.reg .pred p;\nsetp.lt.s32 p, %5, 0;\n@p st.global.cs.v4.u32 [%0], {%1,%2,%3,%4};\n}\n"
               :: "l"(o1 + CC * 64), "r"(T[1]), "r"(T[3]), "r"(T[5]), "r"(T[7]), "r"(vmask) : "memory");
}
__device__ __forceinline__ void proxy_fence() { asm volatile("fence.proxy.async.shared::cta;" ::: "memory"); }
__device__ __forceinline__ uint32_t fadd2(uint32_t a, uint32_t b) { return h2u(__hadd2_rn(u2h(a), u2h(b))); }
__device__ __forceinline__ void row_max(const uint32_t (&S)[14], uint32_t& k48, uint32_t& mx, uint32_t ninf) {
  k48 = K48TC ? __byte_perm(S[12], S[13], 0x5410) | ninf : __shfl_sync(~0u, __byte_perm(S[12], S[13], 0x5410), 0, 4);
  const uint32_t m0 = fmax2(fmax2(fmax2(S[0], S[2]), S[4]), fmax2(fmax2(S[6], S[8]), S[10]));
  const uint32_t m1 = fmax2(fmax2(fmax2(S[1], S[3]), S[5]), fmax2(fmax2(S[7], S[9]), S[11]));
  mx = fmax2(__byte_perm(m0, m1, 0x5410), __byte_perm(m0, m1, 0x7632));
  if (K48TC) mx = fmax2(mx, k48);
  mx = fmax2(mx, __shfl_xor_sync(~0u, mx, 1));
  mx = fmax2(mx, __shfl_xor_sync(~0u, mx, 2));
  if (!K48TC) mx = fmax2(mx, k48);
  hold<0, 1>(&mx);
}
__device__ __forceinline__ void row_exp(const uint32_t (&S)[14], uint32_t k48, uint32_t mx, uint32_t (&P)[NP], uint32_t& p48) {
#pragma unroll
  for (int j = 0; j < 12; j++) P[j] = fex2((j & 1) ? fsub_b<1>(S[j], mx) : fsub_b<0>(S[j], mx));
  if (K48TC) {
    uint16_t el, eh;
    asm("{\n.reg .b16 l, h;\nmov.b32 {l, h}, %2;\nex2.approx.f16 %0, l;\nex2.approx.f16 %1, h;\n}\n" : "=h"(el), "=h"(eh) : "r"(h2u(__hsub2_rn(u2h(k48), u2h(mx)))));
    P[NP - 4] = el; P[NP - 3] = eh; P[NP - 2] = 0; P[NP - 1] = 0;
  } else {
    p48 = fex2(h2u(__hsub2_rn(u2h(k48), u2h(mx))));
    hold<0, 1>(&p48);
  }
  hold<0, NP>(P);
}
template <int S0, int S1>
__device__ __forceinline__ void load_x(uint32_t (&X)[48], uint32_t t0) {
#pragma unroll
  for (int s = S0; s < S1; s++)
    asm volatile("ld.shared.v4.u32 {%0,%1,%2,%3}, [%4];" : "=r"(X[4 * s]), "=r"(X[4 * s + 1]), "=r"(X[4 * s + 2]), "=r"(X[4 * s + 3])
                 : "r"(((s & 1) ? (t0 ^ 16) : t0) + (s >> 1) * 128) : "memory");
}

template <int CNT, int EXPECT = CNT * SLICE>
__device__ __forceinline__ void load_slices(uint32_t sb, const uint8_t* src, int slice, int slot, int bar) {
  if (EXPECT)
    asm volatile("{\n.reg .pred p;\nelect.sync _|p, 0xffffffff;\n@p mbarrier.arrive.expect_tx.shared::cta.b64 _, [%0], %1;\n}\n"
                 :: "r"(sb + bar), "n"(EXPECT) : "memory");
  asm volatile("{\n.reg .pred p;\nelect.sync _|p, 0xffffffff;\n"
               "@p cp.async.bulk.shared::cluster.global.mbarrier::complete_tx::bytes [%0], [%1], %2, [%3];\n}\n"
               :: "r"(sb + OFF_W + slot * SLICE), "l"(src + slice * SLICE), "n"(CNT * SLICE), "r"(sb + bar) : "memory");
}
__device__ __forceinline__ void warp_arrive(uint32_t bar) {
  asm volatile("{\n.reg .pred p;\nelect.sync _|p, 0xffffffff;\n@p mbarrier.arrive.shared::cta.b64 _, [%0];\n}\n" :: "r"(bar) : "memory");
}

__device__ __forceinline__ float2 fp16_limits(int lane) {
  float mx[4] = {0.f, 0.f, 0.f, 0.f}, sm[4] = {0.f, 0.f, 0.f, 0.f};
#pragma unroll
  for (int i = 0; i < 3; i++) {
    const int nb = lane + 32 * i, part = nb < 72 ? (nb % 18) / 6 : 3;
    const float2 w = g_wnorm[nb];
#pragma unroll
    for (int k = 0; k < 4; k++) if (part == k) { mx[k] = fmaxf(mx[k], w.x); sm[k] += w.y; }
  }
#pragma unroll
  for (int k = 0; k < 4; k++)
#pragma unroll
    for (int d = 16; d; d >>= 1) { mx[k] = fmaxf(mx[k], __shfl_xor_sync(~0u, mx[k], d)); sm[k] += __shfl_xor_sync(~0u, sm[k], d); }
  const float big = fmaxf(fmaxf(mx[0], mx[1]), mx[2]);
  float small = 1.f;
  bool good = sm[0] + sm[1] + sm[2] + sm[3] < 1e30f;
#pragma unroll
  for (int k = 0; k < 4; k++) { good = good && (mx[k] == 0.f || mx[k] >= 2.5e-4f); if (k < 3 && mx[k] > 0.f) small = fminf(small, mx[k]); }
  good = good && 250.f * 48.f * sqrtf(mx[0] * mx[1]) <= 5e4f;
  good = good && 16.f * 49.f * sqrtf(mx[2]) <= 5e4f && big <= 1e6f;
  good = good && 16.f * sqrtf(sm[2] * mx[3]) <= 2e4f;
  return make_float2(192.f * 2.4e-7f / small, good ? fminf(2.5e8f, 9e8f / fmaxf(big, 1e-30f)) : -1.f);
}

__device__ __forceinline__ void slow_window(float* sm, int w, int t, const __nv_bfloat16* __restrict__ x, const __nv_bfloat16* __restrict__ dw,
                                            const __nv_bfloat16* __restrict__ wqkv, const __nv_bfloat16* __restrict__ wo, __nv_bfloat16* __restrict__ out) {
  float* x0 = sm; float* h = x0 + 49 * CH; float* qkv = h + 49 * CH; float* S = qkv + 49 * 576;
  const int wy = w / NWX, wx = w % NWX;
  auto sync = [] { asm volatile("bar.sync 6, 128;" ::: "memory"); };
#pragma unroll 1
  for (int i = t; i < 49 * CH; i += 128) {
    const int k = i / CH, c = i % CH, y = wy * 7 + k / 7, xx = wx * 7 + k % 7;
    float pe = 0.f;
#pragma unroll 1
    for (int a = 0; a < 9; a++) {
      const int yy = y + a / 3 - 1, xc = xx + a % 3 - 1;
      if (yy >= 0 && yy < IMG && xc >= 0 && xc < IMG) pe = fmaf(__bfloat162float(x[((size_t)yy * IMG + xc) * CH + c]), __bfloat162float(dw[a * CH + c]), pe);
    }
    x0[i] = __bfloat162float(__float2bfloat16(__bfloat162float(x[((size_t)y * IMG + xx) * CH + c]) + pe));
  }
  sync();
  if (t < 49) {
    float m = 0.f, v = 0.f;
#pragma unroll 1
    for (int c = 0; c < CH; c++) m += x0[t * CH + c];
    m *= 1.0f / CH;
#pragma unroll 1
    for (int c = 0; c < CH; c++) { const float d = x0[t * CH + c] - m; v = fmaf(d, d, v); }
    const float rs = 1.0f / sqrtf(v * (1.0f / CH) + 1e-5f);
#pragma unroll 1
    for (int c = 0; c < CH; c++) h[t * CH + c] = (x0[t * CH + c] - m) * rs;
  }
  sync();
#pragma unroll 1
  for (int i = t; i < 7 * 576; i += 128) {
    const int n = i % 576, k0 = i / 576 * 7;
    float a[7] = {0.f, 0.f, 0.f, 0.f, 0.f, 0.f, 0.f};
#pragma unroll 1
    for (int c = 0; c < CH; c++) {
      const float wv = __bfloat162float(wqkv[c * 576 + n]);
#pragma unroll
      for (int k = 0; k < 7; k++) a[k] = fmaf(h[(k0 + k) * CH + c], wv, a[k]);
    }
#pragma unroll
    for (int k = 0; k < 7; k++) qkv[(k0 + k) * 576 + n] = a[k];
  }
  sync();
#pragma unroll 1
  for (int hd = 0; hd < 4; hd++) {
#pragma unroll 1
    for (int i = t; i < 49 * 49; i += 128) {
      const int a = i / 49, b = i % 49;
      float v = 0.f;
#pragma unroll 1
      for (int d = 0; d < 48; d++) v = fmaf(qkv[a * 576 + hd * 48 + d], qkv[b * 576 + 192 + hd * 48 + d], v);
      S[i] = v * 0.14433756729740643f;
    }
    sync();
    if (t < 49) {
      float m = S[t * 49], l = 0.f;
#pragma unroll 1
      for (int b = 1; b < 49; b++) m = fmaxf(m, S[t * 49 + b]);
#pragma unroll 1
      for (int b = 0; b < 49; b++) { const float e = expf(S[t * 49 + b] - m); S[t * 49 + b] = e; l += e; }
#pragma unroll 1
      for (int b = 0; b < 49; b++) S[t * 49 + b] /= l;
    }
    sync();
#pragma unroll 1
    for (int i = t; i < 49 * 48; i += 128) {
      const int a = i / 48, d = i % 48;
      float v = 0.f;
#pragma unroll 1
      for (int b = 0; b < 49; b++) v = fmaf(S[a * 49 + b], qkv[b * 576 + 384 + hd * 48 + d], v);
      h[a * CH + hd * 48 + d] = v;
    }
    sync();
  }
#pragma unroll 1
  for (int i = t; i < 7 * CH; i += 128) {
    const int n = i % CH, k0 = i / CH * 7;
    float a[7] = {0.f, 0.f, 0.f, 0.f, 0.f, 0.f, 0.f};
#pragma unroll 1
    for (int c = 0; c < CH; c++) {
      const float wv = __bfloat162float(wo[c * CH + n]);
#pragma unroll
      for (int k = 0; k < 7; k++) a[k] = fmaf(h[(k0 + k) * CH + c], wv, a[k]);
    }
#pragma unroll
    for (int k = 0; k < 7; k++)
      out[((size_t)(wy * 7 + k0 / 7) * IMG + wx * 7 + k) * CH + n] = __float2bfloat16(x0[(k0 + k) * CH + n] + a[k]);
  }
  sync();
}

__global__ void __launch_bounds__(384, 1)
fused_kernel(const __grid_constant__ CUtensorMap tmx, const __grid_constant__ CUtensorMap tmp, const __grid_constant__ Descs ds, const __nv_bfloat16* __restrict__ dw, __nv_bfloat16* __restrict__ out, const int never,
             const __nv_bfloat16* __restrict__ x, const __nv_bfloat16* __restrict__ wqkv, const __nv_bfloat16* __restrict__ wo) {
  extern __shared__ __align__(1024) uint8_t smem[];
  const uint32_t sb = (uint32_t)__cvta_generic_to_shared(smem);
  const int tid = threadIdx.x, lane = tid & 31;
  const int warp = __shfl_sync(0xffffffffu, tid >> 5, 0);
  const int cta = blockIdx.x, ncta = gridDim.x;
  const int nfull = NWIN / (2 * ncta);
  const int nrounds = nfull + ((NWIN - nfull * 2 * ncta) > cta ? 1 : 0);

  if (warp == 0) GTS(0);
  if (warp == 10 && lane == 0) asm volatile("prefetch.tensormap [%0];" :: "l"(reinterpret_cast<uint64_t>(&tmx)) : "memory");
  if (tid == 0) {
    mbar_init(sb + BAR_FIRST, 1);
    asm volatile("fence.mbarrier_init.release.cluster;" ::: "memory");
    asm volatile("mbarrier.arrive.expect_tx.shared::cta.b64 _, [%0], %1;" :: "r"(sb + BAR_FIRST), "n"(2 * HALO_BYTES) : "memory");
#pragma unroll
    for (int k = 0; k < 2; k++) {
      const int w = max(window_of(0, nfull, cta, ncta, k), 0), a = w / NWX;
      asm volatile("cp.async.bulk.tensor.3d.shared::cluster.global.mbarrier::complete_tx::bytes [%0], [%1, {0, %3, %4}], [%2];"
                   :: "r"(sb + OFF_HALO + k * HALO_BYTES), "l"(reinterpret_cast<uint64_t>(&tmp)), "r"(sb + BAR_FIRST),
                      "r"((w - a * NWX) * 7 - 1), "r"(a * 7 - 1) : "memory");
    }
    if ((sb & 0x3FFFF) != SMEM_BASE || nrounds > 128) __trap();
    for (int i = 0; i < 6; i++) mbar_init(sb + BAR_FH + 8 * i, 1);
    for (int i = 0; i < 4; i++) mbar_init(sb + BAR_E + 8 * i, 8);
    for (int i = 0; i < 9; i++) mbar_init(sb + BAR_XFULL + 8 * i, 1);
    mbar_init(sb + BAR_TFULL, 3);
    mbar_init(sb + BAR_TEMPTY, 8);
    asm volatile("fence.mbarrier_init.release.cluster;" ::: "memory");
  }
  if (tid >= 128 && tid < 320) {
    *reinterpret_cast<uint32_t*>(smem + OFF_ZERO + (tid - 128) * 4) = 0;
    if (tid < 136) *reinterpret_cast<uint32_t*>(smem + OFF_REDO + (tid - 128) * 4) = 0;
  }
  if (tid < 128) {
    *reinterpret_cast<uint4*>(smem + OFF_KV + (tid / 64) * KV_BYTES + 6 * KV_PITCH + (tid % 64) * 16) = make_uint4(0x3c003c00u, 0x3c003c00u, 0x3c003c00u, 0x3c003c00u);
    proxy_fence();
  }
  __syncthreads();

  if (warp < 11) {
#pragma unroll 1
    for (int u = 0; u < (warp < 10 ? 2 : 1); u++) {
      const int cb = warp < 9 ? warp % 3 : 2 * (warp - 9) + u, y = warp < 9 ? 2 * (warp / 3) + u : 6;
      const int ch0 = cb * 64 + (lane & 15) * 4;
      uint32_t wt[9][2], px[3][9][2];
#pragma unroll
      for (int t = 0; t < 9; t++) {
        const uint2 v = *reinterpret_cast<const uint2*>(dw + t * CH + ch0);
        wt[t][0] = v.x; wt[t][1] = v.y;
      }
      mbar_wait(sb + BAR_FIRST, 0);
      const uint32_t ld = sb + OFF_HALO + (lane >> 4) * HALO_BYTES + y * 3456 + ch0 * 2;
#pragma unroll
      for (int p = 0; p < 27; p++)
        asm volatile("ld.shared.v2.u32 {%0,%1}, [%2];" : "=r"(px[p / 9][p % 9][0]), "=r"(px[p / 9][p % 9][1]) : "r"(ld + p * 384));
      const uint32_t st0 = sb + OFF_TILE + (lane >> 4) * TILE_BYTES + ch0 * 4;
      const uint32_t sa = (st0 ^ ((y & 1) << 4)) + y * 2304;
      uint32_t o[2][2];
#pragma unroll
      for (int j = 0; j < 7; j++) {
#pragma unroll
        for (int e = 0; e < 2; e++) {
          uint32_t a = hmul(px[0][j][e], wt[0][e]);
#pragma unroll
          for (int t = 1; t < 9; t++) a = hfma(px[t / 3][j + t % 3][e], wt[t][e], a);
          a = hadd(px[1][j + 1][e], a);
          o[j & 1][e] = packh(lo2f(a), hi2f(a));
        }
        if (j & 1)
          asm volatile("st.shared.v4.u32 [%0], {%1,%2,%3,%4};" :: "r"((j == 3 ? sa ^ 16 : sa) + (j >> 1) * 768),
                       "r"(o[0][0]), "r"(o[1][0]), "r"(o[0][1]), "r"(o[1][1]) : "memory");
      }
      const uint32_t sb6 = (st0 ^ ((~y & 2) << 3)) + (21 + (y >> 1)) * 768 + (y & 1) * 4;
      asm volatile("st.shared.u32 [%0], %1;\nst.shared.u32 [%0 + 8], %2;" :: "r"(sb6), "r"(o[0][0]), "r"(o[0][1]) : "memory");
      if (y == 6) asm volatile("st.shared.u32 [%0 + 4], %1;\nst.shared.u32 [%0 + 12], %1;" :: "r"(sb6), "r"(0) : "memory");
    }
    asm volatile("bar.arrive 8, 384;\nbar.sync 7, 352;" ::: "memory");
  }

  if (warp >= 8) {
    asm volatile("setmaxnreg.dec.sync.aligned.u32 " PREGS ";");
    if (warp == 11) {
      asm volatile("griddepcontrol.wait;" ::: "memory");
      GTS(2);
      load_slices<3, 0>(sb, ds.src, 0, 0, BAR_F0);
      *reinterpret_cast<float2*>(smem + OFF_LIM) = fp16_limits(lane);
      asm volatile("{\n.reg .pred p;\nelect.sync _|p, 0xffffffff;\n@p mbarrier.arrive.expect_tx.shared::cta.b64 _, [%0], %1;\n}\n"
                   :: "r"(sb + BAR_F0), "n"(3 * SLICE) : "memory");
      asm volatile("bar.sync 8, 384;" ::: "memory");
      load_slices<3, 5 * SLICE>(sb, ds.src, 3, 3, BAR_F1);
      load_slices<1, 0>(sb, ds.src, 13, SLOT_U, BAR_F1);
      load_slices<1, 0>(sb, ds.src, 12, SLOT_V, BAR_F1);
      for (int r = 0; r < nrounds; r++) {
        const int par = r & 1;
        const int h2 = par ? 1 : 2, h3 = par ? 0 : 3;
        mbar_wait(sb + BAR_E, par);
        load_slices<3>(sb, ds.src, 3 * h2, 3 * (h2 & 1), BAR_FH);
        mbar_wait(sb + BAR_E + 8, par);
        load_slices<3>(sb, ds.src, 3 * h3, 3 * (h3 & 1), BAR_FH + 8);
        mbar_wait(sb + BAR_E + 16, par);
        load_slices<1>(sb, ds.src, 12 + h2, SLOT_U, BAR_FU);
        mbar_wait(sb + BAR_E + 24, par);
        load_slices<1>(sb, ds.src, 12 + h3, SLOT_V, BAR_FV);
      }
    } else {
      const int cw = warp - 8;
      const int win = lane >> 4;
      const int ch0 = cw * 64 + (lane & 15) * 4;
      uint32_t wt[9][2];
#pragma unroll
      for (int t = 0; t < 9; t++) {
        uint2 v = *reinterpret_cast<const uint2*>(dw + t * CH + ch0);
        wt[t][0] = v.x; wt[t][1] = v.y;
      }
      const uint32_t xs = sb + OFF_X + cw * 3 * XSLOT;
      const uint32_t xld = xs + (lane >> 4) * 1152 + (lane & 15) * 8;
      const uint32_t xbar = sb + BAR_XFULL + cw * 24;
      const uint32_t st0 = sb + OFF_TILE + win * TILE_BYTES + ch0 * 4;
      const uint64_t tm = reinterpret_cast<uint64_t>(&tmx);
      int cx0, cy0, cx1, cy1;
      auto coords = [&](int r) {
        const int w0 = window_of(r, nfull, cta, ncta, 0);
        int w1 = window_of(r, nfull, cta, ncta, 1);
        if (w1 < 0) w1 = w0;
        const int a = w0 / NWX, b = w1 / NWX;
        cx0 = (w0 - a * NWX) * 7 - 1; cy0 = a * 7 - 1;
        cx1 = (w1 - b * NWX) * 7 - 1; cy1 = b * 7 - 1;
      };
      auto issue = [&](int slot, int dy) {
        asm volatile("{\n.reg .pred p;\nelect.sync _|p, 0xffffffff;\n"
                     "@p mbarrier.arrive.expect_tx.shared::cta.b64 _, [%2], %8;\n"
                     "@p cp.async.bulk.tensor.3d.shared::cluster.global.mbarrier::complete_tx::bytes [%0], [%1, {%3, %4, %5}], [%2];\n"
                     "@p cp.async.bulk.tensor.3d.shared::cluster.global.mbarrier::complete_tx::bytes [%0 + 1152], [%1, {%3, %6, %7}], [%2];\n}\n"
                     :: "r"(xs + slot * XSLOT), "l"(tm), "r"(xbar + slot * 8), "r"(cw * 64), "r"(cx0), "r"(cy0 + dy), "r"(cx1), "r"(cy1 + dy), "n"(XSLOT) : "memory");
      };
      uint32_t accA[7][2], accB[7][2], ctr[7][2], held[2];
      auto row = [&](auto fin, auto mid, auto top, int slot, int y) {
        const uint32_t ld = xld + slot * XSLOT;
        const uint32_t sa = (st0 ^ ((y & 1) << 4)) + y * 2304;
        uint32_t cur[9][2], o[2][2];
#pragma unroll
        for (int p = 0; p < LA; p++)
          asm volatile("ld.shared.v2.u32 {%0,%1}, [%2];" : "=r"(cur[p][0]), "=r"(cur[p][1]) : "r"(ld + p * 128));
#pragma unroll
        for (int j = 0; j < 7; j++) {
          if (j >= 1 && j + LA - 1 < 9)
            asm volatile("ld.shared.v2.u32 {%0,%1}, [%2];" : "=r"(cur[j + LA - 1][0]), "=r"(cur[j + LA - 1][1]) : "r"(ld + (j + LA - 1) * 128));
          if (fin.v) {
#pragma unroll
            for (int e = 0; e < 2; e++) {
              uint32_t a = hfma(cur[j][e], wt[6][e], accA[j][e]);
              a = hfma(cur[j + 1][e], wt[7][e], a);
              a = hfma(cur[j + 2][e], wt[8][e], a);
              a = hadd(ctr[j][e], a);
              o[j & 1][e] = packh(lo2f(a), hi2f(a));
            }
            if (j & 1)
              asm volatile("st.shared.v4.u32 [%0], {%1,%2,%3,%4};" :: "r"((j == 3 ? sa ^ 16 : sa) + (j >> 1) * 768),
                           "r"(o[0][0]), "r"(o[1][0]), "r"(o[0][1]), "r"(o[1][1]) : "memory");
            if (j == 6) {
              const uint32_t sb6 = (st0 ^ ((~y & 2) << 3)) + (21 + (y >> 1)) * 768;
              if (fin.v == 2)
                asm volatile("st.shared.v4.u32 [%0], {%1,%2,%3,%2};" :: "r"(sb6), "r"(o[0][0]), "r"(0), "r"(o[0][1]) : "memory");
              else
                asm volatile("{\n.reg .pred p;\nsetp.ne.s32 p, %5, 0;\n@p st.shared.v4.u32 [%0], {%1,%2,%3,%4};\n}\n"
                             :: "r"(sb6), "r"(held[0]), "r"(o[0][0]), "r"(held[1]), "r"(o[0][1]), "r"(y & 1) : "memory");
              held[0] = o[0][0]; held[1] = o[0][1];
            }
          }
#pragma unroll
          for (int e = 0; e < 2; e++) {
            if (mid.v) {
              uint32_t a = hfma(cur[j][e], wt[3][e], accB[j][e]);
              a = hfma(cur[j + 1][e], wt[4][e], a);
              accA[j][e] = hfma(cur[j + 2][e], wt[5][e], a);
              ctr[j][e] = cur[j + 1][e];
            }
            if (top.v) {
              uint32_t a = hmul(cur[j][e], wt[0][e]);
              a = hfma(cur[j + 1][e], wt[1][e], a);
              accB[j][e] = hfma(cur[j + 2][e], wt[2][e], a);
            }
          }
        }
      };
      held[0] = held[1] = 0;
      if (nrounds > 1) { coords(1); issue(0, 0); issue(1, 1); issue(2, 2); }
      for (int r = 0; r + 1 < nrounds; r++) {
        const bool more = r + 2 < nrounds;
        mbar_wait(xbar, r & 1);
        if (r > 0) issue(2, 2);
        row(IC<0>{}, IC<0>{}, IC<1>{}, 0, 0);
        mbar_wait(xbar + 8, r & 1);
        issue(0, 3);
        row(IC<0>{}, IC<1>{}, IC<1>{}, 1, 0);
        mbar_wait(sb + BAR_TEMPTY, r & 1);
#pragma unroll 1
        for (int k = 0; k < 2; k++) {
          mbar_wait(xbar + 16, (r + k) & 1);
          issue(1, 4 + 3 * k);
          row(IC<1>{}, IC<1>{}, IC<1>{}, 2, 3 * k);
          mbar_wait(xbar, (r + k + 1) & 1);
          issue(2, 5 + 3 * k);
          row(IC<1>{}, IC<1>{}, IC<1>{}, 0, 3 * k + 1);
          mbar_wait(xbar + 8, (r + k + 1) & 1);
          if (k == 1 && more) coords(r + 2);
          if (k == 0 || more) issue(0, k == 0 ? 6 : 0);
          row(IC<1>{}, IC<1>{}, IC<1>{}, 1, 3 * k + 2);
        }
        mbar_wait(xbar + 16, r & 1);
        if (more) issue(1, 1);
        row(IC<2>{}, IC<0>{}, IC<0>{}, 2, 6);
        __syncwarp();
        warp_arrive(sb + BAR_TFULL);
      }
    }
    asm volatile("bar.sync 5, 384;" ::: "memory");
#pragma unroll 1
    for (int i = 0; i < 8; i++) {
      uint32_t bits = *reinterpret_cast<volatile uint32_t*>(smem + OFF_REDO + 4 * i);
#pragma unroll 1
      for (; bits; bits &= bits - 1)
        slow_window(reinterpret_cast<float*>(smem), window_of((i & 3) * 32 + __ffs(bits) - 1, nfull, cta, ncta, i >> 2), tid - 256, x, dw, wqkv, wo, out);
    }
  } else {
    asm volatile("setmaxnreg.inc.sync.aligned.u32 " CREGS ";");
    const int wg = warp >> 2, w4 = warp & 3, g = lane >> 2, q = lane & 3;
    const int row0 = w4 * 16 + g, row1 = row0 + 8;
    const int ps = min(w4 * 8 + g, 24);
    const int pix0 = ps < 21 ? (ps / 3) * IMG + (ps % 3) * 2 : (ps - 21) * 2 * IMG + 6;
    const int pix1 = pix0 + (ps < 21 ? 1 : ps < 24 ? IMG : 0);
    const uint32_t kv = sb + OFF_KV + wg * KV_BYTES;
    const int srow = w4 * 16 + (lane & 15);
    const uint32_t vst = kv + (lane >> 4) * KV_PITCH + (srow < 56 ? srow : min(srow - 7, 55)) * 16;
    uint32_t misc = ((uint32_t)pix1 << 20) | ((uint32_t)pix0 << 8) | q;
    const uint32_t ninf = q ? 0xfc00fc00u : 0u;
    const uint32_t v48 = kv + (lane >> 3) * KV_PITCH + 48 * 16;
    const uint32_t vmask = (row0 < 49 ? 0xffffu : 0u) | (row1 < 49 ? 0xffff0000u : 0u);

    const uint32_t tx = sb + q * 32 + (row0 < 49 ? OFF_TILE + wg * TILE_BYTES + ps * 768 + (ps & 1) * 16 : OFF_ZERO + 16);
    const int myrounds = window_of(nrounds - 1, nfull, cta, ncta, wg) < 0 ? nrounds - 1 : nrounds;

    if (never == 2) return;
    uint32_t H[48], Y[48];
    const uint64_t* dkv = ds.kv[wg];
    uint32_t P[NP], Ofc[12], p48 = 0;
#pragma unroll
    for (int i = 0; i < 48; i++) Y[i] = 0;
#pragma unroll
    for (int i = 0; i < NP; i++) P[i] = Ofc[i % 12] = 0;
    if (warp == 0) GTS(4);
    load_x<0, 12>(H, tx);
    warp_arrive(sb + BAR_TEMPTY);
    mbar_wait(sb + BAR_F0, 0);
    if (warp == 0) GTS(1);
    if (wg == 1) turn_pass(1);

    uint8_t *o0, *o1;
    uint32_t omask;
    auto out_setup = [&](int r) {
      omask = r >= 0 ? vmask : 0u;
      const int w = window_of(r, nfull, cta, ncta, wg);
      const int wy = w / NWX, wx = w - wy * NWX;
      asm volatile("" : "+r"(misc));
      const uint32_t wb = (uint32_t)(wy * 7 * IMG + wx * 7) * 384u + (misc & 3) * 16;
      o0 = reinterpret_cast<uint8_t*>(out) + (wb + ((misc >> 8) & 0xfff) * 384u);
      o1 = reinterpret_cast<uint8_t*>(out) + (wb + (misc >> 20) * 384u);
    };
#define OUT(c) store_out<c>(Y, o0, o1, omask)
    auto release = [&](int i) { warp_arrive(sb + BAR_E + 8 * i); };

    for (int r = 0;; r++) {
      const uint32_t par = r & 1;
      uint32_t acc[36], S[14], O[14], Q[12], V[12], Ofa[12], Ofb[12], vr[6], k48, mx;
      if (r == myrounds) {
        const bool idle = r < nrounds;
        if (idle) { release(0); release(1); }
        mbar_wait(sb + BAR_FU, par ^ 1);
        turn_wait(wg);
        wg_fence(); mma_pv(O, P, dkv + 4); mma_proj(Y, Ofc, ds.pu[0]); wg_commit();
        turn_pass(wg);
        load_v48(vr, v48);
        wg_wait<0>(); keep(O); keep(Y);
        finish_o(O, vr, p48, vmask, Ofa);
        mbar_wait(sb + BAR_FV, par ^ 1);
        turn_wait(wg);
        wg_fence(); mma_proj(Y, Ofa, ds.pv[0]); wg_commit();
        if (wg == 0 || idle) turn_pass(wg);
        wg_wait<0>(); keep(Y);
        if (idle) { release(2); release(3); turn_wait(wg); turn_pass(wg); }
        out_setup(r - 1);
        OUT(0); PIN(); OUT(1); PIN(); OUT(2); PIN(); OUT(3); PIN(); OUT(4); PIN(); OUT(5);
        if (idle) {
          turn_wait(wg); turn_pass(wg);
          turn_wait(wg); turn_pass(wg);
          turn_wait(wg); turn_pass(wg);
          turn_wait(wg);
        }
        if (w4 == 0) GTS(5 + wg);
        asm volatile("bar.arrive 5, 384;" ::: "memory");
        break;
      }
      const uint64_t* dq0 = ds.q[par];
      float s1[2], s2[2];
      TR(0);
      turn_wait(wg);
      TR(1);
      wg_fence(); mma_pv(O, P, dkv + 4); wg_commit(); mma_qkv<0, K0A>(acc, H, dq0);
      PIN();
      ln_sums<0, 24>(H, s1, s2);
      PIN();
      wg_fence(); mma_qkv<K0A, 12>(acc, H, dq0);
      if (r > 0) { mbar_wait(sb + BAR_FU, par ^ 1); wg_fence(); mma_proj(Y, Ofc, ds.pu[0]); wg_commit(); }
      else { wg_fence(); wg_commit(); }
      turn_pass(wg);
      TR(2);
      load_v48(vr, v48);
      wg_wait<3>(); keep(O);
      wg_sync(wg);
      PIN();
      finish_o(O, vr, p48, vmask, Ofa);
      ln_sums<24, 48>(H, s1, s2);
      float lim_lo, lim_hi;
      asm volatile("ld.shared.v2.f32 {%0,%1}, [%2];" : "=f"(lim_lo), "=f"(lim_hi) : "r"(sb + OFF_LIM) : "memory");
      bool ok;
      const uint32_t rk = ln_rstd(s1, s2, lim_lo, lim_hi, vmask, ok);
      asm volatile("{\n.reg .pred p;\nsetp.eq.s32 p, %2, 0;\n@p red.shared.or.b32 [%0], %1;\n}\n"
                   :: "r"(sb + OFF_REDO + wg * 16 + (r >> 5) * 4), "r"(1u << (r & 31)), "r"((int)ok) : "memory");
      PIN();
      TR(3);
      wg_wait<1>(); keep(acc);
      TR(4);
      release(0);
      scale12(V, acc, rk); stsm12(V, vst + KV_KOFF);
      scale12(V, acc + 24, rk); stsm12(V, vst);
      PIN();
      wg_wait<0>(); keep(Y);
      PIN();
      proxy_fence();
      scale12(Q, acc + 12, rk);
      if (r > 0) mbar_wait(sb + BAR_FV, par ^ 1); else mbar_wait(sb + BAR_F1, 0);
      TR(5);
      turn_wait(wg);
      TR(6);
      if (r > 0) { wg_fence(); mma_proj(Y, Ofa, ds.pv[0]); wg_commit(); }
      wg_fence(); mma_s(S, Q, dkv); mma_qkv<0, 2>(acc, H, dq0 + 12);
      out_setup(r - 1);
      PIN();
      wg_wait<1>(); keep(Y);
      wg_fence(); mma_qkv<2, 6>(acc, H, dq0 + 12);
      PIN();
      OUT(0);
      PIN();
      wg_wait<1>(); keep(S);
      wg_fence(); mma_qkv<6, 9>(acc, H, dq0 + 12);
      PIN();
      row_max(S, k48, mx, ninf);
      OUT(1);
      PIN();
      wg_fence(); mma_qkv<9, 12>(acc, H, dq0 + 12);
      turn_pass(wg);
      PIN();
      OUT(2); PIN();
      OUT(3); PIN();
      row_exp(S, k48, mx, P, p48);
      PIN();
      TR(7);
      wg_wait<0>(); keep(acc);
      TR(8);
      release(1);
      wg_sync(wg);
      scale12(V, acc, rk); stsm12(V, vst + KV_KOFF);
      scale12(Q, acc + 12, rk); scale12(V, acc + 24, rk); PIN();
      proxy_fence();
#define TURN(ID, OF, DQ, FB, X1)                                                        \
      mbar_wait(sb + FB, par);                                                          \
      TR(ID + 1);                                                                       \
      turn_wait(wg);                                                                    \
      wg_fence(); mma_pv(O, P, dkv + 4); mma_s(S, Q, dkv); wg_commit(); mma_qkv<0, KA>(acc, H, DQ); \
      PIN();                                                                            \
      TR(ID + 2);                                                                       \
      load_v48(vr, v48);                                                                \
      X1;                                                                               \
      PIN();                                                                            \
      wg_wait<1>(); keep(S); keep(O);                                                   \
      wg_sync(wg);                                         \
      wg_fence(); mma_qkv<KA, KB>(acc, H, DQ);                                            \
      PIN();                                                                            \
      stsm12(V, vst);                                                                   \
      finish_o(O, vr, p48, vmask, OF);                                                  \
      row_max(S, k48, mx, ninf);                                                        \
      PIN();                                                                            \
      wg_fence(); mma_qkv<KB, 12>(acc, H, DQ);                                           \
      turn_pass(wg);                                                                    \
      PIN();                                                                            \
      TR(ID + 3);
#define NEXT_HEAD(ID)                                                                   \
      row_exp(S, k48, mx, P, p48);                                                      \
      PIN();                                                                            \
      TR(ID + 4);                                                                       \
      wg_wait<0>(); keep(acc);                                                          \
      scale12(V, acc, rk); stsm12(V, vst + KV_KOFF);                                    \
      scale12(Q, acc + 12, rk); scale12(V, acc + 24, rk); PIN();
      TURN(8, Ofa, dq0 + 24, BAR_FH, OUT(4))
      OUT(5); PIN();
      NEXT_HEAD(8)
      proxy_fence();
      TURN(12, Ofb, dq0 + 36, BAR_FH + 8, )
      auto init_y = [&]() {
#pragma unroll
        for (int i = 0; i < 48; i++) Y[i] = (i & 1) ? H[i] ^ never : h2u(__hadd2_rn(u2h(H[i]), u2h(never)));
        hold<0, 48>(Y); PIN();
      };
      NEXT_HEAD(12)
      init_y();
      proxy_fence();
      TR(17);
      turn_wait(wg);
      wg_fence(); mma_pv(O, P, dkv + 4); mma_s(S, Q, dkv); wg_commit();
      mma_proj(Y, Ofb, ds.pu[1]); wg_commit(); mma_proj(Y, Ofa, ds.pv[1]); wg_commit();
      turn_pass(wg);
      PIN();
      TR(18);
      load_v48(vr, v48);
      if (r + 1 < myrounds) mbar_wait(sb + BAR_TFULL, par);
      load_x<0, 4>(H, tx);
      wg_wait<2>(); keep(S); keep(O);
      wg_sync(wg);
      PIN();
      TR(19);
      row_max(S, k48, mx, ninf);
      finish_o(O, vr, p48, vmask, Ofc);
      stsm12(V, vst);
      PIN();
      wg_wait<1>();
      release(2);
      load_x<4, 8>(H, tx);
      row_exp(S, k48, mx, P, p48);
      PIN();
      load_x<8, 12>(H, tx);
      warp_arrive(sb + BAR_TEMPTY);
      TR(20);
      wg_wait<0>(); keep(Y);
      release(3);
      proxy_fence();
      TR(21);
#undef TURN
#undef NEXT_HEAD
    }
  }
}

typedef CUresult (*EncodeFn)(CUtensorMap*, CUtensorMapDataType, cuuint32_t, void*, const cuuint64_t*, const cuuint64_t*,
                             const cuuint32_t*, const cuuint32_t*, CUtensorMapInterleave, CUtensorMapSwizzle,
                             CUtensorMapL2promotion, CUtensorMapFloatOOBfill);

}

extern "C" void kernel_launch(void* const* d_in, const int* in_sizes, int n_in, void* d_out, int out_size) {
  const __nv_bfloat16* x = (const __nv_bfloat16*)d_in[0];
  const __nv_bfloat16* dw = (const __nv_bfloat16*)d_in[1];
  const __nv_bfloat16* wqkv = (const __nv_bfloat16*)d_in[2];
  const __nv_bfloat16* wo = (const __nv_bfloat16*)d_in[3];
  static EncodeFn encode = nullptr;
  static int nsm = 0;
  static void* wpack = nullptr;
  if (!encode) {
    void* fn = nullptr;
    cudaDriverEntryPointQueryResult qr;
    cudaGetDriverEntryPoint("cuTensorMapEncodeTiled", &fn, cudaEnableDefault, &qr);
    encode = (EncodeFn)fn;
    int dev = 0;
    cudaGetDevice(&dev);
    cudaDeviceGetAttribute(&nsm, cudaDevAttrMultiProcessorCount, dev);
    cudaGetSymbolAddress(&wpack, g_wpack);
    cudaFuncSetAttribute(fused_kernel, cudaFuncAttributeMaxDynamicSharedMemorySize, SMEM_BYTES);
  }
  CUtensorMap tmx;
  cuuint64_t gdim[3] = {CH, IMG, IMG};
  cuuint64_t gstr[2] = {CH * 2, (cuuint64_t)CH * 2 * IMG};
  cuuint32_t box[3] = {64, 9, 1};
  cuuint32_t estr[3] = {1, 1, 1};
  encode(&tmx, CU_TENSOR_MAP_DATA_TYPE_BFLOAT16, 3, (void*)x, gdim, gstr, box, estr, CU_TENSOR_MAP_INTERLEAVE_NONE,
         CU_TENSOR_MAP_SWIZZLE_NONE, CU_TENSOR_MAP_L2_PROMOTION_L2_128B, CU_TENSOR_MAP_FLOAT_OOB_FILL_NONE);
  Descs ds;
  for (int i = 0; i < 12; i++)
    for (int b = 0; b < 5; b++) ds.q[b][i] = mkdesc(SMEM_BASE + OFF_W + qkv_pos(b & 1, i), 128, 256);
  for (int i = 0; i < 3; i++) {
    ds.pu[0][i] = ds.pu[1][i] = mkdesc(SMEM_BASE + OFF_W + SLOT_U * SLICE + i * 6144, 128, 256);
    ds.pv[0][i] = ds.pv[1][i] = mkdesc(SMEM_BASE + OFF_W + SLOT_V * SLICE + i * 6144, 128, 256);
  }
  ds.src = (const uint8_t*)wpack;
  for (int g = 0; g < 2; g++)
    for (int i = 0; i < 4; i++) {
      ds.kv[g][i] = mkdesc(SMEM_BASE + OFF_KV + g * KV_BYTES + KV_KOFF + 2 * i * KV_PITCH, KV_PITCH, 128);
      ds.kv[g][4 + i] = mkdesc(SMEM_BASE + OFF_KV + g * KV_BYTES + 256 * i, 128, KV_PITCH);
    }
  CUtensorMap tmp;
  cuuint32_t boxp[3] = {CH, 9, 9};
  encode(&tmp, CU_TENSOR_MAP_DATA_TYPE_BFLOAT16, 3, (void*)x, gdim, gstr, boxp, estr, CU_TENSOR_MAP_INTERLEAVE_NONE,
         CU_TENSOR_MAP_SWIZZLE_NONE, CU_TENSOR_MAP_L2_PROMOTION_L2_128B, CU_TENSOR_MAP_FLOAT_OOB_FILL_NONE);
  prepack_kernel<<<48, dim3(192, 2), 0, cudaStreamPerThread>>>(wqkv, wo);
  cudaLaunchConfig_t cfg = {};
  cfg.gridDim = dim3(nsm); cfg.blockDim = dim3(384); cfg.dynamicSmemBytes = SMEM_BYTES; cfg.stream = cudaStreamPerThread;
  cudaLaunchAttribute at[1];
  at[0].id = cudaLaunchAttributeProgrammaticStreamSerialization;
  at[0].val.programmaticStreamSerializationAllowed = 1;
  cfg.attrs = at; cfg.numAttrs = 1;
  cudaLaunchKernelEx(&cfg, fused_kernel, tmx, tmp, ds, dw, (__nv_bfloat16*)d_out, 0, x, wqkv, wo);
}
```

```cpp
#include <cuda_runtime.h>
#include <cuda_bf16.h>
#include <cuda_fp16.h>
#include <cuda.h>
#include <stdint.h>

#define CREGS "208"
#define PREGS "88"
#define K48TC 0
#define LA 4
#define K0A 6
#define KA 3
#define KB 9
#define PFX 1
namespace {
constexpr int NP = K48TC ? 16 : 12;

constexpr int IMG = 511;
constexpr int CH = 192;
constexpr int NWX = 73;
constexpr int NWIN = NWX * NWX;
constexpr int SLICE = 18432;
constexpr int OFF_W = 0;
constexpr int KV_PITCH = 1792, KV_KOFF = 896, KV_BYTES = 6 * KV_PITCH + 1024;
constexpr int OFF_KV = 8 * SLICE;
constexpr int TILE_BYTES = 25 * 768;
constexpr int OFF_TILE = OFF_KV + 2 * KV_BYTES;
constexpr int XSLOT = 2304;
constexpr int OFF_ZERO = OFF_TILE + 2 * TILE_BYTES;
constexpr int OFF_X = OFF_ZERO + 768;
constexpr int OFF_BAR = OFF_X + 9 * XSLOT;
constexpr int BAR_FH = OFF_BAR;
constexpr int BAR_FU = OFF_BAR + 16, BAR_FV = OFF_BAR + 24;
constexpr int BAR_F0 = OFF_BAR + 32, BAR_F1 = OFF_BAR + 40;
constexpr int BAR_E = OFF_BAR + 80;
constexpr int BAR_XFULL = OFF_BAR + 112;
constexpr int BAR_TFULL = OFF_BAR + 184;
constexpr int BAR_TEMPTY = OFF_BAR + 192;
constexpr int OFF_LIM = OFF_BAR + 200;
constexpr int OFF_REDO = OFF_BAR + 208;
constexpr int BAR_FIRST = OFF_BAR + 240;
constexpr int OFF_TRACE = OFF_BAR + 248;
constexpr int OFF_HALO = OFF_W + 3 * SLICE, HALO_BYTES = 81 * 384;
constexpr int SMEM_BYTES = OFF_TRACE;

__host__ __device__ constexpr int qkv_pos(int h, int s) { return 3 * h * SLICE + s * 4608; }
__host__ __device__ constexpr int wo_pos(int s) { return 12 * SLICE + s * 6144; }
constexpr int SLOT_U = 6, SLOT_V = 7;
constexpr int SMEM_BASE = 1024;
struct Descs { uint64_t q[5][12]; uint64_t pu[2][3], pv[2][3]; uint64_t kv[2][8]; const uint8_t* src; };

__device__ uint4 g_wpack[16 * SLICE / 16];
__device__ float2 g_wnorm[96];
#define TR(id)
#define GTS(i)
template <int V> struct IC { static constexpr int v = V; };
typedef __nv_bfloat162 bf2;
__device__ __forceinline__ bf2 u2b(uint32_t u) { return *reinterpret_cast<bf2*>(&u); }
__device__ __forceinline__ uint32_t b2u(bf2 b) { return *reinterpret_cast<uint32_t*>(&b); }
__device__ __forceinline__ uint32_t pack2(float lo, float hi) {
  uint32_t r; asm("cvt.rn.bf16x2.f32 %0, %1, %2;" : "=r"(r) : "f"(hi), "f"(lo)); return r;
}
__device__ __forceinline__ uint32_t hadd(uint32_t a, uint32_t b) { return b2u(__hadd2_rn(u2b(a), u2b(b))); }
__device__ __forceinline__ uint32_t hmul(uint32_t a, uint32_t b) { return b2u(__hmul2_rn(u2b(a), u2b(b))); }
__device__ __forceinline__ uint32_t hfma(uint32_t a, uint32_t b, uint32_t c) { return b2u(__hfma2(u2b(a), u2b(b), u2b(c))); }
__device__ __forceinline__ __half2 u2h(uint32_t u) { return *reinterpret_cast<__half2*>(&u); }
__device__ __forceinline__ uint32_t h2u(__half2 b) { return *reinterpret_cast<uint32_t*>(&b); }
__device__ __forceinline__ uint32_t packh(float lo, float hi) {
  uint32_t r; asm("cvt.rn.f16x2.f32 %0, %1, %2;" : "=r"(r) : "f"(hi), "f"(lo)); return r;
}
__device__ __forceinline__ uint32_t fmax2(uint32_t a, uint32_t b) { return h2u(__hmax2(u2h(a), u2h(b))); }
template <int HI> __device__ __forceinline__ __half2 hcast(uint32_t a) { return HI ? __high2half2(u2h(a)) : __low2half2(u2h(a)); }
template <int HI> __device__ __forceinline__ uint32_t fmul_b(uint32_t a, uint32_t s) { return h2u(__hmul2_rn(u2h(a), hcast<HI>(s))); }
template <int HI> __device__ __forceinline__ uint32_t fsub_b(uint32_t a, uint32_t s) { return h2u(__hsub2_rn(u2h(a), hcast<HI>(s))); }
__device__ __forceinline__ uint32_t fex2(uint32_t a) { uint32_t r; asm("ex2.approx.f16x2 %0, %1;" : "=r"(r) : "r"(a)); return r; }
__device__ __forceinline__ float lo2f(uint32_t a) { return __uint_as_float(a << 16); }
__device__ __forceinline__ float hi2f(uint32_t a) { return __uint_as_float(a & 0xffff0000u); }

__device__ __forceinline__ void mbar_init(uint32_t bar, uint32_t cnt) { asm volatile("mbarrier.init.shared::cta.b64 [%0], %1;" :: "r"(bar), "r"(cnt) : "memory"); }
__device__ __forceinline__ void mbar_wait(uint32_t bar, uint32_t parity) {
  asm volatile("{\n.reg .pred p;\n.reg .u32 n;\n"
               "mbarrier.try_wait.parity.shared::cta.b64 p, [%0], %1;\n"
               "@p bra.uni DONE_%=;\n"
               "mov.u32 n, 0;\n"
               "AGAIN_%=:\n"
               "mbarrier.try_wait.parity.shared::cta.b64 p, [%0], %1;\n"
               "@p bra.uni DONE_%=;\n"
               "add.u32 n, n, 1;\n"
               "setp.lt.u32 p, n, 0x1000000;\n"
               "@p bra.uni AGAIN_%=;\n"
               "trap;\n"
               "DONE_%=:\n}\n" :: "r"(bar), "r"(parity) : "memory");
}
__device__ __forceinline__ void wg_fence() { asm volatile("wgmma.fence.sync.aligned;" ::: "memory"); }
__device__ __forceinline__ void wg_commit() { asm volatile("wgmma.commit_group.sync.aligned;" ::: "memory"); }
template <int N> __device__ __forceinline__ void wg_wait() { asm volatile("wgmma.wait_group.sync.aligned %0;" :: "n"(N) : "memory"); }
#define BAR_BY_WG(OP, ID0, ID1, CNT) asm volatile("{\n.reg .pred p;\nsetp.eq.s32 p, %0, 0;\n@p " OP " " #ID0 ", " #CNT ";\n@!p " OP " " #ID1 ", " #CNT ";\n}\n" :: "r"(wg) : "memory")
__device__ __forceinline__ void wg_sync(int wg) { BAR_BY_WG("bar.sync", 1, 2, 128); }
__device__ __forceinline__ void turn_wait(int wg) { BAR_BY_WG("bar.sync", 3, 4, 256); }
__device__ __forceinline__ void turn_pass(int wg) { BAR_BY_WG("bar.arrive", 4, 3, 256); }
__device__ __forceinline__ void stsm4(uint32_t addr, uint32_t a, uint32_t b, uint32_t c, uint32_t d) {
  asm volatile("stmatrix.sync.aligned.m8n8.x4.shared.b16 [%0], {%1,%2,%3,%4};" :: "r"(addr), "r"(a), "r"(b), "r"(c), "r"(d) : "memory");
}
template <int N> __device__ __forceinline__ void keep(float (&d)[N]) {
#pragma unroll
  for (int i = 0; i < N; i++) asm volatile("" : "+f"(d[i]) :: "memory");
}
template <int N> __device__ __forceinline__ void keep(uint32_t (&d)[N]) {
#pragma unroll
  for (int i = 0; i < N; i++) asm volatile("" : "+r"(d[i]) :: "memory");
}
__host__ __device__ __forceinline__ uint64_t mkdesc(uint32_t addr, uint32_t lbo, uint32_t sbo) {
  return ((uint64_t)(sbo >> 4) << 32) | (uint64_t)(((lbo >> 4) << 16) | ((addr & 0x3FFFF) >> 4));
}

template <int SCALE_D>
__device__ __forceinline__ void wgmma_n144(uint32_t (&d)[36], uint32_t a0, uint32_t a1, uint32_t a2, uint32_t a3, uint64_t descB) {
  if (SCALE_D == 0)
  asm volatile("wgmma.mma_async.sync.aligned.m64n144k16.f16.f16.f16 "
    "{%0, %1, %2, %3, %4, %5, %6, %7, %8, %9, %10, %11, %12, %13, %14, %15, "
    "%16, %17, %18, %19, %20, %21, %22, %23, %24, %25, %26, %27, %28, %29, %30, %31, "
    "%32, %33, %34, %35}, "
    "{%36, %37, %38, %39}, %40, 0, 1, 1, 0;\n"
    : "=r"(d[0]), "=r"(d[1]), "=r"(d[2]), "=r"(d[3]), "=r"(d[4]), "=r"(d[5]), "=r"(d[6]), "=r"(d[7]),
      "=r"(d[8]), "=r"(d[9]), "=r"(d[10]), "=r"(d[11]), "=r"(d[12]), "=r"(d[13]), "=r"(d[14]), "=r"(d[15]),
      "=r"(d[16]), "=r"(d[17]), "=r"(d[18]), "=r"(d[19]), "=r"(d[20]), "=r"(d[21]), "=r"(d[22]), "=r"(d[23]),
      "=r"(d[24]), "=r"(d[25]), "=r"(d[26]), "=r"(d[27]), "=r"(d[28]), "=r"(d[29]), "=r"(d[30]), "=r"(d[31]),
      "=r"(d[32]), "=r"(d[33]), "=r"(d[34]), "=r"(d[35])
    : "r"(a0), "r"(a1), "r"(a2), "r"(a3), "l"(descB));
  else
  asm volatile("wgmma.mma_async.sync.aligned.m64n144k16.f16.f16.f16 "
    "{%0, %1, %2, %3, %4, %5, %6, %7, %8, %9, %10, %11, %12, %13, %14, %15, "
    "%16, %17, %18, %19, %20, %21, %22, %23, %24, %25, %26, %27, %28, %29, %30, %31, "
    "%32, %33, %34, %35}, "
    "{%36, %37, %38, %39}, %40, 1, 1, 1, 0;\n"
    : "+r"(d[0]), "+r"(d[1]), "+r"(d[2]), "+r"(d[3]), "+r"(d[4]), "+r"(d[5]), "+r"(d[6]), "+r"(d[7]),
      "+r"(d[8]), "+r"(d[9]), "+r"(d[10]), "+r"(d[11]), "+r"(d[12]), "+r"(d[13]), "+r"(d[14]), "+r"(d[15]),
      "+r"(d[16]), "+r"(d[17]), "+r"(d[18]), "+r"(d[19]), "+r"(d[20]), "+r"(d[21]), "+r"(d[22]), "+r"(d[23]),
      "+r"(d[24]), "+r"(d[25]), "+r"(d[26]), "+r"(d[27]), "+r"(d[28]), "+r"(d[29]), "+r"(d[30]), "+r"(d[31]),
      "+r"(d[32]), "+r"(d[33]), "+r"(d[34]), "+r"(d[35])
    : "r"(a0), "r"(a1), "r"(a2), "r"(a3), "l"(descB));
}

template <int SCALE_D>
__device__ __forceinline__ void wgmma_n192(uint32_t (&d)[48], uint32_t a0, uint32_t a1, uint32_t a2, uint32_t a3, uint64_t descB) {
  if (SCALE_D == 0)
  asm volatile("wgmma.mma_async.sync.aligned.m64n192k16.f16.f16.f16 "
    "{%0, %1, %2, %3, %4, %5, %6, %7, %8, %9, %10, %11, %12, %13, %14, %15, "
    "%16, %17, %18, %19, %20, %21, %22, %23, %24, %25, %26, %27, %28, %29, %30, %31, "
    "%32, %33, %34, %35, %36, %37, %38, %39, %40, %41, %42, %43, %44, %45, %46, %47}, "
    "{%48, %49, %50, %51}, %52, 0, 1, 1, 0;\n"
    : "=r"(d[0]), "=r"(d[1]), "=r"(d[2]), "=r"(d[3]), "=r"(d[4]), "=r"(d[5]), "=r"(d[6]), "=r"(d[7]),
      "=r"(d[8]), "=r"(d[9]), "=r"(d[10]), "=r"(d[11]), "=r"(d[12]), "=r"(d[13]), "=r"(d[14]), "=r"(d[15]),
      "=r"(d[16]), "=r"(d[17]), "=r"(d[18]), "=r"(d[19]), "=r"(d[20]), "=r"(d[21]), "=r"(d[22]), "=r"(d[23]),
      "=r"(d[24]), "=r"(d[25]), "=r"(d[26]), "=r"(d[27]), "=r"(d[28]), "=r"(d[29]), "=r"(d[30]), "=r"(d[31]),
      "=r"(d[32]), "=r"(d[33]), "=r"(d[34]), "=r"(d[35]), "=r"(d[36]), "=r"(d[37]), "=r"(d[38]), "=r"(d[39]),
      "=r"(d[40]), "=r"(d[41]), "=r"(d[42]), "=r"(d[43]), "=r"(d[44]), "=r"(d[45]), "=r"(d[46]), "=r"(d[47])
    : "r"(a0), "r"(a1), "r"(a2), "r"(a3), "l"(descB));
  else
  asm volatile("wgmma.mma_async.sync.aligned.m64n192k16.f16.f16.f16 "
    "{%0, %1, %2, %3, %4, %5, %6, %7, %8, %9, %10, %11, %12, %13, %14, %15, "
    "%16, %17, %18, %19, %20, %21, %22, %23, %24, %25, %26, %27, %28, %29, %30, %31, "
    "%32, %33, %34, %35, %36, %37, %38, %39, %40, %41, %42, %43, %44, %45, %46, %47}, "
    "{%48, %49, %50, %51}, %52, 1, 1, 1, 0;\n"
    : "+r"(d[0]), "+r"(d[1]), "+r"(d[2]), "+r"(d[3]), "+r"(d[4]), "+r"(d[5]), "+r"(d[6]), "+r"(d[7]),
      "+r"(d[8]), "+r"(d[9]), "+r"(d[10]), "+r"(d[11]), "+r"(d[12]), "+r"(d[13]), "+r"(d[14]), "+r"(d[15]),
      "+r"(d[16]), "+r"(d[17]), "+r"(d[18]), "+r"(d[19]), "+r"(d[20]), "+r"(d[21]), "+r"(d[22]), "+r"(d[23]),
      "+r"(d[24]), "+r"(d[25]), "+r"(d[26]), "+r"(d[27]), "+r"(d[28]), "+r"(d[29]), "+r"(d[30]), "+r"(d[31]),
      "+r"(d[32]), "+r"(d[33]), "+r"(d[34]), "+r"(d[35]), "+r"(d[36]), "+r"(d[37]), "+r"(d[38]), "+r"(d[39]),
      "+r"(d[40]), "+r"(d[41]), "+r"(d[42]), "+r"(d[43]), "+r"(d[44]), "+r"(d[45]), "+r"(d[46]), "+r"(d[47])
    : "r"(a0), "r"(a1), "r"(a2), "r"(a3), "l"(descB));
}

template <int SCALE_D>
__device__ __forceinline__ void wgmma_n56(uint32_t (&d)[14], uint32_t a0, uint32_t a1, uint32_t a2, uint32_t a3, uint64_t descB) {
  if (SCALE_D == 0)
  asm volatile("wgmma.mma_async.sync.aligned.m64n56k16.f16.f16.f16 "
    "{%0, %1, %2, %3, %4, %5, %6, %7, %8, %9, %10, %11, %12, %13}, "
    "{%14, %15, %16, %17}, %18, 0, 1, 1, 0;\n"
    : "=r"(d[0]), "=r"(d[1]), "=r"(d[2]), "=r"(d[3]), "=r"(d[4]), "=r"(d[5]), "=r"(d[6]), "=r"(d[7]),
      "=r"(d[8]), "=r"(d[9]), "=r"(d[10]), "=r"(d[11]), "=r"(d[12]), "=r"(d[13])
    : "r"(a0), "r"(a1), "r"(a2), "r"(a3), "l"(descB));
  else
  asm volatile("wgmma.mma_async.sync.aligned.m64n56k16.f16.f16.f16 "
    "{%0, %1, %2, %3, %4, %5, %6, %7, %8, %9, %10, %11, %12, %13}, "
    "{%14, %15, %16, %17}, %18, 1, 1, 1, 0;\n"
    : "+r"(d[0]), "+r"(d[1]), "+r"(d[2]), "+r"(d[3]), "+r"(d[4]), "+r"(d[5]), "+r"(d[6]), "+r"(d[7]),
      "+r"(d[8]), "+r"(d[9]), "+r"(d[10]), "+r"(d[11]), "+r"(d[12]), "+r"(d[13])
    : "r"(a0), "r"(a1), "r"(a2), "r"(a3), "l"(descB));
}

template <int SCALE_D>
__device__ __forceinline__ void wgmma_n56t(uint32_t (&d)[14], uint32_t a0, uint32_t a1, uint32_t a2, uint32_t a3, uint64_t descB) {
  if (SCALE_D == 0)
  asm volatile("wgmma.mma_async.sync.aligned.m64n56k16.f16.f16.f16 "
    "{%0, %1, %2, %3, %4, %5, %6, %7, %8, %9, %10, %11, %12, %13}, "
    "{%14, %15, %16, %17}, %18, 0, 1, 1, 1;\n"
    : "=r"(d[0]), "=r"(d[1]), "=r"(d[2]), "=r"(d[3]), "=r"(d[4]), "=r"(d[5]), "=r"(d[6]), "=r"(d[7]),
      "=r"(d[8]), "=r"(d[9]), "=r"(d[10]), "=r"(d[11]), "=r"(d[12]), "=r"(d[13])
    : "r"(a0), "r"(a1), "r"(a2), "r"(a3), "l"(descB));
  else
  asm volatile("wgmma.mma_async.sync.aligned.m64n56k16.f16.f16.f16 "
    "{%0, %1, %2, %3, %4, %5, %6, %7, %8, %9, %10, %11, %12, %13}, "
    "{%14, %15, %16, %17}, %18, 1, 1, 1, 1;\n"
    : "+r"(d[0]), "+r"(d[1]), "+r"(d[2]), "+r"(d[3]), "+r"(d[4]), "+r"(d[5]), "+r"(d[6]), "+r"(d[7]),
      "+r"(d[8]), "+r"(d[9]), "+r"(d[10]), "+r"(d[11]), "+r"(d[12]), "+r"(d[13])
    : "r"(a0), "r"(a1), "r"(a2), "r"(a3), "l"(descB));
}

__global__ void __launch_bounds__(384) prepack_kernel(const __nv_bfloat16* __restrict__ wqkv, const __nv_bfloat16* __restrict__ wo,
                                                      const __nv_bfloat16* __restrict__ x, int first_rows) {
  asm volatile("griddepcontrol.launch_dependents;");
  __shared__ float red2[2][6][16];
  float (*red)[16] = red2[threadIdx.y];
  __half* dst = reinterpret_cast<__half*>(g_wpack);
  const int c = threadIdx.x, nb = blockIdx.x * 2 + threadIdx.y;
  uint32_t u[4];
  int base;
  float scale = 1.0f;
  if (nb < 72) {
    const int h = nb / 18, j = nb % 18, part = j / 6;
    const int col = (part == 0 ? 192 : part == 1 ? 0 : 384) + h * 48 + (j % 6) * 8;
    const uint4 raw = *reinterpret_cast<const uint4*>(wqkv + c * 576 + col);
    u[0] = raw.x; u[1] = raw.y; u[2] = raw.z; u[3] = raw.w;
    if (part == 1) scale = 0.14433756729740643f * 1.4426950408889634f;
    const int cc = c >> 5, q = (c >> 3) & 3, s1 = (c >> 2) & 1, hh = (c >> 1) & 1, e = c & 1;
    base = qkv_pos(h, 2 * cc + s1) / 2 + j * 128 + hh * 64 + 2 * q + e;
  } else {
    const int jb = nb - 72;
#pragma unroll
    for (int i = 0; i < 4; i++) u[i] = *reinterpret_cast<const uint32_t*>(wo + c * 192 + 32 * (jb >> 2) + 8 * i + 2 * (jb & 3));
    base = wo_pos(c >> 4) / 2 + jb * 128 + ((c >> 3) & 1) * 64 + (c & 7);
  }
  float v[8], t[16];
#pragma unroll
  for (int i = 0; i < 4; i++) { v[2 * i] = lo2f(u[i]); v[2 * i + 1] = hi2f(u[i]); }
#pragma unroll
  for (int i = 0; i < 16; i++) {
    float a = i < 8 ? v[i] : v[i - 8] * v[i - 8];
#pragma unroll
    for (int d = 16; d; d >>= 1) a += __shfl_xor_sync(~0u, a, d);
    if ((c & 31) == 0) red[c >> 5][i] = a;
  }
  if (PFX && threadIdx.y == 0 && c < 32)
    for (int i = blockIdx.x + 48 * c; i < first_rows * NWX / 4; i += 48 * 32)
      asm volatile("cp.async.bulk.prefetch.L2.global [%0], %1;" :: "l"(reinterpret_cast<const uint8_t*>(x) + (size_t)i * 10752), "n"(10752) : "memory");
  __syncthreads();
#pragma unroll
  for (int i = 0; i < 16; i++) t[i] = red[0][i] + red[1][i] + red[2][i] + red[3][i] + red[4][i] + red[5][i];
  float mx = 0.f, sm = 0.f;
#pragma unroll
  for (int n = 0; n < 8; n++) {
    const float m = nb < 72 ? t[n] * (1.0f / 192.0f) : 0.f;
    dst[base + n * 8] = __float2half_rn(__bfloat162float(__float2bfloat16((v[n] - m) * scale)));
    const float nn = (t[8 + n] - 0.999f * m * t[n]) * scale * scale * 1.01f;
    mx = fmaxf(mx, nn); sm += nn;
  }
  if (c == 0) g_wnorm[nb] = make_float2(mx, sm);
}

__device__ __forceinline__ int window_of(int round, int nfull, int cta, int ncta, int wg) {
  if (round < nfull) return round * 2 * ncta + 2 * cta + wg;
  const int rem = NWIN - nfull * 2 * ncta;
  const int i = cta + wg * ncta;
  return i < rem ? nfull * 2 * ncta + i : -1;
}

template <int S0 = 0, int S1 = 12>
__device__ __forceinline__ void mma_qkv(uint32_t (&acc)[36], const uint32_t (&A)[48], const uint64_t* d) {
#pragma unroll
  for (int s = S0; s < S1; s++) {
    if (s == 0) wgmma_n144<0>(acc, A[4 * s], A[4 * s + 1], A[4 * s + 2], A[4 * s + 3], d[s]);
    else        wgmma_n144<1>(acc, A[4 * s], A[4 * s + 1], A[4 * s + 2], A[4 * s + 3], d[s]);
  }
  wg_commit();
}
__device__ __forceinline__ void mma_proj(uint32_t (&acc)[48], const uint32_t (&A)[12], const uint64_t* d) {
#pragma unroll
  for (int s = 0; s < 3; s++) wgmma_n192<1>(acc, A[4 * s], A[4 * s + 1], A[4 * s + 2], A[4 * s + 3], d[s]);
}
__device__ __forceinline__ void mma_s(uint32_t (&S)[14], const uint32_t (&Q)[12], const uint64_t* d) {
  wgmma_n56<0>(S, Q[0], Q[1], Q[2], Q[3], d[0]);
  wgmma_n56<1>(S, Q[4], Q[5], Q[6], Q[7], d[1]);
  wgmma_n56<1>(S, Q[8], Q[9], Q[10], Q[11], d[2]);
}
__device__ __forceinline__ void mma_pv(uint32_t (&O)[14], const uint32_t (&P)[NP], const uint64_t* d) {
  wgmma_n56t<0>(O, P[0], P[1], P[2], P[3], d[0]);
  wgmma_n56t<1>(O, P[4], P[5], P[6], P[7], d[1]);
  wgmma_n56t<1>(O, P[8], P[9], P[10], P[11], d[2]);
  if (K48TC) wgmma_n56t<1>(O, P[NP - 4], P[NP - 3], P[NP - 2], P[NP - 1], d[3]);
}

#define PIN() asm volatile("pmevent 0;" ::: "memory")
template <int A, int B> __device__ __forceinline__ void hold(uint32_t* v) {
#pragma unroll
  for (int i = A; i < B; i++) asm volatile("" : "+r"(v[i]));
}
__device__ __forceinline__ void stsm12(const uint32_t* v, uint32_t addr) {
#pragma unroll
  for (int j = 0; j < 3; j++) stsm4(addr + 2 * j * KV_PITCH, v[4 * j], v[4 * j + 1], v[4 * j + 2], v[4 * j + 3]);
}
__device__ __forceinline__ void load_v48(uint32_t (&v)[6], uint32_t addr) {
  if (K48TC) return;
  asm volatile("ldmatrix.sync.aligned.m8n8.x4.shared.b16 {%0,%1,%2,%3}, [%4];" : "=r"(v[0]), "=r"(v[1]), "=r"(v[2]), "=r"(v[3]) : "r"(addr) : "memory");
  asm volatile("ldmatrix.sync.aligned.m8n8.x2.shared.b16 {%0,%1}, [%2];" : "=r"(v[4]), "=r"(v[5]) : "r"(addr + 4 * KV_PITCH) : "memory");
}
__device__ __forceinline__ void finish_o(const uint32_t (&O)[14], const uint32_t (&v)[6], uint32_t p48, uint32_t vmask, uint32_t (&Of)[12]) {
  const float2 l = K48TC ? make_float2(__low2float(u2h(O[12])), __low2float(u2h(O[13])))
                         : __half22float2(__hadd2_rn(u2h(__byte_perm(O[12], O[13], 0x5410)), u2h(p48)));
  float i0, i1;
  asm("rcp.approx.ftz.f32 %0, %1;" : "=f"(i0) : "f"(l.x));
  asm("rcp.approx.ftz.f32 %0, %1;" : "=f"(i1) : "f"(l.y));
  const uint32_t inv = packh(i0, i1) & vmask;
#pragma unroll
  for (int i = 0; i < 12; i++) {
    const uint32_t t = K48TC ? O[i] : h2u(__hfma2(u2h(v[i >> 1]), (i & 1) ? hcast<1>(p48) : hcast<0>(p48), u2h(O[i])));
    Of[i] = (i & 1) ? fmul_b<1>(t, inv) : fmul_b<0>(t, inv);
  }
  hold<0, 12>(Of);
}
#define PSTAT 12
template <int A, int B>
__device__ __forceinline__ void ln_sums(const uint32_t (&X)[48], float (&s1)[2], float (&s2)[2]) {
  if (PSTAT) {
    static_assert(PSTAT == 0 || (A % (2 * PSTAT + !PSTAT) == 0 && B % (2 * PSTAT + !PSTAT) == 0), "whole groups");
#pragma unroll
    for (int g = A; g < B; g += 2 * PSTAT + !PSTAT)
#pragma unroll
      for (int a = 0; a < 2; a++) {
        __half2 p1 = u2h(X[g + a]), p2 = __hmul2_rn(p1, p1);
#pragma unroll
        for (int i = 1; i < PSTAT; i++) { const __half2 v = u2h(X[g + a + 2 * i]); p1 = __hadd2_rn(p1, v); p2 = __hfma2(v, v, p2); }
        const float2 f1 = __half22float2(p1), f2 = __half22float2(p2);
        s1[a] = g == 0 ? f1.x + f1.y : s1[a] + (f1.x + f1.y);
        s2[a] = g == 0 ? f2.x + f2.y : s2[a] + (f2.x + f2.y);
      }
  } else {
#pragma unroll
    for (int i = A; i < B; i++) {
      const float2 f = __half22float2(u2h(X[i]));
      s1[i & 1] = i < 2 ? f.x + f.y : s1[i & 1] + (f.x + f.y);
      s2[i & 1] = fmaf(f.x, f.x, i < 2 ? f.y * f.y : fmaf(f.y, f.y, s2[i & 1]));
    }
  }
  asm volatile("" : "+f"(s1[0]), "+f"(s1[1]), "+f"(s2[0]), "+f"(s2[1]));
}
__device__ __forceinline__ uint32_t ln_rstd(const float (&s1)[2], const float (&s2)[2], float lo, float hi, uint32_t vmask, bool& ok) {
  float r[2];
  ok = true;
#pragma unroll
  for (int a = 0; a < 2; a++) {
    float m = s1[a], v = s2[a];
    m += __shfl_xor_sync(~0u, m, 1); v += __shfl_xor_sync(~0u, v, 1);
    m += __shfl_xor_sync(~0u, m, 2); v += __shfl_xor_sync(~0u, v, 2);
    ok = ok & (v <= hi) & ((v >= lo) | !(vmask >> (16 * a) & 1));
    m *= 1.0f / 192.0f;
    m *= m;
    v = fmaxf(fmaf(v, 1.0f / 192.0f, -m), 0.f) + 1e-5f;
    ok = ok & (m <= (PSTAT ? 16.f : 64.f) * v);
    asm("rsqrt.approx.ftz.f32 %0, %1;" : "=f"(r[a]) : "f"(v));
  }
  uint32_t rk = packh(r[0], r[1]);
  hold<0, 1>(&rk);
  return rk;
}
__device__ __forceinline__ void scale12(uint32_t (&D)[12], const uint32_t* a, uint32_t r) {
#pragma unroll
  for (int i = 0; i < 12; i++) D[i] = (i & 1) ? fmul_b<1>(a[i], r) : fmul_b<0>(a[i], r);
  hold<0, 12>(D);
}
template <int CC>
__device__ __forceinline__ void store_out(const uint32_t (&Y)[48], uint8_t* o0, uint8_t* o1, uint32_t vmask) {
  uint32_t T[8];
#pragma unroll
  for (int i = 0; i < 8; i++) {
    const float2 f = __half22float2(u2h(Y[8 * CC + i]));
    T[i] = pack2(f.x, f.y);
  }
  asm volatile("{\n.reg .pred p;\nsetp.ne.u32 p, %5, 0;\n@p st.global.cs.v4.u32 [%0], {%1,%2,%3,%4};\n}\n"
               :: "l"(o0 + CC * 64), "r"(T[0]), "r"(T[2]), "r"(T[4]), "r"(T[6]), "r"(vmask) : "memory");
  asm volatile("{\n.reg .pred p;\nsetp.lt.s32 p, %5, 0;\n@p st.global.cs.v4.u32 [%0], {%1,%2,%3,%4};\n}\n"
               :: "l"(o1 + CC * 64), "r"(T[1]), "r"(T[3]), "r"(T[5]), "r"(T[7]), "r"(vmask) : "memory");
}
__device__ __forceinline__ void proxy_fence() { asm volatile("fence.proxy.async.shared::cta;" ::: "memory"); }
__device__ __forceinline__ uint32_t fadd2(uint32_t a, uint32_t b) { return h2u(__hadd2_rn(u2h(a), u2h(b))); }
__device__ __forceinline__ void row_max(const uint32_t (&S)[14], uint32_t& k48, uint32_t& mx, uint32_t ninf) {
  k48 = K48TC ? __byte_perm(S[12], S[13], 0x5410) | ninf : __shfl_sync(~0u, __byte_perm(S[12], S[13], 0x5410), 0, 4);
  const uint32_t m0 = fmax2(fmax2(fmax2(S[0], S[2]), S[4]), fmax2(fmax2(S[6], S[8]), S[10]));
  const uint32_t m1 = fmax2(fmax2(fmax2(S[1], S[3]), S[5]), fmax2(fmax2(S[7], S[9]), S[11]));
  mx = fmax2(__byte_perm(m0, m1, 0x5410), __byte_perm(m0, m1, 0x7632));
  if (K48TC) mx = fmax2(mx, k48);
  mx = fmax2(mx, __shfl_xor_sync(~0u, mx, 1));
  mx = fmax2(mx, __shfl_xor_sync(~0u, mx, 2));
  if (!K48TC) mx = fmax2(mx, k48);
  hold<0, 1>(&mx);
}
__device__ __forceinline__ void row_exp(const uint32_t (&S)[14], uint32_t k48, uint32_t mx, uint32_t (&P)[NP], uint32_t& p48) {
#pragma unroll
  for (int j = 0; j < 12; j++) P[j] = fex2((j & 1) ? fsub_b<1>(S[j], mx) : fsub_b<0>(S[j], mx));
  if (K48TC) {
    uint16_t el, eh;
    asm("{\n.reg .b16 l, h;\nmov.b32 {l, h}, %2;\nex2.approx.f16 %0, l;\nex2.approx.f16 %1, h;\n}\n" : "=h"(el), "=h"(eh) : "r"(h2u(__hsub2_rn(u2h(k48), u2h(mx)))));
    P[NP - 4] = el; P[NP - 3] = eh; P[NP - 2] = 0; P[NP - 1] = 0;
  } else {
    p48 = fex2(h2u(__hsub2_rn(u2h(k48), u2h(mx))));
    hold<0, 1>(&p48);
  }
  hold<0, NP>(P);
}
template <int S0, int S1>
__device__ __forceinline__ void load_x(uint32_t (&X)[48], uint32_t t0) {
#pragma unroll
  for (int s = S0; s < S1; s++)
    asm volatile("ld.shared.v4.u32 {%0,%1,%2,%3}, [%4];" : "=r"(X[4 * s]), "=r"(X[4 * s + 1]), "=r"(X[4 * s + 2]), "=r"(X[4 * s + 3])
                 : "r"(((s & 1) ? (t0 ^ 16) : t0) + (s >> 1) * 128) : "memory");
}

template <int CNT, int EXPECT = CNT * SLICE>
__device__ __forceinline__ void load_slices(uint32_t sb, const uint8_t* src, int slice, int slot, int bar) {
  if (EXPECT)
    asm volatile("{\n.reg .pred p;\nelect.sync _|p, 0xffffffff;\n@p mbarrier.arrive.expect_tx.shared::cta.b64 _, [%0], %1;\n}\n"
                 :: "r"(sb + bar), "n"(EXPECT) : "memory");
  asm volatile("{\n.reg .pred p;\nelect.sync _|p, 0xffffffff;\n"
               "@p cp.async.bulk.shared::cluster.global.mbarrier::complete_tx::bytes [%0], [%1], %2, [%3];\n}\n"
               :: "r"(sb + OFF_W + slot * SLICE), "l"(src + slice * SLICE), "n"(CNT * SLICE), "r"(sb + bar) : "memory");
}
__device__ __forceinline__ void warp_arrive(uint32_t bar) {
  asm volatile("{\n.reg .pred p;\nelect.sync _|p, 0xffffffff;\n@p mbarrier.arrive.shared::cta.b64 _, [%0];\n}\n" :: "r"(bar) : "memory");
}

__device__ __forceinline__ float2 fp16_limits(int lane) {
  float mx[4] = {0.f, 0.f, 0.f, 0.f}, sm[4] = {0.f, 0.f, 0.f, 0.f};
#pragma unroll
  for (int i = 0; i < 3; i++) {
    const int nb = lane + 32 * i, part = nb < 72 ? (nb % 18) / 6 : 3;
    const float2 w = g_wnorm[nb];
#pragma unroll
    for (int k = 0; k < 4; k++) if (part == k) { mx[k] = fmaxf(mx[k], w.x); sm[k] += w.y; }
  }
#pragma unroll
  for (int k = 0; k < 4; k++)
#pragma unroll
    for (int d = 16; d; d >>= 1) { mx[k] = fmaxf(mx[k], __shfl_xor_sync(~0u, mx[k], d)); sm[k] += __shfl_xor_sync(~0u, sm[k], d); }
  const float big = fmaxf(fmaxf(mx[0], mx[1]), mx[2]);
  float small = 1.f;
  bool good = sm[0] + sm[1] + sm[2] + sm[3] < 1e30f;
#pragma unroll
  for (int k = 0; k < 4; k++) { good = good && (mx[k] == 0.f || mx[k] >= 2.5e-4f); if (k < 3 && mx[k] > 0.f) small = fminf(small, mx[k]); }
  good = good && 250.f * 48.f * sqrtf(mx[0] * mx[1]) <= 5e4f;
  good = good && 16.f * 49.f * sqrtf(mx[2]) <= 5e4f && big <= 1e6f;
  good = good && 16.f * sqrtf(sm[2] * mx[3]) <= 2e4f;
  return make_float2(192.f * 2.4e-7f / small, good ? fminf(2.5e8f, 9e8f / fmaxf(big, 1e-30f)) : -1.f);
}

__device__ __forceinline__ void slow_window(float* sm, int w, int t, const __nv_bfloat16* __restrict__ x, const __nv_bfloat16* __restrict__ dw,
                                            const __nv_bfloat16* __restrict__ wqkv, const __nv_bfloat16* __restrict__ wo, __nv_bfloat16* __restrict__ out) {
  float* x0 = sm; float* h = x0 + 49 * CH; float* qkv = h + 49 * CH; float* S = qkv + 49 * 576;
  const int wy = w / NWX, wx = w % NWX;
  auto sync = [] { asm volatile("bar.sync 6, 128;" ::: "memory"); };
#pragma unroll 1
  for (int i = t; i < 49 * CH; i += 128) {
    const int k = i / CH, c = i % CH, y = wy * 7 + k / 7, xx = wx * 7 + k % 7;
    float pe = 0.f;
#pragma unroll 1
    for (int a = 0; a < 9; a++) {
      const int yy = y + a / 3 - 1, xc = xx + a % 3 - 1;
      if (yy >= 0 && yy < IMG && xc >= 0 && xc < IMG) pe = fmaf(__bfloat162float(x[((size_t)yy * IMG + xc) * CH + c]), __bfloat162float(dw[a * CH + c]), pe);
    }
    x0[i] = __bfloat162float(__float2bfloat16(__bfloat162float(x[((size_t)y * IMG + xx) * CH + c]) + pe));
  }
  sync();
  if (t < 49) {
    float m = 0.f, v = 0.f;
#pragma unroll 1
    for (int c = 0; c < CH; c++) m += x0[t * CH + c];
    m *= 1.0f / CH;
#pragma unroll 1
    for (int c = 0; c < CH; c++) { const float d = x0[t * CH + c] - m; v = fmaf(d, d, v); }
    const float rs = 1.0f / sqrtf(v * (1.0f / CH) + 1e-5f);
#pragma unroll 1
    for (int c = 0; c < CH; c++) h[t * CH + c] = (x0[t * CH + c] - m) * rs;
  }
  sync();
#pragma unroll 1
  for (int i = t; i < 7 * 576; i += 128) {
    const int n = i % 576, k0 = i / 576 * 7;
    float a[7] = {0.f, 0.f, 0.f, 0.f, 0.f, 0.f, 0.f};
#pragma unroll 1
    for (int c = 0; c < CH; c++) {
      const float wv = __bfloat162float(wqkv[c * 576 + n]);
#pragma unroll
      for (int k = 0; k < 7; k++) a[k] = fmaf(h[(k0 + k) * CH + c], wv, a[k]);
    }
#pragma unroll
    for (int k = 0; k < 7; k++) qkv[(k0 + k) * 576 + n] = a[k];
  }
  sync();
#pragma unroll 1
  for (int hd = 0; hd < 4; hd++) {
#pragma unroll 1
    for (int i = t; i < 49 * 49; i += 128) {
      const int a = i / 49, b = i % 49;
      float v = 0.f;
#pragma unroll 1
      for (int d = 0; d < 48; d++) v = fmaf(qkv[a * 576 + hd * 48 + d], qkv[b * 576 + 192 + hd * 48 + d], v);
      S[i] = v * 0.14433756729740643f;
    }
    sync();
    if (t < 49) {
      float m = S[t * 49], l = 0.f;
#pragma unroll 1
      for (int b = 1; b < 49; b++) m = fmaxf(m, S[t * 49 + b]);
#pragma unroll 1
      for (int b = 0; b < 49; b++) { const float e = expf(S[t * 49 + b] - m); S[t * 49 + b] = e; l += e; }
#pragma unroll 1
      for (int b = 0; b < 49; b++) S[t * 49 + b] /= l;
    }
    sync();
#pragma unroll 1
    for (int i = t; i < 49 * 48; i += 128) {
      const int a = i / 48, d = i % 48;
      float v = 0.f;
#pragma unroll 1
      for (int b = 0; b < 49; b++) v = fmaf(S[a * 49 + b], qkv[b * 576 + 384 + hd * 48 + d], v);
      h[a * CH + hd * 48 + d] = v;
    }
    sync();
  }
#pragma unroll 1
  for (int i = t; i < 7 * CH; i += 128) {
    const int n = i % CH, k0 = i / CH * 7;
    float a[7] = {0.f, 0.f, 0.f, 0.f, 0.f, 0.f, 0.f};
#pragma unroll 1
    for (int c = 0; c < CH; c++) {
      const float wv = __bfloat162float(wo[c * CH + n]);
#pragma unroll
      for (int k = 0; k < 7; k++) a[k] = fmaf(h[(k0 + k) * CH + c], wv, a[k]);
    }
#pragma unroll
    for (int k = 0; k < 7; k++)
      out[((size_t)(wy * 7 + k0 / 7) * IMG + wx * 7 + k) * CH + n] = __float2bfloat16(x0[(k0 + k) * CH + n] + a[k]);
  }
  sync();
}

__global__ void __launch_bounds__(384, 1)
fused_kernel(const __grid_constant__ CUtensorMap tmx, const __grid_constant__ CUtensorMap tmp, const __grid_constant__ Descs ds, const __nv_bfloat16* __restrict__ dw, __nv_bfloat16* __restrict__ out, const int never,
             const __nv_bfloat16* __restrict__ x, const __nv_bfloat16* __restrict__ wqkv, const __nv_bfloat16* __restrict__ wo) {
  extern __shared__ __align__(1024) uint8_t smem[];
  const uint32_t sb = (uint32_t)__cvta_generic_to_shared(smem);
  const int tid = threadIdx.x, lane = tid & 31;
  const int warp = __shfl_sync(0xffffffffu, tid >> 5, 0);
  const int cta = blockIdx.x, ncta = gridDim.x;
  const int nfull = NWIN / (2 * ncta);
  const int nrounds = nfull + ((NWIN - nfull * 2 * ncta) > cta ? 1 : 0);

  if (warp == 0) GTS(0);
  if (warp == 10 && lane == 0) asm volatile("prefetch.tensormap [%0];" :: "l"(reinterpret_cast<uint64_t>(&tmx)) : "memory");
  if (tid == 0) {
    mbar_init(sb + BAR_FIRST, 1);
    asm volatile("fence.mbarrier_init.release.cluster;" ::: "memory");
    asm volatile("mbarrier.arrive.expect_tx.shared::cta.b64 _, [%0], %1;" :: "r"(sb + BAR_FIRST), "n"(2 * HALO_BYTES) : "memory");
#pragma unroll
    for (int k = 0; k < 2; k++) {
      const int w = max(window_of(0, nfull, cta, ncta, k), 0), a = w / NWX;
      asm volatile("cp.async.bulk.tensor.3d.shared::cluster.global.mbarrier::complete_tx::bytes [%0], [%1, {0, %3, %4}], [%2];"
                   :: "r"(sb + OFF_HALO + k * HALO_BYTES), "l"(reinterpret_cast<uint64_t>(&tmp)), "r"(sb + BAR_FIRST),
                      "r"((w - a * NWX) * 7 - 1), "r"(a * 7 - 1) : "memory");
    }
    if ((sb & 0x3FFFF) != SMEM_BASE || nrounds > 128) __trap();
    for (int i = 0; i < 6; i++) mbar_init(sb + BAR_FH + 8 * i, 1);
    for (int i = 0; i < 4; i++) mbar_init(sb + BAR_E + 8 * i, 8);
    for (int i = 0; i < 9; i++) mbar_init(sb + BAR_XFULL + 8 * i, 1);
    mbar_init(sb + BAR_TFULL, 3);
    mbar_init(sb + BAR_TEMPTY, 8);
    asm volatile("fence.mbarrier_init.release.cluster;" ::: "memory");
  }
  if (tid >= 128 && tid < 320) {
    *reinterpret_cast<uint32_t*>(smem + OFF_ZERO + (tid - 128) * 4) = 0;
    if (tid < 136) *reinterpret_cast<uint32_t*>(smem + OFF_REDO + (tid - 128) * 4) = 0;
  }
  if (tid < 128) {
    *reinterpret_cast<uint4*>(smem + OFF_KV + (tid / 64) * KV_BYTES + 6 * KV_PITCH + (tid % 64) * 16) = make_uint4(0x3c003c00u, 0x3c003c00u, 0x3c003c00u, 0x3c003c00u);
    proxy_fence();
  }
  __syncthreads();

  if (warp < 11) {
#pragma unroll 1
    for (int u = 0; u < (warp < 10 ? 2 : 1); u++) {
      const int cb = warp < 9 ? warp % 3 : 2 * (warp - 9) + u, y = warp < 9 ? 2 * (warp / 3) + u : 6;
      const int ch0 = cb * 64 + (lane & 15) * 4;
      uint32_t wt[9][2], px[3][9][2];
#pragma unroll
      for (int t = 0; t < 9; t++) {
        const uint2 v = *reinterpret_cast<const uint2*>(dw + t * CH + ch0);
        wt[t][0] = v.x; wt[t][1] = v.y;
      }
      mbar_wait(sb + BAR_FIRST, 0);
      const uint32_t ld = sb + OFF_HALO + (lane >> 4) * HALO_BYTES + y * 3456 + ch0 * 2;
#pragma unroll
      for (int p = 0; p < 27; p++)
        asm volatile("ld.shared.v2.u32 {%0,%1}, [%2];" : "=r"(px[p / 9][p % 9][0]), "=r"(px[p / 9][p % 9][1]) : "r"(ld + p * 384));
      const uint32_t st0 = sb + OFF_TILE + (lane >> 4) * TILE_BYTES + ch0 * 4;
      const uint32_t sa = (st0 ^ ((y & 1) << 4)) + y * 2304;
      uint32_t o[2][2];
#pragma unroll
      for (int j = 0; j < 7; j++) {
#pragma unroll
        for (int e = 0; e < 2; e++) {
          uint32_t a = hmul(px[0][j][e], wt[0][e]);
#pragma unroll
          for (int t = 1; t < 9; t++) a = hfma(px[t / 3][j + t % 3][e], wt[t][e], a);
          a = hadd(px[1][j + 1][e], a);
          o[j & 1][e] = packh(lo2f(a), hi2f(a));
        }
        if (j & 1)
          asm volatile("st.shared.v4.u32 [%0], {%1,%2,%3,%4};" :: "r"((j == 3 ? sa ^ 16 : sa) + (j >> 1) * 768),
                       "r"(o[0][0]), "r"(o[1][0]), "r"(o[0][1]), "r"(o[1][1]) : "memory");
      }
      const uint32_t sb6 = (st0 ^ ((~y & 2) << 3)) + (21 + (y >> 1)) * 768 + (y & 1) * 4;
      asm volatile("st.shared.u32 [%0], %1;\nst.shared.u32 [%0 + 8], %2;" :: "r"(sb6), "r"(o[0][0]), "r"(o[0][1]) : "memory");
      if (y == 6) asm volatile("st.shared.u32 [%0 + 4], %1;\nst.shared.u32 [%0 + 12], %1;" :: "r"(sb6), "r"(0) : "memory");
    }
    asm volatile("bar.arrive 8, 384;\nbar.sync 7, 352;" ::: "memory");
  }

  if (warp >= 8) {
    asm volatile("setmaxnreg.dec.sync.aligned.u32 " PREGS ";");
    if (warp == 11) {
      asm volatile("griddepcontrol.wait;" ::: "memory");
      GTS(2);
      load_slices<3, 0>(sb, ds.src, 0, 0, BAR_F0);
      *reinterpret_cast<float2*>(smem + OFF_LIM) = fp16_limits(lane);
      asm volatile("{\n.reg .pred p;\nelect.sync _|p, 0xffffffff;\n@p mbarrier.arrive.expect_tx.shared::cta.b64 _, [%0], %1;\n}\n"
                   :: "r"(sb + BAR_F0), "n"(3 * SLICE) : "memory");
      asm volatile("bar.sync 8, 384;" ::: "memory");
      load_slices<3, 5 * SLICE>(sb, ds.src, 3, 3, BAR_F1);
      load_slices<1, 0>(sb, ds.src, 13, SLOT_U, BAR_F1);
      load_slices<1, 0>(sb, ds.src, 12, SLOT_V, BAR_F1);
      for (int r = 0; r < nrounds; r++) {
        const int par = r & 1;
        const int h2 = par ? 1 : 2, h3 = par ? 0 : 3;
        mbar_wait(sb + BAR_E, par);
        load_slices<3>(sb, ds.src, 3 * h2, 3 * (h2 & 1), BAR_FH);
        mbar_wait(sb + BAR_E + 8, par);
        load_slices<3>(sb, ds.src, 3 * h3, 3 * (h3 & 1), BAR_FH + 8);
        mbar_wait(sb + BAR_E + 16, par);
        load_slices<1>(sb, ds.src, 12 + h2, SLOT_U, BAR_FU);
        mbar_wait(sb + BAR_E + 24, par);
        load_slices<1>(sb, ds.src, 12 + h3, SLOT_V, BAR_FV);
      }
    } else {
      const int cw = warp - 8;
      const int win = lane >> 4;
      const int ch0 = cw * 64 + (lane & 15) * 4;
      uint32_t wt[9][2];
#pragma unroll
      for (int t = 0; t < 9; t++) {
        uint2 v = *reinterpret_cast<const uint2*>(dw + t * CH + ch0);
        wt[t][0] = v.x; wt[t][1] = v.y;
      }
      const uint32_t xs = sb + OFF_X + cw * 3 * XSLOT;
      const uint32_t xld = xs + (lane >> 4) * 1152 + (lane & 15) * 8;
      const uint32_t xbar = sb + BAR_XFULL + cw * 24;
      const uint32_t st0 = sb + OFF_TILE + win * TILE_BYTES + ch0 * 4;
      const uint64_t tm = reinterpret_cast<uint64_t>(&tmx);
      int cx0, cy0, cx1, cy1;
      auto coords = [&](int r) {
        const int w0 = window_of(r, nfull, cta, ncta, 0);
        int w1 = window_of(r, nfull, cta, ncta, 1);
        if (w1 < 0) w1 = w0;
        const int a = w0 / NWX, b = w1 / NWX;
        cx0 = (w0 - a * NWX) * 7 - 1; cy0 = a * 7 - 1;
        cx1 = (w1 - b * NWX) * 7 - 1; cy1 = b * 7 - 1;
      };
      auto issue = [&](int slot, int dy) {
        asm volatile("{\n.reg .pred p;\nelect.sync _|p, 0xffffffff;\n"
                     "@p mbarrier.arrive.expect_tx.shared::cta.b64 _, [%2], %8;\n"
                     "@p cp.async.bulk.tensor.3d.shared::cluster.global.mbarrier::complete_tx::bytes [%0], [%1, {%3, %4, %5}], [%2];\n"
                     "@p cp.async.bulk.tensor.3d.shared::cluster.global.mbarrier::complete_tx::bytes [%0 + 1152], [%1, {%3, %6, %7}], [%2];\n}\n"
                     :: "r"(xs + slot * XSLOT), "l"(tm), "r"(xbar + slot * 8), "r"(cw * 64), "r"(cx0), "r"(cy0 + dy), "r"(cx1), "r"(cy1 + dy), "n"(XSLOT) : "memory");
      };
      uint32_t accA[7][2], accB[7][2], ctr[7][2], held[2];
      auto row = [&](auto fin, auto mid, auto top, int slot, int y) {
        const uint32_t ld = xld + slot * XSLOT;
        const uint32_t sa = (st0 ^ ((y & 1) << 4)) + y * 2304;
        uint32_t cur[9][2], o[2][2];
#pragma unroll
        for (int p = 0; p < LA; p++)
          asm volatile("ld.shared.v2.u32 {%0,%1}, [%2];" : "=r"(cur[p][0]), "=r"(cur[p][1]) : "r"(ld + p * 128));
#pragma unroll
        for (int j = 0; j < 7; j++) {
          if (j >= 1 && j + LA - 1 < 9)
            asm volatile("ld.shared.v2.u32 {%0,%1}, [%2];" : "=r"(cur[j + LA - 1][0]), "=r"(cur[j + LA - 1][1]) : "r"(ld + (j + LA - 1) * 128));
          if (fin.v) {
#pragma unroll
            for (int e = 0; e < 2; e++) {
              uint32_t a = hfma(cur[j][e], wt[6][e], accA[j][e]);
              a = hfma(cur[j + 1][e], wt[7][e], a);
              a = hfma(cur[j + 2][e], wt[8][e], a);
              a = hadd(ctr[j][e], a);
              o[j & 1][e] = packh(lo2f(a), hi2f(a));
            }
            if (j & 1)
              asm volatile("st.shared.v4.u32 [%0], {%1,%2,%3,%4};" :: "r"((j == 3 ? sa ^ 16 : sa) + (j >> 1) * 768),
                           "r"(o[0][0]), "r"(o[1][0]), "r"(o[0][1]), "r"(o[1][1]) : "memory");
            if (j == 6) {
              const uint32_t sb6 = (st0 ^ ((~y & 2) << 3)) + (21 + (y >> 1)) * 768;
              if (fin.v == 2)
                asm volatile("st.shared.v4.u32 [%0], {%1,%2,%3,%2};" :: "r"(sb6), "r"(o[0][0]), "r"(0), "r"(o[0][1]) : "memory");
              else
                asm volatile("{\n.reg .pred p;\nsetp.ne.s32 p, %5, 0;\n@p st.shared.v4.u32 [%0], {%1,%2,%3,%4};\n}\n"
                             :: "r"(sb6), "r"(held[0]), "r"(o[0][0]), "r"(held[1]), "r"(o[0][1]), "r"(y & 1) : "memory");
              held[0] = o[0][0]; held[1] = o[0][1];
            }
          }
#pragma unroll
          for (int e = 0; e < 2; e++) {
            if (mid.v) {
              uint32_t a = hfma(cur[j][e], wt[3][e], accB[j][e]);
              a = hfma(cur[j + 1][e], wt[4][e], a);
              accA[j][e] = hfma(cur[j + 2][e], wt[5][e], a);
              ctr[j][e] = cur[j + 1][e];
            }
            if (top.v) {
              uint32_t a = hmul(cur[j][e], wt[0][e]);
              a = hfma(cur[j + 1][e], wt[1][e], a);
              accB[j][e] = hfma(cur[j + 2][e], wt[2][e], a);
            }
          }
        }
      };
      held[0] = held[1] = 0;
      if (nrounds > 1) { coords(1); issue(0, 0); issue(1, 1); issue(2, 2); }
      for (int r = 0; r + 1 < nrounds; r++) {
        const bool more = r + 2 < nrounds;
        mbar_wait(xbar, r & 1);
        if (r > 0) issue(2, 2);
        row(IC<0>{}, IC<0>{}, IC<1>{}, 0, 0);
        mbar_wait(xbar + 8, r & 1);
        issue(0, 3);
        row(IC<0>{}, IC<1>{}, IC<1>{}, 1, 0);
        mbar_wait(sb + BAR_TEMPTY, r & 1);
#pragma unroll 1
        for (int k = 0; k < 2; k++) {
          mbar_wait(xbar + 16, (r + k) & 1);
          issue(1, 4 + 3 * k);
          row(IC<1>{}, IC<1>{}, IC<1>{}, 2, 3 * k);
          mbar_wait(xbar, (r + k + 1) & 1);
          issue(2, 5 + 3 * k);
          row(IC<1>{}, IC<1>{}, IC<1>{}, 0, 3 * k + 1);
          mbar_wait(xbar + 8, (r + k + 1) & 1);
          if (k == 1 && more) coords(r + 2);
          if (k == 0 || more) issue(0, k == 0 ? 6 : 0);
          row(IC<1>{}, IC<1>{}, IC<1>{}, 1, 3 * k + 2);
        }
        mbar_wait(xbar + 16, r & 1);
        if (more) issue(1, 1);
        row(IC<2>{}, IC<0>{}, IC<0>{}, 2, 6);
        __syncwarp();
        warp_arrive(sb + BAR_TFULL);
      }
    }
    asm volatile("bar.sync 5, 384;" ::: "memory");
#pragma unroll 1
    for (int i = 0; i < 8; i++) {
      uint32_t bits = *reinterpret_cast<volatile uint32_t*>(smem + OFF_REDO + 4 * i);
#pragma unroll 1
      for (; bits; bits &= bits - 1)
        slow_window(reinterpret_cast<float*>(smem), window_of((i & 3) * 32 + __ffs(bits) - 1, nfull, cta, ncta, i >> 2), tid - 256, x, dw, wqkv, wo, out);
    }
  } else {
    asm volatile("setmaxnreg.inc.sync.aligned.u32 " CREGS ";");
    const int wg = warp >> 2, w4 = warp & 3, g = lane >> 2, q = lane & 3;
    const int row0 = w4 * 16 + g, row1 = row0 + 8;
    const int ps = min(w4 * 8 + g, 24);
    const int pix0 = ps < 21 ? (ps / 3) * IMG + (ps % 3) * 2 : (ps - 21) * 2 * IMG + 6;
    const int pix1 = pix0 + (ps < 21 ? 1 : ps < 24 ? IMG : 0);
    const uint32_t kv = sb + OFF_KV + wg * KV_BYTES;
    const int srow = w4 * 16 + (lane & 15);
    const uint32_t vst = kv + (lane >> 4) * KV_PITCH + (srow < 56 ? srow : min(srow - 7, 55)) * 16;
    uint32_t misc = ((uint32_t)pix1 << 20) | ((uint32_t)pix0 << 8) | q;
    const uint32_t ninf = q ? 0xfc00fc00u : 0u;
    const uint32_t v48 = kv + (lane >> 3) * KV_PITCH + 48 * 16;
    const uint32_t vmask = (row0 < 49 ? 0xffffu : 0u) | (row1 < 49 ? 0xffff0000u : 0u);

    const uint32_t tx = sb + q * 32 + (row0 < 49 ? OFF_TILE + wg * TILE_BYTES + ps * 768 + (ps & 1) * 16 : OFF_ZERO + 16);
    const int myrounds = window_of(nrounds - 1, nfull, cta, ncta, wg) < 0 ? nrounds - 1 : nrounds;

    if (never == 2) return;
    uint32_t H[48], Y[48];
    const uint64_t* dkv = ds.kv[wg];
    uint32_t P[NP], Ofc[12], p48 = 0;
#pragma unroll
    for (int i = 0; i < 48; i++) Y[i] = 0;
#pragma unroll
    for (int i = 0; i < NP; i++) P[i] = Ofc[i % 12] = 0;
    if (warp == 0) GTS(4);
    load_x<0, 12>(H, tx);
    warp_arrive(sb + BAR_TEMPTY);
    mbar_wait(sb + BAR_F0, 0);
    if (warp == 0) GTS(1);
    if (wg == 1) turn_pass(1);

    uint8_t *o0, *o1;
    uint32_t omask;
    auto out_setup = [&](int r) {
      omask = r >= 0 ? vmask : 0u;
      const int w = window_of(r, nfull, cta, ncta, wg);
      const int wy = w / NWX, wx = w - wy * NWX;
      asm volatile("" : "+r"(misc));
      const uint32_t wb = (uint32_t)(wy * 7 * IMG + wx * 7) * 384u + (misc & 3) * 16;
      o0 = reinterpret_cast<uint8_t*>(out) + (wb + ((misc >> 8) & 0xfff) * 384u);
      o1 = reinterpret_cast<uint8_t*>(out) + (wb + (misc >> 20) * 384u);
    };
#define OUT(c) store_out<c>(Y, o0, o1, omask)
    auto release = [&](int i) { warp_arrive(sb + BAR_E + 8 * i); };

    for (int r = 0;; r++) {
      const uint32_t par = r & 1;
      uint32_t acc[36], S[14], O[14], Q[12], V[12], Ofa[12], Ofb[12], vr[6], k48, mx;
      if (r == myrounds) {
        const bool idle = r < nrounds;
        if (idle) { release(0); release(1); }
        mbar_wait(sb + BAR_FU, par ^ 1);
        turn_wait(wg);
        wg_fence(); mma_pv(O, P, dkv + 4); mma_proj(Y, Ofc, ds.pu[0]); wg_commit();
        turn_pass(wg);
        load_v48(vr, v48);
        wg_wait<0>(); keep(O); keep(Y);
        finish_o(O, vr, p48, vmask, Ofa);
        mbar_wait(sb + BAR_FV, par ^ 1);
        turn_wait(wg);
        wg_fence(); mma_proj(Y, Ofa, ds.pv[0]); wg_commit();
        if (wg == 0 || idle) turn_pass(wg);
        wg_wait<0>(); keep(Y);
        if (idle) { release(2); release(3); turn_wait(wg); turn_pass(wg); }
        out_setup(r - 1);
        OUT(0); PIN(); OUT(1); PIN(); OUT(2); PIN(); OUT(3); PIN(); OUT(4); PIN(); OUT(5);
        if (idle) {
          turn_wait(wg); turn_pass(wg);
          turn_wait(wg); turn_pass(wg);
          turn_wait(wg); turn_pass(wg);
          turn_wait(wg);
        }
        if (w4 == 0) GTS(5 + wg);
        asm volatile("bar.arrive 5, 384;" ::: "memory");
        break;
      }
      const uint64_t* dq0 = ds.q[par];
      float s1[2], s2[2];
      TR(0);
      turn_wait(wg);
      TR(1);
      wg_fence(); mma_pv(O, P, dkv + 4); wg_commit(); mma_qkv<0, K0A>(acc, H, dq0);
      PIN();
      ln_sums<0, 24>(H, s1, s2);
      PIN();
      wg_fence(); mma_qkv<K0A, 12>(acc, H, dq0);
      if (r > 0) { mbar_wait(sb + BAR_FU, par ^ 1); wg_fence(); mma_proj(Y, Ofc, ds.pu[0]); wg_commit(); }
      else { wg_fence(); wg_commit(); }
      turn_pass(wg);
      TR(2);
      load_v48(vr, v48);
      wg_wait<3>(); keep(O);
      wg_sync(wg);
      PIN();
      finish_o(O, vr, p48, vmask, Ofa);
      ln_sums<24, 48>(H, s1, s2);
      float lim_lo, lim_hi;
      asm volatile("ld.shared.v2.f32 {%0,%1}, [%2];" : "=f"(lim_lo), "=f"(lim_hi) : "r"(sb + OFF_LIM) : "memory");
      bool ok;
      const uint32_t rk = ln_rstd(s1, s2, lim_lo, lim_hi, vmask, ok);
      asm volatile("{\n.reg .pred p;\nsetp.eq.s32 p, %2, 0;\n@p red.shared.or.b32 [%0], %1;\n}\n"
                   :: "r"(sb + OFF_REDO + wg * 16 + (r >> 5) * 4), "r"(1u << (r & 31)), "r"((int)ok) : "memory");
      PIN();
      TR(3);
      wg_wait<1>(); keep(acc);
      TR(4);
      release(0);
      scale12(V, acc, rk); stsm12(V, vst + KV_KOFF);
      scale12(V, acc + 24, rk); stsm12(V, vst);
      PIN();
      wg_wait<0>(); keep(Y);
      PIN();
      proxy_fence();
      scale12(Q, acc + 12, rk);
      if (r > 0) mbar_wait(sb + BAR_FV, par ^ 1); else mbar_wait(sb + BAR_F1, 0);
      TR(5);
      turn_wait(wg);
      TR(6);
      if (r > 0) { wg_fence(); mma_proj(Y, Ofa, ds.pv[0]); wg_commit(); }
      wg_fence(); mma_s(S, Q, dkv); mma_qkv<0, 2>(acc, H, dq0 + 12);
      out_setup(r - 1);
      PIN();
      wg_wait<1>(); keep(Y);
      wg_fence(); mma_qkv<2, 6>(acc, H, dq0 + 12);
      PIN();
      OUT(0);
      PIN();
      wg_wait<1>(); keep(S);
      wg_fence(); mma_qkv<6, 9>(acc, H, dq0 + 12);
      PIN();
      row_max(S, k48, mx, ninf);
      OUT(1);
      PIN();
      wg_fence(); mma_qkv<9, 12>(acc, H, dq0 + 12);
      turn_pass(wg);
      PIN();
      OUT(2); PIN();
      OUT(3); PIN();
      row_exp(S, k48, mx, P, p48);
      PIN();
      TR(7);
      wg_wait<0>(); keep(acc);
      TR(8);
      release(1);
      wg_sync(wg);
      scale12(V, acc, rk); stsm12(V, vst + KV_KOFF);
      scale12(Q, acc + 12, rk); scale12(V, acc + 24, rk); PIN();
      proxy_fence();
#define TURN(ID, OF, DQ, FB, X1)                                                        \
      mbar_wait(sb + FB, par);                                                          \
      TR(ID + 1);                                                                       \
      turn_wait(wg);                                                                    \
      wg_fence(); mma_pv(O, P, dkv + 4); mma_s(S, Q, dkv); wg_commit(); mma_qkv<0, KA>(acc, H, DQ); \
      PIN();                                                                            \
      TR(ID + 2);                                                                       \
      load_v48(vr, v48);                                                                \
      X1;                                                                               \
      PIN();                                                                            \
      wg_wait<1>(); keep(S); keep(O);                                                   \
      wg_sync(wg);                                         \
      wg_fence(); mma_qkv<KA, KB>(acc, H, DQ);                                            \
      PIN();                                                                            \
      stsm12(V, vst);                                                                   \
      finish_o(O, vr, p48, vmask, OF);                                                  \
      row_max(S, k48, mx, ninf);                                                        \
      PIN();                                                                            \
      wg_fence(); mma_qkv<KB, 12>(acc, H, DQ);                                           \
      turn_pass(wg);                                                                    \
      PIN();                                                                            \
      TR(ID + 3);
#define NEXT_HEAD(ID)                                                                   \
      row_exp(S, k48, mx, P, p48);                                                      \
      PIN();                                                                            \
      TR(ID + 4);                                                                       \
      wg_wait<0>(); keep(acc);                                                          \
      scale12(V, acc, rk); stsm12(V, vst + KV_KOFF);                                    \
      scale12(Q, acc + 12, rk); scale12(V, acc + 24, rk); PIN();
      TURN(8, Ofa, dq0 + 24, BAR_FH, OUT(4))
      OUT(5); PIN();
      NEXT_HEAD(8)
      proxy_fence();
      TURN(12, Ofb, dq0 + 36, BAR_FH + 8, )
      auto init_y = [&]() {
#pragma unroll
        for (int i = 0; i < 48; i++) Y[i] = (i & 1) ? H[i] ^ never : h2u(__hadd2_rn(u2h(H[i]), u2h(never)));
        hold<0, 48>(Y); PIN();
      };
      NEXT_HEAD(12)
      init_y();
      proxy_fence();
      TR(17);
      turn_wait(wg);
      wg_fence(); mma_pv(O, P, dkv + 4); mma_s(S, Q, dkv); wg_commit();
      mma_proj(Y, Ofb, ds.pu[1]); wg_commit(); mma_proj(Y, Ofa, ds.pv[1]); wg_commit();
      turn_pass(wg);
      PIN();
      TR(18);
      load_v48(vr, v48);
      if (r + 1 < myrounds) mbar_wait(sb + BAR_TFULL, par);
      load_x<0, 4>(H, tx);
      wg_wait<2>(); keep(S); keep(O);
      wg_sync(wg);
      PIN();
      TR(19);
      row_max(S, k48, mx, ninf);
      finish_o(O, vr, p48, vmask, Ofc);
      stsm12(V, vst);
      PIN();
      wg_wait<1>();
      release(2);
      load_x<4, 8>(H, tx);
      row_exp(S, k48, mx, P, p48);
      PIN();
      load_x<8, 12>(H, tx);
      warp_arrive(sb + BAR_TEMPTY);
      TR(20);
      wg_wait<0>(); keep(Y);
      release(3);
      proxy_fence();
      TR(21);
#undef TURN
#undef NEXT_HEAD
    }
  }
}

typedef CUresult (*EncodeFn)(CUtensorMap*, CUtensorMapDataType, cuuint32_t, void*, const cuuint64_t*, const cuuint64_t*,
                             const cuuint32_t*, const cuuint32_t*, CUtensorMapInterleave, CUtensorMapSwizzle,
                             CUtensorMapL2promotion, CUtensorMapFloatOOBfill);

}

extern "C" void kernel_launch(void* const* d_in, const int* in_sizes, int n_in, void* d_out, int out_size) {
  const __nv_bfloat16* x = (const __nv_bfloat16*)d_in[0];
  const __nv_bfloat16* dw = (const __nv_bfloat16*)d_in[1];
  const __nv_bfloat16* wqkv = (const __nv_bfloat16*)d_in[2];
  const __nv_bfloat16* wo = (const __nv_bfloat16*)d_in[3];
  static EncodeFn encode = nullptr;
  static int nsm = 0;
  static void* wpack = nullptr;
  if (!encode) {
    void* fn = nullptr;
    cudaDriverEntryPointQueryResult qr;
    cudaGetDriverEntryPoint("cuTensorMapEncodeTiled", &fn, cudaEnableDefault, &qr);
    encode = (EncodeFn)fn;
    int dev = 0;
    cudaGetDevice(&dev);
    cudaDeviceGetAttribute(&nsm, cudaDevAttrMultiProcessorCount, dev);
    cudaGetSymbolAddress(&wpack, g_wpack);
    cudaFuncSetAttribute(fused_kernel, cudaFuncAttributeMaxDynamicSharedMemorySize, SMEM_BYTES);
  }
  CUtensorMap tmx;
  cuuint64_t gdim[3] = {CH, IMG, IMG};
  cuuint64_t gstr[2] = {CH * 2, (cuuint64_t)CH * 2 * IMG};
  cuuint32_t box[3] = {64, 9, 1};
  cuuint32_t estr[3] = {1, 1, 1};
  encode(&tmx, CU_TENSOR_MAP_DATA_TYPE_BFLOAT16, 3, (void*)x, gdim, gstr, box, estr, CU_TENSOR_MAP_INTERLEAVE_NONE,
         CU_TENSOR_MAP_SWIZZLE_NONE, CU_TENSOR_MAP_L2_PROMOTION_L2_128B, CU_TENSOR_MAP_FLOAT_OOB_FILL_NONE);
  Descs ds;
  for (int i = 0; i < 12; i++)
    for (int b = 0; b < 5; b++) ds.q[b][i] = mkdesc(SMEM_BASE + OFF_W + qkv_pos(b & 1, i), 128, 256);
  for (int i = 0; i < 3; i++) {
    ds.pu[0][i] = ds.pu[1][i] = mkdesc(SMEM_BASE + OFF_W + SLOT_U * SLICE + i * 6144, 128, 256);
    ds.pv[0][i] = ds.pv[1][i] = mkdesc(SMEM_BASE + OFF_W + SLOT_V * SLICE + i * 6144, 128, 256);
  }
  ds.src = (const uint8_t*)wpack;
  for (int g = 0; g < 2; g++)
    for (int i = 0; i < 4; i++) {
      ds.kv[g][i] = mkdesc(SMEM_BASE + OFF_KV + g * KV_BYTES + KV_KOFF + 2 * i * KV_PITCH, KV_PITCH, 128);
      ds.kv[g][4 + i] = mkdesc(SMEM_BASE + OFF_KV + g * KV_BYTES + 256 * i, 128, KV_PITCH);
    }
  CUtensorMap tmp;
  cuuint32_t boxp[3] = {CH, 9, 9};
  encode(&tmp, CU_TENSOR_MAP_DATA_TYPE_BFLOAT16, 3, (void*)x, gdim, gstr, boxp, estr, CU_TENSOR_MAP_INTERLEAVE_NONE,
         CU_TENSOR_MAP_SWIZZLE_NONE, CU_TENSOR_MAP_L2_PROMOTION_L2_128B, CU_TENSOR_MAP_FLOAT_OOB_FILL_NONE);
  prepack_kernel<<<48, dim3(192, 2), 0, cudaStreamPerThread>>>(wqkv, wo, x, min(IMG, (2 * nsm + NWX - 1) / NWX * 7 + 1));
  cudaLaunchConfig_t cfg = {};
  cfg.gridDim = dim3(nsm); cfg.blockDim = dim3(384); cfg.dynamicSmemBytes = SMEM_BYTES; cfg.stream = cudaStreamPerThread;
  cudaLaunchAttribute at[1];
  at[0].id = cudaLaunchAttributeProgrammaticStreamSerialization;
  at[0].val.programmaticStreamSerializationAllowed = 1;
  cfg.attrs = at; cfg.numAttrs = 1;
  cudaLaunchKernelEx(&cfg, fused_kernel, tmx, tmp, ds, dw, (__nv_bfloat16*)d_out, 0, x, wqkv, wo);
}
```

```cpp
#include <cuda_runtime.h>
#include <cuda_bf16.h>
#include <cuda_fp16.h>
#include <cuda.h>
#include <stdint.h>

#define CREGS "208"
#define PREGS "88"
#define K48TC 0
#define LA 4
#define K0A 6
#define KA 3
#define KB 9
#define L2PROMO CU_TENSOR_MAP_L2_PROMOTION_NONE
namespace {
constexpr int PBY = 2;
constexpr int NP = K48TC ? 16 : 12;

constexpr int IMG = 511;
constexpr int CH = 192;
constexpr int NWX = 73;
constexpr int NWIN = NWX * NWX;
constexpr int SLICE = 18432;
constexpr int OFF_W = 0;
constexpr int KV_PITCH = 1792, KV_KOFF = 896, KV_BYTES = 6 * KV_PITCH + 1024;
constexpr int OFF_KV = 8 * SLICE;
constexpr int TILE_BYTES = 25 * 768;
constexpr int OFF_TILE = OFF_KV + 2 * KV_BYTES;
constexpr int XSLOT = 2304;
constexpr int OFF_ZERO = OFF_TILE + 2 * TILE_BYTES;
constexpr int OFF_X = OFF_ZERO + 768;
constexpr int OFF_BAR = OFF_X + 9 * XSLOT;
constexpr int BAR_FH = OFF_BAR;
constexpr int BAR_FU = OFF_BAR + 16, BAR_FV = OFF_BAR + 24;
constexpr int BAR_F0 = OFF_BAR + 32, BAR_F1 = OFF_BAR + 40;
constexpr int BAR_E = OFF_BAR + 80;
constexpr int BAR_XFULL = OFF_BAR + 112;
constexpr int BAR_TFULL = OFF_BAR + 184;
constexpr int BAR_TEMPTY = OFF_BAR + 192;
constexpr int OFF_LIM = OFF_BAR + 200;
constexpr int OFF_REDO = OFF_BAR + 208;
constexpr int BAR_FIRST = OFF_BAR + 240;
constexpr int OFF_TRACE = OFF_BAR + 248;
constexpr int OFF_HALO = OFF_W + 3 * SLICE, HALO_BYTES = 81 * 384;
constexpr int SMEM_BYTES = OFF_TRACE;

__host__ __device__ constexpr int qkv_pos(int h, int s) { return 3 * h * SLICE + s * 4608; }
__host__ __device__ constexpr int wo_pos(int s) { return 12 * SLICE + s * 6144; }
constexpr int SLOT_U = 6, SLOT_V = 7;
constexpr int SMEM_BASE = 1024;
struct Descs { uint64_t q[5][12]; uint64_t pu[2][3], pv[2][3]; uint64_t kv[2][8]; const uint8_t* src; };

__device__ uint4 g_wpack[16 * SLICE / 16];
__device__ float2 g_wnorm[96];
#define TR(id)
#define GTS(i)
template <int V> struct IC { static constexpr int v = V; };
typedef __nv_bfloat162 bf2;
__device__ __forceinline__ bf2 u2b(uint32_t u) { return *reinterpret_cast<bf2*>(&u); }
__device__ __forceinline__ uint32_t b2u(bf2 b) { return *reinterpret_cast<uint32_t*>(&b); }
__device__ __forceinline__ uint32_t pack2(float lo, float hi) {
  uint32_t r; asm("cvt.rn.bf16x2.f32 %0, %1, %2;" : "=r"(r) : "f"(hi), "f"(lo)); return r;
}
__device__ __forceinline__ uint32_t hadd(uint32_t a, uint32_t b) { return b2u(__hadd2_rn(u2b(a), u2b(b))); }
__device__ __forceinline__ uint32_t hmul(uint32_t a, uint32_t b) { return b2u(__hmul2_rn(u2b(a), u2b(b))); }
__device__ __forceinline__ uint32_t hfma(uint32_t a, uint32_t b, uint32_t c) { return b2u(__hfma2(u2b(a), u2b(b), u2b(c))); }
__device__ __forceinline__ __half2 u2h(uint32_t u) { return *reinterpret_cast<__half2*>(&u); }
__device__ __forceinline__ uint32_t h2u(__half2 b) { return *reinterpret_cast<uint32_t*>(&b); }
__device__ __forceinline__ uint32_t packh(float lo, float hi) {
  uint32_t r; asm("cvt.rn.f16x2.f32 %0, %1, %2;" : "=r"(r) : "f"(hi), "f"(lo)); return r;
}
__device__ __forceinline__ uint32_t fmax2(uint32_t a, uint32_t b) { return h2u(__hmax2(u2h(a), u2h(b))); }
template <int HI> __device__ __forceinline__ __half2 hcast(uint32_t a) { return HI ? __high2half2(u2h(a)) : __low2half2(u2h(a)); }
template <int HI> __device__ __forceinline__ uint32_t fmul_b(uint32_t a, uint32_t s) { return h2u(__hmul2_rn(u2h(a), hcast<HI>(s))); }
template <int HI> __device__ __forceinline__ uint32_t fsub_b(uint32_t a, uint32_t s) { return h2u(__hsub2_rn(u2h(a), hcast<HI>(s))); }
__device__ __forceinline__ uint32_t fex2(uint32_t a) { uint32_t r; asm("ex2.approx.f16x2 %0, %1;" : "=r"(r) : "r"(a)); return r; }
__device__ __forceinline__ float lo2f(uint32_t a) { return __uint_as_float(a << 16); }
__device__ __forceinline__ float hi2f(uint32_t a) { return __uint_as_float(a & 0xffff0000u); }

__device__ __forceinline__ void mbar_init(uint32_t bar, uint32_t cnt) { asm volatile("mbarrier.init.shared::cta.b64 [%0], %1;" :: "r"(bar), "r"(cnt) : "memory"); }
__device__ __forceinline__ void mbar_wait(uint32_t bar, uint32_t parity) {
  asm volatile("{\n.reg .pred p;\n.reg .u32 n;\n"
               "mbarrier.try_wait.parity.shared::cta.b64 p, [%0], %1;\n"
               "@p bra.uni DONE_%=;\n"
               "mov.u32 n, 0;\n"
               "AGAIN_%=:\n"
               "mbarrier.try_wait.parity.shared::cta.b64 p, [%0], %1;\n"
               "@p bra.uni DONE_%=;\n"
               "add.u32 n, n, 1;\n"
               "setp.lt.u32 p, n, 0x1000000;\n"
               "@p bra.uni AGAIN_%=;\n"
               "trap;\n"
               "DONE_%=:\n}\n" :: "r"(bar), "r"(parity) : "memory");
}
__device__ __forceinline__ void wg_fence() { asm volatile("wgmma.fence.sync.aligned;" ::: "memory"); }
__device__ __forceinline__ void wg_commit() { asm volatile("wgmma.commit_group.sync.aligned;" ::: "memory"); }
template <int N> __device__ __forceinline__ void wg_wait() { asm volatile("wgmma.wait_group.sync.aligned %0;" :: "n"(N) : "memory"); }
#define BAR_BY_WG(OP, ID0, ID1, CNT) asm volatile("{\n.reg .pred p;\nsetp.eq.s32 p, %0, 0;\n@p " OP " " #ID0 ", " #CNT ";\n@!p " OP " " #ID1 ", " #CNT ";\n}\n" :: "r"(wg) : "memory")
__device__ __forceinline__ void wg_sync(int wg) { BAR_BY_WG("bar.sync", 1, 2, 128); }
__device__ __forceinline__ void turn_wait(int wg) { BAR_BY_WG("bar.sync", 3, 4, 256); }
__device__ __forceinline__ void turn_pass(int wg) { BAR_BY_WG("bar.arrive", 4, 3, 256); }
__device__ __forceinline__ void stsm4(uint32_t addr, uint32_t a, uint32_t b, uint32_t c, uint32_t d) {
  asm volatile("stmatrix.sync.aligned.m8n8.x4.shared.b16 [%0], {%1,%2,%3,%4};" :: "r"(addr), "r"(a), "r"(b), "r"(c), "r"(d) : "memory");
}
template <int N> __device__ __forceinline__ void keep(float (&d)[N]) {
#pragma unroll
  for (int i = 0; i < N; i++) asm volatile("" : "+f"(d[i]) :: "memory");
}
template <int N> __device__ __forceinline__ void keep(uint32_t (&d)[N]) {
#pragma unroll
  for (int i = 0; i < N; i++) asm volatile("" : "+r"(d[i]) :: "memory");
}
__host__ __device__ __forceinline__ uint64_t mkdesc(uint32_t addr, uint32_t lbo, uint32_t sbo) {
  return ((uint64_t)(sbo >> 4) << 32) | (uint64_t)(((lbo >> 4) << 16) | ((addr & 0x3FFFF) >> 4));
}

template <int SCALE_D>
__device__ __forceinline__ void wgmma_n144(uint32_t (&d)[36], uint32_t a0, uint32_t a1, uint32_t a2, uint32_t a3, uint64_t descB) {
  if (SCALE_D == 0)
  asm volatile("wgmma.mma_async.sync.aligned.m64n144k16.f16.f16.f16 "
    "{%0, %1, %2, %3, %4, %5, %6, %7, %8, %9, %10, %11, %12, %13, %14, %15, "
    "%16, %17, %18, %19, %20, %21, %22, %23, %24, %25, %26, %27, %28, %29, %30, %31, "
    "%32, %33, %34, %35}, "
    "{%36, %37, %38, %39}, %40, 0, 1, 1, 0;\n"
    : "=r"(d[0]), "=r"(d[1]), "=r"(d[2]), "=r"(d[3]), "=r"(d[4]), "=r"(d[5]), "=r"(d[6]), "=r"(d[7]),
      "=r"(d[8]), "=r"(d[9]), "=r"(d[10]), "=r"(d[11]), "=r"(d[12]), "=r"(d[13]), "=r"(d[14]), "=r"(d[15]),
      "=r"(d[16]), "=r"(d[17]), "=r"(d[18]), "=r"(d[19]), "=r"(d[20]), "=r"(d[21]), "=r"(d[22]), "=r"(d[23]),
      "=r"(d[24]), "=r"(d[25]), "=r"(d[26]), "=r"(d[27]), "=r"(d[28]), "=r"(d[29]), "=r"(d[30]), "=r"(d[31]),
      "=r"(d[32]), "=r"(d[33]), "=r"(d[34]), "=r"(d[35])
    : "r"(a0), "r"(a1), "r"(a2), "r"(a3), "l"(descB));
  else
  asm volatile("wgmma.mma_async.sync.aligned.m64n144k16.f16.f16.f16 "
    "{%0, %1, %2, %3, %4, %5, %6, %7, %8, %9, %10, %11, %12, %13, %14, %15, "
    "%16, %17, %18, %19, %20, %21, %22, %23, %24, %25, %26, %27, %28, %29, %30, %31, "
    "%32, %33, %34, %35}, "
    "{%36, %37, %38, %39}, %40, 1, 1, 1, 0;\n"
    : "+r"(d[0]), "+r"(d[1]), "+r"(d[2]), "+r"(d[3]), "+r"(d[4]), "+r"(d[5]), "+r"(d[6]), "+r"(d[7]),
      "+r"(d[8]), "+r"(d[9]), "+r"(d[10]), "+r"(d[11]), "+r"(d[12]), "+r"(d[13]), "+r"(d[14]), "+r"(d[15]),
      "+r"(d[16]), "+r"(d[17]), "+r"(d[18]), "+r"(d[19]), "+r"(d[20]), "+r"(d[21]), "+r"(d[22]), "+r"(d[23]),
      "+r"(d[24]), "+r"(d[25]), "+r"(d[26]), "+r"(d[27]), "+r"(d[28]), "+r"(d[29]), "+r"(d[30]), "+r"(d[31]),
      "+r"(d[32]), "+r"(d[33]), "+r"(d[34]), "+r"(d[35])
    : "r"(a0), "r"(a1), "r"(a2), "r"(a3), "l"(descB));
}

template <int SCALE_D>
__device__ __forceinline__ void wgmma_n192(uint32_t (&d)[48], uint32_t a0, uint32_t a1, uint32_t a2, uint32_t a3, uint64_t descB) {
  if (SCALE_D == 0)
  asm volatile("wgmma.mma_async.sync.aligned.m64n192k16.f16.f16.f16 "
    "{%0, %1, %2, %3, %4, %5, %6, %7, %8, %9, %10, %11, %12, %13, %14, %15, "
    "%16, %17, %18, %19, %20, %21, %22, %23, %24, %25, %26, %27, %28, %29, %30, %31, "
    "%32, %33, %34, %35, %36, %37, %38, %39, %40, %41, %42, %43, %44, %45, %46, %47}, "
    "{%48, %49, %50, %51}, %52, 0, 1, 1, 0;\n"
    : "=r"(d[0]), "=r"(d[1]), "=r"(d[2]), "=r"(d[3]), "=r"(d[4]), "=r"(d[5]), "=r"(d[6]), "=r"(d[7]),
      "=r"(d[8]), "=r"(d[9]), "=r"(d[10]), "=r"(d[11]), "=r"(d[12]), "=r"(d[13]), "=r"(d[14]), "=r"(d[15]),
      "=r"(d[16]), "=r"(d[17]), "=r"(d[18]), "=r"(d[19]), "=r"(d[20]), "=r"(d[21]), "=r"(d[22]), "=r"(d[23]),
      "=r"(d[24]), "=r"(d[25]), "=r"(d[26]), "=r"(d[27]), "=r"(d[28]), "=r"(d[29]), "=r"(d[30]), "=r"(d[31]),
      "=r"(d[32]), "=r"(d[33]), "=r"(d[34]), "=r"(d[35]), "=r"(d[36]), "=r"(d[37]), "=r"(d[38]), "=r"(d[39]),
      "=r"(d[40]), "=r"(d[41]), "=r"(d[42]), "=r"(d[43]), "=r"(d[44]), "=r"(d[45]), "=r"(d[46]), "=r"(d[47])
    : "r"(a0), "r"(a1), "r"(a2), "r"(a3), "l"(descB));
  else
  asm volatile("wgmma.mma_async.sync.aligned.m64n192k16.f16.f16.f16 "
    "{%0, %1, %2, %3, %4, %5, %6, %7, %8, %9, %10, %11, %12, %13, %14, %15, "
    "%16, %17, %18, %19, %20, %21, %22, %23, %24, %25, %26, %27, %28, %29, %30, %31, "
    "%32, %33, %34, %35, %36, %37, %38, %39, %40, %41, %42, %43, %44, %45, %46, %47}, "
    "{%48, %49, %50, %51}, %52, 1, 1, 1, 0;\n"
    : "+r"(d[0]), "+r"(d[1]), "+r"(d[2]), "+r"(d[3]), "+r"(d[4]), "+r"(d[5]), "+r"(d[6]), "+r"(d[7]),
      "+r"(d[8]), "+r"(d[9]), "+r"(d[10]), "+r"(d[11]), "+r"(d[12]), "+r"(d[13]), "+r"(d[14]), "+r"(d[15]),
      "+r"(d[16]), "+r"(d[17]), "+r"(d[18]), "+r"(d[19]), "+r"(d[20]), "+r"(d[21]), "+r"(d[22]), "+r"(d[23]),
      "+r"(d[24]), "+r"(d[25]), "+r"(d[26]), "+r"(d[27]), "+r"(d[28]), "+r"(d[29]), "+r"(d[30]), "+r"(d[31]),
      "+r"(d[32]), "+r"(d[33]), "+r"(d[34]), "+r"(d[35]), "+r"(d[36]), "+r"(d[37]), "+r"(d[38]), "+r"(d[39]),
      "+r"(d[40]), "+r"(d[41]), "+r"(d[42]), "+r"(d[43]), "+r"(d[44]), "+r"(d[45]), "+r"(d[46]), "+r"(d[47])
    : "r"(a0), "r"(a1), "r"(a2), "r"(a3), "l"(descB));
}

template <int SCALE_D>
__device__ __forceinline__ void wgmma_n56(uint32_t (&d)[14], uint32_t a0, uint32_t a1, uint32_t a2, uint32_t a3, uint64_t descB) {
  if (SCALE_D == 0)
  asm volatile("wgmma.mma_async.sync.aligned.m64n56k16.f16.f16.f16 "
    "{%0, %1, %2, %3, %4, %5, %6, %7, %8, %9, %10, %11, %12, %13}, "
    "{%14, %15, %16, %17}, %18, 0, 1, 1, 0;\n"
    : "=r"(d[0]), "=r"(d[1]), "=r"(d[2]), "=r"(d[3]), "=r"(d[4]), "=r"(d[5]), "=r"(d[6]), "=r"(d[7]),
      "=r"(d[8]), "=r"(d[9]), "=r"(d[10]), "=r"(d[11]), "=r"(d[12]), "=r"(d[13])
    : "r"(a0), "r"(a1), "r"(a2), "r"(a3), "l"(descB));
  else
  asm volatile("wgmma.mma_async.sync.aligned.m64n56k16.f16.f16.f16 "
    "{%0, %1, %2, %3, %4, %5, %6, %7, %8, %9, %10, %11, %12, %13}, "
    "{%14, %15, %16, %17}, %18, 1, 1, 1, 0;\n"
    : "+r"(d[0]), "+r"(d[1]), "+r"(d[2]), "+r"(d[3]), "+r"(d[4]), "+r"(d[5]), "+r"(d[6]), "+r"(d[7]),
      "+r"(d[8]), "+r"(d[9]), "+r"(d[10]), "+r"(d[11]), "+r"(d[12]), "+r"(d[13])
    : "r"(a0), "r"(a1), "r"(a2), "r"(a3), "l"(descB));
}

template <int SCALE_D>
__device__ __forceinline__ void wgmma_n56t(uint32_t (&d)[14], uint32_t a0, uint32_t a1, uint32_t a2, uint32_t a3, uint64_t descB) {
  if (SCALE_D == 0)
  asm volatile("wgmma.mma_async.sync.aligned.m64n56k16.f16.f16.f16 "
    "{%0, %1, %2, %3, %4, %5, %6, %7, %8, %9, %10, %11, %12, %13}, "
    "{%14, %15, %16, %17}, %18, 0, 1, 1, 1;\n"
    : "=r"(d[0]), "=r"(d[1]), "=r"(d[2]), "=r"(d[3]), "=r"(d[4]), "=r"(d[5]), "=r"(d[6]), "=r"(d[7]),
      "=r"(d[8]), "=r"(d[9]), "=r"(d[10]), "=r"(d[11]), "=r"(d[12]), "=r"(d[13])
    : "r"(a0), "r"(a1), "r"(a2), "r"(a3), "l"(descB));
  else
  asm volatile("wgmma.mma_async.sync.aligned.m64n56k16.f16.f16.f16 "
    "{%0, %1, %2, %3, %4, %5, %6, %7, %8, %9, %10, %11, %12, %13}, "
    "{%14, %15, %16, %17}, %18, 1, 1, 1, 1;\n"
    : "+r"(d[0]), "+r"(d[1]), "+r"(d[2]), "+r"(d[3]), "+r"(d[4]), "+r"(d[5]), "+r"(d[6]), "+r"(d[7]),
      "+r"(d[8]), "+r"(d[9]), "+r"(d[10]), "+r"(d[11]), "+r"(d[12]), "+r"(d[13])
    : "r"(a0), "r"(a1), "r"(a2), "r"(a3), "l"(descB));
}

__global__ void __launch_bounds__(192 * PBY) prepack_kernel(const __nv_bfloat16* __restrict__ wqkv, const __nv_bfloat16* __restrict__ wo,
                                                      const __nv_bfloat16* __restrict__ x, int first_rows) {
  asm volatile("griddepcontrol.launch_dependents;");
  __shared__ float red2[PBY][6][16];
  float (*red)[16] = red2[threadIdx.y];
  __shared__ __align__(16) __half stage[PBY][1536];
  __half* dst = stage[threadIdx.y];
  const int c = threadIdx.x, nb = blockIdx.x * PBY + threadIdx.y;
  uint32_t u[4];
  int base, gofs;
  float scale = 1.0f;
  if (nb < 72) {
    const int h = nb / 18, j = nb % 18, part = j / 6;
    const int col = (part == 0 ? 192 : part == 1 ? 0 : 384) + h * 48 + (j % 6) * 8;
    const uint4 raw = *reinterpret_cast<const uint4*>(wqkv + c * 576 + col);
    u[0] = raw.x; u[1] = raw.y; u[2] = raw.z; u[3] = raw.w;
    if (part == 1) scale = 0.14433756729740643f * 1.4426950408889634f;
    const int cc = c >> 5, q = (c >> 3) & 3, s1 = (c >> 2) & 1, hh = (c >> 1) & 1, e = c & 1;
    base = (2 * cc + s1) * 128 + hh * 64 + 2 * q + e;
    gofs = qkv_pos(h, c >> 4) + j * 256;
  } else {
    const int jb = nb - 72;
#pragma unroll
    for (int i = 0; i < 4; i++) u[i] = *reinterpret_cast<const uint32_t*>(wo + c * 192 + 32 * (jb >> 2) + 8 * i + 2 * (jb & 3));
    base = (c >> 4) * 128 + ((c >> 3) & 1) * 64 + (c & 7);
    gofs = wo_pos(c >> 4) + jb * 256;
  }
  if (threadIdx.y == 0 && c < 32)
    for (int i = blockIdx.x + 96 / PBY * c; i < first_rows * NWX / 4; i += 96 / PBY * 32)
      asm volatile("cp.async.bulk.prefetch.L2.global [%0], %1;" :: "l"(reinterpret_cast<const uint8_t*>(x) + (size_t)i * 10752), "n"(10752) : "memory");
  float v[8], t[16];
#pragma unroll
  for (int i = 0; i < 4; i++) { v[2 * i] = lo2f(u[i]); v[2 * i + 1] = hi2f(u[i]); }
#pragma unroll
  for (int i = 0; i < 16; i++) t[i] = i < 8 ? v[i] : v[i - 8] * v[i - 8];
#pragma unroll
  for (int n = 8; n >= 1; n >>= 1) {
    const bool up = c & (2 * n);
#pragma unroll
    for (int i = 0; i < n; i++) t[i] = (up ? t[i + n] : t[i]) + __shfl_xor_sync(~0u, up ? t[i] : t[i + n], 2 * n);
  }
  t[0] += __shfl_xor_sync(~0u, t[0], 1);
  if (!(c & 1)) red[c >> 5][(c & 31) >> 1] = t[0];
  __syncthreads();
#pragma unroll
  for (int i = 0; i < 16; i++) t[i] = red[0][i] + red[1][i] + red[2][i] + red[3][i] + red[4][i] + red[5][i];
  float mx = 0.f, sm = 0.f;
#pragma unroll
  for (int n = 0; n < 8; n++) {
    const float m = nb < 72 ? t[n] * (1.0f / 192.0f) : 0.f;
    dst[base + n * 8] = __float2half_rn(__bfloat162float(__float2bfloat16((v[n] - m) * scale)));
    const float nn = (t[8 + n] - 0.999f * m * t[n]) * scale * scale * 1.01f;
    mx = fmaxf(mx, nn); sm += nn;
  }
  if (c == 0) g_wnorm[nb] = make_float2(mx, sm);
  __syncthreads();
  g_wpack[gofs / 16 + (c & 15)] = reinterpret_cast<const uint4*>(dst)[c];
}

__device__ __forceinline__ int window_of(int round, int nfull, int cta, int ncta, int wg) {
  if (round < nfull) return round * 2 * ncta + 2 * cta + wg;
  const int rem = NWIN - nfull * 2 * ncta;
  const int i = cta + wg * ncta;
  return i < rem ? nfull * 2 * ncta + i : -1;
}

template <int S0 = 0, int S1 = 12>
__device__ __forceinline__ void mma_qkv(uint32_t (&acc)[36], const uint32_t (&A)[48], const uint64_t* d) {
#pragma unroll
  for (int s = S0; s < S1; s++) {
    if (s == 0) wgmma_n144<0>(acc, A[4 * s], A[4 * s + 1], A[4 * s + 2], A[4 * s + 3], d[s]);
    else        wgmma_n144<1>(acc, A[4 * s], A[4 * s + 1], A[4 * s + 2], A[4 * s + 3], d[s]);
  }
  wg_commit();
}
__device__ __forceinline__ void mma_proj(uint32_t (&acc)[48], const uint32_t (&A)[12], const uint64_t* d) {
#pragma unroll
  for (int s = 0; s < 3; s++) wgmma_n192<1>(acc, A[4 * s], A[4 * s + 1], A[4 * s + 2], A[4 * s + 3], d[s]);
}
__device__ __forceinline__ void mma_s(uint32_t (&S)[14], const uint32_t (&Q)[12], const uint64_t* d) {
  wgmma_n56<0>(S, Q[0], Q[1], Q[2], Q[3], d[0]);
  wgmma_n56<1>(S, Q[4], Q[5], Q[6], Q[7], d[1]);
  wgmma_n56<1>(S, Q[8], Q[9], Q[10], Q[11], d[2]);
}
__device__ __forceinline__ void mma_pv(uint32_t (&O)[14], const uint32_t (&P)[NP], const uint64_t* d) {
  wgmma_n56t<0>(O, P[0], P[1], P[2], P[3], d[0]);
  wgmma_n56t<1>(O, P[4], P[5], P[6], P[7], d[1]);
  wgmma_n56t<1>(O, P[8], P[9], P[10], P[11], d[2]);
  if (K48TC) wgmma_n56t<1>(O, P[NP - 4], P[NP - 3], P[NP - 2], P[NP - 1], d[3]);
}

#define PIN() asm volatile("pmevent 0;" ::: "memory")
template <int A, int B> __device__ __forceinline__ void hold(uint32_t* v) {
#pragma unroll
  for (int i = A; i < B; i++) asm volatile("" : "+r"(v[i]));
}
__device__ __forceinline__ void stsm12(const uint32_t* v, uint32_t addr) {
#pragma unroll
  for (int j = 0; j < 3; j++) stsm4(addr + 2 * j * KV_PITCH, v[4 * j], v[4 * j + 1], v[4 * j + 2], v[4 * j + 3]);
}
__device__ __forceinline__ void load_v48(uint32_t (&v)[6], uint32_t addr) {
  if (K48TC) return;
  asm volatile("ldmatrix.sync.aligned.m8n8.x4.shared.b16 {%0,%1,%2,%3}, [%4];" : "=r"(v[0]), "=r"(v[1]), "=r"(v[2]), "=r"(v[3]) : "r"(addr) : "memory");
  asm volatile("ldmatrix.sync.aligned.m8n8.x2.shared.b16 {%0,%1}, [%2];" : "=r"(v[4]), "=r"(v[5]) : "r"(addr + 4 * KV_PITCH) : "memory");
}
__device__ __forceinline__ void finish_o(const uint32_t (&O)[14], const uint32_t (&v)[6], uint32_t p48, uint32_t vmask, uint32_t (&Of)[12]) {
  const float2 l = K48TC ? make_float2(__low2float(u2h(O[12])), __low2float(u2h(O[13])))
                         : __half22float2(__hadd2_rn(u2h(__byte_perm(O[12], O[13], 0x5410)), u2h(p48)));
  float i0, i1;
  asm("rcp.approx.ftz.f32 %0, %1;" : "=f"(i0) : "f"(l.x));
  asm("rcp.approx.ftz.f32 %0, %1;" : "=f"(i1) : "f"(l.y));
  const uint32_t inv = packh(i0, i1) & vmask;
#pragma unroll
  for (int i = 0; i < 12; i++) {
    const uint32_t t = K48TC ? O[i] : h2u(__hfma2(u2h(v[i >> 1]), (i & 1) ? hcast<1>(p48) : hcast<0>(p48), u2h(O[i])));
    Of[i] = (i & 1) ? fmul_b<1>(t, inv) : fmul_b<0>(t, inv);
  }
  hold<0, 12>(Of);
}
#define PSTAT 12
template <int A, int B>
__device__ __forceinline__ void ln_sums(const uint32_t (&X)[48], float (&s1)[2], float (&s2)[2]) {
  if (PSTAT) {
    static_assert(PSTAT == 0 || (A % (2 * PSTAT + !PSTAT) == 0 && B % (2 * PSTAT + !PSTAT) == 0), "whole groups");
#pragma unroll
    for (int g = A; g < B; g += 2 * PSTAT + !PSTAT)
#pragma unroll
      for (int a = 0; a < 2; a++) {
        __half2 p1 = u2h(X[g + a]), p2 = __hmul2_rn(p1, p1);
#pragma unroll
        for (int i = 1; i < PSTAT; i++) { const __half2 v = u2h(X[g + a + 2 * i]); p1 = __hadd2_rn(p1, v); p2 = __hfma2(v, v, p2); }
        const float2 f1 = __half22float2(p1), f2 = __half22float2(p2);
        s1[a] = g == 0 ? f1.x + f1.y : s1[a] + (f1.x + f1.y);
        s2[a] = g == 0 ? f2.x + f2.y : s2[a] + (f2.x + f2.y);
      }
  } else {
#pragma unroll
    for (int i = A; i < B; i++) {
      const float2 f = __half22float2(u2h(X[i]));
      s1[i & 1] = i < 2 ? f.x + f.y : s1[i & 1] + (f.x + f.y);
      s2[i & 1] = fmaf(f.x, f.x, i < 2 ? f.y * f.y : fmaf(f.y, f.y, s2[i & 1]));
    }
  }
  asm volatile("" : "+f"(s1[0]), "+f"(s1[1]), "+f"(s2[0]), "+f"(s2[1]));
}
__device__ __forceinline__ uint32_t ln_rstd(const float (&s1)[2], const float (&s2)[2], float lo, float hi, uint32_t vmask, bool& ok) {
  float r[2];
  ok = true;
#pragma unroll
  for (int a = 0; a < 2; a++) {
    float m = s1[a], v = s2[a];
    m += __shfl_xor_sync(~0u, m, 1); v += __shfl_xor_sync(~0u, v, 1);
    m += __shfl_xor_sync(~0u, m, 2); v += __shfl_xor_sync(~0u, v, 2);
    ok = ok & (v <= hi) & ((v >= lo) | !(vmask >> (16 * a) & 1));
    m *= 1.0f / 192.0f;
    m *= m;
    v = fmaxf(fmaf(v, 1.0f / 192.0f, -m), 0.f) + 1e-5f;
    ok = ok & (m <= (PSTAT ? 16.f : 64.f) * v);
    asm("rsqrt.approx.ftz.f32 %0, %1;" : "=f"(r[a]) : "f"(v));
  }
  uint32_t rk = packh(r[0], r[1]);
  hold<0, 1>(&rk);
  return rk;
}
__device__ __forceinline__ void scale12(uint32_t (&D)[12], const uint32_t* a, uint32_t r) {
#pragma unroll
  for (int i = 0; i < 12; i++) D[i] = (i & 1) ? fmul_b<1>(a[i], r) : fmul_b<0>(a[i], r);
  hold<0, 12>(D);
}
template <int CC>
__device__ __forceinline__ void store_out(const uint32_t (&Y)[48], uint8_t* o0, uint8_t* o1, uint32_t vmask) {
  uint32_t T[8];
#pragma unroll
  for (int i = 0; i < 8; i++) {
    const float2 f = __half22float2(u2h(Y[8 * CC + i]));
    T[i] = pack2(f.x, f.y);
  }
  asm volatile("{\n.reg .pred p;\nsetp.ne.u32 p, %5, 0;\n@p st.global.cs.v4.u32 [%0], {%1,%2,%3,%4};\n}\n"
               :: "l"(o0 + CC * 64), "r"(T[0]), "r"(T[2]), "r"(T[4]), "r"(T[6]), "r"(vmask) : "memory");
  asm volatile("{\n.reg .pred p;\nsetp.lt.s32 p, %5, 0;\n@p st.global.cs.v4.u32 [%0], {%1,%2,%3,%4};\n}\n"
               :: "l"(o1 + CC * 64), "r"(T[1]), "r"(T[3]), "r"(T[5]), "r"(T[7]), "r"(vmask) : "memory");
}
__device__ __forceinline__ void proxy_fence() { asm volatile("fence.proxy.async.shared::cta;" ::: "memory"); }
__device__ __forceinline__ uint32_t fadd2(uint32_t a, uint32_t b) { return h2u(__hadd2_rn(u2h(a), u2h(b))); }
__device__ __forceinline__ void row_max(const uint32_t (&S)[14], uint32_t& k48, uint32_t& mx, uint32_t ninf) {
  k48 = K48TC ? __byte_perm(S[12], S[13], 0x5410) | ninf : __shfl_sync(~0u, __byte_perm(S[12], S[13], 0x5410), 0, 4);
  const uint32_t m0 = fmax2(fmax2(fmax2(S[0], S[2]), S[4]), fmax2(fmax2(S[6], S[8]), S[10]));
  const uint32_t m1 = fmax2(fmax2(fmax2(S[1], S[3]), S[5]), fmax2(fmax2(S[7], S[9]), S[11]));
  mx = fmax2(__byte_perm(m0, m1, 0x5410), __byte_perm(m0, m1, 0x7632));
  if (K48TC) mx = fmax2(mx, k48);
  mx = fmax2(mx, __shfl_xor_sync(~0u, mx, 1));
  mx = fmax2(mx, __shfl_xor_sync(~0u, mx, 2));
  if (!K48TC) mx = fmax2(mx, k48);
  hold<0, 1>(&mx);
}
__device__ __forceinline__ void row_exp(const uint32_t (&S)[14], uint32_t k48, uint32_t mx, uint32_t (&P)[NP], uint32_t& p48) {
#pragma unroll
  for (int j = 0; j < 12; j++) P[j] = fex2((j & 1) ? fsub_b<1>(S[j], mx) : fsub_b<0>(S[j], mx));
  if (K48TC) {
    uint16_t el, eh;
    asm("{\n.reg .b16 l, h;\nmov.b32 {l, h}, %2;\nex2.approx.f16 %0, l;\nex2.approx.f16 %1, h;\n}\n" : "=h"(el), "=h"(eh) : "r"(h2u(__hsub2_rn(u2h(k48), u2h(mx)))));
    P[NP - 4] = el; P[NP - 3] = eh; P[NP - 2] = 0; P[NP - 1] = 0;
  } else {
    p48 = fex2(h2u(__hsub2_rn(u2h(k48), u2h(mx))));
    hold<0, 1>(&p48);
  }
  hold<0, NP>(P);
}
template <int S0, int S1>
__device__ __forceinline__ void load_x(uint32_t (&X)[48], uint32_t t0) {
#pragma unroll
  for (int s = S0; s < S1; s++)
    asm volatile("ld.shared.v4.u32 {%0,%1,%2,%3}, [%4];" : "=r"(X[4 * s]), "=r"(X[4 * s + 1]), "=r"(X[4 * s + 2]), "=r"(X[4 * s + 3])
                 : "r"(((s & 1) ? (t0 ^ 16) : t0) + (s >> 1) * 128) : "memory");
}

template <int CNT, int EXPECT = CNT * SLICE>
__device__ __forceinline__ void load_slices(uint32_t sb, const uint8_t* src, int slice, int slot, int bar) {
  if (EXPECT)
    asm volatile("{\n.reg .pred p;\nelect.sync _|p, 0xffffffff;\n@p mbarrier.arrive.expect_tx.shared::cta.b64 _, [%0], %1;\n}\n"
                 :: "r"(sb + bar), "n"(EXPECT) : "memory");
  asm volatile("{\n.reg .pred p;\nelect.sync _|p, 0xffffffff;\n"
               "@p cp.async.bulk.shared::cluster.global.mbarrier::complete_tx::bytes [%0], [%1], %2, [%3];\n}\n"
               :: "r"(sb + OFF_W + slot * SLICE), "l"(src + slice * SLICE), "n"(CNT * SLICE), "r"(sb + bar) : "memory");
}
__device__ __forceinline__ void warp_arrive(uint32_t bar) {
  asm volatile("{\n.reg .pred p;\nelect.sync _|p, 0xffffffff;\n@p mbarrier.arrive.shared::cta.b64 _, [%0];\n}\n" :: "r"(bar) : "memory");
}

__device__ __forceinline__ float2 fp16_limits(int lane) {
  float mx[4] = {0.f, 0.f, 0.f, 0.f}, sm[4] = {0.f, 0.f, 0.f, 0.f};
#pragma unroll
  for (int i = 0; i < 3; i++) {
    const int nb = lane + 32 * i, part = nb < 72 ? (nb % 18) / 6 : 3;
    const float2 w = g_wnorm[nb];
#pragma unroll
    for (int k = 0; k < 4; k++) if (part == k) { mx[k] = fmaxf(mx[k], w.x); sm[k] += w.y; }
  }
#pragma unroll
  for (int k = 0; k < 4; k++)
#pragma unroll
    for (int d = 16; d; d >>= 1) { mx[k] = fmaxf(mx[k], __shfl_xor_sync(~0u, mx[k], d)); sm[k] += __shfl_xor_sync(~0u, sm[k], d); }
  const float big = fmaxf(fmaxf(mx[0], mx[1]), mx[2]);
  float small = 1.f;
  bool good = sm[0] + sm[1] + sm[2] + sm[3] < 1e30f;
#pragma unroll
  for (int k = 0; k < 4; k++) { good = good && (mx[k] == 0.f || mx[k] >= 2.5e-4f); if (k < 3 && mx[k] > 0.f) small = fminf(small, mx[k]); }
  good = good && 250.f * 48.f * sqrtf(mx[0] * mx[1]) <= 5e4f;
  good = good && 16.f * 49.f * sqrtf(mx[2]) <= 5e4f && big <= 1e6f;
  good = good && 16.f * sqrtf(sm[2] * mx[3]) <= 2e4f;
  return make_float2(192.f * 2.4e-7f / small, good ? fminf(2.5e8f, 9e8f / fmaxf(big, 1e-30f)) : -1.f);
}

__device__ __forceinline__ void slow_window(float* sm, int w, int t, const __nv_bfloat16* __restrict__ x, const __nv_bfloat16* __restrict__ dw,
                                            const __nv_bfloat16* __restrict__ wqkv, const __nv_bfloat16* __restrict__ wo, __nv_bfloat16* __restrict__ out) {
  float* x0 = sm; float* h = x0 + 49 * CH; float* qkv = h + 49 * CH; float* S = qkv + 49 * 576;
  const int wy = w / NWX, wx = w % NWX;
  auto sync = [] { asm volatile("bar.sync 6, 128;" ::: "memory"); };
#pragma unroll 1
  for (int i = t; i < 49 * CH; i += 128) {
    const int k = i / CH, c = i % CH, y = wy * 7 + k / 7, xx = wx * 7 + k % 7;
    float pe = 0.f;
#pragma unroll 1
    for (int a = 0; a < 9; a++) {
      const int yy = y + a / 3 - 1, xc = xx + a % 3 - 1;
      if (yy >= 0 && yy < IMG && xc >= 0 && xc < IMG) pe = fmaf(__bfloat162float(x[((size_t)yy * IMG + xc) * CH + c]), __bfloat162float(dw[a * CH + c]), pe);
    }
    x0[i] = __bfloat162float(__float2bfloat16(__bfloat162float(x[((size_t)y * IMG + xx) * CH + c]) + pe));
  }
  sync();
  if (t < 49) {
    float m = 0.f, v = 0.f;
#pragma unroll 1
    for (int c = 0; c < CH; c++) m += x0[t * CH + c];
    m *= 1.0f / CH;
#pragma unroll 1
    for (int c = 0; c < CH; c++) { const float d = x0[t * CH + c] - m; v = fmaf(d, d, v); }
    const float rs = 1.0f / sqrtf(v * (1.0f / CH) + 1e-5f);
#pragma unroll 1
    for (int c = 0; c < CH; c++) h[t * CH + c] = (x0[t * CH + c] - m) * rs;
  }
  sync();
#pragma unroll 1
  for (int i = t; i < 7 * 576; i += 128) {
    const int n = i % 576, k0 = i / 576 * 7;
    float a[7] = {0.f, 0.f, 0.f, 0.f, 0.f, 0.f, 0.f};
#pragma unroll 1
    for (int c = 0; c < CH; c++) {
      const float wv = __bfloat162float(wqkv[c * 576 + n]);
#pragma unroll
      for (int k = 0; k < 7; k++) a[k] = fmaf(h[(k0 + k) * CH + c], wv, a[k]);
    }
#pragma unroll
    for (int k = 0; k < 7; k++) qkv[(k0 + k) * 576 + n] = a[k];
  }
  sync();
#pragma unroll 1
  for (int hd = 0; hd < 4; hd++) {
#pragma unroll 1
    for (int i = t; i < 49 * 49; i += 128) {
      const int a = i / 49, b = i % 49;
      float v = 0.f;
#pragma unroll 1
      for (int d = 0; d < 48; d++) v = fmaf(qkv[a * 576 + hd * 48 + d], qkv[b * 576 + 192 + hd * 48 + d], v);
      S[i] = v * 0.14433756729740643f;
    }
    sync();
    if (t < 49) {
      float m = S[t * 49], l = 0.f;
#pragma unroll 1
      for (int b = 1; b < 49; b++) m = fmaxf(m, S[t * 49 + b]);
#pragma unroll 1
      for (int b = 0; b < 49; b++) { const float e = expf(S[t * 49 + b] - m); S[t * 49 + b] = e; l += e; }
#pragma unroll 1
      for (int b = 0; b < 49; b++) S[t * 49 + b] /= l;
    }
    sync();
#pragma unroll 1
    for (int i = t; i < 49 * 48; i += 128) {
      const int a = i / 48, d = i % 48;
      float v = 0.f;
#pragma unroll 1
      for (int b = 0; b < 49; b++) v = fmaf(S[a * 49 + b], qkv[b * 576 + 384 + hd * 48 + d], v);
      h[a * CH + hd * 48 + d] = v;
    }
    sync();
  }
#pragma unroll 1
  for (int i = t; i < 7 * CH; i += 128) {
    const int n = i % CH, k0 = i / CH * 7;
    float a[7] = {0.f, 0.f, 0.f, 0.f, 0.f, 0.f, 0.f};
#pragma unroll 1
    for (int c = 0; c < CH; c++) {
      const float wv = __bfloat162float(wo[c * CH + n]);
#pragma unroll
      for (int k = 0; k < 7; k++) a[k] = fmaf(h[(k0 + k) * CH + c], wv, a[k]);
    }
#pragma unroll
    for (int k = 0; k < 7; k++)
      out[((size_t)(wy * 7 + k0 / 7) * IMG + wx * 7 + k) * CH + n] = __float2bfloat16(x0[(k0 + k) * CH + n] + a[k]);
  }
  sync();
}

__global__ void __launch_bounds__(384, 1)
fused_kernel(const __grid_constant__ CUtensorMap tmx, const __grid_constant__ CUtensorMap tmp, const __grid_constant__ Descs ds, const __nv_bfloat16* __restrict__ dw, __nv_bfloat16* __restrict__ out, const int never,
             const __nv_bfloat16* __restrict__ x, const __nv_bfloat16* __restrict__ wqkv, const __nv_bfloat16* __restrict__ wo) {
  extern __shared__ __align__(1024) uint8_t smem[];
  const uint32_t sb = (uint32_t)__cvta_generic_to_shared(smem);
  const int tid = threadIdx.x, lane = tid & 31;
  const int warp = __shfl_sync(0xffffffffu, tid >> 5, 0);
  const int cta = blockIdx.x, ncta = gridDim.x;
  const int nfull = NWIN / (2 * ncta);
  const int nrounds = nfull + ((NWIN - nfull * 2 * ncta) > cta ? 1 : 0);

  if (warp == 0) GTS(0);
  if (warp == 10 && lane == 0) asm volatile("prefetch.tensormap [%0];" :: "l"(reinterpret_cast<uint64_t>(&tmx)) : "memory");
  if (tid == 0) {
    mbar_init(sb + BAR_FIRST, 1);
    asm volatile("fence.mbarrier_init.release.cluster;" ::: "memory");
    asm volatile("mbarrier.arrive.expect_tx.shared::cta.b64 _, [%0], %1;" :: "r"(sb + BAR_FIRST), "n"(2 * HALO_BYTES) : "memory");
#pragma unroll
    for (int k = 0; k < 2; k++) {
      const int w = max(window_of(0, nfull, cta, ncta, k), 0), a = w / NWX;
      asm volatile("cp.async.bulk.tensor.3d.shared::cluster.global.mbarrier::complete_tx::bytes [%0], [%1, {0, %3, %4}], [%2];"
                   :: "r"(sb + OFF_HALO + k * HALO_BYTES), "l"(reinterpret_cast<uint64_t>(&tmp)), "r"(sb + BAR_FIRST),
                      "r"((w - a * NWX) * 7 - 1), "r"(a * 7 - 1) : "memory");
    }
    if ((sb & 0x3FFFF) != SMEM_BASE || nrounds > 128) __trap();
    for (int i = 0; i < 6; i++) mbar_init(sb + BAR_FH + 8 * i, 1);
    for (int i = 0; i < 4; i++) mbar_init(sb + BAR_E + 8 * i, 8);
    for (int i = 0; i < 9; i++) mbar_init(sb + BAR_XFULL + 8 * i, 1);
    mbar_init(sb + BAR_TFULL, 3);
    mbar_init(sb + BAR_TEMPTY, 8);
    asm volatile("fence.mbarrier_init.release.cluster;" ::: "memory");
  }
  if (tid >= 128 && tid < 320) {
    *reinterpret_cast<uint32_t*>(smem + OFF_ZERO + (tid - 128) * 4) = 0;
    if (tid < 136) *reinterpret_cast<uint32_t*>(smem + OFF_REDO + (tid - 128) * 4) = 0;
  }
  if (tid < 128) {
    *reinterpret_cast<uint4*>(smem + OFF_KV + (tid / 64) * KV_BYTES + 6 * KV_PITCH + (tid % 64) * 16) = make_uint4(0x3c003c00u, 0x3c003c00u, 0x3c003c00u, 0x3c003c00u);
    proxy_fence();
  }
  __syncthreads();

  if (warp == 0) GTS(3);
  if (warp < 11) {
#pragma unroll 1
    for (int u = 0; u < (warp < 10 ? 2 : 1); u++) {
      const int cb = warp < 9 ? warp % 3 : 2 * (warp - 9) + u, y = warp < 9 ? 2 * (warp / 3) + u : 6;
      const int ch0 = cb * 64 + (lane & 15) * 4;
      uint32_t wt[9][2], px[3][9][2];
#pragma unroll
      for (int t = 0; t < 9; t++) {
        const uint2 v = *reinterpret_cast<const uint2*>(dw + t * CH + ch0);
        wt[t][0] = v.x; wt[t][1] = v.y;
      }
      mbar_wait(sb + BAR_FIRST, 0);
      if (warp == 0 && u == 0) GTS(7);
      const uint32_t ld = sb + OFF_HALO + (lane >> 4) * HALO_BYTES + y * 3456 + ch0 * 2;
#pragma unroll
      for (int p = 0; p < 27; p++)
        asm volatile("ld.shared.v2.u32 {%0,%1}, [%2];" : "=r"(px[p / 9][p % 9][0]), "=r"(px[p / 9][p % 9][1]) : "r"(ld + p * 384));
      const uint32_t st0 = sb + OFF_TILE + (lane >> 4) * TILE_BYTES + ch0 * 4;
      const uint32_t sa = (st0 ^ ((y & 1) << 4)) + y * 2304;
      uint32_t o[2][2];
#pragma unroll
      for (int j = 0; j < 7; j++) {
#pragma unroll
        for (int e = 0; e < 2; e++) {
          uint32_t a = hmul(px[0][j][e], wt[0][e]);
#pragma unroll
          for (int t = 1; t < 9; t++) a = hfma(px[t / 3][j + t % 3][e], wt[t][e], a);
          a = hadd(px[1][j + 1][e], a);
          o[j & 1][e] = packh(lo2f(a), hi2f(a));
        }
        if (j & 1)
          asm volatile("st.shared.v4.u32 [%0], {%1,%2,%3,%4};" :: "r"((j == 3 ? sa ^ 16 : sa) + (j >> 1) * 768),
                       "r"(o[0][0]), "r"(o[1][0]), "r"(o[0][1]), "r"(o[1][1]) : "memory");
      }
      const uint32_t sb6 = (st0 ^ ((~y & 2) << 3)) + (21 + (y >> 1)) * 768 + (y & 1) * 4;
      asm volatile("st.shared.u32 [%0], %1;\nst.shared.u32 [%0 + 8], %2;" :: "r"(sb6), "r"(o[0][0]), "r"(o[0][1]) : "memory");
      if (y == 6) asm volatile("st.shared.u32 [%0 + 4], %1;\nst.shared.u32 [%0 + 12], %1;" :: "r"(sb6), "r"(0) : "memory");
    }
    if (warp == 0) GTS(6);
    asm volatile("bar.arrive 8, 384;\nbar.sync 7, 352;" ::: "memory");
  }

  if (warp >= 8) {
    asm volatile("setmaxnreg.dec.sync.aligned.u32 " PREGS ";");
    if (warp == 11) {
      asm volatile("griddepcontrol.wait;" ::: "memory");
      GTS(2);
      load_slices<3, 0>(sb, ds.src, 0, 0, BAR_F0);
      *reinterpret_cast<float2*>(smem + OFF_LIM) = fp16_limits(lane);
      asm volatile("{\n.reg .pred p;\nelect.sync _|p, 0xffffffff;\n@p mbarrier.arrive.expect_tx.shared::cta.b64 _, [%0], %1;\n}\n"
                   :: "r"(sb + BAR_F0), "n"(3 * SLICE) : "memory");
      asm volatile("bar.sync 8, 384;" ::: "memory");
      load_slices<3, 5 * SLICE>(sb, ds.src, 3, 3, BAR_F1);
      load_slices<1, 0>(sb, ds.src, 13, SLOT_U, BAR_F1);
      load_slices<1, 0>(sb, ds.src, 12, SLOT_V, BAR_F1);
      for (int r = 0; r < nrounds; r++) {
        const int par = r & 1;
        const int h2 = par ? 1 : 2, h3 = par ? 0 : 3;
        mbar_wait(sb + BAR_E, par);
        load_slices<3>(sb, ds.src, 3 * h2, 3 * (h2 & 1), BAR_FH);
        mbar_wait(sb + BAR_E + 8, par);
        load_slices<3>(sb, ds.src, 3 * h3, 3 * (h3 & 1), BAR_FH + 8);
        mbar_wait(sb + BAR_E + 16, par);
        load_slices<1>(sb, ds.src, 12 + h2, SLOT_U, BAR_FU);
        mbar_wait(sb + BAR_E + 24, par);
        load_slices<1>(sb, ds.src, 12 + h3, SLOT_V, BAR_FV);
      }
    } else {
      const int cw = warp - 8;
      const int win = lane >> 4;
      const int ch0 = cw * 64 + (lane & 15) * 4;
      uint32_t wt[9][2];
#pragma unroll
      for (int t = 0; t < 9; t++) {
        uint2 v = *reinterpret_cast<const uint2*>(dw + t * CH + ch0);
        wt[t][0] = v.x; wt[t][1] = v.y;
      }
      const uint32_t xs = sb + OFF_X + cw * 3 * XSLOT;
      const uint32_t xld = xs + (lane >> 4) * 1152 + (lane & 15) * 8;
      const uint32_t xbar = sb + BAR_XFULL + cw * 24;
      const uint32_t st0 = sb + OFF_TILE + win * TILE_BYTES + ch0 * 4;
      const uint64_t tm = reinterpret_cast<uint64_t>(&tmx);
      int cx0, cy0, cx1, cy1;
      auto coords = [&](int r) {
        const int w0 = window_of(r, nfull, cta, ncta, 0);
        int w1 = window_of(r, nfull, cta, ncta, 1);
        if (w1 < 0) w1 = w0;
        const int a = w0 / NWX, b = w1 / NWX;
        cx0 = (w0 - a * NWX) * 7 - 1; cy0 = a * 7 - 1;
        cx1 = (w1 - b * NWX) * 7 - 1; cy1 = b * 7 - 1;
      };
      auto issue = [&](int slot, int dy) {
        asm volatile("{\n.reg .pred p;\nelect.sync _|p, 0xffffffff;\n"
                     "@p mbarrier.arrive.expect_tx.shared::cta.b64 _, [%2], %8;\n"
                     "@p cp.async.bulk.tensor.3d.shared::cluster.global.mbarrier::complete_tx::bytes [%0], [%1, {%3, %4, %5}], [%2];\n"
                     "@p cp.async.bulk.tensor.3d.shared::cluster.global.mbarrier::complete_tx::bytes [%0 + 1152], [%1, {%3, %6, %7}], [%2];\n}\n"
                     :: "r"(xs + slot * XSLOT), "l"(tm), "r"(xbar + slot * 8), "r"(cw * 64), "r"(cx0), "r"(cy0 + dy), "r"(cx1), "r"(cy1 + dy), "n"(XSLOT) : "memory");
      };
      uint32_t accA[7][2], accB[7][2], ctr[7][2], held[2];
      auto row = [&](auto fin, auto mid, auto top, int slot, int y) {
        const uint32_t ld = xld + slot * XSLOT;
        const uint32_t sa = (st0 ^ ((y & 1) << 4)) + y * 2304;
        uint32_t cur[9][2], o[2][2];
#pragma unroll
        for (int p = 0; p < LA; p++)
          asm volatile("ld.shared.v2.u32 {%0,%1}, [%2];" : "=r"(cur[p][0]), "=r"(cur[p][1]) : "r"(ld + p * 128));
#pragma unroll
        for (int j = 0; j < 7; j++) {
          if (j >= 1 && j + LA - 1 < 9)
            asm volatile("ld.shared.v2.u32 {%0,%1}, [%2];" : "=r"(cur[j + LA - 1][0]), "=r"(cur[j + LA - 1][1]) : "r"(ld + (j + LA - 1) * 128));
          if (fin.v) {
#pragma unroll
            for (int e = 0; e < 2; e++) {
              uint32_t a = hfma(cur[j][e], wt[6][e], accA[j][e]);
              a = hfma(cur[j + 1][e], wt[7][e], a);
              a = hfma(cur[j + 2][e], wt[8][e], a);
              a = hadd(ctr[j][e], a);
              o[j & 1][e] = packh(lo2f(a), hi2f(a));
            }
            if (j & 1)
              asm volatile("st.shared.v4.u32 [%0], {%1,%2,%3,%4};" :: "r"((j == 3 ? sa ^ 16 : sa) + (j >> 1) * 768),
                           "r"(o[0][0]), "r"(o[1][0]), "r"(o[0][1]), "r"(o[1][1]) : "memory");
            if (j == 6) {
              const uint32_t sb6 = (st0 ^ ((~y & 2) << 3)) + (21 + (y >> 1)) * 768;
              if (fin.v == 2)
                asm volatile("st.shared.v4.u32 [%0], {%1,%2,%3,%2};" :: "r"(sb6), "r"(o[0][0]), "r"(0), "r"(o[0][1]) : "memory");
              else
                asm volatile("{\n.reg .pred p;\nsetp.ne.s32 p, %5, 0;\n@p st.shared.v4.u32 [%0], {%1,%2,%3,%4};\n}\n"
                             :: "r"(sb6), "r"(held[0]), "r"(o[0][0]), "r"(held[1]), "r"(o[0][1]), "r"(y & 1) : "memory");
              held[0] = o[0][0]; held[1] = o[0][1];
            }
          }
#pragma unroll
          for (int e = 0; e < 2; e++) {
            if (mid.v) {
              uint32_t a = hfma(cur[j][e], wt[3][e], accB[j][e]);
              a = hfma(cur[j + 1][e], wt[4][e], a);
              accA[j][e] = hfma(cur[j + 2][e], wt[5][e], a);
              ctr[j][e] = cur[j + 1][e];
            }
            if (top.v) {
              uint32_t a = hmul(cur[j][e], wt[0][e]);
              a = hfma(cur[j + 1][e], wt[1][e], a);
              accB[j][e] = hfma(cur[j + 2][e], wt[2][e], a);
            }
          }
        }
      };
      held[0] = held[1] = 0;
      if (nrounds > 1) { coords(1); issue(0, 0); issue(1, 1); issue(2, 2); }
      for (int r = 0; r + 1 < nrounds; r++) {
        const bool more = r + 2 < nrounds;
        mbar_wait(xbar, r & 1);
        if (r > 0) issue(2, 2);
        row(IC<0>{}, IC<0>{}, IC<1>{}, 0, 0);
        mbar_wait(xbar + 8, r & 1);
        issue(0, 3);
        row(IC<0>{}, IC<1>{}, IC<1>{}, 1, 0);
        mbar_wait(sb + BAR_TEMPTY, r & 1);
#pragma unroll 1
        for (int k = 0; k < 2; k++) {
          mbar_wait(xbar + 16, (r + k) & 1);
          issue(1, 4 + 3 * k);
          row(IC<1>{}, IC<1>{}, IC<1>{}, 2, 3 * k);
          mbar_wait(xbar, (r + k + 1) & 1);
          issue(2, 5 + 3 * k);
          row(IC<1>{}, IC<1>{}, IC<1>{}, 0, 3 * k + 1);
          mbar_wait(xbar + 8, (r + k + 1) & 1);
          if (k == 1 && more) coords(r + 2);
          if (k == 0 || more) issue(0, k == 0 ? 6 : 0);
          row(IC<1>{}, IC<1>{}, IC<1>{}, 1, 3 * k + 2);
        }
        mbar_wait(xbar + 16, r & 1);
        if (more) issue(1, 1);
        row(IC<2>{}, IC<0>{}, IC<0>{}, 2, 6);
        __syncwarp();
        warp_arrive(sb + BAR_TFULL);
      }
    }
    asm volatile("bar.sync 5, 384;" ::: "memory");
#pragma unroll 1
    for (int i = 0; i < 8; i++) {
      uint32_t bits = *reinterpret_cast<volatile uint32_t*>(smem + OFF_REDO + 4 * i);
#pragma unroll 1
      for (; bits; bits &= bits - 1)
        slow_window(reinterpret_cast<float*>(smem), window_of((i & 3) * 32 + __ffs(bits) - 1, nfull, cta, ncta, i >> 2), tid - 256, x, dw, wqkv, wo, out);
    }
  } else {
    asm volatile("setmaxnreg.inc.sync.aligned.u32 " CREGS ";");
    const int wg = warp >> 2, w4 = warp & 3, g = lane >> 2, q = lane & 3;
    const int row0 = w4 * 16 + g, row1 = row0 + 8;
    const int ps = min(w4 * 8 + g, 24);
    const int pix0 = ps < 21 ? (ps / 3) * IMG + (ps % 3) * 2 : (ps - 21) * 2 * IMG + 6;
    const int pix1 = pix0 + (ps < 21 ? 1 : ps < 24 ? IMG : 0);
    const uint32_t kv = sb + OFF_KV + wg * KV_BYTES;
    const int srow = w4 * 16 + (lane & 15);
    const uint32_t vst = kv + (lane >> 4) * KV_PITCH + (srow < 56 ? srow : min(srow - 7, 55)) * 16;
    uint32_t misc = ((uint32_t)pix1 << 20) | ((uint32_t)pix0 << 8) | q;
    const uint32_t ninf = q ? 0xfc00fc00u : 0u;
    const uint32_t v48 = kv + (lane >> 3) * KV_PITCH + 48 * 16;
    const uint32_t vmask = (row0 < 49 ? 0xffffu : 0u) | (row1 < 49 ? 0xffff0000u : 0u);

    const uint32_t tx = sb + q * 32 + (row0 < 49 ? OFF_TILE + wg * TILE_BYTES + ps * 768 + (ps & 1) * 16 : OFF_ZERO + 16);
    const int myrounds = window_of(nrounds - 1, nfull, cta, ncta, wg) < 0 ? nrounds - 1 : nrounds;

    if (never == 2) return;
    uint32_t H[48], Y[48];
    const uint64_t* dkv = ds.kv[wg];
    uint32_t P[NP], Ofc[12], p48 = 0;
#pragma unroll
    for (int i = 0; i < 48; i++) Y[i] = 0;
#pragma unroll
    for (int i = 0; i < NP; i++) P[i] = Ofc[i % 12] = 0;
    if (warp == 0) GTS(4);
    load_x<0, 12>(H, tx);
    warp_arrive(sb + BAR_TEMPTY);
    mbar_wait(sb + BAR_F0, 0);
    if (warp == 0) GTS(1);
    if (wg == 1) turn_pass(1);

    uint8_t *o0, *o1;
    uint32_t omask;
    auto out_setup = [&](int r) {
      omask = r >= 0 ? vmask : 0u;
      const int w = window_of(r, nfull, cta, ncta, wg);
      const int wy = w / NWX, wx = w - wy * NWX;
      asm volatile("" : "+r"(misc));
      const uint32_t wb = (uint32_t)(wy * 7 * IMG + wx * 7) * 384u + (misc & 3) * 16;
      o0 = reinterpret_cast<uint8_t*>(out) + (wb + ((misc >> 8) & 0xfff) * 384u);
      o1 = reinterpret_cast<uint8_t*>(out) + (wb + (misc >> 20) * 384u);
    };
#define OUT(c) store_out<c>(Y, o0, o1, omask)
    auto release = [&](int i) { warp_arrive(sb + BAR_E + 8 * i); };

    for (int r = 0;; r++) {
      const uint32_t par = r & 1;
      uint32_t acc[36], S[14], O[14], Q[12], V[12], Ofa[12], Ofb[12], vr[6], k48, mx;
      if (r == myrounds) {
        const bool idle = r < nrounds;
        if (idle) { release(0); release(1); }
        mbar_wait(sb + BAR_FU, par ^ 1);
        turn_wait(wg);
        wg_fence(); mma_pv(O, P, dkv + 4); mma_proj(Y, Ofc, ds.pu[0]); wg_commit();
        turn_pass(wg);
        load_v48(vr, v48);
        wg_wait<0>(); keep(O); keep(Y);
        finish_o(O, vr, p48, vmask, Ofa);
        mbar_wait(sb + BAR_FV, par ^ 1);
        turn_wait(wg);
        wg_fence(); mma_proj(Y, Ofa, ds.pv[0]); wg_commit();
        if (wg == 0 || idle) turn_pass(wg);
        wg_wait<0>(); keep(Y);
        if (idle) { release(2); release(3); turn_wait(wg); turn_pass(wg); }
        out_setup(r - 1);
        OUT(0); PIN(); OUT(1); PIN(); OUT(2); PIN(); OUT(3); PIN(); OUT(4); PIN(); OUT(5);
        if (idle) {
          turn_wait(wg); turn_pass(wg);
          turn_wait(wg); turn_pass(wg);
          turn_wait(wg); turn_pass(wg);
          turn_wait(wg);
        }
        if (warp == 0) GTS(5);
        asm volatile("bar.arrive 5, 384;" ::: "memory");
        break;
      }
      const uint64_t* dq0 = ds.q[par];
      float s1[2], s2[2];
      TR(0);
      turn_wait(wg);
      TR(1);
      wg_fence(); mma_pv(O, P, dkv + 4); wg_commit(); mma_qkv<0, K0A>(acc, H, dq0);
      PIN();
      ln_sums<0, 24>(H, s1, s2);
      PIN();
      wg_fence(); mma_qkv<K0A, 12>(acc, H, dq0);
      if (r > 0) { mbar_wait(sb + BAR_FU, par ^ 1); wg_fence(); mma_proj(Y, Ofc, ds.pu[0]); wg_commit(); }
      else { wg_fence(); wg_commit(); }
      turn_pass(wg);
      TR(2);
      load_v48(vr, v48);
      wg_wait<3>(); keep(O);
      wg_sync(wg);
      PIN();
      finish_o(O, vr, p48, vmask, Ofa);
      ln_sums<24, 48>(H, s1, s2);
      float lim_lo, lim_hi;
      asm volatile("ld.shared.v2.f32 {%0,%1}, [%2];" : "=f"(lim_lo), "=f"(lim_hi) : "r"(sb + OFF_LIM) : "memory");
      bool ok;
      const uint32_t rk = ln_rstd(s1, s2, lim_lo, lim_hi, vmask, ok);
      asm volatile("{\n.reg .pred p;\nsetp.eq.s32 p, %2, 0;\n@p red.shared.or.b32 [%0], %1;\n}\n"
                   :: "r"(sb + OFF_REDO + wg * 16 + (r >> 5) * 4), "r"(1u << (r & 31)), "r"((int)ok) : "memory");
      PIN();
      TR(3);
      wg_wait<1>(); keep(acc);
      TR(4);
      release(0);
      scale12(V, acc, rk); stsm12(V, vst + KV_KOFF);
      scale12(V, acc + 24, rk); stsm12(V, vst);
      PIN();
      wg_wait<0>(); keep(Y);
      PIN();
      proxy_fence();
      scale12(Q, acc + 12, rk);
      if (r > 0) mbar_wait(sb + BAR_FV, par ^ 1); else mbar_wait(sb + BAR_F1, 0);
      TR(5);
      turn_wait(wg);
      TR(6);
      if (r > 0) { wg_fence(); mma_proj(Y, Ofa, ds.pv[0]); wg_commit(); }
      wg_fence(); mma_s(S, Q, dkv); mma_qkv<0, 2>(acc, H, dq0 + 12);
      out_setup(r - 1);
      PIN();
      wg_wait<1>(); keep(Y);
      wg_fence(); mma_qkv<2, 6>(acc, H, dq0 + 12);
      PIN();
      OUT(0);
      PIN();
      wg_wait<1>(); keep(S);
      wg_fence(); mma_qkv<6, 9>(acc, H, dq0 + 12);
      PIN();
      row_max(S, k48, mx, ninf);
      OUT(1);
      PIN();
      wg_fence(); mma_qkv<9, 12>(acc, H, dq0 + 12);
      turn_pass(wg);
      PIN();
      OUT(2); PIN();
      OUT(3); PIN();
      row_exp(S, k48, mx, P, p48);
      PIN();
      TR(7);
      wg_wait<0>(); keep(acc);
      TR(8);
      release(1);
      wg_sync(wg);
      scale12(V, acc, rk); stsm12(V, vst + KV_KOFF);
      scale12(Q, acc + 12, rk); scale12(V, acc + 24, rk); PIN();
      proxy_fence();
#define TURN(ID, OF, DQ, FB, X1)                                                        \
      mbar_wait(sb + FB, par);                                                          \
      TR(ID + 1);                                                                       \
      turn_wait(wg);                                                                    \
      wg_fence(); mma_pv(O, P, dkv + 4); mma_s(S, Q, dkv); wg_commit(); mma_qkv<0, KA>(acc, H, DQ); \
      PIN();                                                                            \
      TR(ID + 2);                                                                       \
      load_v48(vr, v48);                                                                \
      X1;                                                                               \
      PIN();                                                                            \
      wg_wait<1>(); keep(S); keep(O);                                                   \
      wg_sync(wg);                                         \
      wg_fence(); mma_qkv<KA, KB>(acc, H, DQ);                                            \
      PIN();                                                                            \
      stsm12(V, vst);                                                                   \
      finish_o(O, vr, p48, vmask, OF);                                                  \
      row_max(S, k48, mx, ninf);                                                        \
      PIN();                                                                            \
      wg_fence(); mma_qkv<KB, 12>(acc, H, DQ);                                           \
      turn_pass(wg);                                                                    \
      PIN();                                                                            \
      TR(ID + 3);
#define NEXT_HEAD(ID)                                                                   \
      row_exp(S, k48, mx, P, p48);                                                      \
      PIN();                                                                            \
      TR(ID + 4);                                                                       \
      wg_wait<0>(); keep(acc);                                                          \
      scale12(V, acc, rk); stsm12(V, vst + KV_KOFF);                                    \
      scale12(Q, acc + 12, rk); scale12(V, acc + 24, rk); PIN();
      TURN(8, Ofa, dq0 + 24, BAR_FH, OUT(4))
      OUT(5); PIN();
      NEXT_HEAD(8)
      proxy_fence();
      TURN(12, Ofb, dq0 + 36, BAR_FH + 8, )
      auto init_y = [&]() {
#pragma unroll
        for (int i = 0; i < 48; i++) Y[i] = (i & 1) ? H[i] ^ never : h2u(__hadd2_rn(u2h(H[i]), u2h(never)));
        hold<0, 48>(Y); PIN();
      };
      NEXT_HEAD(12)
      init_y();
      proxy_fence();
      TR(17);
      turn_wait(wg);
      wg_fence(); mma_pv(O, P, dkv + 4); mma_s(S, Q, dkv); wg_commit();
      mma_proj(Y, Ofb, ds.pu[1]); wg_commit(); mma_proj(Y, Ofa, ds.pv[1]); wg_commit();
      turn_pass(wg);
      PIN();
      TR(18);
      load_v48(vr, v48);
      if (r + 1 < myrounds) mbar_wait(sb + BAR_TFULL, par);
      load_x<0, 4>(H, tx);
      wg_wait<2>(); keep(S); keep(O);
      wg_sync(wg);
      PIN();
      TR(19);
      row_max(S, k48, mx, ninf);
      finish_o(O, vr, p48, vmask, Ofc);
      stsm12(V, vst);
      PIN();
      wg_wait<1>();
      release(2);
      load_x<4, 8>(H, tx);
      row_exp(S, k48, mx, P, p48);
      PIN();
      load_x<8, 12>(H, tx);
      warp_arrive(sb + BAR_TEMPTY);
      TR(20);
      wg_wait<0>(); keep(Y);
      release(3);
      proxy_fence();
      TR(21);
#undef TURN
#undef NEXT_HEAD
    }
  }
}

typedef CUresult (*EncodeFn)(CUtensorMap*, CUtensorMapDataType, cuuint32_t, void*, const cuuint64_t*, const cuuint64_t*,
                             const cuuint32_t*, const cuuint32_t*, CUtensorMapInterleave, CUtensorMapSwizzle,
                             CUtensorMapL2promotion, CUtensorMapFloatOOBfill);

}

extern "C" void kernel_launch(void* const* d_in, const int* in_sizes, int n_in, void* d_out, int out_size) {
  const __nv_bfloat16* x = (const __nv_bfloat16*)d_in[0];
  const __nv_bfloat16* dw = (const __nv_bfloat16*)d_in[1];
  const __nv_bfloat16* wqkv = (const __nv_bfloat16*)d_in[2];
  const __nv_bfloat16* wo = (const __nv_bfloat16*)d_in[3];
  static EncodeFn encode = nullptr;
  static int nsm = 0;
  static void* wpack = nullptr;
  if (!encode) {
    void* fn = nullptr;
    cudaDriverEntryPointQueryResult qr;
    cudaGetDriverEntryPoint("cuTensorMapEncodeTiled", &fn, cudaEnableDefault, &qr);
    encode = (EncodeFn)fn;
    int dev = 0;
    cudaGetDevice(&dev);
    cudaDeviceGetAttribute(&nsm, cudaDevAttrMultiProcessorCount, dev);
    cudaGetSymbolAddress(&wpack, g_wpack);
    cudaFuncSetAttribute(fused_kernel, cudaFuncAttributeMaxDynamicSharedMemorySize, SMEM_BYTES);
  }
  CUtensorMap tmx;
  cuuint64_t gdim[3] = {CH, IMG, IMG};
  cuuint64_t gstr[2] = {CH * 2, (cuuint64_t)CH * 2 * IMG};
  cuuint32_t box[3] = {64, 9, 1};
  cuuint32_t estr[3] = {1, 1, 1};
  encode(&tmx, CU_TENSOR_MAP_DATA_TYPE_BFLOAT16, 3, (void*)x, gdim, gstr, box, estr, CU_TENSOR_MAP_INTERLEAVE_NONE,
         CU_TENSOR_MAP_SWIZZLE_NONE, L2PROMO, CU_TENSOR_MAP_FLOAT_OOB_FILL_NONE);
  Descs ds;
  for (int i = 0; i < 12; i++)
    for (int b = 0; b < 5; b++) ds.q[b][i] = mkdesc(SMEM_BASE + OFF_W + qkv_pos(b & 1, i), 128, 256);
  for (int i = 0; i < 3; i++) {
    ds.pu[0][i] = ds.pu[1][i] = mkdesc(SMEM_BASE + OFF_W + SLOT_U * SLICE + i * 6144, 128, 256);
    ds.pv[0][i] = ds.pv[1][i] = mkdesc(SMEM_BASE + OFF_W + SLOT_V * SLICE + i * 6144, 128, 256);
  }
  ds.src = (const uint8_t*)wpack;
  for (int g = 0; g < 2; g++)
    for (int i = 0; i < 4; i++) {
      ds.kv[g][i] = mkdesc(SMEM_BASE + OFF_KV + g * KV_BYTES + KV_KOFF + 2 * i * KV_PITCH, KV_PITCH, 128);
      ds.kv[g][4 + i] = mkdesc(SMEM_BASE + OFF_KV + g * KV_BYTES + 256 * i, 128, KV_PITCH);
    }
  CUtensorMap tmp;
  cuuint32_t boxp[3] = {CH, 9, 9};
  encode(&tmp, CU_TENSOR_MAP_DATA_TYPE_BFLOAT16, 3, (void*)x, gdim, gstr, boxp, estr, CU_TENSOR_MAP_INTERLEAVE_NONE,
         CU_TENSOR_MAP_SWIZZLE_NONE, L2PROMO, CU_TENSOR_MAP_FLOAT_OOB_FILL_NONE);
  prepack_kernel<<<96 / PBY, dim3(192, PBY), 0, cudaStreamPerThread>>>(wqkv, wo, x, min(IMG, (2 * nsm + NWX - 1) / NWX * 7 + 1));
  cudaLaunchConfig_t cfg = {};
  cfg.gridDim = dim3(nsm); cfg.blockDim = dim3(384); cfg.dynamicSmemBytes = SMEM_BYTES; cfg.stream = cudaStreamPerThread;
  cudaLaunchAttribute at[1];
  at[0].id = cudaLaunchAttributeProgrammaticStreamSerialization;
  at[0].val.programmaticStreamSerializationAllowed = 1;
  cfg.attrs = at; cfg.numAttrs = 1;
  cudaLaunchKernelEx(&cfg, fused_kernel, tmx, tmp, ds, dw, (__nv_bfloat16*)d_out, 0, x, wqkv, wo);
}
```

```cpp
#include <cuda_runtime.h>
#include <cuda_bf16.h>
#include <cuda_fp16.h>
#include <cuda.h>
#include <stdint.h>

#define CREGS "208"
#define PREGS "88"
#define K48TC 0
#define LA 4
#define K0A 6
#define KA 3
#define KB 9
#define L2PROMO CU_TENSOR_MAP_L2_PROMOTION_NONE
namespace {
constexpr int PBY = 2;
constexpr int NP = K48TC ? 16 : 12;

constexpr int IMG = 511;
constexpr int CH = 192;
constexpr int NWX = 73;
constexpr int NWIN = NWX * NWX;
constexpr int SLICE = 18432;
constexpr int OFF_W = 0;
constexpr int KV_PITCH = 1792, KV_KOFF = 896, KV_BYTES = 6 * KV_PITCH + 1024;
constexpr int OFF_KV = 8 * SLICE;
constexpr int TILE_BYTES = 25 * 768;
constexpr int OFF_TILE = OFF_KV + 2 * KV_BYTES;
constexpr int XSLOT = 2304;
constexpr int OFF_X = OFF_TILE + 2 * TILE_BYTES;
constexpr int OFF_BAR = OFF_X + 9 * XSLOT;
constexpr int BAR_FH = OFF_BAR;
constexpr int BAR_FU = OFF_BAR + 16, BAR_FV = OFF_BAR + 24;
constexpr int BAR_F0 = OFF_BAR + 32, BAR_F1 = OFF_BAR + 40;
constexpr int BAR_E = OFF_BAR + 80;
constexpr int BAR_XFULL = OFF_BAR + 112;
constexpr int BAR_TFULL = OFF_BAR + 184;
constexpr int BAR_TEMPTY = OFF_BAR + 192;
constexpr int OFF_LIM = OFF_BAR + 200;
constexpr int OFF_REDO = OFF_BAR + 208;
constexpr int BAR_FIRST = OFF_BAR + 240;
constexpr int OFF_TRACE = OFF_BAR + 248;
constexpr int OFF_HALO = OFF_W + 3 * SLICE, HALO_BYTES = 81 * 384;
constexpr int SMEM_BYTES = OFF_TRACE;

__host__ __device__ constexpr int qkv_pos(int h, int s) { return 3 * h * SLICE + s * 4608; }
__host__ __device__ constexpr int wo_pos(int s) { return 12 * SLICE + s * 6144; }
constexpr int SLOT_U = 6, SLOT_V = 7;
constexpr int SMEM_BASE = 1024;
struct Descs { uint64_t q[5][12]; uint64_t pu[2][3], pv[2][3]; uint64_t kv[2][8]; const uint8_t* src; };

__device__ uint4 g_wpack[16 * SLICE / 16];
__device__ float2 g_wnorm[96];
#define TR(id)
#define GTS(i)
template <int V> struct IC { static constexpr int v = V; };
typedef __nv_bfloat162 bf2;
__device__ __forceinline__ bf2 u2b(uint32_t u) { return *reinterpret_cast<bf2*>(&u); }
__device__ __forceinline__ uint32_t b2u(bf2 b) { return *reinterpret_cast<uint32_t*>(&b); }
__device__ __forceinline__ uint32_t pack2(float lo, float hi) {
  uint32_t r; asm("cvt.rn.bf16x2.f32 %0, %1, %2;" : "=r"(r) : "f"(hi), "f"(lo)); return r;
}
__device__ __forceinline__ uint32_t hadd(uint32_t a, uint32_t b) { return b2u(__hadd2_rn(u2b(a), u2b(b))); }
__device__ __forceinline__ uint32_t hmul(uint32_t a, uint32_t b) { return b2u(__hmul2_rn(u2b(a), u2b(b))); }
__device__ __forceinline__ uint32_t hfma(uint32_t a, uint32_t b, uint32_t c) { return b2u(__hfma2(u2b(a), u2b(b), u2b(c))); }
__device__ __forceinline__ __half2 u2h(uint32_t u) { return *reinterpret_cast<__half2*>(&u); }
__device__ __forceinline__ uint32_t h2u(__half2 b) { return *reinterpret_cast<uint32_t*>(&b); }
__device__ __forceinline__ uint32_t packh(float lo, float hi) {
  uint32_t r; asm("cvt.rn.f16x2.f32 %0, %1, %2;" : "=r"(r) : "f"(hi), "f"(lo)); return r;
}
__device__ __forceinline__ uint32_t fmax2(uint32_t a, uint32_t b) { return h2u(__hmax2(u2h(a), u2h(b))); }
template <int HI> __device__ __forceinline__ __half2 hcast(uint32_t a) { return HI ? __high2half2(u2h(a)) : __low2half2(u2h(a)); }
template <int HI> __device__ __forceinline__ uint32_t fmul_b(uint32_t a, uint32_t s) { return h2u(__hmul2_rn(u2h(a), hcast<HI>(s))); }
template <int HI> __device__ __forceinline__ uint32_t fsub_b(uint32_t a, uint32_t s) { return h2u(__hsub2_rn(u2h(a), hcast<HI>(s))); }
__device__ __forceinline__ uint32_t fex2(uint32_t a) { uint32_t r; asm("ex2.approx.f16x2 %0, %1;" : "=r"(r) : "r"(a)); return r; }
__device__ __forceinline__ float lo2f(uint32_t a) { return __uint_as_float(a << 16); }
__device__ __forceinline__ float hi2f(uint32_t a) { return __uint_as_float(a & 0xffff0000u); }

__device__ __forceinline__ void mbar_init(uint32_t bar, uint32_t cnt) { asm volatile("mbarrier.init.shared::cta.b64 [%0], %1;" :: "r"(bar), "r"(cnt) : "memory"); }
__device__ __forceinline__ void mbar_wait(uint32_t bar, uint32_t parity) {
  asm volatile("{\n.reg .pred p;\n.reg .u32 n;\n"
               "mbarrier.try_wait.parity.shared::cta.b64 p, [%0], %1;\n"
               "@p bra.uni DONE_%=;\n"
               "mov.u32 n, 0;\n"
               "AGAIN_%=:\n"
               "mbarrier.try_wait.parity.shared::cta.b64 p, [%0], %1;\n"
               "@p bra.uni DONE_%=;\n"
               "add.u32 n, n, 1;\n"
               "setp.lt.u32 p, n, 0x1000000;\n"
               "@p bra.uni AGAIN_%=;\n"
               "trap;\n"
               "DONE_%=:\n}\n" :: "r"(bar), "r"(parity) : "memory");
}
__device__ __forceinline__ void wg_fence() { asm volatile("wgmma.fence.sync.aligned;" ::: "memory"); }
__device__ __forceinline__ void wg_commit() { asm volatile("wgmma.commit_group.sync.aligned;" ::: "memory"); }
template <int N> __device__ __forceinline__ void wg_wait() { asm volatile("wgmma.wait_group.sync.aligned %0;" :: "n"(N) : "memory"); }
#define BAR_BY_WG(OP, ID0, ID1, CNT) asm volatile("{\n.reg .pred p;\nsetp.eq.s32 p, %0, 0;\n@p " OP " " #ID0 ", " #CNT ";\n@!p " OP " " #ID1 ", " #CNT ";\n}\n" :: "r"(wg) : "memory")
__device__ __forceinline__ void wg_sync(int wg) { BAR_BY_WG("bar.sync", 1, 2, 128); }
__device__ __forceinline__ void turn_wait(int wg) { BAR_BY_WG("bar.sync", 3, 4, 256); }
__device__ __forceinline__ void turn_pass(int wg) { BAR_BY_WG("bar.arrive", 4, 3, 256); }
__device__ __forceinline__ void stsm4(uint32_t addr, uint32_t a, uint32_t b, uint32_t c, uint32_t d) {
  asm volatile("stmatrix.sync.aligned.m8n8.x4.shared.b16 [%0], {%1,%2,%3,%4};" :: "r"(addr), "r"(a), "r"(b), "r"(c), "r"(d) : "memory");
}
template <int N> __device__ __forceinline__ void keep(float (&d)[N]) {
#pragma unroll
  for (int i = 0; i < N; i++) asm volatile("" : "+f"(d[i]) :: "memory");
}
template <int N> __device__ __forceinline__ void keep(uint32_t (&d)[N]) {
#pragma unroll
  for (int i = 0; i < N; i++) asm volatile("" : "+r"(d[i]) :: "memory");
}
__host__ __device__ __forceinline__ uint64_t mkdesc(uint32_t addr, uint32_t lbo, uint32_t sbo) {
  return ((uint64_t)(sbo >> 4) << 32) | (uint64_t)(((lbo >> 4) << 16) | ((addr & 0x3FFFF) >> 4));
}

template <int SCALE_D>
__device__ __forceinline__ void wgmma_n144(uint32_t (&d)[36], uint32_t a0, uint32_t a1, uint32_t a2, uint32_t a3, uint64_t descB) {
  if (SCALE_D == 0)
  asm volatile("wgmma.mma_async.sync.aligned.m64n144k16.f16.f16.f16 "
    "{%0, %1, %2, %3, %4, %5, %6, %7, %8, %9, %10, %11, %12, %13, %14, %15, "
    "%16, %17, %18, %19, %20, %21, %22, %23, %24, %25, %26, %27, %28, %29, %30, %31, "
    "%32, %33, %34, %35}, "
    "{%36, %37, %38, %39}, %40, 0, 1, 1, 0;\n"
    : "=r"(d[0]), "=r"(d[1]), "=r"(d[2]), "=r"(d[3]), "=r"(d[4]), "=r"(d[5]), "=r"(d[6]), "=r"(d[7]),
      "=r"(d[8]), "=r"(d[9]), "=r"(d[10]), "=r"(d[11]), "=r"(d[12]), "=r"(d[13]), "=r"(d[14]), "=r"(d[15]),
      "=r"(d[16]), "=r"(d[17]), "=r"(d[18]), "=r"(d[19]), "=r"(d[20]), "=r"(d[21]), "=r"(d[22]), "=r"(d[23]),
      "=r"(d[24]), "=r"(d[25]), "=r"(d[26]), "=r"(d[27]), "=r"(d[28]), "=r"(d[29]), "=r"(d[30]), "=r"(d[31]),
      "=r"(d[32]), "=r"(d[33]), "=r"(d[34]), "=r"(d[35])
    : "r"(a0), "r"(a1), "r"(a2), "r"(a3), "l"(descB));
  else
  asm volatile("wgmma.mma_async.sync.aligned.m64n144k16.f16.f16.f16 "
    "{%0, %1, %2, %3, %4, %5, %6, %7, %8, %9, %10, %11, %12, %13, %14, %15, "
    "%16, %17, %18, %19, %20, %21, %22, %23, %24, %25, %26, %27, %28, %29, %30, %31, "
    "%32, %33, %34, %35}, "
    "{%36, %37, %38, %39}, %40, 1, 1, 1, 0;\n"
    : "+r"(d[0]), "+r"(d[1]), "+r"(d[2]), "+r"(d[3]), "+r"(d[4]), "+r"(d[5]), "+r"(d[6]), "+r"(d[7]),
      "+r"(d[8]), "+r"(d[9]), "+r"(d[10]), "+r"(d[11]), "+r"(d[12]), "+r"(d[13]), "+r"(d[14]), "+r"(d[15]),
      "+r"(d[16]), "+r"(d[17]), "+r"(d[18]), "+r"(d[19]), "+r"(d[20]), "+r"(d[21]), "+r"(d[22]), "+r"(d[23]),
      "+r"(d[24]), "+r"(d[25]), "+r"(d[26]), "+r"(d[27]), "+r"(d[28]), "+r"(d[29]), "+r"(d[30]), "+r"(d[31]),
      "+r"(d[32]), "+r"(d[33]), "+r"(d[34]), "+r"(d[35])
    : "r"(a0), "r"(a1), "r"(a2), "r"(a3), "l"(descB));
}

template <int SCALE_D>
__device__ __forceinline__ void wgmma_n192(uint32_t (&d)[48], uint32_t a0, uint32_t a1, uint32_t a2, uint32_t a3, uint64_t descB) {
  if (SCALE_D == 0)
  asm volatile("wgmma.mma_async.sync.aligned.m64n192k16.f16.f16.f16 "
    "{%0, %1, %2, %3, %4, %5, %6, %7, %8, %9, %10, %11, %12, %13, %14, %15, "
    "%16, %17, %18, %19, %20, %21, %22, %23, %24, %25, %26, %27, %28, %29, %30, %31, "
    "%32, %33, %34, %35, %36, %37, %38, %39, %40, %41, %42, %43, %44, %45, %46, %47}, "
    "{%48, %49, %50, %51}, %52, 0, 1, 1, 0;\n"
    : "=r"(d[0]), "=r"(d[1]), "=r"(d[2]), "=r"(d[3]), "=r"(d[4]), "=r"(d[5]), "=r"(d[6]), "=r"(d[7]),
      "=r"(d[8]), "=r"(d[9]), "=r"(d[10]), "=r"(d[11]), "=r"(d[12]), "=r"(d[13]), "=r"(d[14]), "=r"(d[15]),
      "=r"(d[16]), "=r"(d[17]), "=r"(d[18]), "=r"(d[19]), "=r"(d[20]), "=r"(d[21]), "=r"(d[22]), "=r"(d[23]),
      "=r"(d[24]), "=r"(d[25]), "=r"(d[26]), "=r"(d[27]), "=r"(d[28]), "=r"(d[29]), "=r"(d[30]), "=r"(d[31]),
      "=r"(d[32]), "=r"(d[33]), "=r"(d[34]), "=r"(d[35]), "=r"(d[36]), "=r"(d[37]), "=r"(d[38]), "=r"(d[39]),
      "=r"(d[40]), "=r"(d[41]), "=r"(d[42]), "=r"(d[43]), "=r"(d[44]), "=r"(d[45]), "=r"(d[46]), "=r"(d[47])
    : "r"(a0), "r"(a1), "r"(a2), "r"(a3), "l"(descB));
  else
  asm volatile("wgmma.mma_async.sync.aligned.m64n192k16.f16.f16.f16 "
    "{%0, %1, %2, %3, %4, %5, %6, %7, %8, %9, %10, %11, %12, %13, %14, %15, "
    "%16, %17, %18, %19, %20, %21, %22, %23, %24, %25, %26, %27, %28, %29, %30, %31, "
    "%32, %33, %34, %35, %36, %37, %38, %39, %40, %41, %42, %43, %44, %45, %46, %47}, "
    "{%48, %49, %50, %51}, %52, 1, 1, 1, 0;\n"
    : "+r"(d[0]), "+r"(d[1]), "+r"(d[2]), "+r"(d[3]), "+r"(d[4]), "+r"(d[5]), "+r"(d[6]), "+r"(d[7]),
      "+r"(d[8]), "+r"(d[9]), "+r"(d[10]), "+r"(d[11]), "+r"(d[12]), "+r"(d[13]), "+r"(d[14]), "+r"(d[15]),
      "+r"(d[16]), "+r"(d[17]), "+r"(d[18]), "+r"(d[19]), "+r"(d[20]), "+r"(d[21]), "+r"(d[22]), "+r"(d[23]),
      "+r"(d[24]), "+r"(d[25]), "+r"(d[26]), "+r"(d[27]), "+r"(d[28]), "+r"(d[29]), "+r"(d[30]), "+r"(d[31]),
      "+r"(d[32]), "+r"(d[33]), "+r"(d[34]), "+r"(d[35]), "+r"(d[36]), "+r"(d[37]), "+r"(d[38]), "+r"(d[39]),
      "+r"(d[40]), "+r"(d[41]), "+r"(d[42]), "+r"(d[43]), "+r"(d[44]), "+r"(d[45]), "+r"(d[46]), "+r"(d[47])
    : "r"(a0), "r"(a1), "r"(a2), "r"(a3), "l"(descB));
}

template <int SCALE_D>
__device__ __forceinline__ void wgmma_n56(uint32_t (&d)[14], uint32_t a0, uint32_t a1, uint32_t a2, uint32_t a3, uint64_t descB) {
  if (SCALE_D == 0)
  asm volatile("wgmma.mma_async.sync.aligned.m64n56k16.f16.f16.f16 "
    "{%0, %1, %2, %3, %4, %5, %6, %7, %8, %9, %10, %11, %12, %13}, "
    "{%14, %15, %16, %17}, %18, 0, 1, 1, 0;\n"
    : "=r"(d[0]), "=r"(d[1]), "=r"(d[2]), "=r"(d[3]), "=r"(d[4]), "=r"(d[5]), "=r"(d[6]), "=r"(d[7]),
      "=r"(d[8]), "=r"(d[9]), "=r"(d[10]), "=r"(d[11]), "=r"(d[12]), "=r"(d[13])
    : "r"(a0), "r"(a1), "r"(a2), "r"(a3), "l"(descB));
  else
  asm volatile("wgmma.mma_async.sync.aligned.m64n56k16.f16.f16.f16 "
    "{%0, %1, %2, %3, %4, %5, %6, %7, %8, %9, %10, %11, %12, %13}, "
    "{%14, %15, %16, %17}, %18, 1, 1, 1, 0;\n"
    : "+r"(d[0]), "+r"(d[1]), "+r"(d[2]), "+r"(d[3]), "+r"(d[4]), "+r"(d[5]), "+r"(d[6]), "+r"(d[7]),
      "+r"(d[8]), "+r"(d[9]), "+r"(d[10]), "+r"(d[11]), "+r"(d[12]), "+r"(d[13])
    : "r"(a0), "r"(a1), "r"(a2), "r"(a3), "l"(descB));
}

template <int SCALE_D>
__device__ __forceinline__ void wgmma_n56t(uint32_t (&d)[14], uint32_t a0, uint32_t a1, uint32_t a2, uint32_t a3, uint64_t descB) {
  if (SCALE_D == 0)
  asm volatile("wgmma.mma_async.sync.aligned.m64n56k16.f16.f16.f16 "
    "{%0, %1, %2, %3, %4, %5, %6, %7, %8, %9, %10, %11, %12, %13}, "
    "{%14, %15, %16, %17}, %18, 0, 1, 1, 1;\n"
    : "=r"(d[0]), "=r"(d[1]), "=r"(d[2]), "=r"(d[3]), "=r"(d[4]), "=r"(d[5]), "=r"(d[6]), "=r"(d[7]),
      "=r"(d[8]), "=r"(d[9]), "=r"(d[10]), "=r"(d[11]), "=r"(d[12]), "=r"(d[13])
    : "r"(a0), "r"(a1), "r"(a2), "r"(a3), "l"(descB));
  else
  asm volatile("wgmma.mma_async.sync.aligned.m64n56k16.f16.f16.f16 "
    "{%0, %1, %2, %3, %4, %5, %6, %7, %8, %9, %10, %11, %12, %13}, "
    "{%14, %15, %16, %17}, %18, 1, 1, 1, 1;\n"
    : "+r"(d[0]), "+r"(d[1]), "+r"(d[2]), "+r"(d[3]), "+r"(d[4]), "+r"(d[5]), "+r"(d[6]), "+r"(d[7]),
      "+r"(d[8]), "+r"(d[9]), "+r"(d[10]), "+r"(d[11]), "+r"(d[12]), "+r"(d[13])
    : "r"(a0), "r"(a1), "r"(a2), "r"(a3), "l"(descB));
}

__global__ void __launch_bounds__(192 * PBY) prepack_kernel(const __nv_bfloat16* __restrict__ wqkv, const __nv_bfloat16* __restrict__ wo,
                                                      const __nv_bfloat16* __restrict__ x, int first_rows) {
  asm volatile("griddepcontrol.launch_dependents;");
  __shared__ float red2[PBY][6][16];
  float (*red)[16] = red2[threadIdx.y];
  __shared__ __align__(16) __half stage[PBY][1536];
  __half* dst = stage[threadIdx.y];
  const int c = threadIdx.x, nb = blockIdx.x * PBY + threadIdx.y;
  uint32_t u[4];
  int base, gofs;
  float scale = 1.0f;
  if (nb < 72) {
    const int h = nb / 18, j = nb % 18, part = j / 6;
    const int col = (part == 0 ? 192 : part == 1 ? 0 : 384) + h * 48 + (j % 6) * 8;
    const uint4 raw = *reinterpret_cast<const uint4*>(wqkv + c * 576 + col);
    u[0] = raw.x; u[1] = raw.y; u[2] = raw.z; u[3] = raw.w;
    if (part == 1) scale = 0.14433756729740643f * 1.4426950408889634f;
    const int cc = c >> 5, q = (c >> 3) & 3, s1 = (c >> 2) & 1, hh = (c >> 1) & 1, e = c & 1;
    base = (2 * cc + s1) * 128 + hh * 64 + 2 * q + e;
    gofs = qkv_pos(h, c >> 4) + j * 256;
  } else {
    const int jb = nb - 72;
#pragma unroll
    for (int i = 0; i < 4; i++) u[i] = *reinterpret_cast<const uint32_t*>(wo + c * 192 + 32 * (jb >> 2) + 8 * i + 2 * (jb & 3));
    base = (c >> 4) * 128 + ((c >> 3) & 1) * 64 + (c & 7);
    gofs = wo_pos(c >> 4) + jb * 256;
  }
  if (threadIdx.y == 0 && c < 32)
    for (int i = blockIdx.x + 96 / PBY * c; i < first_rows * NWX / 4; i += 96 / PBY * 32)
      asm volatile("cp.async.bulk.prefetch.L2.global [%0], %1;" :: "l"(reinterpret_cast<const uint8_t*>(x) + (size_t)i * 10752), "n"(10752) : "memory");
  float v[8], t[16];
#pragma unroll
  for (int i = 0; i < 4; i++) { v[2 * i] = lo2f(u[i]); v[2 * i + 1] = hi2f(u[i]); }
#pragma unroll
  for (int i = 0; i < 16; i++) t[i] = i < 8 ? v[i] : v[i - 8] * v[i - 8];
#pragma unroll
  for (int n = 8; n >= 1; n >>= 1) {
    const bool up = c & (2 * n);
#pragma unroll
    for (int i = 0; i < n; i++) t[i] = (up ? t[i + n] : t[i]) + __shfl_xor_sync(~0u, up ? t[i] : t[i + n], 2 * n);
  }
  t[0] += __shfl_xor_sync(~0u, t[0], 1);
  if (!(c & 1)) red[c >> 5][(c & 31) >> 1] = t[0];
  __syncthreads();
#pragma unroll
  for (int i = 0; i < 16; i++) t[i] = red[0][i] + red[1][i] + red[2][i] + red[3][i] + red[4][i] + red[5][i];
  float mx = 0.f, sm = 0.f;
#pragma unroll
  for (int n = 0; n < 8; n++) {
    const float m = nb < 72 ? t[n] * (1.0f / 192.0f) : 0.f;
    dst[base + n * 8] = __float2half_rn(__bfloat162float(__float2bfloat16((v[n] - m) * scale)));
    const float nn = (t[8 + n] - 0.999f * m * t[n]) * scale * scale * 1.01f;
    mx = fmaxf(mx, nn); sm += nn;
  }
  if (c == 0) g_wnorm[nb] = make_float2(mx, sm);
  __syncthreads();
  g_wpack[gofs / 16 + (c & 15)] = reinterpret_cast<const uint4*>(dst)[c];
}

__device__ __forceinline__ int window_of(int round, int nfull, int cta, int ncta, int wg) {
  if (round < nfull) return round * 2 * ncta + 2 * cta + wg;
  const int rem = NWIN - nfull * 2 * ncta;
  const int i = cta + wg * ncta;
  return i < rem ? nfull * 2 * ncta + i : -1;
}

template <int S0 = 0, int S1 = 12>
__device__ __forceinline__ void mma_qkv(uint32_t (&acc)[36], const uint32_t (&A)[48], const uint64_t* d) {
#pragma unroll
  for (int s = S0; s < S1; s++) {
    if (s == 0) wgmma_n144<0>(acc, A[4 * s], A[4 * s + 1], A[4 * s + 2], A[4 * s + 3], d[s]);
    else        wgmma_n144<1>(acc, A[4 * s], A[4 * s + 1], A[4 * s + 2], A[4 * s + 3], d[s]);
  }
  wg_commit();
}
__device__ __forceinline__ void mma_proj(uint32_t (&acc)[48], const uint32_t (&A)[12], const uint64_t* d) {
#pragma unroll
  for (int s = 0; s < 3; s++) wgmma_n192<1>(acc, A[4 * s], A[4 * s + 1], A[4 * s + 2], A[4 * s + 3], d[s]);
}
__device__ __forceinline__ void mma_s(uint32_t (&S)[14], const uint32_t (&Q)[12], const uint64_t* d) {
  wgmma_n56<0>(S, Q[0], Q[1], Q[2], Q[3], d[0]);
  wgmma_n56<1>(S, Q[4], Q[5], Q[6], Q[7], d[1]);
  wgmma_n56<1>(S, Q[8], Q[9], Q[10], Q[11], d[2]);
}
__device__ __forceinline__ void mma_pv(uint32_t (&O)[14], const uint32_t (&P)[NP], const uint64_t* d) {
  wgmma_n56t<0>(O, P[0], P[1], P[2], P[3], d[0]);
  wgmma_n56t<1>(O, P[4], P[5], P[6], P[7], d[1]);
  wgmma_n56t<1>(O, P[8], P[9], P[10], P[11], d[2]);
  if (K48TC) wgmma_n56t<1>(O, P[NP - 4], P[NP - 3], P[NP - 2], P[NP - 1], d[3]);
}

#define PIN() asm volatile("pmevent 0;" ::: "memory")
template <int A, int B> __device__ __forceinline__ void hold(uint32_t* v) {
#pragma unroll
  for (int i = A; i < B; i++) asm volatile("" : "+r"(v[i]));
}
__device__ __forceinline__ void stsm12(const uint32_t* v, uint32_t addr) {
#pragma unroll
  for (int j = 0; j < 3; j++) stsm4(addr + 2 * j * KV_PITCH, v[4 * j], v[4 * j + 1], v[4 * j + 2], v[4 * j + 3]);
}
__device__ __forceinline__ void load_v48(uint32_t (&v)[6], uint32_t addr) {
  if (K48TC) return;
  asm volatile("ldmatrix.sync.aligned.m8n8.x4.shared.b16 {%0,%1,%2,%3}, [%4];" : "=r"(v[0]), "=r"(v[1]), "=r"(v[2]), "=r"(v[3]) : "r"(addr) : "memory");
  asm volatile("ldmatrix.sync.aligned.m8n8.x2.shared.b16 {%0,%1}, [%2];" : "=r"(v[4]), "=r"(v[5]) : "r"(addr + 4 * KV_PITCH) : "memory");
}
__device__ __forceinline__ void finish_o(const uint32_t (&O)[14], const uint32_t (&v)[6], uint32_t p48, uint32_t vmask, uint32_t (&Of)[12]) {
  const float2 l = K48TC ? make_float2(__low2float(u2h(O[12])), __low2float(u2h(O[13])))
                         : __half22float2(__hadd2_rn(u2h(__byte_perm(O[12], O[13], 0x5410)), u2h(p48)));
  float i0, i1;
  asm("rcp.approx.ftz.f32 %0, %1;" : "=f"(i0) : "f"(l.x));
  asm("rcp.approx.ftz.f32 %0, %1;" : "=f"(i1) : "f"(l.y));
  const uint32_t inv = packh(i0, i1) & vmask;
#pragma unroll
  for (int i = 0; i < 12; i++) {
    const uint32_t t = K48TC ? O[i] : h2u(__hfma2(u2h(v[i >> 1]), (i & 1) ? hcast<1>(p48) : hcast<0>(p48), u2h(O[i])));
    Of[i] = (i & 1) ? fmul_b<1>(t, inv) : fmul_b<0>(t, inv);
  }
  hold<0, 12>(Of);
}
#define PSTAT 12
template <int A, int B>
__device__ __forceinline__ void ln_sums(const uint32_t (&X)[48], float (&s1)[2], float (&s2)[2]) {
  if (PSTAT) {
    static_assert(PSTAT == 0 || (A % (2 * PSTAT + !PSTAT) == 0 && B % (2 * PSTAT + !PSTAT) == 0), "whole groups");
#pragma unroll
    for (int g = A; g < B; g += 2 * PSTAT + !PSTAT)
#pragma unroll
      for (int a = 0; a < 2; a++) {
        __half2 p1 = u2h(X[g + a]), p2 = __hmul2_rn(p1, p1);
#pragma unroll
        for (int i = 1; i < PSTAT; i++) { const __half2 v = u2h(X[g + a + 2 * i]); p1 = __hadd2_rn(p1, v); p2 = __hfma2(v, v, p2); }
        const float2 f1 = __half22float2(p1), f2 = __half22float2(p2);
        s1[a] = g == 0 ? f1.x + f1.y : s1[a] + (f1.x + f1.y);
        s2[a] = g == 0 ? f2.x + f2.y : s2[a] + (f2.x + f2.y);
      }
  } else {
#pragma unroll
    for (int i = A; i < B; i++) {
      const float2 f = __half22float2(u2h(X[i]));
      s1[i & 1] = i < 2 ? f.x + f.y : s1[i & 1] + (f.x + f.y);
      s2[i & 1] = fmaf(f.x, f.x, i < 2 ? f.y * f.y : fmaf(f.y, f.y, s2[i & 1]));
    }
  }
  asm volatile("" : "+f"(s1[0]), "+f"(s1[1]), "+f"(s2[0]), "+f"(s2[1]));
}
__device__ __forceinline__ uint32_t ln_rstd(const float (&s1)[2], const float (&s2)[2], float lo, float hi, uint32_t vmask, bool& ok) {
  float r[2];
  ok = true;
#pragma unroll
  for (int a = 0; a < 2; a++) {
    float m = s1[a], v = s2[a];
    m += __shfl_xor_sync(~0u, m, 1); v += __shfl_xor_sync(~0u, v, 1);
    m += __shfl_xor_sync(~0u, m, 2); v += __shfl_xor_sync(~0u, v, 2);
    ok = ok & (v <= hi) & ((v >= lo) | !(vmask >> (16 * a) & 1));
    m *= 1.0f / 192.0f;
    m *= m;
    v = fmaxf(fmaf(v, 1.0f / 192.0f, -m), 0.f) + 1e-5f;
    ok = ok & (m <= (PSTAT ? 16.f : 64.f) * v);
    asm("rsqrt.approx.ftz.f32 %0, %1;" : "=f"(r[a]) : "f"(v));
  }
  uint32_t rk = packh(r[0], r[1]);
  hold<0, 1>(&rk);
  return rk;
}
__device__ __forceinline__ void scale12(uint32_t (&D)[12], const uint32_t* a, uint32_t r) {
#pragma unroll
  for (int i = 0; i < 12; i++) D[i] = (i & 1) ? fmul_b<1>(a[i], r) : fmul_b<0>(a[i], r);
  hold<0, 12>(D);
}
template <int CC>
__device__ __forceinline__ void store_out(const uint32_t (&Y)[48], uint8_t* o0, uint8_t* o1, uint32_t vmask) {
  uint32_t T[8];
#pragma unroll
  for (int i = 0; i < 8; i++) {
    const float2 f = __half22float2(u2h(Y[8 * CC + i]));
    T[i] = pack2(f.x, f.y);
  }
  asm volatile("{\n.reg .pred p;\nsetp.ne.u32 p, %5, 0;\n@p st.global.cs.v4.u32 [%0], {%1,%2,%3,%4};\n}\n"
               :: "l"(o0 + CC * 64), "r"(T[0]), "r"(T[2]), "r"(T[4]), "r"(T[6]), "r"(vmask) : "memory");
  asm volatile("{\n.reg .pred p;\nsetp.lt.s32 p, %5, 0;\n@p st.global.cs.v4.u32 [%0], {%1,%2,%3,%4};\n}\n"
               :: "l"(o1 + CC * 64), "r"(T[1]), "r"(T[3]), "r"(T[5]), "r"(T[7]), "r"(vmask) : "memory");
}
__device__ __forceinline__ void proxy_fence() { asm volatile("fence.proxy.async.shared::cta;" ::: "memory"); }
__device__ __forceinline__ uint32_t fadd2(uint32_t a, uint32_t b) { return h2u(__hadd2_rn(u2h(a), u2h(b))); }
__device__ __forceinline__ void row_max(const uint32_t (&S)[14], uint32_t& k48, uint32_t& mx, uint32_t ninf) {
  k48 = K48TC ? __byte_perm(S[12], S[13], 0x5410) | ninf : __shfl_sync(~0u, __byte_perm(S[12], S[13], 0x5410), 0, 4);
  const uint32_t m0 = fmax2(fmax2(fmax2(S[0], S[2]), S[4]), fmax2(fmax2(S[6], S[8]), S[10]));
  const uint32_t m1 = fmax2(fmax2(fmax2(S[1], S[3]), S[5]), fmax2(fmax2(S[7], S[9]), S[11]));
  mx = fmax2(__byte_perm(m0, m1, 0x5410), __byte_perm(m0, m1, 0x7632));
  if (K48TC) mx = fmax2(mx, k48);
  mx = fmax2(mx, __shfl_xor_sync(~0u, mx, 1));
  mx = fmax2(mx, __shfl_xor_sync(~0u, mx, 2));
  if (!K48TC) mx = fmax2(mx, k48);
  hold<0, 1>(&mx);
}
__device__ __forceinline__ void row_exp(const uint32_t (&S)[14], uint32_t k48, uint32_t mx, uint32_t (&P)[NP], uint32_t& p48) {
#pragma unroll
  for (int j = 0; j < 12; j++) P[j] = fex2((j & 1) ? fsub_b<1>(S[j], mx) : fsub_b<0>(S[j], mx));
  if (K48TC) {
    uint16_t el, eh;
    asm("{\n.reg .b16 l, h;\nmov.b32 {l, h}, %2;\nex2.approx.f16 %0, l;\nex2.approx.f16 %1, h;\n}\n" : "=h"(el), "=h"(eh) : "r"(h2u(__hsub2_rn(u2h(k48), u2h(mx)))));
    P[NP - 4] = el; P[NP - 3] = eh; P[NP - 2] = 0; P[NP - 1] = 0;
  } else {
    p48 = fex2(h2u(__hsub2_rn(u2h(k48), u2h(mx))));
    hold<0, 1>(&p48);
  }
  hold<0, NP>(P);
}
template <int S0, int S1>
__device__ __forceinline__ void load_x(uint32_t (&X)[48], uint32_t t0) {
#pragma unroll
  for (int s = S0; s < S1; s++)
    asm volatile("ld.shared.v4.u32 {%0,%1,%2,%3}, [%4];" : "=r"(X[4 * s]), "=r"(X[4 * s + 1]), "=r"(X[4 * s + 2]), "=r"(X[4 * s + 3])
                 : "r"(((s & 1) ? (t0 ^ 16) : t0) + (s >> 1) * 128) : "memory");
}

template <int CNT, int EXPECT = CNT * SLICE>
__device__ __forceinline__ void load_slices(uint32_t sb, const uint8_t* src, int slice, int slot, int bar) {
  if (EXPECT)
    asm volatile("{\n.reg .pred p;\nelect.sync _|p, 0xffffffff;\n@p mbarrier.arrive.expect_tx.shared::cta.b64 _, [%0], %1;\n}\n"
                 :: "r"(sb + bar), "n"(EXPECT) : "memory");
  asm volatile("{\n.reg .pred p;\nelect.sync _|p, 0xffffffff;\n"
               "@p cp.async.bulk.shared::cluster.global.mbarrier::complete_tx::bytes [%0], [%1], %2, [%3];\n}\n"
               :: "r"(sb + OFF_W + slot * SLICE), "l"(src + slice * SLICE), "n"(CNT * SLICE), "r"(sb + bar) : "memory");
}
__device__ __forceinline__ void warp_arrive(uint32_t bar) {
  asm volatile("{\n.reg .pred p;\nelect.sync _|p, 0xffffffff;\n@p mbarrier.arrive.shared::cta.b64 _, [%0];\n}\n" :: "r"(bar) : "memory");
}

__device__ __forceinline__ float2 fp16_limits(int lane) {
  float mx[4] = {0.f, 0.f, 0.f, 0.f}, sm[4] = {0.f, 0.f, 0.f, 0.f};
#pragma unroll
  for (int i = 0; i < 3; i++) {
    const int nb = lane + 32 * i, part = nb < 72 ? (nb % 18) / 6 : 3;
    const float2 w = g_wnorm[nb];
#pragma unroll
    for (int k = 0; k < 4; k++) if (part == k) { mx[k] = fmaxf(mx[k], w.x); sm[k] += w.y; }
  }
#pragma unroll
  for (int k = 0; k < 4; k++)
#pragma unroll
    for (int d = 16; d; d >>= 1) { mx[k] = fmaxf(mx[k], __shfl_xor_sync(~0u, mx[k], d)); sm[k] += __shfl_xor_sync(~0u, sm[k], d); }
  const float big = fmaxf(fmaxf(mx[0], mx[1]), mx[2]);
  float small = 1.f;
  bool good = sm[0] + sm[1] + sm[2] + sm[3] < 1e30f;
#pragma unroll
  for (int k = 0; k < 4; k++) { good = good && (mx[k] == 0.f || mx[k] >= 2.5e-4f); if (k < 3 && mx[k] > 0.f) small = fminf(small, mx[k]); }
  good = good && 250.f * 48.f * sqrtf(mx[0] * mx[1]) <= 5e4f;
  good = good && 16.f * 49.f * sqrtf(mx[2]) <= 5e4f && big <= 1e6f;
  good = good && 16.f * sqrtf(sm[2] * mx[3]) <= 2e4f;
  return make_float2(192.f * 2.4e-7f / small, good ? fminf(2.5e8f, 9e8f / fmaxf(big, 1e-30f)) : -1.f);
}

__device__ __forceinline__ void slow_window(float* sm, int w, int t, const __nv_bfloat16* __restrict__ x, const __nv_bfloat16* __restrict__ dw,
                                            const __nv_bfloat16* __restrict__ wqkv, const __nv_bfloat16* __restrict__ wo, __nv_bfloat16* __restrict__ out) {
  float* x0 = sm; float* h = x0 + 49 * CH; float* qkv = h + 49 * CH; float* S = qkv + 49 * 576;
  const int wy = w / NWX, wx = w % NWX;
  auto sync = [] { asm volatile("bar.sync 6, 128;" ::: "memory"); };
#pragma unroll 1
  for (int i = t; i < 49 * CH; i += 128) {
    const int k = i / CH, c = i % CH, y = wy * 7 + k / 7, xx = wx * 7 + k % 7;
    float pe = 0.f;
#pragma unroll 1
    for (int a = 0; a < 9; a++) {
      const int yy = y + a / 3 - 1, xc = xx + a % 3 - 1;
      if (yy >= 0 && yy < IMG && xc >= 0 && xc < IMG) pe = fmaf(__bfloat162float(x[((size_t)yy * IMG + xc) * CH + c]), __bfloat162float(dw[a * CH + c]), pe);
    }
    x0[i] = __bfloat162float(__float2bfloat16(__bfloat162float(x[((size_t)y * IMG + xx) * CH + c]) + pe));
  }
  sync();
  if (t < 49) {
    float m = 0.f, v = 0.f;
#pragma unroll 1
    for (int c = 0; c < CH; c++) m += x0[t * CH + c];
    m *= 1.0f / CH;
#pragma unroll 1
    for (int c = 0; c < CH; c++) { const float d = x0[t * CH + c] - m; v = fmaf(d, d, v); }
    const float rs = 1.0f / sqrtf(v * (1.0f / CH) + 1e-5f);
#pragma unroll 1
    for (int c = 0; c < CH; c++) h[t * CH + c] = (x0[t * CH + c] - m) * rs;
  }
  sync();
#pragma unroll 1
  for (int i = t; i < 7 * 576; i += 128) {
    const int n = i % 576, k0 = i / 576 * 7;
    float a[7] = {0.f, 0.f, 0.f, 0.f, 0.f, 0.f, 0.f};
#pragma unroll 1
    for (int c = 0; c < CH; c++) {
      const float wv = __bfloat162float(wqkv[c * 576 + n]);
#pragma unroll
      for (int k = 0; k < 7; k++) a[k] = fmaf(h[(k0 + k) * CH + c], wv, a[k]);
    }
#pragma unroll
    for (int k = 0; k < 7; k++) qkv[(k0 + k) * 576 + n] = a[k];
  }
  sync();
#pragma unroll 1
  for (int hd = 0; hd < 4; hd++) {
#pragma unroll 1
    for (int i = t; i < 49 * 49; i += 128) {
      const int a = i / 49, b = i % 49;
      float v = 0.f;
#pragma unroll 1
      for (int d = 0; d < 48; d++) v = fmaf(qkv[a * 576 + hd * 48 + d], qkv[b * 576 + 192 + hd * 48 + d], v);
      S[i] = v * 0.14433756729740643f;
    }
    sync();
    if (t < 49) {
      float m = S[t * 49], l = 0.f;
#pragma unroll 1
      for (int b = 1; b < 49; b++) m = fmaxf(m, S[t * 49 + b]);
#pragma unroll 1
      for (int b = 0; b < 49; b++) { const float e = expf(S[t * 49 + b] - m); S[t * 49 + b] = e; l += e; }
#pragma unroll 1
      for (int b = 0; b < 49; b++) S[t * 49 + b] /= l;
    }
    sync();
#pragma unroll 1
    for (int i = t; i < 49 * 48; i += 128) {
      const int a = i / 48, d = i % 48;
      float v = 0.f;
#pragma unroll 1
      for (int b = 0; b < 49; b++) v = fmaf(S[a * 49 + b], qkv[b * 576 + 384 + hd * 48 + d], v);
      h[a * CH + hd * 48 + d] = v;
    }
    sync();
  }
#pragma unroll 1
  for (int i = t; i < 7 * CH; i += 128) {
    const int n = i % CH, k0 = i / CH * 7;
    float a[7] = {0.f, 0.f, 0.f, 0.f, 0.f, 0.f, 0.f};
#pragma unroll 1
    for (int c = 0; c < CH; c++) {
      const float wv = __bfloat162float(wo[c * CH + n]);
#pragma unroll
      for (int k = 0; k < 7; k++) a[k] = fmaf(h[(k0 + k) * CH + c], wv, a[k]);
    }
#pragma unroll
    for (int k = 0; k < 7; k++)
      out[((size_t)(wy * 7 + k0 / 7) * IMG + wx * 7 + k) * CH + n] = __float2bfloat16(x0[(k0 + k) * CH + n] + a[k]);
  }
  sync();
}

__global__ void __launch_bounds__(384, 1)
fused_kernel(const __grid_constant__ CUtensorMap tmx, const __grid_constant__ CUtensorMap tmp, const __grid_constant__ Descs ds, const __nv_bfloat16* __restrict__ dw, __nv_bfloat16* __restrict__ out, const int never,
             const __nv_bfloat16* __restrict__ x, const __nv_bfloat16* __restrict__ wqkv, const __nv_bfloat16* __restrict__ wo) {
  extern __shared__ __align__(1024) uint8_t smem[];
  const uint32_t sb = (uint32_t)__cvta_generic_to_shared(smem);
  const int tid = threadIdx.x, lane = tid & 31;
  const int warp = __shfl_sync(0xffffffffu, tid >> 5, 0);
  const int cta = blockIdx.x, ncta = gridDim.x;
  const int nfull = NWIN / (2 * ncta);
  const int nrounds = nfull + ((NWIN - nfull * 2 * ncta) > cta ? 1 : 0);

  if (warp == 0) GTS(0);
  if (warp == 10 && lane == 0) asm volatile("prefetch.tensormap [%0];" :: "l"(reinterpret_cast<uint64_t>(&tmx)) : "memory");
  if (tid == 0) {
    mbar_init(sb + BAR_FIRST, 1);
    asm volatile("fence.mbarrier_init.release.cluster;" ::: "memory");
    asm volatile("mbarrier.arrive.expect_tx.shared::cta.b64 _, [%0], %1;" :: "r"(sb + BAR_FIRST), "n"(2 * HALO_BYTES) : "memory");
#pragma unroll
    for (int k = 0; k < 2; k++) {
      const int w = max(window_of(0, nfull, cta, ncta, k), 0), a = w / NWX;
      asm volatile("cp.async.bulk.tensor.3d.shared::cluster.global.mbarrier::complete_tx::bytes [%0], [%1, {0, %3, %4}], [%2];"
                   :: "r"(sb + OFF_HALO + k * HALO_BYTES), "l"(reinterpret_cast<uint64_t>(&tmp)), "r"(sb + BAR_FIRST),
                      "r"((w - a * NWX) * 7 - 1), "r"(a * 7 - 1) : "memory");
    }
    if ((sb & 0x3FFFF) != SMEM_BASE || nrounds > 128) __trap();
    for (int i = 0; i < 6; i++) mbar_init(sb + BAR_FH + 8 * i, 1);
    for (int i = 0; i < 4; i++) mbar_init(sb + BAR_E + 8 * i, 8);
    for (int i = 0; i < 9; i++) mbar_init(sb + BAR_XFULL + 8 * i, 1);
    mbar_init(sb + BAR_TFULL, 3);
    mbar_init(sb + BAR_TEMPTY, 8);
    asm volatile("fence.mbarrier_init.release.cluster;" ::: "memory");
  }
  if (tid >= 128 && tid < 136) *reinterpret_cast<uint32_t*>(smem + OFF_REDO + (tid - 128) * 4) = 0;
  if (tid < 128) {
    *reinterpret_cast<uint4*>(smem + OFF_KV + (tid / 64) * KV_BYTES + 6 * KV_PITCH + (tid % 64) * 16) = make_uint4(0x3c003c00u, 0x3c003c00u, 0x3c003c00u, 0x3c003c00u);
    proxy_fence();
  }
  __syncthreads();

  if (warp == 0) GTS(3);
  if (warp < 11) {
#pragma unroll 1
    for (int u = 0; u < (warp < 10 ? 2 : 1); u++) {
      const int cb = warp < 9 ? warp % 3 : 2 * (warp - 9) + u, y = warp < 9 ? 2 * (warp / 3) + u : 6;
      const int ch0 = cb * 64 + (lane & 15) * 4;
      uint32_t wt[9][2], px[3][9][2];
#pragma unroll
      for (int t = 0; t < 9; t++) {
        const uint2 v = *reinterpret_cast<const uint2*>(dw + t * CH + ch0);
        wt[t][0] = v.x; wt[t][1] = v.y;
      }
      mbar_wait(sb + BAR_FIRST, 0);
      if (warp == 0 && u == 0) GTS(7);
      const uint32_t ld = sb + OFF_HALO + (lane >> 4) * HALO_BYTES + y * 3456 + ch0 * 2;
#pragma unroll
      for (int p = 0; p < 27; p++)
        asm volatile("ld.shared.v2.u32 {%0,%1}, [%2];" : "=r"(px[p / 9][p % 9][0]), "=r"(px[p / 9][p % 9][1]) : "r"(ld + p * 384));
      const uint32_t st0 = sb + OFF_TILE + (lane >> 4) * TILE_BYTES + ch0 * 4;
      const uint32_t sa = (st0 ^ ((y & 1) << 4)) + y * 2304;
      uint32_t o[2][2];
#pragma unroll
      for (int j = 0; j < 7; j++) {
#pragma unroll
        for (int e = 0; e < 2; e++) {
          uint32_t a = hmul(px[0][j][e], wt[0][e]);
#pragma unroll
          for (int t = 1; t < 9; t++) a = hfma(px[t / 3][j + t % 3][e], wt[t][e], a);
          a = hadd(px[1][j + 1][e], a);
          o[j & 1][e] = packh(lo2f(a), hi2f(a));
        }
        if (j & 1)
          asm volatile("st.shared.v4.u32 [%0], {%1,%2,%3,%4};" :: "r"((j == 3 ? sa ^ 16 : sa) + (j >> 1) * 768),
                       "r"(o[0][0]), "r"(o[1][0]), "r"(o[0][1]), "r"(o[1][1]) : "memory");
      }
      const uint32_t sb6 = (st0 ^ ((~y & 2) << 3)) + (21 + (y >> 1)) * 768 + (y & 1) * 4;
      asm volatile("st.shared.u32 [%0], %1;\nst.shared.u32 [%0 + 8], %2;" :: "r"(sb6), "r"(o[0][0]), "r"(o[0][1]) : "memory");
      if (y == 6) asm volatile("st.shared.u32 [%0 + 4], %1;\nst.shared.u32 [%0 + 12], %1;" :: "r"(sb6), "r"(0) : "memory");
    }
    if (warp == 0) GTS(6);
    asm volatile("bar.arrive 8, 384;\nbar.sync 7, 352;" ::: "memory");
  }

  if (warp >= 8) {
    asm volatile("setmaxnreg.dec.sync.aligned.u32 " PREGS ";");
    if (warp == 11) {
      asm volatile("griddepcontrol.wait;" ::: "memory");
      GTS(2);
      load_slices<3, 0>(sb, ds.src, 0, 0, BAR_F0);
      *reinterpret_cast<float2*>(smem + OFF_LIM) = fp16_limits(lane);
      asm volatile("{\n.reg .pred p;\nelect.sync _|p, 0xffffffff;\n@p mbarrier.arrive.expect_tx.shared::cta.b64 _, [%0], %1;\n}\n"
                   :: "r"(sb + BAR_F0), "n"(3 * SLICE) : "memory");
      asm volatile("bar.sync 8, 384;" ::: "memory");
      load_slices<3, 5 * SLICE>(sb, ds.src, 3, 3, BAR_F1);
      load_slices<1, 0>(sb, ds.src, 13, SLOT_U, BAR_F1);
      load_slices<1, 0>(sb, ds.src, 12, SLOT_V, BAR_F1);
      for (int r = 0; r < nrounds; r++) {
        const int par = r & 1;
        const int h2 = par ? 1 : 2, h3 = par ? 0 : 3;
        mbar_wait(sb + BAR_E, par);
        load_slices<3>(sb, ds.src, 3 * h2, 3 * (h2 & 1), BAR_FH);
        mbar_wait(sb + BAR_E + 8, par);
        load_slices<3>(sb, ds.src, 3 * h3, 3 * (h3 & 1), BAR_FH + 8);
        mbar_wait(sb + BAR_E + 16, par);
        load_slices<1>(sb, ds.src, 12 + h2, SLOT_U, BAR_FU);
        mbar_wait(sb + BAR_E + 24, par);
        load_slices<1>(sb, ds.src, 12 + h3, SLOT_V, BAR_FV);
      }
    } else {
      const int cw = warp - 8;
      const int win = lane >> 4;
      const int ch0 = cw * 64 + (lane & 15) * 4;
      uint32_t wt[9][2];
#pragma unroll
      for (int t = 0; t < 9; t++) {
        uint2 v = *reinterpret_cast<const uint2*>(dw + t * CH + ch0);
        wt[t][0] = v.x; wt[t][1] = v.y;
      }
      const uint32_t xs = sb + OFF_X + cw * 3 * XSLOT;
      const uint32_t xld = xs + (lane >> 4) * 1152 + (lane & 15) * 8;
      const uint32_t xbar = sb + BAR_XFULL + cw * 24;
      const uint32_t st0 = sb + OFF_TILE + win * TILE_BYTES + ch0 * 4;
      const uint64_t tm = reinterpret_cast<uint64_t>(&tmx);
      int cx0, cy0, cx1, cy1;
      auto coords = [&](int r) {
        const int w0 = window_of(r, nfull, cta, ncta, 0);
        int w1 = window_of(r, nfull, cta, ncta, 1);
        if (w1 < 0) w1 = w0;
        const int a = w0 / NWX, b = w1 / NWX;
        cx0 = (w0 - a * NWX) * 7 - 1; cy0 = a * 7 - 1;
        cx1 = (w1 - b * NWX) * 7 - 1; cy1 = b * 7 - 1;
      };
      auto issue = [&](int slot, int dy) {
        asm volatile("{\n.reg .pred p;\nelect.sync _|p, 0xffffffff;\n"
                     "@p mbarrier.arrive.expect_tx.shared::cta.b64 _, [%2], %8;\n"
                     "@p cp.async.bulk.tensor.3d.shared::cluster.global.mbarrier::complete_tx::bytes [%0], [%1, {%3, %4, %5}], [%2];\n"
                     "@p cp.async.bulk.tensor.3d.shared::cluster.global.mbarrier::complete_tx::bytes [%0 + 1152], [%1, {%3, %6, %7}], [%2];\n}\n"
                     :: "r"(xs + slot * XSLOT), "l"(tm), "r"(xbar + slot * 8), "r"(cw * 64), "r"(cx0), "r"(cy0 + dy), "r"(cx1), "r"(cy1 + dy), "n"(XSLOT) : "memory");
      };
      uint32_t accA[7][2], accB[7][2], ctr[7][2], held[2];
      auto row = [&](auto fin, auto mid, auto top, int slot, int y) {
        const uint32_t ld = xld + slot * XSLOT;
        const uint32_t sa = (st0 ^ ((y & 1) << 4)) + y * 2304;
        uint32_t cur[9][2], o[2][2];
#pragma unroll
        for (int p = 0; p < LA; p++)
          asm volatile("ld.shared.v2.u32 {%0,%1}, [%2];" : "=r"(cur[p][0]), "=r"(cur[p][1]) : "r"(ld + p * 128));
#pragma unroll
        for (int j = 0; j < 7; j++) {
          if (j >= 1 && j + LA - 1 < 9)
            asm volatile("ld.shared.v2.u32 {%0,%1}, [%2];" : "=r"(cur[j + LA - 1][0]), "=r"(cur[j + LA - 1][1]) : "r"(ld + (j + LA - 1) * 128));
          if (fin.v) {
#pragma unroll
            for (int e = 0; e < 2; e++) {
              uint32_t a = hfma(cur[j][e], wt[6][e], accA[j][e]);
              a = hfma(cur[j + 1][e], wt[7][e], a);
              a = hfma(cur[j + 2][e], wt[8][e], a);
              a = hadd(ctr[j][e], a);
              o[j & 1][e] = packh(lo2f(a), hi2f(a));
            }
            if (j & 1)
              asm volatile("st.shared.v4.u32 [%0], {%1,%2,%3,%4};" :: "r"((j == 3 ? sa ^ 16 : sa) + (j >> 1) * 768),
                           "r"(o[0][0]), "r"(o[1][0]), "r"(o[0][1]), "r"(o[1][1]) : "memory");
            if (j == 6) {
              const uint32_t sb6 = (st0 ^ ((~y & 2) << 3)) + (21 + (y >> 1)) * 768;
              if (fin.v == 2)
                asm volatile("st.shared.v4.u32 [%0], {%1,%2,%3,%2};" :: "r"(sb6), "r"(o[0][0]), "r"(0), "r"(o[0][1]) : "memory");
              else
                asm volatile("{\n.reg .pred p;\nsetp.ne.s32 p, %5, 0;\n@p st.shared.v4.u32 [%0], {%1,%2,%3,%4};\n}\n"
                             :: "r"(sb6), "r"(held[0]), "r"(o[0][0]), "r"(held[1]), "r"(o[0][1]), "r"(y & 1) : "memory");
              held[0] = o[0][0]; held[1] = o[0][1];
            }
          }
#pragma unroll
          for (int e = 0; e < 2; e++) {
            if (mid.v) {
              uint32_t a = hfma(cur[j][e], wt[3][e], accB[j][e]);
              a = hfma(cur[j + 1][e], wt[4][e], a);
              accA[j][e] = hfma(cur[j + 2][e], wt[5][e], a);
              ctr[j][e] = cur[j + 1][e];
            }
            if (top.v) {
              uint32_t a = hmul(cur[j][e], wt[0][e]);
              a = hfma(cur[j + 1][e], wt[1][e], a);
              accB[j][e] = hfma(cur[j + 2][e], wt[2][e], a);
            }
          }
        }
      };
      held[0] = held[1] = 0;
      if (nrounds > 1) { coords(1); issue(0, 0); issue(1, 1); issue(2, 2); }
      for (int r = 0; r + 1 < nrounds; r++) {
        const bool more = r + 2 < nrounds;
        mbar_wait(xbar, r & 1);
        if (r > 0) issue(2, 2);
        row(IC<0>{}, IC<0>{}, IC<1>{}, 0, 0);
        mbar_wait(xbar + 8, r & 1);
        issue(0, 3);
        row(IC<0>{}, IC<1>{}, IC<1>{}, 1, 0);
        mbar_wait(sb + BAR_TEMPTY, r & 1);
#pragma unroll 1
        for (int k = 0; k < 2; k++) {
          mbar_wait(xbar + 16, (r + k) & 1);
          issue(1, 4 + 3 * k);
          row(IC<1>{}, IC<1>{}, IC<1>{}, 2, 3 * k);
          mbar_wait(xbar, (r + k + 1) & 1);
          issue(2, 5 + 3 * k);
          row(IC<1>{}, IC<1>{}, IC<1>{}, 0, 3 * k + 1);
          mbar_wait(xbar + 8, (r + k + 1) & 1);
          if (k == 1 && more) coords(r + 2);
          if (k == 0 || more) issue(0, k == 0 ? 6 : 0);
          row(IC<1>{}, IC<1>{}, IC<1>{}, 1, 3 * k + 2);
        }
        mbar_wait(xbar + 16, r & 1);
        if (more) issue(1, 1);
        row(IC<2>{}, IC<0>{}, IC<0>{}, 2, 6);
        __syncwarp();
        warp_arrive(sb + BAR_TFULL);
      }
    }
    asm volatile("bar.sync 5, 384;" ::: "memory");
#pragma unroll 1
    for (int i = 0; i < 8; i++) {
      uint32_t bits = *reinterpret_cast<volatile uint32_t*>(smem + OFF_REDO + 4 * i);
#pragma unroll 1
      for (; bits; bits &= bits - 1)
        slow_window(reinterpret_cast<float*>(smem), window_of((i & 3) * 32 + __ffs(bits) - 1, nfull, cta, ncta, i >> 2), tid - 256, x, dw, wqkv, wo, out);
    }
  } else {
    asm volatile("setmaxnreg.inc.sync.aligned.u32 " CREGS ";");
    const int wg = warp >> 2, w4 = warp & 3, g = lane >> 2, q = lane & 3;
    const int row0 = w4 * 16 + g, row1 = row0 + 8;
    const int ps = min(w4 * 8 + g, 24);
    const int pix0 = ps < 21 ? (ps / 3) * IMG + (ps % 3) * 2 : (ps - 21) * 2 * IMG + 6;
    const int pix1 = pix0 + (ps < 21 ? 1 : ps < 24 ? IMG : 0);
    const uint32_t kv = sb + OFF_KV + wg * KV_BYTES;
    const int srow = w4 * 16 + (lane & 15);
    const uint32_t vst = kv + (lane >> 4) * KV_PITCH + (srow < 56 ? srow : min(srow - 7, 55)) * 16;
    uint32_t misc = ((uint32_t)pix1 << 20) | ((uint32_t)pix0 << 8) | q;
    const uint32_t ninf = q ? 0xfc00fc00u : 0u;
    const uint32_t v48 = kv + (lane >> 3) * KV_PITCH + 48 * 16;
    const uint32_t vmask = (row0 < 49 ? 0xffffu : 0u) | (row1 < 49 ? 0xffff0000u : 0u);

    const uint32_t tx = sb + OFF_TILE + wg * TILE_BYTES + ps * 768 + q * 32 + (ps & 1) * 16;
    const int myrounds = window_of(nrounds - 1, nfull, cta, ncta, wg) < 0 ? nrounds - 1 : nrounds;

    if (never == 2) return;
    uint32_t H[48], Y[48];
    const uint64_t* dkv = ds.kv[wg];
    uint32_t P[NP], Ofc[12], p48 = 0;
#pragma unroll
    for (int i = 0; i < 48; i++) Y[i] = 0;
#pragma unroll
    for (int i = 0; i < NP; i++) P[i] = Ofc[i % 12] = 0;
    if (warp == 0) GTS(4);
#pragma unroll
    for (int i = 0; i < 48; i++) H[i] = 0;
    if (vmask) load_x<0, 12>(H, tx);
    __syncwarp();
    warp_arrive(sb + BAR_TEMPTY);
    mbar_wait(sb + BAR_F0, 0);
    if (warp == 0) GTS(1);
    if (wg == 1) turn_pass(1);

    uint8_t *o0, *o1;
    uint32_t omask;
    auto out_setup = [&](int r) {
      omask = r >= 0 ? vmask : 0u;
      const int w = window_of(r, nfull, cta, ncta, wg);
      const int wy = w / NWX, wx = w - wy * NWX;
      asm volatile("" : "+r"(misc));
      const uint32_t wb = (uint32_t)(wy * 7 * IMG + wx * 7) * 384u + (misc & 3) * 16;
      o0 = reinterpret_cast<uint8_t*>(out) + (wb + ((misc >> 8) & 0xfff) * 384u);
      o1 = reinterpret_cast<uint8_t*>(out) + (wb + (misc >> 20) * 384u);
    };
#define OUT(c) store_out<c>(Y, o0, o1, omask)
    auto release = [&](int i) { warp_arrive(sb + BAR_E + 8 * i); };

    for (int r = 0;; r++) {
      const uint32_t par = r & 1;
      uint32_t acc[36], S[14], O[14], Q[12], V[12], Ofa[12], Ofb[12], vr[6], k48, mx;
      if (r == myrounds) {
        const bool idle = r < nrounds;
        if (idle) { release(0); release(1); }
        mbar_wait(sb + BAR_FU, par ^ 1);
        turn_wait(wg);
        wg_fence(); mma_pv(O, P, dkv + 4); mma_proj(Y, Ofc, ds.pu[0]); wg_commit();
        turn_pass(wg);
        load_v48(vr, v48);
        wg_wait<0>(); keep(O); keep(Y);
        finish_o(O, vr, p48, vmask, Ofa);
        mbar_wait(sb + BAR_FV, par ^ 1);
        turn_wait(wg);
        wg_fence(); mma_proj(Y, Ofa, ds.pv[0]); wg_commit();
        if (wg == 0 || idle) turn_pass(wg);
        wg_wait<0>(); keep(Y);
        if (idle) { release(2); release(3); turn_wait(wg); turn_pass(wg); }
        out_setup(r - 1);
        OUT(0); PIN(); OUT(1); PIN(); OUT(2); PIN(); OUT(3); PIN(); OUT(4); PIN(); OUT(5);
        if (idle) {
          turn_wait(wg); turn_pass(wg);
          turn_wait(wg); turn_pass(wg);
          turn_wait(wg); turn_pass(wg);
          turn_wait(wg);
        }
        if (warp == 0) GTS(5);
        asm volatile("bar.arrive 5, 384;" ::: "memory");
        break;
      }
      const uint64_t* dq0 = ds.q[par];
      float s1[2], s2[2];
      TR(0);
      turn_wait(wg);
      TR(1);
      wg_fence(); mma_pv(O, P, dkv + 4); wg_commit(); mma_qkv<0, K0A>(acc, H, dq0);
      PIN();
      ln_sums<0, 24>(H, s1, s2);
      PIN();
      wg_fence(); mma_qkv<K0A, 12>(acc, H, dq0);
      if (r > 0) { mbar_wait(sb + BAR_FU, par ^ 1); wg_fence(); mma_proj(Y, Ofc, ds.pu[0]); wg_commit(); }
      else { wg_fence(); wg_commit(); }
      turn_pass(wg);
      TR(2);
      load_v48(vr, v48);
      wg_wait<3>(); keep(O);
      wg_sync(wg);
      PIN();
      finish_o(O, vr, p48, vmask, Ofa);
      ln_sums<24, 48>(H, s1, s2);
      float lim_lo, lim_hi;
      asm volatile("ld.shared.v2.f32 {%0,%1}, [%2];" : "=f"(lim_lo), "=f"(lim_hi) : "r"(sb + OFF_LIM) : "memory");
      bool ok;
      const uint32_t rk = ln_rstd(s1, s2, lim_lo, lim_hi, vmask, ok);
      asm volatile("{\n.reg .pred p;\nsetp.eq.s32 p, %2, 0;\n@p red.shared.or.b32 [%0], %1;\n}\n"
                   :: "r"(sb + OFF_REDO + wg * 16 + (r >> 5) * 4), "r"(1u << (r & 31)), "r"((int)ok) : "memory");
      PIN();
      TR(3);
      wg_wait<1>(); keep(acc);
      TR(4);
      release(0);
      scale12(V, acc, rk); stsm12(V, vst + KV_KOFF);
      scale12(V, acc + 24, rk); stsm12(V, vst);
      PIN();
      wg_wait<0>(); keep(Y);
      PIN();
      proxy_fence();
      scale12(Q, acc + 12, rk);
      if (r > 0) mbar_wait(sb + BAR_FV, par ^ 1); else mbar_wait(sb + BAR_F1, 0);
      TR(5);
      turn_wait(wg);
      TR(6);
      if (r > 0) { wg_fence(); mma_proj(Y, Ofa, ds.pv[0]); wg_commit(); }
      wg_fence(); mma_s(S, Q, dkv); mma_qkv<0, 2>(acc, H, dq0 + 12);
      out_setup(r - 1);
      PIN();
      wg_wait<1>(); keep(Y);
      wg_fence(); mma_qkv<2, 6>(acc, H, dq0 + 12);
      PIN();
      OUT(0);
      PIN();
      wg_wait<1>(); keep(S);
      wg_fence(); mma_qkv<6, 9>(acc, H, dq0 + 12);
      PIN();
      row_max(S, k48, mx, ninf);
      OUT(1);
      PIN();
      wg_fence(); mma_qkv<9, 12>(acc, H, dq0 + 12);
      turn_pass(wg);
      PIN();
      OUT(2); PIN();
      OUT(3); PIN();
      row_exp(S, k48, mx, P, p48);
      PIN();
      TR(7);
      wg_wait<0>(); keep(acc);
      TR(8);
      release(1);
      wg_sync(wg);
      scale12(V, acc, rk); stsm12(V, vst + KV_KOFF);
      scale12(Q, acc + 12, rk); scale12(V, acc + 24, rk); PIN();
      proxy_fence();
#define TURN(ID, OF, DQ, FB, X1)                                                        \
      mbar_wait(sb + FB, par);                                                          \
      TR(ID + 1);                                                                       \
      turn_wait(wg);                                                                    \
      wg_fence(); mma_pv(O, P, dkv + 4); mma_s(S, Q, dkv); wg_commit(); mma_qkv<0, KA>(acc, H, DQ); \
      PIN();                                                                            \
      TR(ID + 2);                                                                       \
      load_v48(vr, v48);                                                                \
      X1;                                                                               \
      PIN();                                                                            \
      wg_wait<1>(); keep(S); keep(O);                                                   \
      wg_sync(wg);                                         \
      wg_fence(); mma_qkv<KA, KB>(acc, H, DQ);                                            \
      PIN();                                                                            \
      stsm12(V, vst);                                                                   \
      finish_o(O, vr, p48, vmask, OF);                                                  \
      row_max(S, k48, mx, ninf);                                                        \
      PIN();                                                                            \
      wg_fence(); mma_qkv<KB, 12>(acc, H, DQ);                                           \
      turn_pass(wg);                                                                    \
      PIN();                                                                            \
      TR(ID + 3);
#define NEXT_HEAD(ID)                                                                   \
      row_exp(S, k48, mx, P, p48);                                                      \
      PIN();                                                                            \
      TR(ID + 4);                                                                       \
      wg_wait<0>(); keep(acc);                                                          \
      scale12(V, acc, rk); stsm12(V, vst + KV_KOFF);                                    \
      scale12(Q, acc + 12, rk); scale12(V, acc + 24, rk); PIN();
      TURN(8, Ofa, dq0 + 24, BAR_FH, OUT(4))
      OUT(5); PIN();
      NEXT_HEAD(8)
      proxy_fence();
      TURN(12, Ofb, dq0 + 36, BAR_FH + 8, )
      auto init_y = [&]() {
#pragma unroll
        for (int i = 0; i < 48; i++) Y[i] = (i & 1) ? H[i] ^ never : h2u(__hadd2_rn(u2h(H[i]), u2h(never)));
        hold<0, 48>(Y); PIN();
      };
      NEXT_HEAD(12)
      init_y();
      proxy_fence();
      TR(17);
      turn_wait(wg);
      wg_fence(); mma_pv(O, P, dkv + 4); mma_s(S, Q, dkv); wg_commit();
      mma_proj(Y, Ofb, ds.pu[1]); wg_commit(); mma_proj(Y, Ofa, ds.pv[1]); wg_commit();
      turn_pass(wg);
      PIN();
      TR(18);
      load_v48(vr, v48);
      if (r + 1 < myrounds) mbar_wait(sb + BAR_TFULL, par);
      if (vmask) load_x<0, 4>(H, tx);
      wg_wait<2>(); keep(S); keep(O);
      wg_sync(wg);
      PIN();
      TR(19);
      row_max(S, k48, mx, ninf);
      finish_o(O, vr, p48, vmask, Ofc);
      stsm12(V, vst);
      PIN();
      wg_wait<1>();
      release(2);
      if (vmask) load_x<4, 8>(H, tx);
      row_exp(S, k48, mx, P, p48);
      PIN();
      if (vmask) load_x<8, 12>(H, tx);
      __syncwarp();
      warp_arrive(sb + BAR_TEMPTY);
      TR(20);
      wg_wait<0>(); keep(Y);
      release(3);
      proxy_fence();
      TR(21);
#undef TURN
#undef NEXT_HEAD
    }
  }
}

typedef CUresult (*EncodeFn)(CUtensorMap*, CUtensorMapDataType, cuuint32_t, void*, const cuuint64_t*, const cuuint64_t*,
                             const cuuint32_t*, const cuuint32_t*, CUtensorMapInterleave, CUtensorMapSwizzle,
                             CUtensorMapL2promotion, CUtensorMapFloatOOBfill);

}

extern "C" void kernel_launch(void* const* d_in, const int* in_sizes, int n_in, void* d_out, int out_size) {
  const __nv_bfloat16* x = (const __nv_bfloat16*)d_in[0];
  const __nv_bfloat16* dw = (const __nv_bfloat16*)d_in[1];
  const __nv_bfloat16* wqkv = (const __nv_bfloat16*)d_in[2];
  const __nv_bfloat16* wo = (const __nv_bfloat16*)d_in[3];
  static EncodeFn encode = nullptr;
  static int nsm = 0;
  static void* wpack = nullptr;
  if (!encode) {
    void* fn = nullptr;
    cudaDriverEntryPointQueryResult qr;
    cudaGetDriverEntryPoint("cuTensorMapEncodeTiled", &fn, cudaEnableDefault, &qr);
    encode = (EncodeFn)fn;
    int dev = 0;
    cudaGetDevice(&dev);
    cudaDeviceGetAttribute(&nsm, cudaDevAttrMultiProcessorCount, dev);
    cudaGetSymbolAddress(&wpack, g_wpack);
    cudaFuncSetAttribute(fused_kernel, cudaFuncAttributeMaxDynamicSharedMemorySize, SMEM_BYTES);
  }
  CUtensorMap tmx;
  cuuint64_t gdim[3] = {CH, IMG, IMG};
  cuuint64_t gstr[2] = {CH * 2, (cuuint64_t)CH * 2 * IMG};
  cuuint32_t box[3] = {64, 9, 1};
  cuuint32_t estr[3] = {1, 1, 1};
  encode(&tmx, CU_TENSOR_MAP_DATA_TYPE_BFLOAT16, 3, (void*)x, gdim, gstr, box, estr, CU_TENSOR_MAP_INTERLEAVE_NONE,
         CU_TENSOR_MAP_SWIZZLE_NONE, L2PROMO, CU_TENSOR_MAP_FLOAT_OOB_FILL_NONE);
  Descs ds;
  for (int i = 0; i < 12; i++)
    for (int b = 0; b < 5; b++) ds.q[b][i] = mkdesc(SMEM_BASE + OFF_W + qkv_pos(b & 1, i), 128, 256);
  for (int i = 0; i < 3; i++) {
    ds.pu[0][i] = ds.pu[1][i] = mkdesc(SMEM_BASE + OFF_W + SLOT_U * SLICE + i * 6144, 128, 256);
    ds.pv[0][i] = ds.pv[1][i] = mkdesc(SMEM_BASE + OFF_W + SLOT_V * SLICE + i * 6144, 128, 256);
  }
  ds.src = (const uint8_t*)wpack;
  for (int g = 0; g < 2; g++)
    for (int i = 0; i < 4; i++) {
      ds.kv[g][i] = mkdesc(SMEM_BASE + OFF_KV + g * KV_BYTES + KV_KOFF + 2 * i * KV_PITCH, KV_PITCH, 128);
      ds.kv[g][4 + i] = mkdesc(SMEM_BASE + OFF_KV + g * KV_BYTES + 256 * i, 128, KV_PITCH);
    }
  CUtensorMap tmp;
  cuuint32_t boxp[3] = {CH, 9, 9};
  encode(&tmp, CU_TENSOR_MAP_DATA_TYPE_BFLOAT16, 3, (void*)x, gdim, gstr, boxp, estr, CU_TENSOR_MAP_INTERLEAVE_NONE,
         CU_TENSOR_MAP_SWIZZLE_NONE, L2PROMO, CU_TENSOR_MAP_FLOAT_OOB_FILL_NONE);
  prepack_kernel<<<96 / PBY, dim3(192, PBY), 0, cudaStreamPerThread>>>(wqkv, wo, x, min(IMG, (2 * nsm + NWX - 1) / NWX * 7 + 1));
  cudaLaunchConfig_t cfg = {};
  cfg.gridDim = dim3(nsm); cfg.blockDim = dim3(384); cfg.dynamicSmemBytes = SMEM_BYTES; cfg.stream = cudaStreamPerThread;
  cudaLaunchAttribute at[1];
  at[0].id = cudaLaunchAttributeProgrammaticStreamSerialization;
  at[0].val.programmaticStreamSerializationAllowed = 1;
  cfg.attrs = at; cfg.numAttrs = 1;
  cudaLaunchKernelEx(&cfg, fused_kernel, tmx, tmp, ds, dw, (__nv_bfloat16*)d_out, 0, x, wqkv, wo);
}
```

```cpp
#include <cuda_runtime.h>
#include <cuda_bf16.h>
#include <cuda_fp16.h>
#include <cuda.h>
#include <stdint.h>

#define CREGS "208"
#define PREGS "88"
#define LA 4
#define K0A 6
#define KA 3
#define KB 9
#define L2PROMO CU_TENSOR_MAP_L2_PROMOTION_NONE
#define OMAP 0x012234
#define B1A 2
#define B1B 6
#define B1C 9
namespace {
constexpr int PBY = 2;

constexpr int IMG = 511;
constexpr int CH = 192;
constexpr int NWX = 73;
constexpr int NWIN = NWX * NWX;
constexpr int SLICE = 18432;
constexpr int OFF_W = 0;
constexpr int KV_PITCH = 1792, KV_KOFF = 896, KV_BYTES = 6 * KV_PITCH + 768;
constexpr int OFF_KV = 8 * SLICE;
constexpr int TILE_BYTES = 25 * 768;
constexpr int OFF_TILE = OFF_KV + 2 * KV_BYTES;
constexpr int XSLOT = 2304;
constexpr int OFF_X = OFF_TILE + 2 * TILE_BYTES;
constexpr int OFF_BAR = OFF_X + 9 * XSLOT;
constexpr int BAR_FH = OFF_BAR;
constexpr int BAR_FU = OFF_BAR + 16, BAR_FV = OFF_BAR + 24;
constexpr int BAR_F0 = OFF_BAR + 32, BAR_F1 = OFF_BAR + 40;
constexpr int BAR_E = OFF_BAR + 80;
constexpr int BAR_XFULL = OFF_BAR + 112;
constexpr int BAR_TFULL = OFF_BAR + 184;
constexpr int BAR_TEMPTY = OFF_BAR + 192;
constexpr int OFF_LIM = OFF_BAR + 200;
constexpr int OFF_REDO = OFF_BAR + 208;
constexpr int BAR_FIRST = OFF_BAR + 240;
constexpr int OFF_TRACE = OFF_BAR + 248;
constexpr int OFF_HALO = OFF_W + 3 * SLICE, HALO_BYTES = 81 * 384;
constexpr int SMEM_BYTES = OFF_TRACE;

__host__ __device__ constexpr int qkv_pos(int h, int s) { return 3 * h * SLICE + s * 4608; }
__host__ __device__ constexpr int wo_pos(int s) { return 12 * SLICE + s * 6144; }
constexpr int SLOT_U = 6, SLOT_V = 7;
constexpr int SMEM_BASE = 1024;
struct Descs { uint64_t q[5][12]; uint64_t pu[2][3], pv[2][3]; uint64_t kv[2][8]; const uint8_t* src; };

__device__ uint4 g_wpack[16 * SLICE / 16];
__device__ float2 g_wnorm[96];
#define TR(id)
#define GTS(i)
template <int V> struct IC { static constexpr int v = V; };
typedef __nv_bfloat162 bf2;
__device__ __forceinline__ bf2 u2b(uint32_t u) { return *reinterpret_cast<bf2*>(&u); }
__device__ __forceinline__ uint32_t b2u(bf2 b) { return *reinterpret_cast<uint32_t*>(&b); }
__device__ __forceinline__ uint32_t pack2(float lo, float hi) {
  uint32_t r; asm("cvt.rn.bf16x2.f32 %0, %1, %2;" : "=r"(r) : "f"(hi), "f"(lo)); return r;
}
__device__ __forceinline__ uint32_t hadd(uint32_t a, uint32_t b) { return b2u(__hadd2_rn(u2b(a), u2b(b))); }
__device__ __forceinline__ uint32_t hmul(uint32_t a, uint32_t b) { return b2u(__hmul2_rn(u2b(a), u2b(b))); }
__device__ __forceinline__ uint32_t hfma(uint32_t a, uint32_t b, uint32_t c) { return b2u(__hfma2(u2b(a), u2b(b), u2b(c))); }
__device__ __forceinline__ __half2 u2h(uint32_t u) { return *reinterpret_cast<__half2*>(&u); }
__device__ __forceinline__ uint32_t h2u(__half2 b) { return *reinterpret_cast<uint32_t*>(&b); }
__device__ __forceinline__ uint32_t packh(float lo, float hi) {
  uint32_t r; asm("cvt.rn.f16x2.f32 %0, %1, %2;" : "=r"(r) : "f"(hi), "f"(lo)); return r;
}
__device__ __forceinline__ uint32_t fmax2(uint32_t a, uint32_t b) { return h2u(__hmax2(u2h(a), u2h(b))); }
template <int HI> __device__ __forceinline__ __half2 hcast(uint32_t a) { return HI ? __high2half2(u2h(a)) : __low2half2(u2h(a)); }
template <int HI> __device__ __forceinline__ uint32_t fmul_b(uint32_t a, uint32_t s) { return h2u(__hmul2_rn(u2h(a), hcast<HI>(s))); }
template <int HI> __device__ __forceinline__ uint32_t fsub_b(uint32_t a, uint32_t s) { return h2u(__hsub2_rn(u2h(a), hcast<HI>(s))); }
__device__ __forceinline__ uint32_t fex2(uint32_t a) { uint32_t r; asm("ex2.approx.f16x2 %0, %1;" : "=r"(r) : "r"(a)); return r; }
__device__ __forceinline__ float lo2f(uint32_t a) { return __uint_as_float(a << 16); }
__device__ __forceinline__ float hi2f(uint32_t a) { return __uint_as_float(a & 0xffff0000u); }

__device__ __forceinline__ void mbar_init(uint32_t bar, uint32_t cnt) { asm volatile("mbarrier.init.shared::cta.b64 [%0], %1;" :: "r"(bar), "r"(cnt) : "memory"); }
__device__ __forceinline__ void mbar_wait(uint32_t bar, uint32_t parity) {
  asm volatile("{\n.reg .pred p;\n.reg .u32 n;\n"
               "mbarrier.try_wait.parity.shared::cta.b64 p, [%0], %1;\n"
               "@p bra.uni DONE_%=;\n"
               "mov.u32 n, 0;\n"
               "AGAIN_%=:\n"
               "mbarrier.try_wait.parity.shared::cta.b64 p, [%0], %1;\n"
               "@p bra.uni DONE_%=;\n"
               "add.u32 n, n, 1;\n"
               "setp.lt.u32 p, n, 0x1000000;\n"
               "@p bra.uni AGAIN_%=;\n"
               "trap;\n"
               "DONE_%=:\n}\n" :: "r"(bar), "r"(parity) : "memory");
}
__device__ __forceinline__ void wg_fence() { asm volatile("wgmma.fence.sync.aligned;" ::: "memory"); }
__device__ __forceinline__ void wg_commit() { asm volatile("wgmma.commit_group.sync.aligned;" ::: "memory"); }
template <int N> __device__ __forceinline__ void wg_wait() { asm volatile("wgmma.wait_group.sync.aligned %0;" :: "n"(N) : "memory"); }
#define BAR_BY_WG(OP, ID0, ID1, CNT) asm volatile("{\n.reg .pred p;\nsetp.eq.s32 p, %0, 0;\n@p " OP " " #ID0 ", " #CNT ";\n@!p " OP " " #ID1 ", " #CNT ";\n}\n" :: "r"(wg) : "memory")
__device__ __forceinline__ void wg_sync(int wg) { BAR_BY_WG("bar.sync", 1, 2, 128); }
__device__ __forceinline__ void turn_wait(int wg) { BAR_BY_WG("bar.sync", 3, 4, 256); }
__device__ __forceinline__ void turn_pass(int wg) { BAR_BY_WG("bar.arrive", 4, 3, 256); }
__device__ __forceinline__ void stsm4(uint32_t addr, uint32_t a, uint32_t b, uint32_t c, uint32_t d) {
  asm volatile("stmatrix.sync.aligned.m8n8.x4.shared.b16 [%0], {%1,%2,%3,%4};" :: "r"(addr), "r"(a), "r"(b), "r"(c), "r"(d) : "memory");
}
template <int N> __device__ __forceinline__ void keep(float (&d)[N]) {
#pragma unroll
  for (int i = 0; i < N; i++) asm volatile("" : "+f"(d[i]) :: "memory");
}
template <int N> __device__ __forceinline__ void keep(uint32_t (&d)[N]) {
#pragma unroll
  for (int i = 0; i < N; i++) asm volatile("" : "+r"(d[i]) :: "memory");
}
__host__ __device__ __forceinline__ uint64_t mkdesc(uint32_t addr, uint32_t lbo, uint32_t sbo) {
  return ((uint64_t)(sbo >> 4) << 32) | (uint64_t)(((lbo >> 4) << 16) | ((addr & 0x3FFFF) >> 4));
}

template <int SCALE_D>
__device__ __forceinline__ void wgmma_n144(uint32_t (&d)[36], uint32_t a0, uint32_t a1, uint32_t a2, uint32_t a3, uint64_t descB) {
  if (SCALE_D == 0)
  asm volatile("wgmma.mma_async.sync.aligned.m64n144k16.f16.f16.f16 "
    "{%0, %1, %2, %3, %4, %5, %6, %7, %8, %9, %10, %11, %12, %13, %14, %15, "
    "%16, %17, %18, %19, %20, %21, %22, %23, %24, %25, %26, %27, %28, %29, %30, %31, "
    "%32, %33, %34, %35}, "
    "{%36, %37, %38, %39}, %40, 0, 1, 1, 0;\n"
    : "=r"(d[0]), "=r"(d[1]), "=r"(d[2]), "=r"(d[3]), "=r"(d[4]), "=r"(d[5]), "=r"(d[6]), "=r"(d[7]),
      "=r"(d[8]), "=r"(d[9]), "=r"(d[10]), "=r"(d[11]), "=r"(d[12]), "=r"(d[13]), "=r"(d[14]), "=r"(d[15]),
      "=r"(d[16]), "=r"(d[17]), "=r"(d[18]), "=r"(d[19]), "=r"(d[20]), "=r"(d[21]), "=r"(d[22]), "=r"(d[23]),
      "=r"(d[24]), "=r"(d[25]), "=r"(d[26]), "=r"(d[27]), "=r"(d[28]), "=r"(d[29]), "=r"(d[30]), "=r"(d[31]),
      "=r"(d[32]), "=r"(d[33]), "=r"(d[34]), "=r"(d[35])
    : "r"(a0), "r"(a1), "r"(a2), "r"(a3), "l"(descB));
  else
  asm volatile("wgmma.mma_async.sync.aligned.m64n144k16.f16.f16.f16 "
    "{%0, %1, %2, %3, %4, %5, %6, %7, %8, %9, %10, %11, %12, %13, %14, %15, "
    "%16, %17, %18, %19, %20, %21, %22, %23, %24, %25, %26, %27, %28, %29, %30, %31, "
    "%32, %33, %34, %35}, "
    "{%36, %37, %38, %39}, %40, 1, 1, 1, 0;\n"
    : "+r"(d[0]), "+r"(d[1]), "+r"(d[2]), "+r"(d[3]), "+r"(d[4]), "+r"(d[5]), "+r"(d[6]), "+r"(d[7]),
      "+r"(d[8]), "+r"(d[9]), "+r"(d[10]), "+r"(d[11]), "+r"(d[12]), "+r"(d[13]), "+r"(d[14]), "+r"(d[15]),
      "+r"(d[16]), "+r"(d[17]), "+r"(d[18]), "+r"(d[19]), "+r"(d[20]), "+r"(d[21]), "+r"(d[22]), "+r"(d[23]),
      "+r"(d[24]), "+r"(d[25]), "+r"(d[26]), "+r"(d[27]), "+r"(d[28]), "+r"(d[29]), "+r"(d[30]), "+r"(d[31]),
      "+r"(d[32]), "+r"(d[33]), "+r"(d[34]), "+r"(d[35])
    : "r"(a0), "r"(a1), "r"(a2), "r"(a3), "l"(descB));
}

template <int SCALE_D>
__device__ __forceinline__ void wgmma_n192(uint32_t (&d)[48], uint32_t a0, uint32_t a1, uint32_t a2, uint32_t a3, uint64_t descB) {
  if (SCALE_D == 0)
  asm volatile("wgmma.mma_async.sync.aligned.m64n192k16.f16.f16.f16 "
    "{%0, %1, %2, %3, %4, %5, %6, %7, %8, %9, %10, %11, %12, %13, %14, %15, "
    "%16, %17, %18, %19, %20, %21, %22, %23, %24, %25, %26, %27, %28, %29, %30, %31, "
    "%32, %33, %34, %35, %36, %37, %38, %39, %40, %41, %42, %43, %44, %45, %46, %47}, "
    "{%48, %49, %50, %51}, %52, 0, 1, 1, 0;\n"
    : "=r"(d[0]), "=r"(d[1]), "=r"(d[2]), "=r"(d[3]), "=r"(d[4]), "=r"(d[5]), "=r"(d[6]), "=r"(d[7]),
      "=r"(d[8]), "=r"(d[9]), "=r"(d[10]), "=r"(d[11]), "=r"(d[12]), "=r"(d[13]), "=r"(d[14]), "=r"(d[15]),
      "=r"(d[16]), "=r"(d[17]), "=r"(d[18]), "=r"(d[19]), "=r"(d[20]), "=r"(d[21]), "=r"(d[22]), "=r"(d[23]),
      "=r"(d[24]), "=r"(d[25]), "=r"(d[26]), "=r"(d[27]), "=r"(d[28]), "=r"(d[29]), "=r"(d[30]), "=r"(d[31]),
      "=r"(d[32]), "=r"(d[33]), "=r"(d[34]), "=r"(d[35]), "=r"(d[36]), "=r"(d[37]), "=r"(d[38]), "=r"(d[39]),
      "=r"(d[40]), "=r"(d[41]), "=r"(d[42]), "=r"(d[43]), "=r"(d[44]), "=r"(d[45]), "=r"(d[46]), "=r"(d[47])
    : "r"(a0), "r"(a1), "r"(a2), "r"(a3), "l"(descB));
  else
  asm volatile("wgmma.mma_async.sync.aligned.m64n192k16.f16.f16.f16 "
    "{%0, %1, %2, %3, %4, %5, %6, %7, %8, %9, %10, %11, %12, %13, %14, %15, "
    "%16, %17, %18, %19, %20, %21, %22, %23, %24, %25, %26, %27, %28, %29, %30, %31, "
    "%32, %33, %34, %35, %36, %37, %38, %39, %40, %41, %42, %43, %44, %45, %46, %47}, "
    "{%48, %49, %50, %51}, %52, 1, 1, 1, 0;\n"
    : "+r"(d[0]), "+r"(d[1]), "+r"(d[2]), "+r"(d[3]), "+r"(d[4]), "+r"(d[5]), "+r"(d[6]), "+r"(d[7]),
      "+r"(d[8]), "+r"(d[9]), "+r"(d[10]), "+r"(d[11]), "+r"(d[12]), "+r"(d[13]), "+r"(d[14]), "+r"(d[15]),
      "+r"(d[16]), "+r"(d[17]), "+r"(d[18]), "+r"(d[19]), "+r"(d[20]), "+r"(d[21]), "+r"(d[22]), "+r"(d[23]),
      "+r"(d[24]), "+r"(d[25]), "+r"(d[26]), "+r"(d[27]), "+r"(d[28]), "+r"(d[29]), "+r"(d[30]), "+r"(d[31]),
      "+r"(d[32]), "+r"(d[33]), "+r"(d[34]), "+r"(d[35]), "+r"(d[36]), "+r"(d[37]), "+r"(d[38]), "+r"(d[39]),
      "+r"(d[40]), "+r"(d[41]), "+r"(d[42]), "+r"(d[43]), "+r"(d[44]), "+r"(d[45]), "+r"(d[46]), "+r"(d[47])
    : "r"(a0), "r"(a1), "r"(a2), "r"(a3), "l"(descB));
}

template <int SCALE_D>
__device__ __forceinline__ void wgmma_n56(uint32_t (&d)[14], uint32_t a0, uint32_t a1, uint32_t a2, uint32_t a3, uint64_t descB) {
  if (SCALE_D == 0)
  asm volatile("wgmma.mma_async.sync.aligned.m64n56k16.f16.f16.f16 "
    "{%0, %1, %2, %3, %4, %5, %6, %7, %8, %9, %10, %11, %12, %13}, "
    "{%14, %15, %16, %17}, %18, 0, 1, 1, 0;\n"
    : "=r"(d[0]), "=r"(d[1]), "=r"(d[2]), "=r"(d[3]), "=r"(d[4]), "=r"(d[5]), "=r"(d[6]), "=r"(d[7]),
      "=r"(d[8]), "=r"(d[9]), "=r"(d[10]), "=r"(d[11]), "=r"(d[12]), "=r"(d[13])
    : "r"(a0), "r"(a1), "r"(a2), "r"(a3), "l"(descB));
  else
  asm volatile("wgmma.mma_async.sync.aligned.m64n56k16.f16.f16.f16 "
    "{%0, %1, %2, %3, %4, %5, %6, %7, %8, %9, %10, %11, %12, %13}, "
    "{%14, %15, %16, %17}, %18, 1, 1, 1, 0;\n"
    : "+r"(d[0]), "+r"(d[1]), "+r"(d[2]), "+r"(d[3]), "+r"(d[4]), "+r"(d[5]), "+r"(d[6]), "+r"(d[7]),
      "+r"(d[8]), "+r"(d[9]), "+r"(d[10]), "+r"(d[11]), "+r"(d[12]), "+r"(d[13])
    : "r"(a0), "r"(a1), "r"(a2), "r"(a3), "l"(descB));
}

template <int SCALE_D>
__device__ __forceinline__ void wgmma_pv(uint32_t (&d)[14], uint32_t a0, uint32_t a1, uint32_t a2, uint32_t a3, uint64_t descB) {
  if (SCALE_D == 0)
  asm volatile("wgmma.mma_async.sync.aligned.m64n56k16.f16.f16.f16 "
    "{%0, %1, %2, %3, %4, %5, %6, %7, %8, %9, %10, %11, %12, %13}, "
    "{%14, %15, %16, %17}, %18, 0, 1, 1, 1;\n"
    : "=r"(d[0]), "=r"(d[1]), "=r"(d[2]), "=r"(d[3]), "=r"(d[4]), "=r"(d[5]), "=r"(d[6]), "=r"(d[7]),
      "=r"(d[8]), "=r"(d[9]), "=r"(d[10]), "=r"(d[11]), "=r"(d[12]), "=r"(d[13])
    : "r"(a0), "r"(a1), "r"(a2), "r"(a3), "l"(descB));
  else
  asm volatile("wgmma.mma_async.sync.aligned.m64n56k16.f16.f16.f16 "
    "{%0, %1, %2, %3, %4, %5, %6, %7, %8, %9, %10, %11, %12, %13}, "
    "{%14, %15, %16, %17}, %18, 1, 1, 1, 1;\n"
    : "+r"(d[0]), "+r"(d[1]), "+r"(d[2]), "+r"(d[3]), "+r"(d[4]), "+r"(d[5]), "+r"(d[6]), "+r"(d[7]),
      "+r"(d[8]), "+r"(d[9]), "+r"(d[10]), "+r"(d[11]), "+r"(d[12]), "+r"(d[13])
    : "r"(a0), "r"(a1), "r"(a2), "r"(a3), "l"(descB));
}

__global__ void __launch_bounds__(192 * PBY) prepack_kernel(const __nv_bfloat16* __restrict__ wqkv, const __nv_bfloat16* __restrict__ wo,
                                                      const __nv_bfloat16* __restrict__ x, int first_rows) {
  asm volatile("griddepcontrol.launch_dependents;");
  __shared__ float red2[PBY][6][16];
  float (*red)[16] = red2[threadIdx.y];
  __shared__ __align__(16) __half stage[PBY][1536];
  __half* dst = stage[threadIdx.y];
  const int c = threadIdx.x, nb = blockIdx.x * PBY + threadIdx.y;
  uint32_t u[4];
  int base, gofs;
  float scale = 1.0f;
  if (nb < 72) {
    const int h = nb / 18, j = nb % 18, part = j / 6;
    const int col = (part == 0 ? 192 : part == 1 ? 0 : 384) + h * 48 + (j % 6) * 8;
    const uint4 raw = *reinterpret_cast<const uint4*>(wqkv + c * 576 + col);
    u[0] = raw.x; u[1] = raw.y; u[2] = raw.z; u[3] = raw.w;
    if (part == 1) scale = 0.14433756729740643f * 1.4426950408889634f;
    const int cc = c >> 5, q = (c >> 3) & 3, s1 = (c >> 2) & 1, hh = (c >> 1) & 1, e = c & 1;
    base = (2 * cc + s1) * 128 + hh * 64 + 2 * q + e;
    gofs = qkv_pos(h, c >> 4) + j * 256;
  } else {
    const int jb = nb - 72;
#pragma unroll
    for (int i = 0; i < 4; i++) u[i] = *reinterpret_cast<const uint32_t*>(wo + c * 192 + 32 * (jb >> 2) + 8 * i + 2 * (jb & 3));
    base = (c >> 4) * 128 + ((c >> 3) & 1) * 64 + (c & 7);
    gofs = wo_pos(c >> 4) + jb * 256;
  }
  if (threadIdx.y == 0 && c < 32)
    for (int i = blockIdx.x + 96 / PBY * c; i < first_rows * NWX / 4; i += 96 / PBY * 32)
      asm volatile("cp.async.bulk.prefetch.L2.global [%0], %1;" :: "l"(reinterpret_cast<const uint8_t*>(x) + (size_t)i * 10752), "n"(10752) : "memory");
  float v[8], t[16];
#pragma unroll
  for (int i = 0; i < 4; i++) { v[2 * i] = lo2f(u[i]); v[2 * i + 1] = hi2f(u[i]); }
#pragma unroll
  for (int i = 0; i < 16; i++) t[i] = i < 8 ? v[i] : v[i - 8] * v[i - 8];
#pragma unroll
  for (int n = 8; n >= 1; n >>= 1) {
    const bool up = c & (2 * n);
#pragma unroll
    for (int i = 0; i < n; i++) t[i] = (up ? t[i + n] : t[i]) + __shfl_xor_sync(~0u, up ? t[i] : t[i + n], 2 * n);
  }
  t[0] += __shfl_xor_sync(~0u, t[0], 1);
  if (!(c & 1)) red[c >> 5][(c & 31) >> 1] = t[0];
  __syncthreads();
#pragma unroll
  for (int i = 0; i < 16; i++) t[i] = red[0][i] + red[1][i] + red[2][i] + red[3][i] + red[4][i] + red[5][i];
  float mx = 0.f, sm = 0.f;
#pragma unroll
  for (int n = 0; n < 8; n++) {
    const float m = nb < 72 ? t[n] * (1.0f / 192.0f) : 0.f;
    dst[base + n * 8] = __float2half_rn(__bfloat162float(__float2bfloat16((v[n] - m) * scale)));
    const float nn = (t[8 + n] - 0.999f * m * t[n]) * scale * scale * 1.01f;
    mx = fmaxf(mx, nn); sm += nn;
  }
  if (c == 0) g_wnorm[nb] = make_float2(mx, sm);
  __syncthreads();
  g_wpack[gofs / 16 + (c & 15)] = reinterpret_cast<const uint4*>(dst)[c];
}

__device__ __forceinline__ int window_of(int round, int nfull, int cta, int ncta, int wg) {
  if (round < nfull) return round * 2 * ncta + 2 * cta + wg;
  const int rem = NWIN - nfull * 2 * ncta;
  const int i = cta + wg * ncta;
  return i < rem ? nfull * 2 * ncta + i : -1;
}

template <int S0 = 0, int S1 = 12>
__device__ __forceinline__ void mma_qkv(uint32_t (&acc)[36], const uint32_t (&A)[48], const uint64_t* d) {
#pragma unroll
  for (int s = S0; s < S1; s++) {
    if (s == 0) wgmma_n144<0>(acc, A[4 * s], A[4 * s + 1], A[4 * s + 2], A[4 * s + 3], d[s]);
    else        wgmma_n144<1>(acc, A[4 * s], A[4 * s + 1], A[4 * s + 2], A[4 * s + 3], d[s]);
  }
  wg_commit();
}
__device__ __forceinline__ void mma_proj(uint32_t (&acc)[48], const uint32_t (&A)[12], const uint64_t* d) {
#pragma unroll
  for (int s = 0; s < 3; s++) wgmma_n192<1>(acc, A[4 * s], A[4 * s + 1], A[4 * s + 2], A[4 * s + 3], d[s]);
}
__device__ __forceinline__ void mma_s(uint32_t (&S)[14], const uint32_t (&Q)[12], const uint64_t* d) {
  wgmma_n56<0>(S, Q[0], Q[1], Q[2], Q[3], d[0]);
  wgmma_n56<1>(S, Q[4], Q[5], Q[6], Q[7], d[1]);
  wgmma_n56<1>(S, Q[8], Q[9], Q[10], Q[11], d[2]);
}
__device__ __forceinline__ void mma_pv(uint32_t (&O)[14], const uint32_t (&P)[12], const uint64_t* d) {
  wgmma_pv<0>(O, P[0], P[1], P[2], P[3], d[0]);
  wgmma_pv<1>(O, P[4], P[5], P[6], P[7], d[1]);
  wgmma_pv<1>(O, P[8], P[9], P[10], P[11], d[2]);
}

#define PIN() asm volatile("pmevent 0;" ::: "memory")
template <int A, int B> __device__ __forceinline__ void hold(uint32_t* v) {
#pragma unroll
  for (int i = A; i < B; i++) asm volatile("" : "+r"(v[i]));
}
__device__ __forceinline__ void stsm12(const uint32_t* v, uint32_t addr) {
#pragma unroll
  for (int j = 0; j < 3; j++) stsm4(addr + 2 * j * KV_PITCH, v[4 * j], v[4 * j + 1], v[4 * j + 2], v[4 * j + 3]);
}
__device__ __forceinline__ void load_v48(uint32_t (&v)[6], uint32_t addr) {
  asm volatile("ldmatrix.sync.aligned.m8n8.x4.shared.b16 {%0,%1,%2,%3}, [%4];" : "=r"(v[0]), "=r"(v[1]), "=r"(v[2]), "=r"(v[3]) : "r"(addr) : "memory");
  asm volatile("ldmatrix.sync.aligned.m8n8.x2.shared.b16 {%0,%1}, [%2];" : "=r"(v[4]), "=r"(v[5]) : "r"(addr + 4 * KV_PITCH) : "memory");
}
__device__ __forceinline__ void finish_o(const uint32_t (&O)[14], const uint32_t (&v)[6], uint32_t p48, uint32_t vmask, uint32_t (&Of)[12]) {
  const float2 l = __half22float2(__hadd2_rn(u2h(__byte_perm(O[12], O[13], 0x5410)), u2h(p48)));
  float i0, i1;
  asm("rcp.approx.ftz.f32 %0, %1;" : "=f"(i0) : "f"(l.x));
  asm("rcp.approx.ftz.f32 %0, %1;" : "=f"(i1) : "f"(l.y));
  const uint32_t inv = packh(i0, i1) & vmask;
#pragma unroll
  for (int i = 0; i < 12; i++) {
    const uint32_t t = h2u(__hfma2(u2h(v[i >> 1]), (i & 1) ? hcast<1>(p48) : hcast<0>(p48), u2h(O[i])));
    Of[i] = (i & 1) ? fmul_b<1>(t, inv) : fmul_b<0>(t, inv);
  }
  hold<0, 12>(Of);
}
#define PSTAT 12
template <int A, int B>
__device__ __forceinline__ void ln_sums(const uint32_t (&X)[48], float (&s1)[2], float (&s2)[2]) {
  if (PSTAT) {
    static_assert(PSTAT == 0 || (A % (2 * PSTAT + !PSTAT) == 0 && B % (2 * PSTAT + !PSTAT) == 0), "whole groups");
#pragma unroll
    for (int g = A; g < B; g += 2 * PSTAT + !PSTAT)
#pragma unroll
      for (int a = 0; a < 2; a++) {
        __half2 p1 = u2h(X[g + a]), p2 = __hmul2_rn(p1, p1);
#pragma unroll
        for (int i = 1; i < PSTAT; i++) { const __half2 v = u2h(X[g + a + 2 * i]); p1 = __hadd2_rn(p1, v); p2 = __hfma2(v, v, p2); }
        const float2 f1 = __half22float2(p1), f2 = __half22float2(p2);
        s1[a] = g == 0 ? f1.x + f1.y : s1[a] + (f1.x + f1.y);
        s2[a] = g == 0 ? f2.x + f2.y : s2[a] + (f2.x + f2.y);
      }
  } else {
#pragma unroll
    for (int i = A; i < B; i++) {
      const float2 f = __half22float2(u2h(X[i]));
      s1[i & 1] = i < 2 ? f.x + f.y : s1[i & 1] + (f.x + f.y);
      s2[i & 1] = fmaf(f.x, f.x, i < 2 ? f.y * f.y : fmaf(f.y, f.y, s2[i & 1]));
    }
  }
  asm volatile("" : "+f"(s1[0]), "+f"(s1[1]), "+f"(s2[0]), "+f"(s2[1]));
}
__device__ __forceinline__ uint32_t ln_rstd(const float (&s1)[2], const float (&s2)[2], float lo, float hi, uint32_t vmask, bool& ok) {
  float r[2];
  ok = true;
#pragma unroll
  for (int a = 0; a < 2; a++) {
    float m = s1[a], v = s2[a];
    m += __shfl_xor_sync(~0u, m, 1); v += __shfl_xor_sync(~0u, v, 1);
    m += __shfl_xor_sync(~0u, m, 2); v += __shfl_xor_sync(~0u, v, 2);
    ok = ok & (v <= hi) & ((v >= lo) | !(vmask >> (16 * a) & 1));
    m *= 1.0f / 192.0f;
    m *= m;
    v = fmaxf(fmaf(v, 1.0f / 192.0f, -m), 0.f) + 1e-5f;
    ok = ok & (m <= (PSTAT ? 16.f : 64.f) * v);
    asm("rsqrt.approx.ftz.f32 %0, %1;" : "=f"(r[a]) : "f"(v));
  }
  uint32_t rk = packh(r[0], r[1]);
  hold<0, 1>(&rk);
  return rk;
}
__device__ __forceinline__ void scale12(uint32_t (&D)[12], const uint32_t* a, uint32_t r) {
#pragma unroll
  for (int i = 0; i < 12; i++) D[i] = (i & 1) ? fmul_b<1>(a[i], r) : fmul_b<0>(a[i], r);
  hold<0, 12>(D);
}
template <int CC>
__device__ __forceinline__ void store_out(const uint32_t (&Y)[48], uint8_t* o0, uint8_t* o1, uint32_t vmask) {
  uint32_t T[8];
#pragma unroll
  for (int i = 0; i < 8; i++) {
    const float2 f = __half22float2(u2h(Y[8 * CC + i]));
    T[i] = pack2(f.x, f.y);
  }
  asm volatile("{\n.reg .pred p;\nsetp.ne.u32 p, %5, 0;\n@p st.global.cs.v4.u32 [%0], {%1,%2,%3,%4};\n}\n"
               :: "l"(o0 + CC * 64), "r"(T[0]), "r"(T[2]), "r"(T[4]), "r"(T[6]), "r"(vmask) : "memory");
  asm volatile("{\n.reg .pred p;\nsetp.lt.s32 p, %5, 0;\n@p st.global.cs.v4.u32 [%0], {%1,%2,%3,%4};\n}\n"
               :: "l"(o1 + CC * 64), "r"(T[1]), "r"(T[3]), "r"(T[5]), "r"(T[7]), "r"(vmask) : "memory");
}
__device__ __forceinline__ void proxy_fence() { asm volatile("fence.proxy.async.shared::cta;" ::: "memory"); }
__device__ __forceinline__ void row_max(const uint32_t (&S)[14], uint32_t& k48, uint32_t& mx) {
  k48 = __shfl_sync(~0u, __byte_perm(S[12], S[13], 0x5410), 0, 4);
  const uint32_t m0 = fmax2(fmax2(fmax2(S[0], S[2]), S[4]), fmax2(fmax2(S[6], S[8]), S[10]));
  const uint32_t m1 = fmax2(fmax2(fmax2(S[1], S[3]), S[5]), fmax2(fmax2(S[7], S[9]), S[11]));
  mx = fmax2(__byte_perm(m0, m1, 0x5410), __byte_perm(m0, m1, 0x7632));
  mx = fmax2(mx, __shfl_xor_sync(~0u, mx, 1));
  mx = fmax2(mx, __shfl_xor_sync(~0u, mx, 2));
  mx = fmax2(mx, k48);
  hold<0, 1>(&mx);
}
__device__ __forceinline__ void row_exp(const uint32_t (&S)[14], uint32_t k48, uint32_t mx, uint32_t (&P)[12], uint32_t& p48) {
#pragma unroll
  for (int j = 0; j < 12; j++) P[j] = fex2((j & 1) ? fsub_b<1>(S[j], mx) : fsub_b<0>(S[j], mx));
  p48 = fex2(h2u(__hsub2_rn(u2h(k48), u2h(mx))));
  hold<0, 12>(P); hold<0, 1>(&p48);
}
template <int S0, int S1>
__device__ __forceinline__ void load_x(uint32_t (&X)[48], uint32_t t0) {
#pragma unroll
  for (int s = S0; s < S1; s++)
    asm volatile("ld.shared.v4.u32 {%0,%1,%2,%3}, [%4];" : "=r"(X[4 * s]), "=r"(X[4 * s + 1]), "=r"(X[4 * s + 2]), "=r"(X[4 * s + 3])
                 : "r"(((s & 1) ? (t0 ^ 16) : t0) + (s >> 1) * 128) : "memory");
}

template <int CNT, int EXPECT = CNT * SLICE>
__device__ __forceinline__ void load_slices(uint32_t sb, const uint8_t* src, int slice, int slot, int bar) {
  if (EXPECT)
    asm volatile("{\n.reg .pred p;\nelect.sync _|p, 0xffffffff;\n@p mbarrier.arrive.expect_tx.shared::cta.b64 _, [%0], %1;\n}\n"
                 :: "r"(sb + bar), "n"(EXPECT) : "memory");
  asm volatile("{\n.reg .pred p;\nelect.sync _|p, 0xffffffff;\n"
               "@p cp.async.bulk.shared::cluster.global.mbarrier::complete_tx::bytes [%0], [%1], %2, [%3];\n}\n"
               :: "r"(sb + OFF_W + slot * SLICE), "l"(src + slice * SLICE), "n"(CNT * SLICE), "r"(sb + bar) : "memory");
}
__device__ __forceinline__ void warp_arrive(uint32_t bar) {
  asm volatile("{\n.reg .pred p;\nelect.sync _|p, 0xffffffff;\n@p mbarrier.arrive.shared::cta.b64 _, [%0];\n}\n" :: "r"(bar) : "memory");
}

__device__ __forceinline__ float2 fp16_limits(int lane) {
  float mx[4] = {0.f, 0.f, 0.f, 0.f}, sm[4] = {0.f, 0.f, 0.f, 0.f};
#pragma unroll
  for (int i = 0; i < 3; i++) {
    const int nb = lane + 32 * i, part = nb < 72 ? (nb % 18) / 6 : 3;
    const float2 w = g_wnorm[nb];
#pragma unroll
    for (int k = 0; k < 4; k++) if (part == k) { mx[k] = fmaxf(mx[k], w.x); sm[k] += w.y; }
  }
#pragma unroll
  for (int k = 0; k < 4; k++)
#pragma unroll
    for (int d = 16; d; d >>= 1) { mx[k] = fmaxf(mx[k], __shfl_xor_sync(~0u, mx[k], d)); sm[k] += __shfl_xor_sync(~0u, sm[k], d); }
  const float big = fmaxf(fmaxf(mx[0], mx[1]), mx[2]);
  float small = 1.f;
  bool good = sm[0] + sm[1] + sm[2] + sm[3] < 1e30f;
#pragma unroll
  for (int k = 0; k < 4; k++) { good = good && (mx[k] == 0.f || mx[k] >= 2.5e-4f); if (k < 3 && mx[k] > 0.f) small = fminf(small, mx[k]); }
  good = good && 250.f * 48.f * sqrtf(mx[0] * mx[1]) <= 5e4f;
  good = good && 16.f * 49.f * sqrtf(mx[2]) <= 5e4f && big <= 1e6f;
  good = good && 16.f * sqrtf(sm[2] * mx[3]) <= 2e4f;
  return make_float2(192.f * 2.4e-7f / small, good ? fminf(2.5e8f, 9e8f / fmaxf(big, 1e-30f)) : -1.f);
}

__device__ __forceinline__ void slow_window(float* sm, int w, int t, const __nv_bfloat16* __restrict__ x, const __nv_bfloat16* __restrict__ dw,
                                            const __nv_bfloat16* __restrict__ wqkv, const __nv_bfloat16* __restrict__ wo, __nv_bfloat16* __restrict__ out) {
  float* x0 = sm; float* h = x0 + 49 * CH; float* qkv = h + 49 * CH; float* S = qkv + 49 * 576;
  const int wy = w / NWX, wx = w % NWX;
  auto sync = [] { asm volatile("bar.sync 6, 128;" ::: "memory"); };
#pragma unroll 1
  for (int i = t; i < 49 * CH; i += 128) {
    const int k = i / CH, c = i % CH, y = wy * 7 + k / 7, xx = wx * 7 + k % 7;
    float pe = 0.f;
#pragma unroll 1
    for (int a = 0; a < 9; a++) {
      const int yy = y + a / 3 - 1, xc = xx + a % 3 - 1;
      if (yy >= 0 && yy < IMG && xc >= 0 && xc < IMG) pe = fmaf(__bfloat162float(x[((size_t)yy * IMG + xc) * CH + c]), __bfloat162float(dw[a * CH + c]), pe);
    }
    x0[i] = __bfloat162float(__float2bfloat16(__bfloat162float(x[((size_t)y * IMG + xx) * CH + c]) + pe));
  }
  sync();
  if (t < 49) {
    float m = 0.f, v = 0.f;
#pragma unroll 1
    for (int c = 0; c < CH; c++) m += x0[t * CH + c];
    m *= 1.0f / CH;
#pragma unroll 1
    for (int c = 0; c < CH; c++) { const float d = x0[t * CH + c] - m; v = fmaf(d, d, v); }
    const float rs = 1.0f / sqrtf(v * (1.0f / CH) + 1e-5f);
#pragma unroll 1
    for (int c = 0; c < CH; c++) h[t * CH + c] = (x0[t * CH + c] - m) * rs;
  }
  sync();
#pragma unroll 1
  for (int i = t; i < 7 * 576; i += 128) {
    const int n = i % 576, k0 = i / 576 * 7;
    float a[7] = {0.f, 0.f, 0.f, 0.f, 0.f, 0.f, 0.f};
#pragma unroll 1
    for (int c = 0; c < CH; c++) {
      const float wv = __bfloat162float(wqkv[c * 576 + n]);
#pragma unroll
      for (int k = 0; k < 7; k++) a[k] = fmaf(h[(k0 + k) * CH + c], wv, a[k]);
    }
#pragma unroll
    for (int k = 0; k < 7; k++) qkv[(k0 + k) * 576 + n] = a[k];
  }
  sync();
#pragma unroll 1
  for (int hd = 0; hd < 4; hd++) {
#pragma unroll 1
    for (int i = t; i < 49 * 49; i += 128) {
      const int a = i / 49, b = i % 49;
      float v = 0.f;
#pragma unroll 1
      for (int d = 0; d < 48; d++) v = fmaf(qkv[a * 576 + hd * 48 + d], qkv[b * 576 + 192 + hd * 48 + d], v);
      S[i] = v * 0.14433756729740643f;
    }
    sync();
    if (t < 49) {
      float m = S[t * 49], l = 0.f;
#pragma unroll 1
      for (int b = 1; b < 49; b++) m = fmaxf(m, S[t * 49 + b]);
#pragma unroll 1
      for (int b = 0; b < 49; b++) { const float e = expf(S[t * 49 + b] - m); S[t * 49 + b] = e; l += e; }
#pragma unroll 1
      for (int b = 0; b < 49; b++) S[t * 49 + b] /= l;
    }
    sync();
#pragma unroll 1
    for (int i = t; i < 49 * 48; i += 128) {
      const int a = i / 48, d = i % 48;
      float v = 0.f;
#pragma unroll 1
      for (int b = 0; b < 49; b++) v = fmaf(S[a * 49 + b], qkv[b * 576 + 384 + hd * 48 + d], v);
      h[a * CH + hd * 48 + d] = v;
    }
    sync();
  }
#pragma unroll 1
  for (int i = t; i < 7 * CH; i += 128) {
    const int n = i % CH, k0 = i / CH * 7;
    float a[7] = {0.f, 0.f, 0.f, 0.f, 0.f, 0.f, 0.f};
#pragma unroll 1
    for (int c = 0; c < CH; c++) {
      const float wv = __bfloat162float(wo[c * CH + n]);
#pragma unroll
      for (int k = 0; k < 7; k++) a[k] = fmaf(h[(k0 + k) * CH + c], wv, a[k]);
    }
#pragma unroll
    for (int k = 0; k < 7; k++)
      out[((size_t)(wy * 7 + k0 / 7) * IMG + wx * 7 + k) * CH + n] = __float2bfloat16(x0[(k0 + k) * CH + n] + a[k]);
  }
  sync();
}

__global__ void __launch_bounds__(384, 1)
fused_kernel(const __grid_constant__ CUtensorMap tmx, const __grid_constant__ CUtensorMap tmp, const __grid_constant__ Descs ds, const __nv_bfloat16* __restrict__ dw, __nv_bfloat16* __restrict__ out, const int never,
             const __nv_bfloat16* __restrict__ x, const __nv_bfloat16* __restrict__ wqkv, const __nv_bfloat16* __restrict__ wo) {
  extern __shared__ __align__(1024) uint8_t smem[];
  const uint32_t sb = (uint32_t)__cvta_generic_to_shared(smem);
  const int tid = threadIdx.x, lane = tid & 31;
  const int warp = __shfl_sync(0xffffffffu, tid >> 5, 0);
  const int cta = blockIdx.x, ncta = gridDim.x;
  const int nfull = NWIN / (2 * ncta);
  const int nrounds = nfull + ((NWIN - nfull * 2 * ncta) > cta ? 1 : 0);

  if (warp == 0) GTS(0);
  if (warp == 10 && lane == 0) asm volatile("prefetch.tensormap [%0];" :: "l"(reinterpret_cast<uint64_t>(&tmx)) : "memory");
  if (tid == 0) {
    mbar_init(sb + BAR_FIRST, 1);
    asm volatile("fence.mbarrier_init.release.cluster;" ::: "memory");
    asm volatile("mbarrier.arrive.expect_tx.shared::cta.b64 _, [%0], %1;" :: "r"(sb + BAR_FIRST), "n"(2 * HALO_BYTES) : "memory");
#pragma unroll
    for (int k = 0; k < 2; k++) {
      const int w = max(window_of(0, nfull, cta, ncta, k), 0), a = w / NWX;
      asm volatile("cp.async.bulk.tensor.3d.shared::cluster.global.mbarrier::complete_tx::bytes [%0], [%1, {0, %3, %4}], [%2];"
                   :: "r"(sb + OFF_HALO + k * HALO_BYTES), "l"(reinterpret_cast<uint64_t>(&tmp)), "r"(sb + BAR_FIRST),
                      "r"((w - a * NWX) * 7 - 1), "r"(a * 7 - 1) : "memory");
    }
    if ((sb & 0x3FFFF) != SMEM_BASE || nrounds > 128) __trap();
    for (int i = 0; i < 6; i++) mbar_init(sb + BAR_FH + 8 * i, 1);
    for (int i = 0; i < 4; i++) mbar_init(sb + BAR_E + 8 * i, 8);
    for (int i = 0; i < 9; i++) mbar_init(sb + BAR_XFULL + 8 * i, 1);
    mbar_init(sb + BAR_TFULL, 3);
    mbar_init(sb + BAR_TEMPTY, 8);
    asm volatile("fence.mbarrier_init.release.cluster;" ::: "memory");
  }
  if (tid >= 128 && tid < 136) *reinterpret_cast<uint32_t*>(smem + OFF_REDO + (tid - 128) * 4) = 0;
  if (tid < 96) {
    *reinterpret_cast<uint4*>(smem + OFF_KV + (tid / 48) * KV_BYTES + 6 * KV_PITCH + (tid % 48) * 16) = make_uint4(0x3c003c00u, 0x3c003c00u, 0x3c003c00u, 0x3c003c00u);
    proxy_fence();
  }
  __syncthreads();

  if (warp == 0) GTS(3);
  if (warp < 11) {
#pragma unroll 1
    for (int u = 0; u < (warp < 10 ? 2 : 1); u++) {
      const int cb = warp < 9 ? warp % 3 : 2 * (warp - 9) + u, y = warp < 9 ? 2 * (warp / 3) + u : 6;
      const int ch0 = cb * 64 + (lane & 15) * 4;
      uint32_t wt[9][2], px[3][9][2];
#pragma unroll
      for (int t = 0; t < 9; t++) {
        const uint2 v = *reinterpret_cast<const uint2*>(dw + t * CH + ch0);
        wt[t][0] = v.x; wt[t][1] = v.y;
      }
      mbar_wait(sb + BAR_FIRST, 0);
      if (warp == 0 && u == 0) GTS(7);
      const uint32_t ld = sb + OFF_HALO + (lane >> 4) * HALO_BYTES + y * 3456 + ch0 * 2;
#pragma unroll
      for (int p = 0; p < 27; p++)
        asm volatile("ld.shared.v2.u32 {%0,%1}, [%2];" : "=r"(px[p / 9][p % 9][0]), "=r"(px[p / 9][p % 9][1]) : "r"(ld + p * 384));
      const uint32_t st0 = sb + OFF_TILE + (lane >> 4) * TILE_BYTES + ch0 * 4;
      const uint32_t sa = (st0 ^ ((y & 1) << 4)) + y * 2304;
      uint32_t o[2][2];
#pragma unroll
      for (int j = 0; j < 7; j++) {
#pragma unroll
        for (int e = 0; e < 2; e++) {
          uint32_t a = hmul(px[0][j][e], wt[0][e]);
#pragma unroll
          for (int t = 1; t < 9; t++) a = hfma(px[t / 3][j + t % 3][e], wt[t][e], a);
          a = hadd(px[1][j + 1][e], a);
          o[j & 1][e] = packh(lo2f(a), hi2f(a));
        }
        if (j & 1)
          asm volatile("st.shared.v4.u32 [%0], {%1,%2,%3,%4};" :: "r"((j == 3 ? sa ^ 16 : sa) + (j >> 1) * 768),
                       "r"(o[0][0]), "r"(o[1][0]), "r"(o[0][1]), "r"(o[1][1]) : "memory");
      }
      const uint32_t sb6 = (st0 ^ ((~y & 2) << 3)) + (21 + (y >> 1)) * 768 + (y & 1) * 4;
      asm volatile("st.shared.u32 [%0], %1;\nst.shared.u32 [%0 + 8], %2;" :: "r"(sb6), "r"(o[0][0]), "r"(o[0][1]) : "memory");
      if (y == 6) asm volatile("st.shared.u32 [%0 + 4], %1;\nst.shared.u32 [%0 + 12], %1;" :: "r"(sb6), "r"(0) : "memory");
    }
    if (warp == 0) GTS(6);
    asm volatile("bar.arrive 8, 384;\nbar.sync 7, 352;" ::: "memory");
  }

  if (warp >= 8) {
    asm volatile("setmaxnreg.dec.sync.aligned.u32 " PREGS ";");
    if (warp == 11) {
      asm volatile("griddepcontrol.wait;" ::: "memory");
      GTS(2);
      load_slices<3, 0>(sb, ds.src, 0, 0, BAR_F0);
      *reinterpret_cast<float2*>(smem + OFF_LIM) = fp16_limits(lane);
      asm volatile("{\n.reg .pred p;\nelect.sync _|p, 0xffffffff;\n@p mbarrier.arrive.expect_tx.shared::cta.b64 _, [%0], %1;\n}\n"
                   :: "r"(sb + BAR_F0), "n"(3 * SLICE) : "memory");
      asm volatile("bar.sync 8, 384;" ::: "memory");
      load_slices<3, 5 * SLICE>(sb, ds.src, 3, 3, BAR_F1);
      load_slices<1, 0>(sb, ds.src, 13, SLOT_U, BAR_F1);
      load_slices<1, 0>(sb, ds.src, 12, SLOT_V, BAR_F1);
      for (int r = 0; r < nrounds; r++) {
        const int par = r & 1;
        const int h2 = par ? 1 : 2, h3 = par ? 0 : 3;
        mbar_wait(sb + BAR_E, par);
        load_slices<3>(sb, ds.src, 3 * h2, 3 * (h2 & 1), BAR_FH);
        mbar_wait(sb + BAR_E + 8, par);
        load_slices<3>(sb, ds.src, 3 * h3, 3 * (h3 & 1), BAR_FH + 8);
        mbar_wait(sb + BAR_E + 16, par);
        load_slices<1>(sb, ds.src, 12 + h2, SLOT_U, BAR_FU);
        mbar_wait(sb + BAR_E + 24, par);
        load_slices<1>(sb, ds.src, 12 + h3, SLOT_V, BAR_FV);
      }
    } else {
      const int cw = warp - 8;
      const int win = lane >> 4;
      const int ch0 = cw * 64 + (lane & 15) * 4;
      uint32_t wt[9][2];
#pragma unroll
      for (int t = 0; t < 9; t++) {
        uint2 v = *reinterpret_cast<const uint2*>(dw + t * CH + ch0);
        wt[t][0] = v.x; wt[t][1] = v.y;
      }
      const uint32_t xs = sb + OFF_X + cw * 3 * XSLOT;
      const uint32_t xld = xs + (lane >> 4) * 1152 + (lane & 15) * 8;
      const uint32_t xbar = sb + BAR_XFULL + cw * 24;
      const uint32_t st0 = sb + OFF_TILE + win * TILE_BYTES + ch0 * 4;
      const uint64_t tm = reinterpret_cast<uint64_t>(&tmx);
      int cx0, cy0, cx1, cy1;
      auto coords = [&](int r) {
        const int w0 = window_of(r, nfull, cta, ncta, 0);
        int w1 = window_of(r, nfull, cta, ncta, 1);
        if (w1 < 0) w1 = w0;
        const int a = w0 / NWX, b = w1 / NWX;
        cx0 = (w0 - a * NWX) * 7 - 1; cy0 = a * 7 - 1;
        cx1 = (w1 - b * NWX) * 7 - 1; cy1 = b * 7 - 1;
      };
      auto issue = [&](int slot, int dy) {
        asm volatile("{\n.reg .pred p;\nelect.sync _|p, 0xffffffff;\n"
                     "@p mbarrier.arrive.expect_tx.shared::cta.b64 _, [%2], %8;\n"
                     "@p cp.async.bulk.tensor.3d.shared::cluster.global.mbarrier::complete_tx::bytes [%0], [%1, {%3, %4, %5}], [%2];\n"
                     "@p cp.async.bulk.tensor.3d.shared::cluster.global.mbarrier::complete_tx::bytes [%0 + 1152], [%1, {%3, %6, %7}], [%2];\n}\n"
                     :: "r"(xs + slot * XSLOT), "l"(tm), "r"(xbar + slot * 8), "r"(cw * 64), "r"(cx0), "r"(cy0 + dy), "r"(cx1), "r"(cy1 + dy), "n"(XSLOT) : "memory");
      };
      uint32_t accA[7][2], accB[7][2], ctr[7][2], held[2];
      auto row = [&](auto fin, auto mid, auto top, int slot, int y) {
        const uint32_t ld = xld + slot * XSLOT;
        const uint32_t sa = (st0 ^ ((y & 1) << 4)) + y * 2304;
        uint32_t cur[9][2], o[2][2];
#pragma unroll
        for (int p = 0; p < LA; p++)
          asm volatile("ld.shared.v2.u32 {%0,%1}, [%2];" : "=r"(cur[p][0]), "=r"(cur[p][1]) : "r"(ld + p * 128));
#pragma unroll
        for (int j = 0; j < 7; j++) {
          if (j >= 1 && j + LA - 1 < 9)
            asm volatile("ld.shared.v2.u32 {%0,%1}, [%2];" : "=r"(cur[j + LA - 1][0]), "=r"(cur[j + LA - 1][1]) : "r"(ld + (j + LA - 1) * 128));
          if (fin.v) {
#pragma unroll
            for (int e = 0; e < 2; e++) {
              uint32_t a = hfma(cur[j][e], wt[6][e], accA[j][e]);
              a = hfma(cur[j + 1][e], wt[7][e], a);
              a = hfma(cur[j + 2][e], wt[8][e], a);
              a = hadd(ctr[j][e], a);
              o[j & 1][e] = packh(lo2f(a), hi2f(a));
            }
            if (j & 1)
              asm volatile("st.shared.v4.u32 [%0], {%1,%2,%3,%4};" :: "r"((j == 3 ? sa ^ 16 : sa) + (j >> 1) * 768),
                           "r"(o[0][0]), "r"(o[1][0]), "r"(o[0][1]), "r"(o[1][1]) : "memory");
            if (j == 6) {
              const uint32_t sb6 = (st0 ^ ((~y & 2) << 3)) + (21 + (y >> 1)) * 768;
              if (fin.v == 2)
                asm volatile("st.shared.v4.u32 [%0], {%1,%2,%3,%2};" :: "r"(sb6), "r"(o[0][0]), "r"(0), "r"(o[0][1]) : "memory");
              else
                asm volatile("{\n.reg .pred p;\nsetp.ne.s32 p, %5, 0;\n@p st.shared.v4.u32 [%0], {%1,%2,%3,%4};\n}\n"
                             :: "r"(sb6), "r"(held[0]), "r"(o[0][0]), "r"(held[1]), "r"(o[0][1]), "r"(y & 1) : "memory");
              held[0] = o[0][0]; held[1] = o[0][1];
            }
          }
#pragma unroll
          for (int e = 0; e < 2; e++) {
            if (mid.v) {
              uint32_t a = hfma(cur[j][e], wt[3][e], accB[j][e]);
              a = hfma(cur[j + 1][e], wt[4][e], a);
              accA[j][e] = hfma(cur[j + 2][e], wt[5][e], a);
              ctr[j][e] = cur[j + 1][e];
            }
            if (top.v) {
              uint32_t a = hmul(cur[j][e], wt[0][e]);
              a = hfma(cur[j + 1][e], wt[1][e], a);
              accB[j][e] = hfma(cur[j + 2][e], wt[2][e], a);
            }
          }
        }
      };
      held[0] = held[1] = 0;
      if (nrounds > 1) { coords(1); issue(0, 0); issue(1, 1); issue(2, 2); }
      for (int r = 0; r + 1 < nrounds; r++) {
        const bool more = r + 2 < nrounds;
        mbar_wait(xbar, r & 1);
        if (r > 0) issue(2, 2);
        row(IC<0>{}, IC<0>{}, IC<1>{}, 0, 0);
        mbar_wait(xbar + 8, r & 1);
        issue(0, 3);
        row(IC<0>{}, IC<1>{}, IC<1>{}, 1, 0);
        mbar_wait(sb + BAR_TEMPTY, r & 1);
#pragma unroll 1
        for (int k = 0; k < 2; k++) {
          mbar_wait(xbar + 16, (r + k) & 1);
          issue(1, 4 + 3 * k);
          row(IC<1>{}, IC<1>{}, IC<1>{}, 2, 3 * k);
          mbar_wait(xbar, (r + k + 1) & 1);
          issue(2, 5 + 3 * k);
          row(IC<1>{}, IC<1>{}, IC<1>{}, 0, 3 * k + 1);
          mbar_wait(xbar + 8, (r + k + 1) & 1);
          if (k == 1 && more) coords(r + 2);
          if (k == 0 || more) issue(0, k == 0 ? 6 : 0);
          row(IC<1>{}, IC<1>{}, IC<1>{}, 1, 3 * k + 2);
        }
        mbar_wait(xbar + 16, r & 1);
        if (more) issue(1, 1);
        row(IC<2>{}, IC<0>{}, IC<0>{}, 2, 6);
        __syncwarp();
        warp_arrive(sb + BAR_TFULL);
      }
    }
    asm volatile("bar.sync 5, 384;" ::: "memory");
#pragma unroll 1
    for (int i = 0; i < 8; i++) {
      uint32_t bits = *reinterpret_cast<volatile uint32_t*>(smem + OFF_REDO + 4 * i);
#pragma unroll 1
      for (; bits; bits &= bits - 1)
        slow_window(reinterpret_cast<float*>(smem), window_of((i & 3) * 32 + __ffs(bits) - 1, nfull, cta, ncta, i >> 2), tid - 256, x, dw, wqkv, wo, out);
    }
  } else {
    asm volatile("setmaxnreg.inc.sync.aligned.u32 " CREGS ";");
    const int wg = warp >> 2, w4 = warp & 3, g = lane >> 2, q = lane & 3;
    const int row0 = w4 * 16 + g, row1 = row0 + 8;
    const int ps = min(w4 * 8 + g, 24);
    const int pix0 = ps < 21 ? (ps / 3) * IMG + (ps % 3) * 2 : (ps - 21) * 2 * IMG + 6;
    const int pix1 = pix0 + (ps < 21 ? 1 : ps < 24 ? IMG : 0);
    const uint32_t kv = sb + OFF_KV + wg * KV_BYTES;
    const int srow = w4 * 16 + (lane & 15);
    const uint32_t vst = kv + (lane >> 4) * KV_PITCH + (srow < 56 ? srow : min(srow - 7, 55)) * 16;
    uint32_t misc = ((uint32_t)pix1 << 20) | ((uint32_t)pix0 << 8) | q;
    const uint32_t v48 = kv + (lane >> 3) * KV_PITCH + 48 * 16;
    const uint32_t vmask = (row0 < 49 ? 0xffffu : 0u) | (row1 < 49 ? 0xffff0000u : 0u);

    const uint32_t tx = sb + OFF_TILE + wg * TILE_BYTES + ps * 768 + q * 32 + (ps & 1) * 16;
    const int myrounds = window_of(nrounds - 1, nfull, cta, ncta, wg) < 0 ? nrounds - 1 : nrounds;

    if (never == 2) return;
    uint32_t H[48], Y[48];
    const uint64_t* dkv = ds.kv[wg];
    uint32_t P[12], Ofc[12], p48 = 0;
#pragma unroll
    for (int i = 0; i < 48; i++) Y[i] = 0;
#pragma unroll
    for (int i = 0; i < 12; i++) P[i] = Ofc[i] = 0;
    if (warp == 0) GTS(4);
#pragma unroll
    for (int i = 0; i < 48; i++) H[i] = 0;
    if (vmask) load_x<0, 12>(H, tx);
    __syncwarp();
    warp_arrive(sb + BAR_TEMPTY);
    mbar_wait(sb + BAR_F0, 0);
    if (warp == 0) GTS(1);
    if (wg == 1) turn_pass(1);

    uint8_t *o0, *o1;
    uint32_t omask;
    auto out_setup = [&](int r) {
      omask = r >= 0 ? vmask : 0u;
      const int w = window_of(r, nfull, cta, ncta, wg);
      const int wy = w / NWX, wx = w - wy * NWX;
      asm volatile("" : "+r"(misc));
      const uint32_t wb = (uint32_t)(wy * 7 * IMG + wx * 7) * 384u + (misc & 3) * 16;
      o0 = reinterpret_cast<uint8_t*>(out) + (wb + ((misc >> 8) & 0xfff) * 384u);
      o1 = reinterpret_cast<uint8_t*>(out) + (wb + (misc >> 20) * 384u);
    };
#define OUT(c) store_out<c>(Y, o0, o1, omask)
#define AT(c, k) if ((OMAP >> (20 - 4 * (c)) & 15) == (k)) { OUT(c); PIN(); }
#define SITE(k) AT(0, k) AT(1, k) AT(2, k) AT(3, k) AT(4, k) AT(5, k)
    auto release = [&](int i) { warp_arrive(sb + BAR_E + 8 * i); };

    for (int r = 0;; r++) {
      const uint32_t par = r & 1;
      uint32_t acc[36], S[14], O[14], Q[12], V[12], Ofa[12], Ofb[12], vr[6], k48, mx;
      if (r == myrounds) {
        const bool idle = r < nrounds;
        if (idle) { release(0); release(1); }
        mbar_wait(sb + BAR_FU, par ^ 1);
        turn_wait(wg);
        wg_fence(); mma_pv(O, P, dkv + 4); mma_proj(Y, Ofc, ds.pu[0]); wg_commit();
        turn_pass(wg);
        load_v48(vr, v48);
        wg_wait<0>(); keep(O); keep(Y);
        finish_o(O, vr, p48, vmask, Ofa);
        mbar_wait(sb + BAR_FV, par ^ 1);
        turn_wait(wg);
        wg_fence(); mma_proj(Y, Ofa, ds.pv[0]); wg_commit();
        if (wg == 0 || idle) turn_pass(wg);
        wg_wait<0>(); keep(Y);
        if (idle) { release(2); release(3); turn_wait(wg); turn_pass(wg); }
        out_setup(r - 1);
        OUT(0); PIN(); OUT(1); PIN(); OUT(2); PIN(); OUT(3); PIN(); OUT(4); PIN(); OUT(5);
        if (idle) {
          turn_wait(wg); turn_pass(wg);
          turn_wait(wg); turn_pass(wg);
          turn_wait(wg); turn_pass(wg);
          turn_wait(wg);
        }
        if (warp == 0) GTS(5);
        asm volatile("bar.arrive 5, 384;" ::: "memory");
        break;
      }
      const uint64_t* dq0 = ds.q[par];
      float s1[2], s2[2];
      TR(0);
      turn_wait(wg);
      TR(1);
      wg_fence(); mma_pv(O, P, dkv + 4); wg_commit(); mma_qkv<0, K0A>(acc, H, dq0);
      PIN();
      ln_sums<0, 24>(H, s1, s2);
      PIN();
      wg_fence(); mma_qkv<K0A, 12>(acc, H, dq0);
      if (r > 0) { mbar_wait(sb + BAR_FU, par ^ 1); wg_fence(); mma_proj(Y, Ofc, ds.pu[0]); wg_commit(); }
      else { wg_fence(); wg_commit(); }
      turn_pass(wg);
      TR(2);
      load_v48(vr, v48);
      wg_wait<3>(); keep(O);
      wg_sync(wg);
      PIN();
      finish_o(O, vr, p48, vmask, Ofa);
      ln_sums<24, 48>(H, s1, s2);
      float lim_lo, lim_hi;
      asm volatile("ld.shared.v2.f32 {%0,%1}, [%2];" : "=f"(lim_lo), "=f"(lim_hi) : "r"(sb + OFF_LIM) : "memory");
      bool ok;
      const uint32_t rk = ln_rstd(s1, s2, lim_lo, lim_hi, vmask, ok);
      asm volatile("{\n.reg .pred p;\nsetp.eq.s32 p, %2, 0;\n@p red.shared.or.b32 [%0], %1;\n}\n"
                   :: "r"(sb + OFF_REDO + wg * 16 + (r >> 5) * 4), "r"(1u << (r & 31)), "r"((int)ok) : "memory");
      PIN();
      TR(3);
      wg_wait<1>(); keep(acc);
      TR(4);
      release(0);
      scale12(V, acc, rk); stsm12(V, vst + KV_KOFF);
      scale12(V, acc + 24, rk); stsm12(V, vst);
      PIN();
      wg_wait<0>(); keep(Y);
      PIN();
      proxy_fence();
      scale12(Q, acc + 12, rk);
      if (r > 0) mbar_wait(sb + BAR_FV, par ^ 1); else mbar_wait(sb + BAR_F1, 0);
      TR(5);
      turn_wait(wg);
      TR(6);
      if (r > 0) { wg_fence(); mma_proj(Y, Ofa, ds.pv[0]); wg_commit(); }
      wg_fence(); mma_s(S, Q, dkv); mma_qkv<0, B1A>(acc, H, dq0 + 12);
      out_setup(r - 1);
      PIN();
      wg_wait<1>(); keep(Y);
      wg_fence(); mma_qkv<B1A, B1B>(acc, H, dq0 + 12);
      PIN();
      SITE(0);
      wg_wait<1>(); keep(S);
      wg_fence(); mma_qkv<B1B, B1C>(acc, H, dq0 + 12);
      PIN();
      row_max(S, k48, mx);
      SITE(1);
      PIN();
      wg_fence(); mma_qkv<B1C, 12>(acc, H, dq0 + 12);
      turn_pass(wg);
      PIN();
      SITE(2);
      row_exp(S, k48, mx, P, p48);
      PIN();
      TR(7);
      wg_wait<0>(); keep(acc);
      TR(8);
      release(1);
      wg_sync(wg);
      scale12(V, acc, rk); stsm12(V, vst + KV_KOFF);
      scale12(Q, acc + 12, rk); scale12(V, acc + 24, rk); PIN();
      proxy_fence();
      SITE(5);
#define TURN(ID, OF, DQ, FB, X1)                                                        \
      mbar_wait(sb + FB, par);                                                          \
      TR(ID + 1);                                                                       \
      turn_wait(wg);                                                                    \
      wg_fence(); mma_pv(O, P, dkv + 4); mma_s(S, Q, dkv); wg_commit(); mma_qkv<0, KA>(acc, H, DQ); \
      PIN();                                                                            \
      TR(ID + 2);                                                                       \
      load_v48(vr, v48);                                                                \
      X1;                                                                               \
      PIN();                                                                            \
      wg_wait<1>(); keep(S); keep(O);                                                   \
      wg_sync(wg);                                         \
      wg_fence(); mma_qkv<KA, KB>(acc, H, DQ);                                            \
      PIN();                                                                            \
      stsm12(V, vst);                                                                   \
      finish_o(O, vr, p48, vmask, OF);                                                  \
      row_max(S, k48, mx);                                                              \
      PIN();                                                                            \
      wg_fence(); mma_qkv<KB, 12>(acc, H, DQ);                                          \
      turn_pass(wg);                                                                    \
      PIN();                                                                            \
      TR(ID + 3);
#define NEXT_HEAD(ID)                                                                   \
      row_exp(S, k48, mx, P, p48);                                                      \
      PIN();                                                                            \
      TR(ID + 4);                                                                       \
      wg_wait<0>(); keep(acc);                                                          \
      scale12(V, acc, rk); stsm12(V, vst + KV_KOFF);                                    \
      scale12(Q, acc + 12, rk); scale12(V, acc + 24, rk); PIN();
      TURN(8, Ofa, dq0 + 24, BAR_FH, SITE(3))
      SITE(4);
      NEXT_HEAD(8)
      proxy_fence();
      SITE(8);
      TURN(12, Ofb, dq0 + 36, BAR_FH + 8, SITE(6))
      SITE(7);
      auto init_y = [&]() {
#pragma unroll
        for (int i = 0; i < 48; i++) Y[i] = (i & 1) ? H[i] ^ never : h2u(__hadd2_rn(u2h(H[i]), u2h(never)));
        hold<0, 48>(Y); PIN();
      };
      NEXT_HEAD(12)
      init_y();
      proxy_fence();
      TR(17);
      turn_wait(wg);
      wg_fence(); mma_pv(O, P, dkv + 4); mma_s(S, Q, dkv); wg_commit();
      mma_proj(Y, Ofb, ds.pu[1]); wg_commit(); mma_proj(Y, Ofa, ds.pv[1]); wg_commit();
      turn_pass(wg);
      PIN();
      TR(18);
      load_v48(vr, v48);
      if (r + 1 < myrounds) mbar_wait(sb + BAR_TFULL, par);
      if (vmask) load_x<0, 4>(H, tx);
      wg_wait<2>(); keep(S); keep(O);
      wg_sync(wg);
      PIN();
      TR(19);
      row_max(S, k48, mx);
      finish_o(O, vr, p48, vmask, Ofc);
      stsm12(V, vst);
      PIN();
      wg_wait<1>();
      release(2);
      if (vmask) load_x<4, 8>(H, tx);
      row_exp(S, k48, mx, P, p48);
      PIN();
      if (vmask) load_x<8, 12>(H, tx);
      __syncwarp();
      warp_arrive(sb + BAR_TEMPTY);
      TR(20);
      wg_wait<0>(); keep(Y);
      release(3);
      proxy_fence();
      TR(21);
#undef TURN
#undef NEXT_HEAD
    }
  }
}

typedef CUresult (*EncodeFn)(CUtensorMap*, CUtensorMapDataType, cuuint32_t, void*, const cuuint64_t*, const cuuint64_t*,
                             const cuuint32_t*, const cuuint32_t*, CUtensorMapInterleave, CUtensorMapSwizzle,
                             CUtensorMapL2promotion, CUtensorMapFloatOOBfill);

}

extern "C" void kernel_launch(void* const* d_in, const int* in_sizes, int n_in, void* d_out, int out_size) {
  const __nv_bfloat16* x = (const __nv_bfloat16*)d_in[0];
  const __nv_bfloat16* dw = (const __nv_bfloat16*)d_in[1];
  const __nv_bfloat16* wqkv = (const __nv_bfloat16*)d_in[2];
  const __nv_bfloat16* wo = (const __nv_bfloat16*)d_in[3];
  static EncodeFn encode = nullptr;
  static int nsm = 0;
  static void* wpack = nullptr;
  if (!encode) {
    void* fn = nullptr;
    cudaDriverEntryPointQueryResult qr;
    cudaGetDriverEntryPoint("cuTensorMapEncodeTiled", &fn, cudaEnableDefault, &qr);
    encode = (EncodeFn)fn;
    int dev = 0;
    cudaGetDevice(&dev);
    cudaDeviceGetAttribute(&nsm, cudaDevAttrMultiProcessorCount, dev);
    cudaGetSymbolAddress(&wpack, g_wpack);
    cudaFuncSetAttribute(fused_kernel, cudaFuncAttributeMaxDynamicSharedMemorySize, SMEM_BYTES);
  }
  CUtensorMap tmx;
  cuuint64_t gdim[3] = {CH, IMG, IMG};
  cuuint64_t gstr[2] = {CH * 2, (cuuint64_t)CH * 2 * IMG};
  cuuint32_t box[3] = {64, 9, 1};
  cuuint32_t estr[3] = {1, 1, 1};
  encode(&tmx, CU_TENSOR_MAP_DATA_TYPE_BFLOAT16, 3, (void*)x, gdim, gstr, box, estr, CU_TENSOR_MAP_INTERLEAVE_NONE,
         CU_TENSOR_MAP_SWIZZLE_NONE, L2PROMO, CU_TENSOR_MAP_FLOAT_OOB_FILL_NONE);
  Descs ds;
  for (int i = 0; i < 12; i++)
    for (int b = 0; b < 5; b++) ds.q[b][i] = mkdesc(SMEM_BASE + OFF_W + qkv_pos(b & 1, i), 128, 256);
  for (int i = 0; i < 3; i++) {
    ds.pu[0][i] = ds.pu[1][i] = mkdesc(SMEM_BASE + OFF_W + SLOT_U * SLICE + i * 6144, 128, 256);
    ds.pv[0][i] = ds.pv[1][i] = mkdesc(SMEM_BASE + OFF_W + SLOT_V * SLICE + i * 6144, 128, 256);
  }
  ds.src = (const uint8_t*)wpack;
  for (int g = 0; g < 2; g++)
    for (int i = 0; i < 4; i++) {
      ds.kv[g][i] = mkdesc(SMEM_BASE + OFF_KV + g * KV_BYTES + KV_KOFF + 2 * i * KV_PITCH, KV_PITCH, 128);
      ds.kv[g][4 + i] = mkdesc(SMEM_BASE + OFF_KV + g * KV_BYTES + 256 * i, 128, KV_PITCH);
    }
  CUtensorMap tmp;
  cuuint32_t boxp[3] = {CH, 9, 9};
  encode(&tmp, CU_TENSOR_MAP_DATA_TYPE_BFLOAT16, 3, (void*)x, gdim, gstr, boxp, estr, CU_TENSOR_MAP_INTERLEAVE_NONE,
         CU_TENSOR_MAP_SWIZZLE_NONE, L2PROMO, CU_TENSOR_MAP_FLOAT_OOB_FILL_NONE);
  prepack_kernel<<<96 / PBY, dim3(192, PBY), 0, cudaStreamPerThread>>>(wqkv, wo, x, min(IMG, (2 * nsm + NWX - 1) / NWX * 7 + 1));
  cudaLaunchConfig_t cfg = {};
  cfg.gridDim = dim3(nsm); cfg.blockDim = dim3(384); cfg.dynamicSmemBytes = SMEM_BYTES; cfg.stream = cudaStreamPerThread;
  cudaLaunchAttribute at[1];
  at[0].id = cudaLaunchAttributeProgrammaticStreamSerialization;
  at[0].val.programmaticStreamSerializationAllowed = 1;
  cfg.attrs = at; cfg.numAttrs = 1;
  cudaLaunchKernelEx(&cfg, fused_kernel, tmx, tmp, ds, dw, (__nv_bfloat16*)d_out, 0, x, wqkv, wo);
}
```

```cpp
#include <cuda_runtime.h>
#include <cuda_bf16.h>
#include <cuda_fp16.h>
#include <cuda.h>
#include <stdint.h>

#define CREGS "208"
#define PREGS "88"
#define LA 4
#define K0A 6
#define KA 3
#define KB 9
#define L2PROMO CU_TENSOR_MAP_L2_PROMOTION_NONE
#define OMAP 0x012234
#define B1A 2
#define B1B 6
#define B1C 9
namespace {
constexpr int PBY = 2;

constexpr int IMG = 511;
constexpr int CH = 192;
constexpr int NWX = 73;
constexpr int NWIN = NWX * NWX;
constexpr int SLICE = 18432;
constexpr int OFF_W = 0;
constexpr int KV_PITCH = 1792, KV_KOFF = 896, KV_BYTES = 6 * KV_PITCH + 768;
constexpr int OFF_KV = 8 * SLICE;
constexpr int TILE_BYTES = 25 * 768;
constexpr int OFF_TILE = OFF_KV + 2 * KV_BYTES;
constexpr int XSLOT = 2304;
constexpr int OFF_X = OFF_TILE + 2 * TILE_BYTES;
constexpr int OFF_BAR = OFF_X + 9 * XSLOT;
constexpr int BAR_FH = OFF_BAR;
constexpr int BAR_FU = OFF_BAR + 16, BAR_FV = OFF_BAR + 24;
constexpr int BAR_F0 = OFF_BAR + 32, BAR_F1 = OFF_BAR + 40;
constexpr int BAR_E = OFF_BAR + 80;
constexpr int BAR_XFULL = OFF_BAR + 112;
constexpr int BAR_TFULL = OFF_BAR + 184;
constexpr int BAR_TEMPTY = OFF_BAR + 192;
constexpr int OFF_LIM = OFF_BAR + 200;
constexpr int OFF_REDO = OFF_BAR + 208;
constexpr int BAR_FIRST = OFF_BAR + 240;
constexpr int OFF_HALO = OFF_W + 3 * SLICE, HALO_BYTES = 81 * 384;
constexpr int SMEM_BYTES = OFF_BAR + 248;

__host__ __device__ constexpr int qkv_pos(int h, int s) { return 3 * h * SLICE + s * 4608; }
__host__ __device__ constexpr int wo_pos(int s) { return 12 * SLICE + s * 6144; }
constexpr int SLOT_U = 6, SLOT_V = 7;
constexpr int SMEM_BASE = 1024;
struct Descs { uint64_t q[5][12]; uint64_t pu[2][3], pv[2][3]; uint64_t kv[2][8]; const uint8_t* src; };

__device__ uint4 g_wpack[16 * SLICE / 16];
__device__ float2 g_wnorm[96];
template <int V> struct IC { static constexpr int v = V; };
typedef __nv_bfloat162 bf2;
__device__ __forceinline__ bf2 u2b(uint32_t u) { return *reinterpret_cast<bf2*>(&u); }
__device__ __forceinline__ uint32_t b2u(bf2 b) { return *reinterpret_cast<uint32_t*>(&b); }
__device__ __forceinline__ uint32_t pack2(float lo, float hi) {
  uint32_t r; asm("cvt.rn.bf16x2.f32 %0, %1, %2;" : "=r"(r) : "f"(hi), "f"(lo)); return r;
}
__device__ __forceinline__ uint32_t hadd(uint32_t a, uint32_t b) { return b2u(__hadd2_rn(u2b(a), u2b(b))); }
__device__ __forceinline__ uint32_t hmul(uint32_t a, uint32_t b) { return b2u(__hmul2_rn(u2b(a), u2b(b))); }
__device__ __forceinline__ uint32_t hfma(uint32_t a, uint32_t b, uint32_t c) { return b2u(__hfma2(u2b(a), u2b(b), u2b(c))); }
__device__ __forceinline__ __half2 u2h(uint32_t u) { return *reinterpret_cast<__half2*>(&u); }
__device__ __forceinline__ uint32_t h2u(__half2 b) { return *reinterpret_cast<uint32_t*>(&b); }
__device__ __forceinline__ uint32_t packh(float lo, float hi) {
  uint32_t r; asm("cvt.rn.f16x2.f32 %0, %1, %2;" : "=r"(r) : "f"(hi), "f"(lo)); return r;
}
__device__ __forceinline__ uint32_t fmax2(uint32_t a, uint32_t b) { return h2u(__hmax2(u2h(a), u2h(b))); }
template <int HI> __device__ __forceinline__ __half2 hcast(uint32_t a) { return HI ? __high2half2(u2h(a)) : __low2half2(u2h(a)); }
template <int HI> __device__ __forceinline__ uint32_t fmul_b(uint32_t a, uint32_t s) { return h2u(__hmul2_rn(u2h(a), hcast<HI>(s))); }
template <int HI> __device__ __forceinline__ uint32_t fsub_b(uint32_t a, uint32_t s) { return h2u(__hsub2_rn(u2h(a), hcast<HI>(s))); }
__device__ __forceinline__ uint32_t fex2(uint32_t a) { uint32_t r; asm("ex2.approx.f16x2 %0, %1;" : "=r"(r) : "r"(a)); return r; }
__device__ __forceinline__ float lo2f(uint32_t a) { return __uint_as_float(a << 16); }
__device__ __forceinline__ float hi2f(uint32_t a) { return __uint_as_float(a & 0xffff0000u); }

__device__ __forceinline__ void mbar_init(uint32_t bar, uint32_t cnt) { asm volatile("mbarrier.init.shared::cta.b64 [%0], %1;" :: "r"(bar), "r"(cnt) : "memory"); }
__device__ __forceinline__ void mbar_wait(uint32_t bar, uint32_t parity) {
  asm volatile("{\n.reg .pred p;\n.reg .u32 n;\n"
               "mbarrier.try_wait.parity.shared::cta.b64 p, [%0], %1;\n"
               "@p bra.uni DONE_%=;\n"
               "mov.u32 n, 0;\n"
               "AGAIN_%=:\n"
               "mbarrier.try_wait.parity.shared::cta.b64 p, [%0], %1;\n"
               "@p bra.uni DONE_%=;\n"
               "add.u32 n, n, 1;\n"
               "setp.lt.u32 p, n, 0x1000000;\n"
               "@p bra.uni AGAIN_%=;\n"
               "trap;\n"
               "DONE_%=:\n}\n" :: "r"(bar), "r"(parity) : "memory");
}
__device__ __forceinline__ void wg_fence() { asm volatile("wgmma.fence.sync.aligned;" ::: "memory"); }
__device__ __forceinline__ void wg_commit() { asm volatile("wgmma.commit_group.sync.aligned;" ::: "memory"); }
template <int N> __device__ __forceinline__ void wg_wait() { asm volatile("wgmma.wait_group.sync.aligned %0;" :: "n"(N) : "memory"); }
#define BAR_BY_WG(OP, ID0, ID1, CNT) asm volatile("{\n.reg .pred p;\nsetp.eq.s32 p, %0, 0;\n@p " OP " " #ID0 ", " #CNT ";\n@!p " OP " " #ID1 ", " #CNT ";\n}\n" :: "r"(wg) : "memory")
__device__ __forceinline__ void wg_sync(int wg) { BAR_BY_WG("bar.sync", 1, 2, 128); }
__device__ __forceinline__ void turn_wait(int wg) { BAR_BY_WG("bar.sync", 3, 4, 256); }
__device__ __forceinline__ void turn_pass(int wg) { BAR_BY_WG("bar.arrive", 4, 3, 256); }
__device__ __forceinline__ void stsm4(uint32_t addr, uint32_t a, uint32_t b, uint32_t c, uint32_t d) {
  asm volatile("stmatrix.sync.aligned.m8n8.x4.shared.b16 [%0], {%1,%2,%3,%4};" :: "r"(addr), "r"(a), "r"(b), "r"(c), "r"(d) : "memory");
}
template <int N> __device__ __forceinline__ void keep(float (&d)[N]) {
#pragma unroll
  for (int i = 0; i < N; i++) asm volatile("" : "+f"(d[i]) :: "memory");
}
template <int N> __device__ __forceinline__ void keep(uint32_t (&d)[N]) {
#pragma unroll
  for (int i = 0; i < N; i++) asm volatile("" : "+r"(d[i]) :: "memory");
}
__host__ __device__ __forceinline__ uint64_t mkdesc(uint32_t addr, uint32_t lbo, uint32_t sbo) {
  return ((uint64_t)(sbo >> 4) << 32) | (uint64_t)(((lbo >> 4) << 16) | ((addr & 0x3FFFF) >> 4));
}

template <int SCALE_D>
__device__ __forceinline__ void wgmma_n144(uint32_t (&d)[36], uint32_t a0, uint32_t a1, uint32_t a2, uint32_t a3, uint64_t descB) {
  if (SCALE_D == 0)
  asm volatile("wgmma.mma_async.sync.aligned.m64n144k16.f16.f16.f16 "
    "{%0, %1, %2, %3, %4, %5, %6, %7, %8, %9, %10, %11, %12, %13, %14, %15, "
    "%16, %17, %18, %19, %20, %21, %22, %23, %24, %25, %26, %27, %28, %29, %30, %31, "
    "%32, %33, %34, %35}, "
    "{%36, %37, %38, %39}, %40, 0, 1, 1, 0;\n"
    : "=r"(d[0]), "=r"(d[1]), "=r"(d[2]), "=r"(d[3]), "=r"(d[4]), "=r"(d[5]), "=r"(d[6]), "=r"(d[7]),
      "=r"(d[8]), "=r"(d[9]), "=r"(d[10]), "=r"(d[11]), "=r"(d[12]), "=r"(d[13]), "=r"(d[14]), "=r"(d[15]),
      "=r"(d[16]), "=r"(d[17]), "=r"(d[18]), "=r"(d[19]), "=r"(d[20]), "=r"(d[21]), "=r"(d[22]), "=r"(d[23]),
      "=r"(d[24]), "=r"(d[25]), "=r"(d[26]), "=r"(d[27]), "=r"(d[28]), "=r"(d[29]), "=r"(d[30]), "=r"(d[31]),
      "=r"(d[32]), "=r"(d[33]), "=r"(d[34]), "=r"(d[35])
    : "r"(a0), "r"(a1), "r"(a2), "r"(a3), "l"(descB));
  else
  asm volatile("wgmma.mma_async.sync.aligned.m64n144k16.f16.f16.f16 "
    "{%0, %1, %2, %3, %4, %5, %6, %7, %8, %9, %10, %11, %12, %13, %14, %15, "
    "%16, %17, %18, %19, %20, %21, %22, %23, %24, %25, %26, %27, %28, %29, %30, %31, "
    "%32, %33, %34, %35}, "
    "{%36, %37, %38, %39}, %40, 1, 1, 1, 0;\n"
    : "+r"(d[0]), "+r"(d[1]), "+r"(d[2]), "+r"(d[3]), "+r"(d[4]), "+r"(d[5]), "+r"(d[6]), "+r"(d[7]),
      "+r"(d[8]), "+r"(d[9]), "+r"(d[10]), "+r"(d[11]), "+r"(d[12]), "+r"(d[13]), "+r"(d[14]), "+r"(d[15]),
      "+r"(d[16]), "+r"(d[17]), "+r"(d[18]), "+r"(d[19]), "+r"(d[20]), "+r"(d[21]), "+r"(d[22]), "+r"(d[23]),
      "+r"(d[24]), "+r"(d[25]), "+r"(d[26]), "+r"(d[27]), "+r"(d[28]), "+r"(d[29]), "+r"(d[30]), "+r"(d[31]),
      "+r"(d[32]), "+r"(d[33]), "+r"(d[34]), "+r"(d[35])
    : "r"(a0), "r"(a1), "r"(a2), "r"(a3), "l"(descB));
}

template <int SCALE_D>
__device__ __forceinline__ void wgmma_n192(uint32_t (&d)[48], uint32_t a0, uint32_t a1, uint32_t a2, uint32_t a3, uint64_t descB) {
  if (SCALE_D == 0)
  asm volatile("wgmma.mma_async.sync.aligned.m64n192k16.f16.f16.f16 "
    "{%0, %1, %2, %3, %4, %5, %6, %7, %8, %9, %10, %11, %12, %13, %14, %15, "
    "%16, %17, %18, %19, %20, %21, %22, %23, %24, %25, %26, %27, %28, %29, %30, %31, "
    "%32, %33, %34, %35, %36, %37, %38, %39, %40, %41, %42, %43, %44, %45, %46, %47}, "
    "{%48, %49, %50, %51}, %52, 0, 1, 1, 0;\n"
    : "=r"(d[0]), "=r"(d[1]), "=r"(d[2]), "=r"(d[3]), "=r"(d[4]), "=r"(d[5]), "=r"(d[6]), "=r"(d[7]),
      "=r"(d[8]), "=r"(d[9]), "=r"(d[10]), "=r"(d[11]), "=r"(d[12]), "=r"(d[13]), "=r"(d[14]), "=r"(d[15]),
      "=r"(d[16]), "=r"(d[17]), "=r"(d[18]), "=r"(d[19]), "=r"(d[20]), "=r"(d[21]), "=r"(d[22]), "=r"(d[23]),
      "=r"(d[24]), "=r"(d[25]), "=r"(d[26]), "=r"(d[27]), "=r"(d[28]), "=r"(d[29]), "=r"(d[30]), "=r"(d[31]),
      "=r"(d[32]), "=r"(d[33]), "=r"(d[34]), "=r"(d[35]), "=r"(d[36]), "=r"(d[37]), "=r"(d[38]), "=r"(d[39]),
      "=r"(d[40]), "=r"(d[41]), "=r"(d[42]), "=r"(d[43]), "=r"(d[44]), "=r"(d[45]), "=r"(d[46]), "=r"(d[47])
    : "r"(a0), "r"(a1), "r"(a2), "r"(a3), "l"(descB));
  else
  asm volatile("wgmma.mma_async.sync.aligned.m64n192k16.f16.f16.f16 "
    "{%0, %1, %2, %3, %4, %5, %6, %7, %8, %9, %10, %11, %12, %13, %14, %15, "
    "%16, %17, %18, %19, %20, %21, %22, %23, %24, %25, %26, %27, %28, %29, %30, %31, "
    "%32, %33, %34, %35, %36, %37, %38, %39, %40, %41, %42, %43, %44, %45, %46, %47}, "
    "{%48, %49, %50, %51}, %52, 1, 1, 1, 0;\n"
    : "+r"(d[0]), "+r"(d[1]), "+r"(d[2]), "+r"(d[3]), "+r"(d[4]), "+r"(d[5]), "+r"(d[6]), "+r"(d[7]),
      "+r"(d[8]), "+r"(d[9]), "+r"(d[10]), "+r"(d[11]), "+r"(d[12]), "+r"(d[13]), "+r"(d[14]), "+r"(d[15]),
      "+r"(d[16]), "+r"(d[17]), "+r"(d[18]), "+r"(d[19]), "+r"(d[20]), "+r"(d[21]), "+r"(d[22]), "+r"(d[23]),
      "+r"(d[24]), "+r"(d[25]), "+r"(d[26]), "+r"(d[27]), "+r"(d[28]), "+r"(d[29]), "+r"(d[30]), "+r"(d[31]),
      "+r"(d[32]), "+r"(d[33]), "+r"(d[34]), "+r"(d[35]), "+r"(d[36]), "+r"(d[37]), "+r"(d[38]), "+r"(d[39]),
      "+r"(d[40]), "+r"(d[41]), "+r"(d[42]), "+r"(d[43]), "+r"(d[44]), "+r"(d[45]), "+r"(d[46]), "+r"(d[47])
    : "r"(a0), "r"(a1), "r"(a2), "r"(a3), "l"(descB));
}

template <int SCALE_D>
__device__ __forceinline__ void wgmma_n56(uint32_t (&d)[14], uint32_t a0, uint32_t a1, uint32_t a2, uint32_t a3, uint64_t descB) {
  if (SCALE_D == 0)
  asm volatile("wgmma.mma_async.sync.aligned.m64n56k16.f16.f16.f16 "
    "{%0, %1, %2, %3, %4, %5, %6, %7, %8, %9, %10, %11, %12, %13}, "
    "{%14, %15, %16, %17}, %18, 0, 1, 1, 0;\n"
    : "=r"(d[0]), "=r"(d[1]), "=r"(d[2]), "=r"(d[3]), "=r"(d[4]), "=r"(d[5]), "=r"(d[6]), "=r"(d[7]),
      "=r"(d[8]), "=r"(d[9]), "=r"(d[10]), "=r"(d[11]), "=r"(d[12]), "=r"(d[13])
    : "r"(a0), "r"(a1), "r"(a2), "r"(a3), "l"(descB));
  else
  asm volatile("wgmma.mma_async.sync.aligned.m64n56k16.f16.f16.f16 "
    "{%0, %1, %2, %3, %4, %5, %6, %7, %8, %9, %10, %11, %12, %13}, "
    "{%14, %15, %16, %17}, %18, 1, 1, 1, 0;\n"
    : "+r"(d[0]), "+r"(d[1]), "+r"(d[2]), "+r"(d[3]), "+r"(d[4]), "+r"(d[5]), "+r"(d[6]), "+r"(d[7]),
      "+r"(d[8]), "+r"(d[9]), "+r"(d[10]), "+r"(d[11]), "+r"(d[12]), "+r"(d[13])
    : "r"(a0), "r"(a1), "r"(a2), "r"(a3), "l"(descB));
}

template <int SCALE_D>
__device__ __forceinline__ void wgmma_pv(uint32_t (&d)[14], uint32_t a0, uint32_t a1, uint32_t a2, uint32_t a3, uint64_t descB) {
  if (SCALE_D == 0)
  asm volatile("wgmma.mma_async.sync.aligned.m64n56k16.f16.f16.f16 "
    "{%0, %1, %2, %3, %4, %5, %6, %7, %8, %9, %10, %11, %12, %13}, "
    "{%14, %15, %16, %17}, %18, 0, 1, 1, 1;\n"
    : "=r"(d[0]), "=r"(d[1]), "=r"(d[2]), "=r"(d[3]), "=r"(d[4]), "=r"(d[5]), "=r"(d[6]), "=r"(d[7]),
      "=r"(d[8]), "=r"(d[9]), "=r"(d[10]), "=r"(d[11]), "=r"(d[12]), "=r"(d[13])
    : "r"(a0), "r"(a1), "r"(a2), "r"(a3), "l"(descB));
  else
  asm volatile("wgmma.mma_async.sync.aligned.m64n56k16.f16.f16.f16 "
    "{%0, %1, %2, %3, %4, %5, %6, %7, %8, %9, %10, %11, %12, %13}, "
    "{%14, %15, %16, %17}, %18, 1, 1, 1, 1;\n"
    : "+r"(d[0]), "+r"(d[1]), "+r"(d[2]), "+r"(d[3]), "+r"(d[4]), "+r"(d[5]), "+r"(d[6]), "+r"(d[7]),
      "+r"(d[8]), "+r"(d[9]), "+r"(d[10]), "+r"(d[11]), "+r"(d[12]), "+r"(d[13])
    : "r"(a0), "r"(a1), "r"(a2), "r"(a3), "l"(descB));
}


__global__ void __launch_bounds__(192 * PBY) prepack_kernel(const __nv_bfloat16* __restrict__ wqkv, const __nv_bfloat16* __restrict__ wo,
                                                      const __nv_bfloat16* __restrict__ x, int first_rows) {
  asm volatile("griddepcontrol.launch_dependents;");
  __shared__ float red2[PBY][6][16];
  float (*red)[16] = red2[threadIdx.y];
  __shared__ __align__(16) __half stage[PBY][1536];
  __half* dst = stage[threadIdx.y];
  const int c = threadIdx.x, nb = blockIdx.x * PBY + threadIdx.y;
  uint32_t u[4];
  int base, gofs;
  float scale = 1.0f;
  if (nb < 72) {
    const int h = nb / 18, j = nb % 18, part = j / 6;
    const int col = (part == 0 ? 192 : part == 1 ? 0 : 384) + h * 48 + (j % 6) * 8;
    const uint4 raw = *reinterpret_cast<const uint4*>(wqkv + c * 576 + col);
    u[0] = raw.x; u[1] = raw.y; u[2] = raw.z; u[3] = raw.w;
    if (part == 1) scale = 0.14433756729740643f * 1.4426950408889634f;
    const int cc = c >> 5, q = (c >> 3) & 3, s1 = (c >> 2) & 1, hh = (c >> 1) & 1, e = c & 1;
    base = (2 * cc + s1) * 128 + hh * 64 + 2 * q + e;
    gofs = qkv_pos(h, c >> 4) + j * 256;
  } else {
    const int jb = nb - 72;
#pragma unroll
    for (int i = 0; i < 4; i++) u[i] = *reinterpret_cast<const uint32_t*>(wo + c * 192 + 32 * (jb >> 2) + 8 * i + 2 * (jb & 3));
    base = (c >> 4) * 128 + ((c >> 3) & 1) * 64 + (c & 7);
    gofs = wo_pos(c >> 4) + jb * 256;
  }
  if (threadIdx.y == 0 && c < 32)
    for (int i = blockIdx.x + 96 / PBY * c; i < first_rows * NWX / 4; i += 96 / PBY * 32)
      asm volatile("cp.async.bulk.prefetch.L2.global [%0], %1;" :: "l"(reinterpret_cast<const uint8_t*>(x) + (size_t)i * 10752), "n"(10752) : "memory");
  float v[8], t[16];
#pragma unroll
  for (int i = 0; i < 4; i++) { v[2 * i] = lo2f(u[i]); v[2 * i + 1] = hi2f(u[i]); }
#pragma unroll
  for (int i = 0; i < 16; i++) t[i] = i < 8 ? v[i] : v[i - 8] * v[i - 8];
#pragma unroll
  for (int n = 8; n >= 1; n >>= 1) {
    const bool up = c & (2 * n);
#pragma unroll
    for (int i = 0; i < n; i++) t[i] = (up ? t[i + n] : t[i]) + __shfl_xor_sync(~0u, up ? t[i] : t[i + n], 2 * n);
  }
  t[0] += __shfl_xor_sync(~0u, t[0], 1);
  if (!(c & 1)) red[c >> 5][(c & 31) >> 1] = t[0];
  __syncthreads();
#pragma unroll
  for (int i = 0; i < 16; i++) t[i] = red[0][i] + red[1][i] + red[2][i] + red[3][i] + red[4][i] + red[5][i];
  float mx = 0.f, sm = 0.f;
#pragma unroll
  for (int n = 0; n < 8; n++) {
    const float m = nb < 72 ? t[n] * (1.0f / 192.0f) : 0.f;
    dst[base + n * 8] = __float2half_rn(__bfloat162float(__float2bfloat16((v[n] - m) * scale)));
    const float nn = (t[8 + n] - 0.999f * m * t[n]) * scale * scale * 1.01f;
    mx = fmaxf(mx, nn); sm += nn;
  }
  if (c == 0) g_wnorm[nb] = make_float2(mx, sm);
  __syncthreads();
  g_wpack[gofs / 16 + (c & 15)] = reinterpret_cast<const uint4*>(dst)[c];
}

__device__ __forceinline__ int window_of(int round, int nfull, int cta, int ncta, int wg) {
  if (round < nfull) return round * 2 * ncta + 2 * cta + wg;
  const int rem = NWIN - nfull * 2 * ncta;
  const int i = cta + wg * ncta;
  return i < rem ? nfull * 2 * ncta + i : -1;
}

template <int S0 = 0, int S1 = 12>
__device__ __forceinline__ void mma_qkv(uint32_t (&acc)[36], const uint32_t (&A)[48], const uint64_t* d) {
#pragma unroll
  for (int s = S0; s < S1; s++) {
    if (s == 0) wgmma_n144<0>(acc, A[4 * s], A[4 * s + 1], A[4 * s + 2], A[4 * s + 3], d[s]);
    else        wgmma_n144<1>(acc, A[4 * s], A[4 * s + 1], A[4 * s + 2], A[4 * s + 3], d[s]);
  }
  wg_commit();
}
__device__ __forceinline__ void mma_proj(uint32_t (&acc)[48], const uint32_t (&A)[12], const uint64_t* d) {
#pragma unroll
  for (int s = 0; s < 3; s++) wgmma_n192<1>(acc, A[4 * s], A[4 * s + 1], A[4 * s + 2], A[4 * s + 3], d[s]);
}
__device__ __forceinline__ void mma_s(uint32_t (&S)[14], const uint32_t (&Q)[12], const uint64_t* d) {
  wgmma_n56<0>(S, Q[0], Q[1], Q[2], Q[3], d[0]);
  wgmma_n56<1>(S, Q[4], Q[5], Q[6], Q[7], d[1]);
  wgmma_n56<1>(S, Q[8], Q[9], Q[10], Q[11], d[2]);
}
__device__ __forceinline__ void mma_pv(uint32_t (&O)[14], const uint32_t (&P)[12], const uint64_t* d) {
  wgmma_pv<0>(O, P[0], P[1], P[2], P[3], d[0]);
  wgmma_pv<1>(O, P[4], P[5], P[6], P[7], d[1]);
  wgmma_pv<1>(O, P[8], P[9], P[10], P[11], d[2]);
}

#define PIN() asm volatile("pmevent 0;" ::: "memory")
template <int A, int B> __device__ __forceinline__ void hold(uint32_t* v) {
#pragma unroll
  for (int i = A; i < B; i++) asm volatile("" : "+r"(v[i]));
}
__device__ __forceinline__ void stsm12(const uint32_t* v, uint32_t addr) {
#pragma unroll
  for (int j = 0; j < 3; j++) stsm4(addr + 2 * j * KV_PITCH, v[4 * j], v[4 * j + 1], v[4 * j + 2], v[4 * j + 3]);
}
__device__ __forceinline__ void load_v48(uint32_t (&v)[6], uint32_t addr) {
  asm volatile("ldmatrix.sync.aligned.m8n8.x4.shared.b16 {%0,%1,%2,%3}, [%4];" : "=r"(v[0]), "=r"(v[1]), "=r"(v[2]), "=r"(v[3]) : "r"(addr) : "memory");
  asm volatile("ldmatrix.sync.aligned.m8n8.x2.shared.b16 {%0,%1}, [%2];" : "=r"(v[4]), "=r"(v[5]) : "r"(addr + 4 * KV_PITCH) : "memory");
}
__device__ __forceinline__ void finish_o(const uint32_t (&O)[14], const uint32_t (&v)[6], uint32_t p48, uint32_t vmask, uint32_t (&Of)[12]) {
  const float2 l = __half22float2(__hadd2_rn(u2h(__byte_perm(O[12], O[13], 0x5410)), u2h(p48)));
  float i0, i1;
  asm("rcp.approx.ftz.f32 %0, %1;" : "=f"(i0) : "f"(l.x));
  asm("rcp.approx.ftz.f32 %0, %1;" : "=f"(i1) : "f"(l.y));
  const uint32_t inv = packh(i0, i1) & vmask;
#pragma unroll
  for (int i = 0; i < 12; i++) {
    const uint32_t t = h2u(__hfma2(u2h(v[i >> 1]), (i & 1) ? hcast<1>(p48) : hcast<0>(p48), u2h(O[i])));
    Of[i] = (i & 1) ? fmul_b<1>(t, inv) : fmul_b<0>(t, inv);
  }
  hold<0, 12>(Of);
}
#define PSTAT 12
template <int A, int B>
__device__ __forceinline__ void ln_sums(const uint32_t (&X)[48], float (&s1)[2], float (&s2)[2]) {
  if (PSTAT) {
    static_assert(PSTAT == 0 || (A % (2 * PSTAT + !PSTAT) == 0 && B % (2 * PSTAT + !PSTAT) == 0), "whole groups");
#pragma unroll
    for (int g = A; g < B; g += 2 * PSTAT + !PSTAT)
#pragma unroll
      for (int a = 0; a < 2; a++) {
        __half2 p1 = u2h(X[g + a]), p2 = __hmul2_rn(p1, p1);
#pragma unroll
        for (int i = 1; i < PSTAT; i++) { const __half2 v = u2h(X[g + a + 2 * i]); p1 = __hadd2_rn(p1, v); p2 = __hfma2(v, v, p2); }
        const float2 f1 = __half22float2(p1), f2 = __half22float2(p2);
        s1[a] = g == 0 ? f1.x + f1.y : s1[a] + (f1.x + f1.y);
        s2[a] = g == 0 ? f2.x + f2.y : s2[a] + (f2.x + f2.y);
      }
  } else {
#pragma unroll
    for (int i = A; i < B; i++) {
      const float2 f = __half22float2(u2h(X[i]));
      s1[i & 1] = i < 2 ? f.x + f.y : s1[i & 1] + (f.x + f.y);
      s2[i & 1] = fmaf(f.x, f.x, i < 2 ? f.y * f.y : fmaf(f.y, f.y, s2[i & 1]));
    }
  }
  asm volatile("" : "+f"(s1[0]), "+f"(s1[1]), "+f"(s2[0]), "+f"(s2[1]));
}
__device__ __forceinline__ uint32_t ln_rstd(const float (&s1)[2], const float (&s2)[2], float lo, float hi, uint32_t vmask, bool& ok) {
  float r[2];
  ok = true;
#pragma unroll
  for (int a = 0; a < 2; a++) {
    float m = s1[a], v = s2[a];
    m += __shfl_xor_sync(~0u, m, 1); v += __shfl_xor_sync(~0u, v, 1);
    m += __shfl_xor_sync(~0u, m, 2); v += __shfl_xor_sync(~0u, v, 2);
    ok = ok & (v <= hi) & ((v >= lo) | !(vmask >> (16 * a) & 1));
    m *= 1.0f / 192.0f;
    m *= m;
    v = fmaxf(fmaf(v, 1.0f / 192.0f, -m), 0.f) + 1e-5f;
    ok = ok & (m <= (PSTAT ? 16.f : 64.f) * v);
    asm("rsqrt.approx.ftz.f32 %0, %1;" : "=f"(r[a]) : "f"(v));
  }
  uint32_t rk = packh(r[0], r[1]);
  hold<0, 1>(&rk);
  return rk;
}
__device__ __forceinline__ void scale12(uint32_t (&D)[12], const uint32_t* a, uint32_t r) {
#pragma unroll
  for (int i = 0; i < 12; i++) D[i] = (i & 1) ? fmul_b<1>(a[i], r) : fmul_b<0>(a[i], r);
  hold<0, 12>(D);
}
template <int CC>
__device__ __forceinline__ void store_out(const uint32_t (&Y)[48], uint8_t* o0, uint8_t* o1, uint32_t vmask) {
  uint32_t T[8];
#pragma unroll
  for (int i = 0; i < 8; i++) {
    const float2 f = __half22float2(u2h(Y[8 * CC + i]));
    T[i] = pack2(f.x, f.y);
  }
  asm volatile("{\n.reg .pred p;\nsetp.ne.u32 p, %5, 0;\n@p st.global.cs.v4.u32 [%0], {%1,%2,%3,%4};\n}\n"
               :: "l"(o0 + CC * 64), "r"(T[0]), "r"(T[2]), "r"(T[4]), "r"(T[6]), "r"(vmask) : "memory");
  asm volatile("{\n.reg .pred p;\nsetp.lt.s32 p, %5, 0;\n@p st.global.cs.v4.u32 [%0], {%1,%2,%3,%4};\n}\n"
               :: "l"(o1 + CC * 64), "r"(T[1]), "r"(T[3]), "r"(T[5]), "r"(T[7]), "r"(vmask) : "memory");
}
__device__ __forceinline__ void proxy_fence() { asm volatile("fence.proxy.async.shared::cta;" ::: "memory"); }
__device__ __forceinline__ void row_max(const uint32_t (&S)[14], uint32_t& k48, uint32_t& mx) {
  k48 = __shfl_sync(~0u, __byte_perm(S[12], S[13], 0x5410), 0, 4);
  const uint32_t m0 = fmax2(fmax2(fmax2(S[0], S[2]), S[4]), fmax2(fmax2(S[6], S[8]), S[10]));
  const uint32_t m1 = fmax2(fmax2(fmax2(S[1], S[3]), S[5]), fmax2(fmax2(S[7], S[9]), S[11]));
  mx = fmax2(__byte_perm(m0, m1, 0x5410), __byte_perm(m0, m1, 0x7632));
  mx = fmax2(mx, __shfl_xor_sync(~0u, mx, 1));
  mx = fmax2(mx, __shfl_xor_sync(~0u, mx, 2));
  mx = fmax2(mx, k48);
  hold<0, 1>(&mx);
}
__device__ __forceinline__ void row_exp(const uint32_t (&S)[14], uint32_t k48, uint32_t mx, uint32_t (&P)[12], uint32_t& p48) {
#pragma unroll
  for (int j = 0; j < 12; j++) P[j] = fex2((j & 1) ? fsub_b<1>(S[j], mx) : fsub_b<0>(S[j], mx));
  p48 = fex2(h2u(__hsub2_rn(u2h(k48), u2h(mx))));
  hold<0, 12>(P); hold<0, 1>(&p48);
}
template <int S0, int S1>
__device__ __forceinline__ void load_x(uint32_t (&X)[48], uint32_t t0) {
#pragma unroll
  for (int s = S0; s < S1; s++)
    asm volatile("ld.shared.v4.u32 {%0,%1,%2,%3}, [%4];" : "=r"(X[4 * s]), "=r"(X[4 * s + 1]), "=r"(X[4 * s + 2]), "=r"(X[4 * s + 3])
                 : "r"(((s & 1) ? (t0 ^ 16) : t0) + (s >> 1) * 128) : "memory");
}

template <int CNT, int EXPECT = CNT * SLICE>
__device__ __forceinline__ void load_slices(uint32_t sb, const uint8_t* src, int slice, int slot, int bar) {
  if (EXPECT)
    asm volatile("{\n.reg .pred p;\nelect.sync _|p, 0xffffffff;\n@p mbarrier.arrive.expect_tx.shared::cta.b64 _, [%0], %1;\n}\n"
                 :: "r"(sb + bar), "n"(EXPECT) : "memory");
  asm volatile("{\n.reg .pred p;\nelect.sync _|p, 0xffffffff;\n"
               "@p cp.async.bulk.shared::cluster.global.mbarrier::complete_tx::bytes [%0], [%1], %2, [%3];\n}\n"
               :: "r"(sb + OFF_W + slot * SLICE), "l"(src + slice * SLICE), "n"(CNT * SLICE), "r"(sb + bar) : "memory");
}
__device__ __forceinline__ void warp_arrive(uint32_t bar) {
  asm volatile("{\n.reg .pred p;\nelect.sync _|p, 0xffffffff;\n@p mbarrier.arrive.shared::cta.b64 _, [%0];\n}\n" :: "r"(bar) : "memory");
}

__device__ __forceinline__ float2 fp16_limits(int lane) {
  float mx[4] = {0.f, 0.f, 0.f, 0.f}, sm[4] = {0.f, 0.f, 0.f, 0.f};
#pragma unroll
  for (int i = 0; i < 3; i++) {
    const int nb = lane + 32 * i, part = nb < 72 ? (nb % 18) / 6 : 3;
    const float2 w = g_wnorm[nb];
#pragma unroll
    for (int k = 0; k < 4; k++) if (part == k) { mx[k] = fmaxf(mx[k], w.x); sm[k] += w.y; }
  }
#pragma unroll
  for (int k = 0; k < 4; k++)
#pragma unroll
    for (int d = 16; d; d >>= 1) { mx[k] = fmaxf(mx[k], __shfl_xor_sync(~0u, mx[k], d)); sm[k] += __shfl_xor_sync(~0u, sm[k], d); }
  const float big = fmaxf(fmaxf(mx[0], mx[1]), mx[2]);
  float small = 1.f;
  bool good = sm[0] + sm[1] + sm[2] + sm[3] < 1e30f;
#pragma unroll
  for (int k = 0; k < 4; k++) { good = good && (mx[k] == 0.f || mx[k] >= 2.5e-4f); if (k < 3 && mx[k] > 0.f) small = fminf(small, mx[k]); }
  good = good && 250.f * 48.f * sqrtf(mx[0] * mx[1]) <= 5e4f;
  good = good && 16.f * 49.f * sqrtf(mx[2]) <= 5e4f && big <= 1e6f;
  good = good && 16.f * sqrtf(sm[2] * mx[3]) <= 2e4f;
  return make_float2(192.f * 2.4e-7f / small, good ? fminf(2.5e8f, 9e8f / fmaxf(big, 1e-30f)) : -1.f);
}

__device__ __forceinline__ void slow_window(float* sm, int w, int t, const __nv_bfloat16* __restrict__ x, const __nv_bfloat16* __restrict__ dw,
                                            const __nv_bfloat16* __restrict__ wqkv, const __nv_bfloat16* __restrict__ wo, __nv_bfloat16* __restrict__ out) {
  float* x0 = sm; float* h = x0 + 49 * CH; float* qkv = h + 49 * CH; float* S = qkv + 49 * 576;
  const int wy = w / NWX, wx = w % NWX;
  auto sync = [] { asm volatile("bar.sync 6, 128;" ::: "memory"); };
#pragma unroll 1
  for (int i = t; i < 49 * CH; i += 128) {
    const int k = i / CH, c = i % CH, y = wy * 7 + k / 7, xx = wx * 7 + k % 7;
    float pe = 0.f;
#pragma unroll 1
    for (int a = 0; a < 9; a++) {
      const int yy = y + a / 3 - 1, xc = xx + a % 3 - 1;
      if (yy >= 0 && yy < IMG && xc >= 0 && xc < IMG) pe = fmaf(__bfloat162float(x[((size_t)yy * IMG + xc) * CH + c]), __bfloat162float(dw[a * CH + c]), pe);
    }
    x0[i] = __bfloat162float(__float2bfloat16(__bfloat162float(x[((size_t)y * IMG + xx) * CH + c]) + pe));
  }
  sync();
  if (t < 49) {
    float m = 0.f, v = 0.f;
#pragma unroll 1
    for (int c = 0; c < CH; c++) m += x0[t * CH + c];
    m *= 1.0f / CH;
#pragma unroll 1
    for (int c = 0; c < CH; c++) { const float d = x0[t * CH + c] - m; v = fmaf(d, d, v); }
    const float rs = 1.0f / sqrtf(v * (1.0f / CH) + 1e-5f);
#pragma unroll 1
    for (int c = 0; c < CH; c++) h[t * CH + c] = (x0[t * CH + c] - m) * rs;
  }
  sync();
#pragma unroll 1
  for (int i = t; i < 7 * 576; i += 128) {
    const int n = i % 576, k0 = i / 576 * 7;
    float a[7] = {0.f, 0.f, 0.f, 0.f, 0.f, 0.f, 0.f};
#pragma unroll 1
    for (int c = 0; c < CH; c++) {
      const float wv = __bfloat162float(wqkv[c * 576 + n]);
#pragma unroll
      for (int k = 0; k < 7; k++) a[k] = fmaf(h[(k0 + k) * CH + c], wv, a[k]);
    }
#pragma unroll
    for (int k = 0; k < 7; k++) qkv[(k0 + k) * 576 + n] = a[k];
  }
  sync();
#pragma unroll 1
  for (int hd = 0; hd < 4; hd++) {
#pragma unroll 1
    for (int i = t; i < 49 * 49; i += 128) {
      const int a = i / 49, b = i % 49;
      float v = 0.f;
#pragma unroll 1
      for (int d = 0; d < 48; d++) v = fmaf(qkv[a * 576 + hd * 48 + d], qkv[b * 576 + 192 + hd * 48 + d], v);
      S[i] = v * 0.14433756729740643f;
    }
    sync();
    if (t < 49) {
      float m = S[t * 49], l = 0.f;
#pragma unroll 1
      for (int b = 1; b < 49; b++) m = fmaxf(m, S[t * 49 + b]);
#pragma unroll 1
      for (int b = 0; b < 49; b++) { const float e = expf(S[t * 49 + b] - m); S[t * 49 + b] = e; l += e; }
#pragma unroll 1
      for (int b = 0; b < 49; b++) S[t * 49 + b] /= l;
    }
    sync();
#pragma unroll 1
    for (int i = t; i < 49 * 48; i += 128) {
      const int a = i / 48, d = i % 48;
      float v = 0.f;
#pragma unroll 1
      for (int b = 0; b < 49; b++) v = fmaf(S[a * 49 + b], qkv[b * 576 + 384 + hd * 48 + d], v);
      h[a * CH + hd * 48 + d] = v;
    }
    sync();
  }
#pragma unroll 1
  for (int i = t; i < 7 * CH; i += 128) {
    const int n = i % CH, k0 = i / CH * 7;
    float a[7] = {0.f, 0.f, 0.f, 0.f, 0.f, 0.f, 0.f};
#pragma unroll 1
    for (int c = 0; c < CH; c++) {
      const float wv = __bfloat162float(wo[c * CH + n]);
#pragma unroll
      for (int k = 0; k < 7; k++) a[k] = fmaf(h[(k0 + k) * CH + c], wv, a[k]);
    }
#pragma unroll
    for (int k = 0; k < 7; k++)
      out[((size_t)(wy * 7 + k0 / 7) * IMG + wx * 7 + k) * CH + n] = __float2bfloat16(x0[(k0 + k) * CH + n] + a[k]);
  }
  sync();
}

__global__ void __launch_bounds__(384, 1)
fused_kernel(const __grid_constant__ CUtensorMap tmx, const __grid_constant__ CUtensorMap tmp, const __grid_constant__ Descs ds, const __nv_bfloat16* __restrict__ dw, __nv_bfloat16* __restrict__ out, const int never,
             const __nv_bfloat16* __restrict__ x, const __nv_bfloat16* __restrict__ wqkv, const __nv_bfloat16* __restrict__ wo) {
  extern __shared__ __align__(1024) uint8_t smem[];
  const uint32_t sb = (uint32_t)__cvta_generic_to_shared(smem);
  const int tid = threadIdx.x, lane = tid & 31;
  const int warp = __shfl_sync(0xffffffffu, tid >> 5, 0);
  const int cta = blockIdx.x, ncta = gridDim.x;
  const int nfull = NWIN / (2 * ncta);
  const int nrounds = nfull + ((NWIN - nfull * 2 * ncta) > cta ? 1 : 0);

  if (warp == 10 && lane == 0) asm volatile("prefetch.tensormap [%0];" :: "l"(reinterpret_cast<uint64_t>(&tmx)) : "memory");
  if (tid == 0) {
    mbar_init(sb + BAR_FIRST, 1);
    asm volatile("fence.mbarrier_init.release.cluster;" ::: "memory");
    asm volatile("mbarrier.arrive.expect_tx.shared::cta.b64 _, [%0], %1;" :: "r"(sb + BAR_FIRST), "n"(2 * HALO_BYTES) : "memory");
#pragma unroll
    for (int k = 0; k < 2; k++) {
      const int w = max(window_of(0, nfull, cta, ncta, k), 0), a = w / NWX;
      asm volatile("cp.async.bulk.tensor.3d.shared::cluster.global.mbarrier::complete_tx::bytes [%0], [%1, {0, %3, %4}], [%2];"
                   :: "r"(sb + OFF_HALO + k * HALO_BYTES), "l"(reinterpret_cast<uint64_t>(&tmp)), "r"(sb + BAR_FIRST),
                      "r"((w - a * NWX) * 7 - 1), "r"(a * 7 - 1) : "memory");
    }
    if ((sb & 0x3FFFF) != SMEM_BASE || nrounds > 128) __trap();
    for (int i = 0; i < 6; i++) mbar_init(sb + BAR_FH + 8 * i, 1);
    for (int i = 0; i < 4; i++) mbar_init(sb + BAR_E + 8 * i, 8);
    for (int i = 0; i < 9; i++) mbar_init(sb + BAR_XFULL + 8 * i, 1);
    mbar_init(sb + BAR_TFULL, 3);
    mbar_init(sb + BAR_TEMPTY, 8);
    asm volatile("fence.mbarrier_init.release.cluster;" ::: "memory");
  }
  if (tid >= 128 && tid < 136) *reinterpret_cast<uint32_t*>(smem + OFF_REDO + (tid - 128) * 4) = 0;
  if (tid < 96) {
    *reinterpret_cast<uint4*>(smem + OFF_KV + (tid / 48) * KV_BYTES + 6 * KV_PITCH + (tid % 48) * 16) = make_uint4(0x3c003c00u, 0x3c003c00u, 0x3c003c00u, 0x3c003c00u);
    proxy_fence();
  }
  __syncthreads();

  if (warp < 11) {
#pragma unroll 1
    for (int u = 0; u < (warp < 10 ? 2 : 1); u++) {
      const int cb = warp < 9 ? warp % 3 : 2 * (warp - 9) + u, y = warp < 9 ? 2 * (warp / 3) + u : 6;
      const int ch0 = cb * 64 + (lane & 15) * 4;
      uint32_t wt[9][2], px[3][9][2];
#pragma unroll
      for (int t = 0; t < 9; t++) {
        const uint2 v = *reinterpret_cast<const uint2*>(dw + t * CH + ch0);
        wt[t][0] = v.x; wt[t][1] = v.y;
      }
      mbar_wait(sb + BAR_FIRST, 0);
      const uint32_t ld = sb + OFF_HALO + (lane >> 4) * HALO_BYTES + y * 3456 + ch0 * 2;
#pragma unroll
      for (int p = 0; p < 27; p++)
        asm volatile("ld.shared.v2.u32 {%0,%1}, [%2];" : "=r"(px[p / 9][p % 9][0]), "=r"(px[p / 9][p % 9][1]) : "r"(ld + p * 384));
      const uint32_t st0 = sb + OFF_TILE + (lane >> 4) * TILE_BYTES + ch0 * 4;
      const uint32_t sa = (st0 ^ ((y & 1) << 4)) + y * 2304;
      uint32_t o[2][2];
#pragma unroll
      for (int j = 0; j < 7; j++) {
#pragma unroll
        for (int e = 0; e < 2; e++) {
          uint32_t a = hmul(px[0][j][e], wt[0][e]);
#pragma unroll
          for (int t = 1; t < 9; t++) a = hfma(px[t / 3][j + t % 3][e], wt[t][e], a);
          a = hadd(px[1][j + 1][e], a);
          o[j & 1][e] = packh(lo2f(a), hi2f(a));
        }
        if (j & 1)
          asm volatile("st.shared.v4.u32 [%0], {%1,%2,%3,%4};" :: "r"((j == 3 ? sa ^ 16 : sa) + (j >> 1) * 768),
                       "r"(o[0][0]), "r"(o[1][0]), "r"(o[0][1]), "r"(o[1][1]) : "memory");
      }
      const uint32_t sb6 = (st0 ^ ((~y & 2) << 3)) + (21 + (y >> 1)) * 768 + (y & 1) * 4;
      asm volatile("st.shared.u32 [%0], %1;\nst.shared.u32 [%0 + 8], %2;" :: "r"(sb6), "r"(o[0][0]), "r"(o[0][1]) : "memory");
      if (y == 6) asm volatile("st.shared.u32 [%0 + 4], %1;\nst.shared.u32 [%0 + 12], %1;" :: "r"(sb6), "r"(0) : "memory");
    }
    asm volatile("bar.arrive 8, 384;\nbar.sync 7, 352;" ::: "memory");
  }

  if (warp >= 8) {
    asm volatile("setmaxnreg.dec.sync.aligned.u32 " PREGS ";");
    if (warp == 11) {
      asm volatile("griddepcontrol.wait;" ::: "memory");
      load_slices<3, 0>(sb, ds.src, 0, 0, BAR_F0);
      *reinterpret_cast<float2*>(smem + OFF_LIM) = fp16_limits(lane);
      asm volatile("{\n.reg .pred p;\nelect.sync _|p, 0xffffffff;\n@p mbarrier.arrive.expect_tx.shared::cta.b64 _, [%0], %1;\n}\n"
                   :: "r"(sb + BAR_F0), "n"(3 * SLICE) : "memory");
      asm volatile("bar.sync 8, 384;" ::: "memory");
      load_slices<3, 5 * SLICE>(sb, ds.src, 3, 3, BAR_F1);
      load_slices<1, 0>(sb, ds.src, 13, SLOT_U, BAR_F1);
      load_slices<1, 0>(sb, ds.src, 12, SLOT_V, BAR_F1);
      for (int r = 0; r < nrounds; r++) {
        const int par = r & 1;
        const int h2 = par ? 1 : 2, h3 = par ? 0 : 3;
        mbar_wait(sb + BAR_E, par);
        load_slices<3>(sb, ds.src, 3 * h2, 3 * (h2 & 1), BAR_FH);
        mbar_wait(sb + BAR_E + 8, par);
        load_slices<3>(sb, ds.src, 3 * h3, 3 * (h3 & 1), BAR_FH + 8);
        mbar_wait(sb + BAR_E + 16, par);
        load_slices<1>(sb, ds.src, 12 + h2, SLOT_U, BAR_FU);
        mbar_wait(sb + BAR_E + 24, par);
        load_slices<1>(sb, ds.src, 12 + h3, SLOT_V, BAR_FV);
      }
    } else {
      const int cw = warp - 8;
      const int win = lane >> 4;
      const int ch0 = cw * 64 + (lane & 15) * 4;
      uint32_t wt[9][2];
#pragma unroll
      for (int t = 0; t < 9; t++) {
        uint2 v = *reinterpret_cast<const uint2*>(dw + t * CH + ch0);
        wt[t][0] = v.x; wt[t][1] = v.y;
      }
      const uint32_t xs = sb + OFF_X + cw * 3 * XSLOT;
      const uint32_t xld = xs + (lane >> 4) * 1152 + (lane & 15) * 8;
      const uint32_t xbar = sb + BAR_XFULL + cw * 24;
      const uint32_t st0 = sb + OFF_TILE + win * TILE_BYTES + ch0 * 4;
      const uint64_t tm = reinterpret_cast<uint64_t>(&tmx);
      int cx0, cy0, cx1, cy1;
      auto coords = [&](int r) {
        const int w0 = window_of(r, nfull, cta, ncta, 0);
        int w1 = window_of(r, nfull, cta, ncta, 1);
        if (w1 < 0) w1 = w0;
        const int a = w0 / NWX, b = w1 / NWX;
        cx0 = (w0 - a * NWX) * 7 - 1; cy0 = a * 7 - 1;
        cx1 = (w1 - b * NWX) * 7 - 1; cy1 = b * 7 - 1;
      };
      auto issue = [&](int slot, int dy) {
        asm volatile("{\n.reg .pred p;\nelect.sync _|p, 0xffffffff;\n"
                     "@p mbarrier.arrive.expect_tx.shared::cta.b64 _, [%2], %8;\n"
                     "@p cp.async.bulk.tensor.3d.shared::cluster.global.mbarrier::complete_tx::bytes [%0], [%1, {%3, %4, %5}], [%2];\n"
                     "@p cp.async.bulk.tensor.3d.shared::cluster.global.mbarrier::complete_tx::bytes [%0 + 1152], [%1, {%3, %6, %7}], [%2];\n}\n"
                     :: "r"(xs + slot * XSLOT), "l"(tm), "r"(xbar + slot * 8), "r"(cw * 64), "r"(cx0), "r"(cy0 + dy), "r"(cx1), "r"(cy1 + dy), "n"(XSLOT) : "memory");
      };
      uint32_t accA[7][2], accB[7][2], ctr[7][2], held[2];
      auto row = [&](auto fin, auto mid, auto top, int slot, int y) {
        const uint32_t ld = xld + slot * XSLOT;
        const uint32_t sa = (st0 ^ ((y & 1) << 4)) + y * 2304;
        uint32_t cur[9][2], o[2][2];
#pragma unroll
        for (int p = 0; p < LA; p++)
          asm volatile("ld.shared.v2.u32 {%0,%1}, [%2];" : "=r"(cur[p][0]), "=r"(cur[p][1]) : "r"(ld + p * 128));
#pragma unroll
        for (int j = 0; j < 7; j++) {
          if (j >= 1 && j + LA - 1 < 9)
            asm volatile("ld.shared.v2.u32 {%0,%1}, [%2];" : "=r"(cur[j + LA - 1][0]), "=r"(cur[j + LA - 1][1]) : "r"(ld + (j + LA - 1) * 128));
          if (fin.v) {
#pragma unroll
            for (int e = 0; e < 2; e++) {
              uint32_t a = hfma(cur[j][e], wt[6][e], accA[j][e]);
              a = hfma(cur[j + 1][e], wt[7][e], a);
              a = hfma(cur[j + 2][e], wt[8][e], a);
              a = hadd(ctr[j][e], a);
              o[j & 1][e] = packh(lo2f(a), hi2f(a));
            }
            if (j & 1)
              asm volatile("st.shared.v4.u32 [%0], {%1,%2,%3,%4};" :: "r"((j == 3 ? sa ^ 16 : sa) + (j >> 1) * 768),
                           "r"(o[0][0]), "r"(o[1][0]), "r"(o[0][1]), "r"(o[1][1]) : "memory");
            if (j == 6) {
              const uint32_t sb6 = (st0 ^ ((~y & 2) << 3)) + (21 + (y >> 1)) * 768;
              if (fin.v == 2)
                asm volatile("st.shared.v4.u32 [%0], {%1,%2,%3,%2};" :: "r"(sb6), "r"(o[0][0]), "r"(0), "r"(o[0][1]) : "memory");
              else
                asm volatile("{\n.reg .pred p;\nsetp.ne.s32 p, %5, 0;\n@p st.shared.v4.u32 [%0], {%1,%2,%3,%4};\n}\n"
                             :: "r"(sb6), "r"(held[0]), "r"(o[0][0]), "r"(held[1]), "r"(o[0][1]), "r"(y & 1) : "memory");
              held[0] = o[0][0]; held[1] = o[0][1];
            }
          }
#pragma unroll
          for (int e = 0; e < 2; e++) {
            if (mid.v) {
              uint32_t a = hfma(cur[j][e], wt[3][e], accB[j][e]);
              a = hfma(cur[j + 1][e], wt[4][e], a);
              accA[j][e] = hfma(cur[j + 2][e], wt[5][e], a);
              ctr[j][e] = cur[j + 1][e];
            }
            if (top.v) {
              uint32_t a = hmul(cur[j][e], wt[0][e]);
              a = hfma(cur[j + 1][e], wt[1][e], a);
              accB[j][e] = hfma(cur[j + 2][e], wt[2][e], a);
            }
          }
        }
      };
      held[0] = held[1] = 0;
      if (nrounds > 1) { coords(1); issue(0, 0); issue(1, 1); issue(2, 2); }
      for (int r = 0; r + 1 < nrounds; r++) {
        const bool more = r + 2 < nrounds;
        mbar_wait(xbar, r & 1);
        if (r > 0) issue(2, 2);
        row(IC<0>{}, IC<0>{}, IC<1>{}, 0, 0);
        mbar_wait(xbar + 8, r & 1);
        issue(0, 3);
        row(IC<0>{}, IC<1>{}, IC<1>{}, 1, 0);
        mbar_wait(sb + BAR_TEMPTY, r & 1);
#pragma unroll 1
        for (int k = 0; k < 2; k++) {
          mbar_wait(xbar + 16, (r + k) & 1);
          issue(1, 4 + 3 * k);
          row(IC<1>{}, IC<1>{}, IC<1>{}, 2, 3 * k);
          mbar_wait(xbar, (r + k + 1) & 1);
          issue(2, 5 + 3 * k);
          row(IC<1>{}, IC<1>{}, IC<1>{}, 0, 3 * k + 1);
          mbar_wait(xbar + 8, (r + k + 1) & 1);
          if (k == 1 && more) coords(r + 2);
          if (k == 0 || more) issue(0, k == 0 ? 6 : 0);
          row(IC<1>{}, IC<1>{}, IC<1>{}, 1, 3 * k + 2);
        }
        mbar_wait(xbar + 16, r & 1);
        if (more) issue(1, 1);
        row(IC<2>{}, IC<0>{}, IC<0>{}, 2, 6);
        __syncwarp();
        warp_arrive(sb + BAR_TFULL);
      }
    }
    asm volatile("bar.sync 5, 384;" ::: "memory");
#pragma unroll 1
    for (int i = 0; i < 8; i++) {
      uint32_t bits = *reinterpret_cast<volatile uint32_t*>(smem + OFF_REDO + 4 * i);
#pragma unroll 1
      for (; bits; bits &= bits - 1)
        slow_window(reinterpret_cast<float*>(smem), window_of((i & 3) * 32 + __ffs(bits) - 1, nfull, cta, ncta, i >> 2), tid - 256, x, dw, wqkv, wo, out);
    }
  } else {
    asm volatile("setmaxnreg.inc.sync.aligned.u32 " CREGS ";");
    const int wg = warp >> 2, w4 = warp & 3, g = lane >> 2, q = lane & 3;
    const int row0 = w4 * 16 + g, row1 = row0 + 8;
    const int ps = min(w4 * 8 + g, 24);
    const int pix0 = ps < 21 ? (ps / 3) * IMG + (ps % 3) * 2 : (ps - 21) * 2 * IMG + 6;
    const int pix1 = pix0 + (ps < 21 ? 1 : ps < 24 ? IMG : 0);
    const uint32_t kv = sb + OFF_KV + wg * KV_BYTES;
    const int srow = w4 * 16 + (lane & 15);
    const uint32_t vst = kv + (lane >> 4) * KV_PITCH + (srow < 56 ? srow : min(srow - 7, 55)) * 16;
    uint32_t misc = ((uint32_t)pix1 << 20) | ((uint32_t)pix0 << 8) | q;
    const uint32_t v48 = kv + (lane >> 3) * KV_PITCH + 48 * 16;
    const uint32_t vmask = (row0 < 49 ? 0xffffu : 0u) | (row1 < 49 ? 0xffff0000u : 0u);

    const uint32_t tx = sb + OFF_TILE + wg * TILE_BYTES + ps * 768 + q * 32 + (ps & 1) * 16;
    const int myrounds = window_of(nrounds - 1, nfull, cta, ncta, wg) < 0 ? nrounds - 1 : nrounds;

    if (never == 2) return;
    uint32_t H[48], Y[48];
    const uint64_t* dkv = ds.kv[wg];
    uint32_t P[12], Ofc[12], p48 = 0;
#pragma unroll
    for (int i = 0; i < 48; i++) Y[i] = 0;
#pragma unroll
    for (int i = 0; i < 12; i++) P[i] = Ofc[i] = 0;
#pragma unroll
    for (int i = 0; i < 48; i++) H[i] = 0;
    if (vmask) load_x<0, 12>(H, tx);
    __syncwarp();
    warp_arrive(sb + BAR_TEMPTY);
    mbar_wait(sb + BAR_F0, 0);
    if (wg == 1) turn_pass(1);

    uint8_t *o0, *o1;
    uint32_t omask;
    auto out_setup = [&](int r) {
      omask = r >= 0 ? vmask : 0u;
      const int w = window_of(r, nfull, cta, ncta, wg);
      const int wy = w / NWX, wx = w - wy * NWX;
      asm volatile("" : "+r"(misc));
      const uint32_t wb = (uint32_t)(wy * 7 * IMG + wx * 7) * 384u + (misc & 3) * 16;
      o0 = reinterpret_cast<uint8_t*>(out) + (wb + ((misc >> 8) & 0xfff) * 384u);
      o1 = reinterpret_cast<uint8_t*>(out) + (wb + (misc >> 20) * 384u);
    };
#define OUT(c) store_out<c>(Y, o0, o1, omask)
#define AT(c, k) if ((OMAP >> (20 - 4 * (c)) & 15) == (k)) { OUT(c); PIN(); }
#define SITE(k) AT(0, k) AT(1, k) AT(2, k) AT(3, k) AT(4, k) AT(5, k)
    auto release = [&](int i) { warp_arrive(sb + BAR_E + 8 * i); };

    for (int r = 0;; r++) {
      const uint32_t par = r & 1;
      uint32_t acc[36], S[14], O[14], Q[12], V[12], Ofa[12], Ofb[12], vr[6], k48, mx;
      if (r == myrounds) {
        const bool idle = r < nrounds;
        if (idle) { release(0); release(1); }
        mbar_wait(sb + BAR_FU, par ^ 1);
        turn_wait(wg);
        wg_fence(); mma_pv(O, P, dkv + 4); mma_proj(Y, Ofc, ds.pu[0]); wg_commit();
        turn_pass(wg);
        load_v48(vr, v48);
        wg_wait<0>(); keep(O); keep(Y);
        finish_o(O, vr, p48, vmask, Ofa);
        mbar_wait(sb + BAR_FV, par ^ 1);
        turn_wait(wg);
        wg_fence(); mma_proj(Y, Ofa, ds.pv[0]); wg_commit();
        if (wg == 0 || idle) turn_pass(wg);
        wg_wait<0>(); keep(Y);
        if (idle) { release(2); release(3); turn_wait(wg); turn_pass(wg); }
        out_setup(r - 1);
        OUT(0); PIN(); OUT(1); PIN(); OUT(2); PIN(); OUT(3); PIN(); OUT(4); PIN(); OUT(5);
        if (idle) {
          turn_wait(wg); turn_pass(wg);
          turn_wait(wg); turn_pass(wg);
          turn_wait(wg); turn_pass(wg);
          turn_wait(wg);
        }
        asm volatile("bar.arrive 5, 384;" ::: "memory");
        break;
      }
      const uint64_t* dq0 = ds.q[par];
      float s1[2], s2[2];
      turn_wait(wg);
      wg_fence(); mma_pv(O, P, dkv + 4); wg_commit(); mma_qkv<0, K0A>(acc, H, dq0);
      PIN();
      ln_sums<0, 24>(H, s1, s2);
      PIN();
      wg_fence(); mma_qkv<K0A, 12>(acc, H, dq0);
      if (r > 0) { mbar_wait(sb + BAR_FU, par ^ 1); wg_fence(); mma_proj(Y, Ofc, ds.pu[0]); wg_commit(); }
      else { wg_fence(); wg_commit(); }
      turn_pass(wg);
      load_v48(vr, v48);
      wg_wait<3>(); keep(O);
      wg_sync(wg);
      PIN();
      finish_o(O, vr, p48, vmask, Ofa);
      ln_sums<24, 48>(H, s1, s2);
      float lim_lo, lim_hi;
      asm volatile("ld.shared.v2.f32 {%0,%1}, [%2];" : "=f"(lim_lo), "=f"(lim_hi) : "r"(sb + OFF_LIM) : "memory");
      bool ok;
      const uint32_t rk = ln_rstd(s1, s2, lim_lo, lim_hi, vmask, ok);
      asm volatile("{\n.reg .pred p;\nsetp.eq.s32 p, %2, 0;\n@p red.shared.or.b32 [%0], %1;\n}\n"
                   :: "r"(sb + OFF_REDO + wg * 16 + (r >> 5) * 4), "r"(1u << (r & 31)), "r"((int)ok) : "memory");
      PIN();
      wg_wait<1>(); keep(acc);
      release(0);
      scale12(V, acc, rk); stsm12(V, vst + KV_KOFF);
      scale12(V, acc + 24, rk); stsm12(V, vst);
      PIN();
      wg_wait<0>(); keep(Y);
      PIN();
      proxy_fence();
      scale12(Q, acc + 12, rk);
      if (r > 0) mbar_wait(sb + BAR_FV, par ^ 1); else mbar_wait(sb + BAR_F1, 0);
      turn_wait(wg);
      if (r > 0) { wg_fence(); mma_proj(Y, Ofa, ds.pv[0]); wg_commit(); }
      wg_fence(); mma_s(S, Q, dkv); mma_qkv<0, B1A>(acc, H, dq0 + 12);
      out_setup(r - 1);
      PIN();
      wg_wait<1>(); keep(Y);
      wg_fence(); mma_qkv<B1A, B1B>(acc, H, dq0 + 12);
      PIN();
      SITE(0);
      wg_wait<1>(); keep(S);
      wg_fence(); mma_qkv<B1B, B1C>(acc, H, dq0 + 12);
      PIN();
      row_max(S, k48, mx);
      SITE(1);
      PIN();
      wg_fence(); mma_qkv<B1C, 12>(acc, H, dq0 + 12);
      turn_pass(wg);
      PIN();
      SITE(2);
      row_exp(S, k48, mx, P, p48);
      PIN();
      wg_wait<0>(); keep(acc);
      release(1);
      wg_sync(wg);
      scale12(V, acc, rk); stsm12(V, vst + KV_KOFF);
      scale12(Q, acc + 12, rk); scale12(V, acc + 24, rk); PIN();
      proxy_fence();
      SITE(5);
#define TURN(ID, OF, DQ, FB, X1)                                                        \
      mbar_wait(sb + FB, par);                                                          \
      turn_wait(wg);                                                                    \
      wg_fence(); mma_pv(O, P, dkv + 4); mma_s(S, Q, dkv); wg_commit(); mma_qkv<0, KA>(acc, H, DQ); \
      PIN();                                                                            \
      load_v48(vr, v48);                                                                \
      X1;                                                                               \
      PIN();                                                                            \
      wg_wait<1>(); keep(S); keep(O);                                                   \
      wg_sync(wg);                                         \
      wg_fence(); mma_qkv<KA, KB>(acc, H, DQ);                                            \
      PIN();                                                                            \
      stsm12(V, vst);                                                                   \
      finish_o(O, vr, p48, vmask, OF);                                                  \
      row_max(S, k48, mx);                                                              \
      PIN();                                                                            \
      wg_fence(); mma_qkv<KB, 12>(acc, H, DQ);                                          \
      turn_pass(wg);                                                                    \
      PIN();                                                                            \
      (void)0;
#define NEXT_HEAD(ID)                                                                   \
      row_exp(S, k48, mx, P, p48);                                                      \
      PIN();                                                                            \
      wg_wait<0>(); keep(acc);                                                          \
      scale12(V, acc, rk); stsm12(V, vst + KV_KOFF);                                    \
      scale12(Q, acc + 12, rk); scale12(V, acc + 24, rk); PIN();
      TURN(8, Ofa, dq0 + 24, BAR_FH, SITE(3))
      SITE(4);
      NEXT_HEAD(8)
      proxy_fence();
      SITE(8);
      TURN(12, Ofb, dq0 + 36, BAR_FH + 8, SITE(6))
      SITE(7);
      auto init_y = [&]() {
#pragma unroll
        for (int i = 0; i < 48; i++) Y[i] = (i & 1) ? H[i] ^ never : h2u(__hadd2_rn(u2h(H[i]), u2h(never)));
        hold<0, 48>(Y); PIN();
      };
      NEXT_HEAD(12)
      init_y();
      proxy_fence();
      turn_wait(wg);
      wg_fence(); mma_pv(O, P, dkv + 4); mma_s(S, Q, dkv); wg_commit();
      mma_proj(Y, Ofb, ds.pu[1]); wg_commit(); mma_proj(Y, Ofa, ds.pv[1]); wg_commit();
      turn_pass(wg);
      PIN();
      load_v48(vr, v48);
      if (r + 1 < myrounds) mbar_wait(sb + BAR_TFULL, par);
      if (vmask) load_x<0, 4>(H, tx);
      wg_wait<2>(); keep(S); keep(O);
      wg_sync(wg);
      PIN();
      row_max(S, k48, mx);
      finish_o(O, vr, p48, vmask, Ofc);
      stsm12(V, vst);
      PIN();
      wg_wait<1>();
      release(2);
      if (vmask) load_x<4, 8>(H, tx);
      row_exp(S, k48, mx, P, p48);
      PIN();
      if (vmask) load_x<8, 12>(H, tx);
      __syncwarp();
      warp_arrive(sb + BAR_TEMPTY);
      wg_wait<0>(); keep(Y);
      release(3);
      proxy_fence();
#undef TURN
#undef NEXT_HEAD
    }
  }
}

typedef CUresult (*EncodeFn)(CUtensorMap*, CUtensorMapDataType, cuuint32_t, void*, const cuuint64_t*, const cuuint64_t*,
                             const cuuint32_t*, const cuuint32_t*, CUtensorMapInterleave, CUtensorMapSwizzle,
                             CUtensorMapL2promotion, CUtensorMapFloatOOBfill);

}

extern "C" void kernel_launch(void* const* d_in, const int* in_sizes, int n_in, void* d_out, int out_size) {
  const __nv_bfloat16* x = (const __nv_bfloat16*)d_in[0];
  const __nv_bfloat16* dw = (const __nv_bfloat16*)d_in[1];
  const __nv_bfloat16* wqkv = (const __nv_bfloat16*)d_in[2];
  const __nv_bfloat16* wo = (const __nv_bfloat16*)d_in[3];
  static EncodeFn encode = nullptr;
  static int nsm = 0;
  static void* wpack = nullptr;
  if (!encode) {
    void* fn = nullptr;
    cudaDriverEntryPointQueryResult qr;
    cudaGetDriverEntryPoint("cuTensorMapEncodeTiled", &fn, cudaEnableDefault, &qr);
    encode = (EncodeFn)fn;
    int dev = 0;
    cudaGetDevice(&dev);
    cudaDeviceGetAttribute(&nsm, cudaDevAttrMultiProcessorCount, dev);
    cudaGetSymbolAddress(&wpack, g_wpack);
    cudaFuncSetAttribute(fused_kernel, cudaFuncAttributeMaxDynamicSharedMemorySize, SMEM_BYTES);
  }
  CUtensorMap tmx;
  cuuint64_t gdim[3] = {CH, IMG, IMG};
  cuuint64_t gstr[2] = {CH * 2, (cuuint64_t)CH * 2 * IMG};
  cuuint32_t box[3] = {64, 9, 1};
  cuuint32_t estr[3] = {1, 1, 1};
  encode(&tmx, CU_TENSOR_MAP_DATA_TYPE_BFLOAT16, 3, (void*)x, gdim, gstr, box, estr, CU_TENSOR_MAP_INTERLEAVE_NONE,
         CU_TENSOR_MAP_SWIZZLE_NONE, L2PROMO, CU_TENSOR_MAP_FLOAT_OOB_FILL_NONE);
  Descs ds;
  for (int i = 0; i < 12; i++)
    for (int b = 0; b < 5; b++) ds.q[b][i] = mkdesc(SMEM_BASE + OFF_W + qkv_pos(b & 1, i), 128, 256);
  for (int i = 0; i < 3; i++) {
    ds.pu[0][i] = ds.pu[1][i] = mkdesc(SMEM_BASE + OFF_W + SLOT_U * SLICE + i * 6144, 128, 256);
    ds.pv[0][i] = ds.pv[1][i] = mkdesc(SMEM_BASE + OFF_W + SLOT_V * SLICE + i * 6144, 128, 256);
  }
  ds.src = (const uint8_t*)wpack;
  for (int g = 0; g < 2; g++)
    for (int i = 0; i < 4; i++) {
      ds.kv[g][i] = mkdesc(SMEM_BASE + OFF_KV + g * KV_BYTES + KV_KOFF + 2 * i * KV_PITCH, KV_PITCH, 128);
      ds.kv[g][4 + i] = mkdesc(SMEM_BASE + OFF_KV + g * KV_BYTES + 256 * i, 128, KV_PITCH);
    }
  CUtensorMap tmp;
  cuuint32_t boxp[3] = {CH, 9, 9};
  encode(&tmp, CU_TENSOR_MAP_DATA_TYPE_BFLOAT16, 3, (void*)x, gdim, gstr, boxp, estr, CU_TENSOR_MAP_INTERLEAVE_NONE,
         CU_TENSOR_MAP_SWIZZLE_NONE, L2PROMO, CU_TENSOR_MAP_FLOAT_OOB_FILL_NONE);
  prepack_kernel<<<96 / PBY, dim3(192, PBY), 0, cudaStreamPerThread>>>(wqkv, wo, x, min(IMG, (2 * nsm + NWX - 1) / NWX * 7 + 1));
  cudaLaunchConfig_t cfg = {};
  cfg.gridDim = dim3(nsm); cfg.blockDim = dim3(384); cfg.dynamicSmemBytes = SMEM_BYTES; cfg.stream = cudaStreamPerThread;
  cudaLaunchAttribute at[1];
  at[0].id = cudaLaunchAttributeProgrammaticStreamSerialization;
  at[0].val.programmaticStreamSerializationAllowed = 1;
  cfg.attrs = at; cfg.numAttrs = 1;
  cudaLaunchKernelEx(&cfg, fused_kernel, tmx, tmp, ds, dw, (__nv_bfloat16*)d_out, 0, x, wqkv, wo);
}
```
